```python
import torch

def _softmax(x, axis=-1):
    return torch.softmax(x, dim=axis)
def _gelu(x):
    return torch.nn.functional.gelu(x, approximate="tanh")
def _silu(x):
    return torch.nn.functional.silu(x)
def _sigmoid(x):
    return torch.sigmoid(x)
def _layernorm(x, axis=-1, eps=1e-5):
    m = x.mean(dim=axis, keepdim=True)
    v = x.var(dim=axis, keepdim=True, unbiased=False)
    return (x - m) / torch.sqrt(v + eps)
def _scatter_add(tgt, idx, src, axis=0):
    return tgt.clone().index_add_(axis, idx, src)
def _segment_sum(src, seg, n):
    out = torch.zeros((n,) + src.shape[1:], dtype=src.dtype)
    return out.index_add_(0, seg, src)
def _pad(x, pw):
    flat = tuple(v for pair in reversed(pw) for v in pair)
    return torch.nn.functional.pad(x, flat)

kernel_name = 'interleave_layers__sliding_block_cached__moe_arch_mod__decode'

def setup_inputs():

    _w = (lambda a: (lambda t: t.to(torch.bfloat16) if t.is_floating_point() else t)(torch.as_tensor(a)))
    def _A_setup():
        B, Sq, D = 4, 1, 640
        Hq, Hkv, Sk, Dh = 32, 32, 4096, 192
        assert Hq % Hkv == 0, (Hq, Hkv)
        return {
            "x": _w((lambda *s: torch.randn(*s, dtype=torch.bfloat16) * 0.05)(B, Sq, D)),
            "k_cache": _w((lambda *s: torch.randn(*s, dtype=torch.bfloat16) * 1.6)(B, Hkv, Sk, Dh)),
            "v_cache": _w((lambda *s: torch.randn(*s, dtype=torch.bfloat16) * 1.6)(B, Hkv, Sk, Dh)),
            "wq": _w((lambda *s: torch.randn(*s, dtype=torch.bfloat16) * 1.6)(D, Hq * Dh) * (D ** -0.5)),
            "wo": _w((lambda *s: torch.randn(*s, dtype=torch.bfloat16) * 1.6)(Hq * Dh, D) * ((Hq * Dh) ** -0.5)),
        }
    _A_in = _A_setup()

    def _B_setup():
        B, S, D, F, C = 4, 1, 640, 1536, 1
        return {
            "x": _w((lambda *s: torch.randn(*s, dtype=torch.bfloat16) * 0.05)(B, S, D)),
            "w_r": _w((lambda *s: torch.randn(*s, dtype=torch.bfloat16) * 0.05)(D)),
            "w_gate": _w((lambda *s: torch.randn(*s, dtype=torch.bfloat16) * 0.05)(D, F)),
            "w_up": _w((lambda *s: torch.randn(*s, dtype=torch.bfloat16) * 0.05)(D, F)),
            "w_down": _w((lambda *s: torch.randn(*s, dtype=torch.bfloat16) * 0.05)(F, D)),
        }
    _B_in = _B_setup()

    return {
        "A_x": _A_in["x"],
        "A_k_cache": _A_in["k_cache"],
        "A_v_cache": _A_in["v_cache"],
        "A_wq": _A_in["wq"],
        "A_wo": _A_in["wo"],
        "B_x": _B_in["x"],
        "B_w_r": _B_in["w_r"],
        "B_w_gate": _B_in["w_gate"],
        "B_w_up": _B_in["w_up"],
        "B_w_down": _B_in["w_down"],
    }

def reference(A_x, A_k_cache, A_v_cache, A_wq, A_wo, B_x, B_w_r, B_w_gate, B_w_up, B_w_down):
    def _A_ref(x, k_cache, v_cache, wq, wo):
        B, Sq, D = x.shape
        Hq, Dh = 32, 192
        Hkv, Sk = k_cache.shape[1], k_cache.shape[2]
        W = min(4096, max(256, Sk // 4))
        rep = Hq // Hkv
        q = (lambda x, *d: x.permute(*d))((x @ wq).reshape(B, Sq, Hq, Dh), 0, 2, 1, 3)
        k = (lambda x, n, axis: torch.repeat_interleave(x, n, dim=axis))(k_cache[:, :, Sk - W:, :], rep, axis=1)
        v = (lambda x, n, axis: torch.repeat_interleave(x, n, dim=axis))(v_cache[:, :, Sk - W:, :], rep, axis=1)
        scores = torch.einsum("bhqd,bhkd->bhqk", q, k) * (Dh ** -0.5)
        p = _softmax(scores, axis=-1)
        o = torch.einsum("bhqk,bhkd->bhqd", p, v)
        return (lambda x, *d: x.permute(*d))(o, 0, 2, 1, 3).reshape(B, Sq, Hq * Dh) @ wo

    def _B_ref(x, w_r, w_gate, w_up, w_down):
        B, S, D = x.shape
        C = 1
        r = x @ w_r
        idx = torch.argsort(-r, axis=-1)[:, :C]
        idx_e = (lambda x, n, axis: torch.repeat_interleave(x, n, dim=axis))(idx.reshape(B, C, 1), D, axis=2)
        x_sel = (lambda x, i, axis: torch.take_along_dim(x, i, dim=axis))(x, idx_e, axis=1)
        g = _silu(x_sel @ w_gate)
        u = x_sel @ w_up
        y = (g * u) @ w_down
        r_sel = _sigmoid((lambda x, i, axis: torch.take_along_dim(x, i, dim=axis))(r, idx, axis=1))
        y = y * r_sel.reshape(B, C, 1)
        b_off = (torch.arange(B) * S).reshape(B, 1)
        flat_idx = (idx + b_off).reshape(B * C)
        zero = (x * 0.0).reshape(B * S, D)
        upd = _scatter_add(zero, flat_idx, y.reshape(B * C, D), axis=0)
        return x + upd.reshape(B, S, D)

    x = A_x
    x = x + _A_ref(_layernorm(x, axis=-1), A_k_cache, A_v_cache, A_wq, A_wo)
    x = x + _B_ref(_layernorm(x, axis=-1), B_w_r, B_w_gate, B_w_up, B_w_down)
    x = x + _A_ref(_layernorm(x, axis=-1), A_k_cache, A_v_cache, A_wq, A_wo)
    x = x + _B_ref(_layernorm(x, axis=-1), B_w_r, B_w_gate, B_w_up, B_w_down)
    return x
```

```cpp
#include <cuda_runtime.h>
#include <cuda.h>
#include <cuda_bf16.h>
#include <stdint.h>

namespace {

constexpr int NCTA = 128;
constexpr int NTHR = 384;
constexpr int SLOT = 12288;
constexpr int DPIECE = 6144;
#define WD_AFTER 15
#define WIN_W 4
#define WIN_FIRST 3
#define NPF 2
#define EARLY 3
#define NSELF 4
#define WIN_FREE 4
#define WIN_GAP 2
#define WIN_LAND 6
#define MAXLEAD 14
#define WPROMO CU_TENSOR_MAP_L2_PROMOTION_NONE
#define KPRE 4
#define KPRE2 1
#define DELAY_G 100
#define DELAY_L 150
#define DELAY_E 100
#define REG_LO "24"
#define REG_HI "240"
#define SPIN_LOG 17
constexpr int SPIN_LIMIT = 1 << SPIN_LOG;

__host__ __device__ constexpr uint32_t pairL(uint32_t region, uint32_t c, uint32_t g) { return (g & 1) | ((g >> 1) << 2) | (c << 5) | (region << 6); }
__host__ __device__ constexpr uint32_t pairG(uint32_t d, uint32_t c, uint32_t i) { return (i & 1) | ((i >> 1) << 2) | (d << 4) | (c << 5) | (3u << 6); }
constexpr uint32_t RA = 0, RC = 1, RE = 2, HALF = 16384, COPY = 4096, PMASK = 0x59;
constexpr uint32_t XS = 0;
constexpr uint32_t XS2 = XS + 128 * 7680;
constexpr uint32_t XSEND = XS2 + 128 * 768;
__device__ uint4 g_s[XSEND / 16];
__device__ uint4 g_x[(4u << 20) / 16];
#define SWEEPS(k, n) do {} while (0)

constexpr uint32_t S_WD = 16 * SLOT;
constexpr uint32_t S_DUMMY = S_WD + 15360;
constexpr uint32_t S_FULL = S_DUMMY + DPIECE;
constexpr uint32_t S_RELK = S_FULL + 128, S_RELV = S_RELK + 8, S_RELW = S_RELV + 8, S_DBAR = S_RELW + 24, S_WFULL = S_DBAR + 32;
constexpr uint32_t S_SP = S_WFULL + 96, S_SIDE = S_SP + 4, S_DM = S_SIDE + 4;
constexpr uint32_t S_GATE = S_DM + 8, S_SWR = S_GATE + 4;
constexpr uint32_t S_WMAX = S_SWR + 4;
constexpr uint32_t S_STAT = S_WMAX + 32;
constexpr uint32_t S_XCAR = S_STAT + 32;
constexpr uint32_t S_CSQ = S_XCAR + 320;
constexpr uint32_t S_CSGU = S_CSQ + 768;
constexpr uint32_t S_RED = S_CSGU + 768;
constexpr uint32_t S_OS = S_RED + 5120;
constexpr uint32_t S_PS = S_OS + 1536;
constexpr uint32_t S_QS = S_PS + 512;
constexpr uint32_t S_XQ = S_QS + 1536;
constexpr uint32_t S_XT = S_XQ + 960;
constexpr uint32_t S_HS = S_XT + 480;
constexpr uint32_t S_X0 = S_HS + 384;
constexpr uint32_t S_L0 = S_X0 + 640;
constexpr uint32_t S_SELF = S_L0 + 640;
constexpr int SMEM_BYTES = S_SELF + 32;
static_assert(SMEM_BYTES <= 232448 && S_WMAX % 16 == 0 && S_RED % 16 == 0 && S_XQ % 16 == 0 && S_HS % 16 == 0, "smem");
constexpr uint32_t ST_WQ = 0, ST_WG = 5 * SLOT, ST_WU = ST_WG + 15360, ST_WO = 11 * SLOT;

__device__ __forceinline__ uint32_t smem_u32(const void* p) { return (uint32_t)__cvta_generic_to_shared(p); }
__device__ __forceinline__ void mbar_init(uint32_t bar, uint32_t cnt) { asm volatile("mbarrier.init.shared::cta.b64 [%0], %1;" :: "r"(bar), "r"(cnt) : "memory"); }
__device__ __forceinline__ void mbar_expect(uint32_t bar, uint32_t bytes) { asm volatile("mbarrier.arrive.expect_tx.shared::cta.b64 _, [%0], %1;" :: "r"(bar), "r"(bytes) : "memory"); }
__device__ __forceinline__ void mbar_arrive(uint32_t bar) { asm volatile("mbarrier.arrive.shared::cta.b64 _, [%0];" :: "r"(bar) : "memory"); }
__device__ __forceinline__ bool mbar_try(uint32_t bar, uint32_t parity) {
    uint32_t ok;
    asm volatile("{\n .reg .pred p;\n mbarrier.try_wait.parity.shared::cta.b64 p, [%1], %2;\n selp.u32 %0, 1, 0, p;\n}" : "=r"(ok) : "r"(bar), "r"(parity) : "memory");
    return ok != 0;
}
__device__ __forceinline__ bool mbar_test(uint32_t bar, uint32_t parity) {
    uint32_t ok;
    asm volatile("{\n .reg .pred p;\n mbarrier.test_wait.parity.shared::cta.b64 p, [%1], %2;\n selp.u32 %0, 1, 0, p;\n}" : "=r"(ok) : "r"(bar), "r"(parity) : "memory");
    return ok != 0;
}
__device__ __forceinline__ void mbar_wait(uint32_t bar, uint32_t parity) {
    int n = 0;
    while (!mbar_try(bar, parity) && ++n < SPIN_LIMIT) {}
}
__device__ __forceinline__ unsigned long long gtime() { unsigned long long t; asm volatile("mov.u64 %0, %globaltimer;" : "=l"(t)); return t; }
__device__ __forceinline__ uint32_t gtime32() { uint32_t t; asm volatile("mov.u32 %0, %globaltimer_lo;" : "=r"(t)); return t; }
__device__ __forceinline__ void bar_main() { __syncwarp(); asm volatile("bar.sync 1, 256;" ::: "memory"); }

__device__ __forceinline__ void mma16816(float (&c)[4], uint32_t a0, uint32_t a1, uint32_t a2, uint32_t a3, uint32_t b0, uint32_t b1) {
    asm("mma.sync.aligned.m16n8k16.row.col.f32.bf16.bf16.f32 {%0,%1,%2,%3}, {%4,%5,%6,%7}, {%8,%9}, {%0,%1,%2,%3};"
        : "+f"(c[0]), "+f"(c[1]), "+f"(c[2]), "+f"(c[3]) : "r"(a0), "r"(a1), "r"(a2), "r"(a3), "r"(b0), "r"(b1));
}
__device__ __forceinline__ void mmaA(float (&c)[4], const uint32_t (&a)[4], uint32_t b0, uint32_t b1) { mma16816(c, a[0], a[1], a[2], a[3], b0, b1); }
__device__ __forceinline__ void mmaV(float (&c)[4], const uint4& a, uint32_t b0, uint32_t b1) { mma16816(c, a.x, a.y, a.z, a.w, b0, b1); }
__device__ __forceinline__ void ldsm4(uint32_t (&r)[4], uint32_t addr) {
    asm volatile("ldmatrix.sync.aligned.m8n8.x4.shared.b16 {%0,%1,%2,%3}, [%4];" : "=r"(r[0]), "=r"(r[1]), "=r"(r[2]), "=r"(r[3]) : "r"(addr) : "memory");
}
__device__ __forceinline__ void ldsm4t(uint32_t (&r)[4], uint32_t addr) {
    asm volatile("ldmatrix.sync.aligned.m8n8.x4.trans.shared.b16 {%0,%1,%2,%3}, [%4];" : "=r"(r[0]), "=r"(r[1]), "=r"(r[2]), "=r"(r[3]) : "r"(addr) : "memory");
}
__device__ __forceinline__ uint32_t lds16(uint32_t a) { uint16_t v; asm volatile("ld.shared.u16 %0, [%1];" : "=h"(v) : "r"(a) : "memory"); return v; }
__device__ __forceinline__ uint32_t lds32(uint32_t a) { uint32_t v; asm volatile("ld.shared.u32 %0, [%1];" : "=r"(v) : "r"(a) : "memory"); return v; }
__device__ __forceinline__ float ldsf(uint32_t a) { return __uint_as_float(lds32(a)); }
__device__ __forceinline__ uint2 lds64(uint32_t a) { uint2 v; asm volatile("ld.shared.v2.u32 {%0,%1}, [%2];" : "=r"(v.x), "=r"(v.y) : "r"(a) : "memory"); return v; }
__device__ __forceinline__ uint4 lds128(uint32_t a) { uint4 v; asm volatile("ld.shared.v4.u32 {%0,%1,%2,%3}, [%4];" : "=r"(v.x), "=r"(v.y), "=r"(v.z), "=r"(v.w) : "r"(a) : "memory"); return v; }
__device__ __forceinline__ int ldsvol(uint32_t a) { int v; asm volatile("ld.volatile.shared.u32 %0, [%1];" : "=r"(v) : "r"(a) : "memory"); return v; }
__device__ __forceinline__ void stsvol(uint32_t a, int v) { asm volatile("st.volatile.shared.u32 [%0], %1;" :: "r"(a), "r"(v) : "memory"); }
__device__ __forceinline__ void sts_hi16(uint32_t a, float v) { asm volatile("{\n .reg .b16 lo, hi;\n mov.b32 {lo, hi}, %1;\n st.shared.u16 [%0], hi;\n}" :: "r"(a), "r"(__float_as_uint(v)) : "memory"); }
__device__ __forceinline__ void sts32(uint32_t a, uint32_t v) { asm volatile("st.shared.u32 [%0], %1;" :: "r"(a), "r"(v) : "memory"); }
__device__ __forceinline__ void stsf(uint32_t a, float v) { sts32(a, __float_as_uint(v)); }
__device__ __forceinline__ void sts64(uint32_t a, uint32_t x, uint32_t y) { asm volatile("st.shared.v2.u32 [%0], {%1,%2};" :: "r"(a), "r"(x), "r"(y) : "memory"); }

__device__ __forceinline__ void sts_hi16_if(bool p, uint32_t a, float v) {
    asm volatile("{\n .reg .pred p;\n .reg .b16 lo, hi;\n setp.ne.u32 p, %2, 0;\n mov.b32 {lo, hi}, %1;\n @p st.shared.u16 [%0], hi;\n}" :: "r"(a), "r"(__float_as_uint(v)), "r"((uint32_t)p) : "memory");
}
__device__ __forceinline__ void sts32_if(bool p, uint32_t a, uint32_t v) {
    asm volatile("{\n .reg .pred p;\n setp.ne.u32 p, %2, 0;\n @p st.shared.u32 [%0], %1;\n}" :: "r"(a), "r"(v), "r"((uint32_t)p) : "memory");
}
__device__ __forceinline__ void sts64_if(bool p, uint32_t a, float x, float y) {
    asm volatile("{\n .reg .pred p;\n setp.ne.u32 p, %3, 0;\n @p st.shared.v2.f32 [%0], {%1,%2};\n}" :: "r"(a), "f"(x), "f"(y), "r"((uint32_t)p) : "memory");
}
__device__ __forceinline__ void arrive_if(bool p, uint32_t bar) {
    asm volatile("{\n .reg .pred p;\n setp.ne.u32 p, %1, 0;\n @p mbarrier.arrive.shared::cta.b64 _, [%0];\n}" :: "r"(bar), "r"((uint32_t)p) : "memory");
}
__device__ __forceinline__ void opaque(uint32_t& v) { asm volatile("" : "+r"(v)); }
__device__ __forceinline__ void keep(uint32_t& v) { asm volatile("" : "+r"(v)); }
__device__ __forceinline__ void keep(float& v) { asm volatile("" : "+f"(v)); }
template <class T> __device__ __forceinline__ void keep(T*& v) { asm volatile("" : "+l"(v)); }

__device__ __forceinline__ uint32_t ldp32(const char* p) { uint32_t v; asm volatile("ld.relaxed.gpu.global.u32 %0, [%1];" : "=r"(v) : "l"(p) : "memory"); return v; }
__device__ __forceinline__ uint2 ldp64(const char* p) {
    uint2 v; asm volatile("{\n .reg .b64 d;\n ld.relaxed.gpu.global.b64 d, [%2];\n mov.b64 {%0,%1}, d;\n}" : "=r"(v.x), "=r"(v.y) : "l"(p) : "memory"); return v;
}
__device__ __forceinline__ uint32_t tagw(float f, uint32_t par) { return (__float_as_uint(f) & ~1u) | par; }
__device__ __forceinline__ void stp32(char* p, float a, uint32_t par) { asm volatile("st.relaxed.gpu.global.u32 [%0], %1;" :: "l"(p), "r"(tagw(a, par)) : "memory"); }
__device__ __forceinline__ void stp64(char* p, float a, float b, uint32_t par) {
    asm volatile("{\n .reg .b64 d;\n mov.b64 d, {%1,%2};\n st.relaxed.gpu.global.b64 [%0], d;\n}" :: "l"(p), "r"(tagw(a, par)), "r"(__float_as_uint(b)) : "memory");
}
__device__ __forceinline__ void stp32_if(bool p, char* d, float a, uint32_t par) {
    asm volatile("{\n .reg .pred p;\n setp.ne.u32 p, %2, 0;\n @p st.relaxed.gpu.global.u32 [%0], %1;\n @p st.relaxed.gpu.global.u32 [%0+4096], %1;\n}" :: "l"(d), "r"(tagw(a, par)), "r"((uint32_t)p) : "memory");
}
__device__ __forceinline__ void stp64_if(bool p, char* d, uint32_t lo, uint32_t hi) {
    asm volatile("{\n .reg .pred p;\n .reg .b64 d;\n setp.ne.u32 p, %3, 0;\n mov.b64 d, {%1,%2};\n @p st.relaxed.gpu.global.b64 [%0], d;\n @p st.relaxed.gpu.global.b64 [%0+4096], d;\n}" :: "l"(d), "r"(lo), "r"(hi), "r"((uint32_t)p) : "memory");
}
__device__ __forceinline__ uint32_t chk2(uint32_t a, uint32_t b, uint32_t par) { uint32_t r; asm("lop3.b32 %0, %1, %2, %3, 0x7E;" : "=r"(r) : "r"(a), "r"(b), "r"(par)); return r; }
__device__ __forceinline__ uint32_t or3(uint32_t a, uint32_t b, uint32_t c) { uint32_t r; asm("lop3.b32 %0, %1, %2, %3, 0xFE;" : "=r"(r) : "r"(a), "r"(b), "r"(c)); return r; }
__device__ __forceinline__ uint32_t chk8(const uint32_t (&v)[8], uint32_t par) { return or3(chk2(v[0], v[1], par), chk2(v[2], v[3], par), or3(chk2(v[4], v[5], par), chk2(v[6], v[7], par), 0)); }
__device__ __forceinline__ uint32_t chk8(const uint2 (&v)[8], uint32_t par) { return or3(chk2(v[0].x, v[1].x, par), chk2(v[2].x, v[3].x, par), or3(chk2(v[4].x, v[5].x, par), chk2(v[6].x, v[7].x, par), 0)); }
__device__ __forceinline__ float asf(uint32_t v) { return __uint_as_float(v); }
__device__ __forceinline__ float sum8(const uint32_t (&v)[8]) { return ((asf(v[0]) + asf(v[1])) + (asf(v[2]) + asf(v[3]))) + ((asf(v[4]) + asf(v[5])) + (asf(v[6]) + asf(v[7]))); }
__device__ __forceinline__ float sum8x(const uint2 (&v)[8]) { return ((asf(v[0].x) + asf(v[1].x)) + (asf(v[2].x) + asf(v[3].x))) + ((asf(v[4].x) + asf(v[5].x)) + (asf(v[6].x) + asf(v[7].x))); }
__device__ __forceinline__ float sum8y(const uint2 (&v)[8]) { return ((asf(v[0].y) + asf(v[1].y)) + (asf(v[2].y) + asf(v[3].y))) + ((asf(v[4].y) + asf(v[5].y)) + (asf(v[6].y) + asf(v[7].y))); }

__device__ __forceinline__ uint32_t pack2(float lo, float hi) { uint32_t r; asm("cvt.rn.bf16x2.f32 %0, %1, %2;" : "=r"(r) : "f"(hi), "f"(lo)); return r; }
__device__ __forceinline__ float bfr(float x) { return __uint_as_float(pack2(0.0f, x)); }
__device__ __forceinline__ float ex2(float x) { float r; asm("ex2.approx.ftz.f32 %0, %1;" : "=f"(r) : "f"(x)); return r; }
__device__ __forceinline__ float rcp(float x) { float r; asm("rcp.approx.ftz.f32 %0, %1;" : "=f"(r) : "f"(x)); return r; }
__device__ __forceinline__ float sqrt_(float x) { float r; asm("sqrt.approx.ftz.f32 %0, %1;" : "=f"(r) : "f"(x)); return r; }
__device__ __forceinline__ float bf_lo(uint32_t v) { return __uint_as_float(v << 16); }
__device__ __forceinline__ float bf_hi(uint32_t v) { return __uint_as_float(v & 0xffff0000u); }
__device__ __forceinline__ float sel4(int k, float a, float b, float c, float d) { return (k & 2) ? ((k & 1) ? d : c) : ((k & 1) ? b : a); }
constexpr float LOG2E = 1.4426950408889634f;
constexpr uint32_t ONES = 0x3f803f80u;

__device__ __forceinline__ void ln_stats(float sum, float sq, float& mean, float& den) {
    const float m = sum * (1.0f / 640.0f);
    const float var = fmaxf(fmaf(sq, 1.0f / 640.0f, -m * m), 0.0f);
    mean = bfr(m);
    den = bfr(sqrt_(bfr(bfr(var) + 1e-5f)));
}
__device__ __forceinline__ float sigmoidf_(float x) { return rcp(1.0f + ex2(-x * LOG2E)); }

#define TSTAMP(k) do {} while (0)

#define CSTAMP(k) do {} while (0)
template <int CLK> __device__ __forceinline__ void poll_delay() {
    if (CLK > 0) { uint32_t c0, c; asm volatile("mov.u32 %0, %clock;" : "=r"(c0) :: "memory"); do { asm volatile("mov.u32 %0, %clock;" : "=r"(c) :: "memory"); } while (c - c0 < CLK); }
}
__device__ __forceinline__ void warm_mma(uint32_t& a, uint32_t& b) {
    asm volatile("mma.sync.aligned.m16n8k8.row.col.f16.f16.f16.f16 {%0,%1}, {%0,%1}, {%0}, {%0,%1};" : "+r"(a), "+r"(b) :: "memory");
}
#define KEEPWARM 128
#define KWSTART 4000
#define KWGAP 400
#define KWTAIL 4
template <int STRIDE>
__device__ __forceinline__ float gather8(const char* p, uint32_t par) {
    uint32_t v[8];
    int guard = 0;
    do {
#pragma unroll
        for (int s = 0; s < 8; s++) v[s] = ldp32(p + s * STRIDE);
    } while ((chk8(v, par) & 1) && ++guard < SPIN_LIMIT);
    return sum8(v);
}
__device__ __forceinline__ float gather16(const char* p, uint32_t par, int k) {
    uint32_t v[8], u[8];
    int guard = 0;
    poll_delay<DELAY_G>();
    do {
#pragma unroll
        for (int s = 0; s < 8; s++) v[s] = ldp32(p + s * 512);
#pragma unroll
        for (int s = 0; s < 8; s++) u[s] = ldp32(p + HALF + s * 512);
    } while (((chk8(v, par) | chk8(u, par)) & 1) && ++guard < SPIN_LIMIT);
    const float r = sum8(v) + sum8(u);
    SWEEPS(k, guard);
    return r;
}

struct Params {
    const __nv_bfloat16 *x, *k, *v, *wr;
    __nv_bfloat16* out;
};
struct Maps { CUtensorMap k, v, wq, wo, wg, wu, wd; };

constexpr int KV_BATCH_KEYS = 32 * 4096;

__device__ __forceinline__ void tma2d(uint32_t dst, const CUtensorMap* m, int c0, int c1, uint32_t bar, uint64_t pol) {
    asm volatile("cp.async.bulk.tensor.2d.shared::cluster.global.mbarrier::complete_tx::bytes.L2::cache_hint [%0], [%1, {%3, %4}], [%2], %5;"
                 :: "r"(dst), "l"(m), "r"(bar), "r"(c0), "r"(c1), "l"(pol) : "memory");
}
__device__ __forceinline__ void see_release(uint32_t sb, int& rel) { if (mbar_test(sb + S_RELK + 8 * (rel & 1), (rel >> 1) & 1)) rel++; }
__device__ __forceinline__ void load_k_head(const Maps& M, uint32_t sb, int n, int key0, uint64_t pol) {
    const uint32_t bar = sb + S_FULL + 8 * (n & 7);
    mbar_expect(bar, 4096);
    tma2d(sb + (n & 7) * SLOT, &M.k, 0, key0 + (n >> 4) * KV_BATCH_KEYS + (n & 7) * 32, bar, pol);
}
__device__ __forceinline__ void load_k_rest(const Maps& M, uint32_t sb, int n, int key0, uint64_t pol) {
    const uint32_t bar = sb + S_FULL + 8 * (n & 7);
    const int key = key0 + (n >> 4) * KV_BATCH_KEYS + (n & 7) * 32;
    mbar_expect(bar, 8192);
    tma2d(sb + (n & 7) * SLOT + 4096, &M.k, 64, key, bar, pol);
    tma2d(sb + (n & 7) * SLOT + 8192, &M.k, 128, key, bar, pol);
}
__device__ __forceinline__ void load_slot(const Maps& M, uint32_t sb, int n, int key0, uint64_t pol, bool head = true) {
    if (n & 8) {
        const uint32_t bar = sb + S_FULL + 8 * (n & 15);
        mbar_expect(bar, SLOT);
        tma2d(sb + (n & 15) * SLOT, &M.v, 0, 3 * (key0 + (n >> 4) * KV_BATCH_KEYS + (n & 7) * 32), bar, pol);
    } else {
        if (head) load_k_head(M, sb, n, key0, pol);
        load_k_rest(M, sb, n, key0, pol);
    }
}
__device__ __forceinline__ int first_key() { return (blockIdx.x >> 2) * 4096 + 3072 + (blockIdx.x & 3) * 256; }

__device__ __forceinline__ void stream_warp(const Params& P, const Maps& M, uint32_t sb) {
    uint64_t pol;
    asm volatile("createpolicy.fractional.L2::evict_first.b64 %0, 1.0;" : "=l"(pol));
    const int bid = blockIdx.x, g = bid >> 3, i = bid & 7;
    const uint32_t wf = sb + S_WFULL;
#pragma unroll
    for (int k = 0; k < 10; k++) {
        if (k >= WIN_W) mbar_wait(wf + 8 * (k - WIN_W), 0);
        mbar_expect(wf + 8 * k, 15360);
        if (k < 4) tma2d(sb + ST_WQ + 15360 * k, &M.wq, 384 * g + 192 * (k >> 1), 80 * i + 40 * (k & 1), wf + 8 * k, pol);
        else if (k < 6) tma2d(sb + ST_WG + 15360 * (k - 4), k == 4 ? &M.wg : &M.wu, 96 * g, 80 * i, wf + 8 * k, pol);
        else tma2d(sb + ST_WO + 15360 * (k - 6), &M.wo, 80 * i, 384 * g + 96 * (k - 6), wf + 8 * k, pol);
    }
    const int key0 = first_key();
    uint32_t q0, q1, q2, q3;
    auto wait_q = [](uint32_t q) { mbar_wait(q & ~1u, q & 1); };
#pragma unroll 1
    for (int n = 0; n < 16; n++) {
        if (n == 0 || n == 5 || n == 11) mbar_wait(sb + S_RELW + (n == 0 ? 0 : n == 5 ? 8 : 16), 0);
        mbar_wait(n < WIN_FIRST ? wf + 8 * (10 - WIN_FIRST + n) : sb + S_FULL + 8 * (n - WIN_FIRST), 0);

        load_slot(M, sb, n, key0, pol);
    }
    q3 = sb + S_FULL + 8 * 13; q2 = q3 + 8; q1 = q3 + 16; q0 = wf + 80;
    mbar_wait(sb + S_FULL + 8 * WD_AFTER, 0);
    mbar_expect(wf + 80, 15360); tma2d(sb + S_WD, &M.wd, 80 * i, 96 * g, wf + 80, pol);
    uint32_t dm = 0;
    int nd = 0, rel = 0;
#pragma unroll 1
    for (int n = 16; n < 64; n++) {
        if (n == 32) dm = 0;
        see_release(sb, rel);
        { int k = 0; while (((n - MAXLEAD) >> 3) - 2 >= rel && ++k < SPIN_LIMIT) see_release(sb, rel); }
        const char* src = (const char*)((n & 8) ? P.v : P.k) + (size_t)(key0 + (n >> 4) * KV_BATCH_KEYS + (n & 7) * 32) * 384;
        const uint32_t dbar = sb + S_DBAR + 8 * (nd & 3);
        wait_q(q3);
        if ((n >> 3) - 2 >= rel) {
            if (WIN_GAP < 4) wait_q(q2);
            if (WIN_GAP < 3) wait_q(q1);
            if (WIN_GAP < 2) wait_q(q0);
            see_release(sb, rel);
        } else if (WIN_FREE < 4) wait_q(q2);
        if ((n & 8) && (n >> 3) - 2 == rel) {
            if (NPF > 0) asm volatile("cp.async.bulk.prefetch.L2.global [%0], %1;" :: "l"(src), "r"(min(NPF, 16 - (n & 15)) * SLOT) : "memory");
            int k = 0;
            while ((n >> 3) - 2 == rel && ++k < SPIN_LIMIT) see_release(sb, rel);
        }
        q3 = q2; q2 = q1; q1 = q0;
        if ((n >> 3) - 2 < rel) {
            load_slot(M, sb, n, key0, pol);
            q0 = (sb + S_FULL + 8 * (n & 15)) | ((n >> 4) & 1);
        } else {
            mbar_expect(dbar, SLOT);
#pragma unroll
            for (int q = 0; q < SLOT / DPIECE; q++)
                asm volatile("cp.async.bulk.shared::cluster.global.mbarrier::complete_tx::bytes [%0], [%1], %2, [%3];"
                             :: "r"(sb + S_DUMMY), "l"(src + q * DPIECE), "n"(DPIECE), "r"(dbar) : "memory");
            q0 = dbar | ((nd >> 2) & 1);
            nd++;
            dm |= 1u << (n & 31);
            stsvol(sb + S_DM + 4 * (n >> 5), dm);
        }
        stsvol(sb + S_SP, n + 1);
    }
    wait_q(q3); wait_q(q2); wait_q(q1); wait_q(q0);
}

__device__ __forceinline__ void land_warp(const Maps& M, uint32_t sb, int lane) {
    uint64_t pol;
    asm volatile("createpolicy.fractional.L2::evict_first.b64 %0, 1.0;" : "=l"(pol));
#pragma unroll 1
    for (int m = 16 + lane; m < 64 + lane; m += 8) {
        const uint32_t vk = __shfl_sync(~0u, m, 0) & 8;
        mbar_wait(sb + S_RELK + vk, ((m - lane - 16) >> 4) & 1);
        uint32_t todo = lane < 8 ? (vk ? 1 : ldsvol(sb + S_SELF + 4 * lane) ^ 1) : 0;
        int k = 0;
        while (__any_sync(~0u, todo) && ++k < SPIN_LIMIT) {
            const int sp = ldsvol(sb + S_SP);
            const uint32_t dm = ldsvol(sb + S_DM + 4 * ((m >> 5) & 1));
            const bool go = todo && m < sp && (mbar_test(sb + S_FULL + 8 * ((m - WIN_LAND) & 15), ((m - WIN_LAND) >> 4) & 1));
            if (go && ((dm >> (m & 31)) & 1)) {
                uint32_t mm = m;
                opaque(mm);
                load_slot(M, sb, mm, first_key(), pol, todo == 1);
            }
            if (go) todo = 0;
            __syncwarp();
        }
    }
}

__device__ __forceinline__ char* xwindow() { return reinterpret_cast<char*>((reinterpret_cast<uintptr_t>(g_x) + (2u << 20) - 1) & ~(uintptr_t)((2u << 20) - 1)); }

__device__ __forceinline__ void side_warp(uint32_t sb) {
    const uint32_t bid = blockIdx.x, g = bid >> 3, i = bid & 7, P = pairG(0, 0, i);
    char* p = xwindow() + P * 8192 + (g >> 3) * HALF + (g & 7) * 512 + 448;
    uint32_t best[2] = {~0u, ~0u};
    asm volatile("st.relaxed.gpu.global.b32 [%0], 1;" :: "l"(p) : "memory");
    asm volatile("st.relaxed.gpu.global.b32 [%0], 1;" :: "l"(p + COPY) : "memory");
#pragma unroll 1
    for (int r = 0; r < 64; r++) {
        if (r >= 4 && !(r & 1) && min(best[0], best[1]) < 380 && max(best[0], best[1]) > min(best[0], best[1]) + 80) break;
        uint32_t c0, c1, v;
        asm volatile("mov.u32 %0, %clock;" : "=r"(c0) :: "memory");
        asm volatile("atom.relaxed.gpu.global.exch.b32 %0, [%1], 0;" : "=r"(v) : "l"(p + (r & 1) * COPY) : "memory");
        asm volatile("{\n .reg .pred q;\n setp.eq.u32 q, %1, 0x13579bdf;\n mov.u32 %0, 0;\n @!q mov.u32 %0, %clock;\n}" : "=r"(c1) : "r"(v) : "memory");
        if (r & 1) best[1] = min(best[1], c1 - c0); else best[0] = min(best[0], c1 - c0);
    }
    stsvol(sb + S_SIDE, 1 + ((best[1] < best[0]) ^ (__popc(P & PMASK) & 1)));
}

__device__ __forceinline__ void hop_a(const char* src, const char* ssrc, uint32_t par, uint32_t dst, bool st, int k) {
    uint2 v[8];
    int guard = 0;
    poll_delay<DELAY_L>();
    do {
#pragma unroll
        for (int s = 0; s < 4; s++) v[4 + s] = ldp64(ssrc + s * 1024);
#pragma unroll
        for (int s = 0; s < 4; s++) v[s] = ldp64(src + s * 1024);
    } while ((chk8(v, par) & 1) && ++guard < SPIN_LIMIT);
    const float m0 = asf(v[4].x) * LOG2E, m1 = asf(v[5].x) * LOG2E, m2 = asf(v[6].x) * LOG2E, m3 = asf(v[7].x) * LOG2E;
    const float M = fmaxf(fmaxf(m0, m1), fmaxf(m2, m3));
    const float e0 = ex2(m0 - M), e1 = ex2(m1 - M), e2 = ex2(m2 - M), e3 = ex2(m3 - M);
    const float rl = rcp(fmaf(e0, asf(v[4].y), e1 * asf(v[5].y)) + fmaf(e2, asf(v[6].y), e3 * asf(v[7].y)));
    const float o0 = fmaf(e0, asf(v[0].x), e1 * asf(v[1].x)) + fmaf(e2, asf(v[2].x), e3 * asf(v[3].x));
    const float o1 = fmaf(e0, asf(v[0].y), e1 * asf(v[1].y)) + fmaf(e2, asf(v[2].y), e3 * asf(v[3].y));
    sts32_if(st, dst, pack2(o0 * rl, o1 * rl));
    SWEEPS(k, guard);
    __syncwarp();
}

__global__ void __launch_bounds__(NTHR, 1)
fused_kernel(const Params P, const __grid_constant__ Maps M) {
    extern __shared__ __align__(1024) unsigned char smem[];
    const uint32_t sb = smem_u32(smem);
    const int tid = threadIdx.x, bid = blockIdx.x;
    const int w = tid >> 5, lane = tid & 31;
    constexpr int NB2 = 384;

    if (w >= 8) {
        asm volatile("setmaxnreg.dec.sync.aligned.u32 " REG_LO ";");
        if (w == 8) {
            if (lane < 16) mbar_init(sb + S_FULL + 8 * lane, lane < 8 ? 2 : 1);
            else mbar_init(sb + S_FULL + 8 * lane, lane < 21 ? 8 : 1);
            if (lane < 4) mbar_init(sb + S_FULL + 256 + 8 * lane, 1);
            if (lane == 31) { stsvol(sb + S_SP, 0); stsvol(sb + S_SIDE, 0); stsvol(sb + S_DM, 0); stsvol(sb + S_DM + 4, 0); stsvol(sb + S_GATE, 0); }
            asm volatile("fence.mbarrier_init.release.cluster;" ::: "memory");
            asm volatile("fence.proxy.async.shared::cta;" ::: "memory");
            asm volatile("bar.arrive 2, %0;" :: "n"(NB2) : "memory");
            __syncwarp();
            if (lane == 0) stream_warp(P, M, sb);
        } else asm volatile("bar.sync 2, %0;" :: "n"(NB2) : "memory");
        if (w == 8) {
        } else if (w != 10) {
            if (w == 9) land_warp(M, sb, lane);
            else {
                if (lane == 0) side_warp(sb);
                { int k = 0; while (ldsvol(sb + S_GATE) == 0 && ++k < SPIN_LIMIT) __nanosleep(256); }
                uint4* d = reinterpret_cast<uint4*>(reinterpret_cast<char*>(g_s) + XS + bid * 7680) + lane;
                const uint4 z = make_uint4(0, 0, 0, 0);
#pragma unroll 1
                for (int u = 0; u < 15; u++) d[32 * u] = z;
                d = reinterpret_cast<uint4*>(reinterpret_cast<char*>(g_s) + XS2 + bid * 768) + lane;
                d[0] = z;
                if (lane < 16) d[32] = z;
            }
        }
        else if (bid < KEEPWARM) {
            int k = 0;
            uint32_t a = 0, b = 0;
            poll_delay<KWSTART>();
            while (ldsvol(sb + S_GATE) < 5 && ++k < 4096) { warm_mma(a, b); poll_delay<KWGAP>(); }
            for (int u = 0; u < KWTAIL; u++) { warm_mma(a, b); poll_delay<KWGAP>(); }
            if (a | b) stsvol(sb + S_GATE, 5);
        }
        return;
    }
    asm volatile("setmaxnreg.inc.sync.aligned.u32 " REG_HI ";");

    const int g = bid >> 3, i = bid & 7;
    const int g8 = lane >> 2, t = lane & 3;
    char* const gs = reinterpret_cast<char*>(g_s);
    char* const gx = xwindow();
    TSTAMP(0);

    uint32_t Wq[3][5][4], Wo[5][3][4], Wgu[2][5][4];
    if (w < 4) {
        const uint32_t* xp = reinterpret_cast<const uint32_t*>(P.x + 640 * w);
        float sum = 0.f, sq = 0.f;
#pragma unroll
        for (int u = 0; u < 10; u++) { uint32_t v = xp[lane + 32 * u]; float a = bf_lo(v), b = bf_hi(v); sum += a + b; sq += a * a + b * b; }
#pragma unroll
        for (int o = 16; o > 0; o >>= 1) { sum += __shfl_xor_sync(~0u, sum, o); sq += __shfl_xor_sync(~0u, sq, o); }
        float mean, den; ln_stats(sum, sq, mean, den);
        if (lane < 20) {
            const uint2 v = reinterpret_cast<const uint2*>(P.x + 640 * w + 80 * i)[lane];
            sts64(sb + S_X0 + 160 * w + 8 * lane, v.x, v.y);
            sts64(sb + S_L0 + 160 * w + 8 * lane, pack2(__fdiv_rn(bfr(bf_lo(v.x) - mean), den), __fdiv_rn(bfr(bf_hi(v.x) - mean), den)),
                                                  pack2(__fdiv_rn(bfr(bf_lo(v.y) - mean), den), __fdiv_rn(bfr(bf_hi(v.y) - mean), den)));
        }
    } else if (w == 4) {
        const uint32_t* xp = reinterpret_cast<const uint32_t*>(P.wr);
        float sum = 0.f;
#pragma unroll
        for (int u = 0; u < 10; u++) { uint32_t v = xp[lane + 32 * u]; sum += bf_lo(v) + bf_hi(v); }
#pragma unroll
        for (int o = 16; o > 0; o >>= 1) sum += __shfl_xor_sync(~0u, sum, o);
        if (lane == 0) stsf(sb + S_SWR, sum);
        if (lane < 20) {
            const uint2 v = reinterpret_cast<const uint2*>(P.wr + 80 * i)[lane];
            sts64(sb + S_XQ + 640 + 16 * lane, v.x, 0); sts64(sb + S_XQ + 640 + 16 * lane + 8, v.y, 0);
            sts64(sb + S_XT + 320 + 8 * lane, ONES, ONES);
            sts32(sb + S_XQ + 16 * lane, ONES); sts32(sb + S_XQ + 16 * lane + 8, ONES);
            sts32(sb + S_XQ + 320 + 16 * lane, ONES); sts32(sb + S_XQ + 320 + 16 * lane + 8, ONES);
        }
    }
    asm volatile("bar.sync 2, %0;" :: "n"(NB2) : "memory");
    auto frag = [](uint32_t (&a)[4], uint32_t p, int pitch) {
        const uint32_t r0 = lds32(p), r1 = lds32(p + pitch), r2 = lds32(p + 2 * pitch), r3 = lds32(p + 3 * pitch);
        a[0] = __byte_perm(r0, r1, 0x5410); a[1] = __byte_perm(r0, r1, 0x7632);
        a[2] = __byte_perm(r2, r3, 0x5410); a[3] = __byte_perm(r2, r3, 0x7632);
    };
    mbar_wait(sb + S_WFULL + 16 * (w >> 2), 0);
    mbar_wait(sb + S_WFULL + 16 * (w >> 2) + 8, 0);
    {
        const uint32_t p = sb + ST_WQ + (w >> 2) * 30720 + (20 * t) * 384 + (48 * (w & 3) + 2 * g8) * 2;
#pragma unroll
        for (int s = 0; s < 5; s++)
#pragma unroll
            for (int m = 0; m < 3; m++) frag(Wq[m][s], p + 4 * s * 384 + 32 * m, 384);
    }
    __syncwarp();
    if (lane == 0) mbar_arrive(sb + S_RELW);
    TSTAMP(1);
    {
        float acc[3][4] = {};
#pragma unroll
        for (int s = 0; s < 5; s++) {
            const uint2 b = lds64(sb + (g8 < 4 ? S_L0 + 160 * g8 : S_XT + 320) + 8 * (5 * t + s));
#pragma unroll
            for (int m = 0; m < 3; m++) mmaA(acc[m], Wq[m][s], b.x, b.y);
        }
        if (t < 3) {
            char* d = gs + XS + bid * 7680 + (w >> 2) * 3840 + 2 * t * 768 + (48 * (w & 3) + 2 * g8) * 4;
#pragma unroll
            for (int m = 0; m < 3; m++) {
                stp32(d + 64 * m, acc[m][0], 1); stp32(d + 64 * m + 4, acc[m][2], 1);
                if (t < 2) { stp32(d + 768 + 64 * m, acc[m][1], 1); stp32(d + 768 + 64 * m + 4, acc[m][3], 1); }
            }
        }
    }
    mbar_wait(sb + S_WFULL + 32, 0);
    mbar_wait(sb + S_WFULL + 40, 0);
    {
        const uint32_t p = sb + ST_WG + ((20 * t) * 96 + 16 * min(w, 5) + g8) * 2;
        float acc[2][4] = {};
#pragma unroll
        for (int s = 0; s < 5; s++)
#pragma unroll
            for (int T = 0; T < 2; T++) {
                const uint32_t q = p + 4 * s * 192 + 16 * T;
                Wgu[T][s][0] = __byte_perm(lds16(q), lds16(q + 192), 0x5410);
                Wgu[T][s][1] = __byte_perm(lds16(q + 15360), lds16(q + 15360 + 192), 0x5410);
                Wgu[T][s][2] = __byte_perm(lds16(q + 384), lds16(q + 576), 0x5410);
                Wgu[T][s][3] = __byte_perm(lds16(q + 15360 + 384), lds16(q + 15360 + 576), 0x5410);
                mmaA(acc[T], Wgu[T][s], ONES, ONES);
            }
        if (w < 6 && t < 2) {
            char* d = gs + XS2 + bid * 768 + (16 * w + 8 * t + g8) * 8;
            stp32(d, t ? acc[1][0] : acc[0][0], 1);
            stp32(d + 4, t ? acc[1][2] : acc[0][2], 1);
        }
    }
    __syncwarp();
    if (lane == 0) mbar_arrive(sb + S_RELW + 8);
    const char* srcS = gs + XS + g * 8 * 7680 + (i >> 2) * 3840 + min(tid, 191) * 4;
    uint32_t vs[5][8];
#pragma unroll
    for (int b = 0; b < 5; b++)
#pragma unroll
        for (int s = 0; s < 8; s++) vs[b][s] = ldp32(srcS + b * 768 + s * 7680);
    uint32_t cs2[8];
#pragma unroll
    for (int s = 0; s < 8; s++) cs2[s] = ldp32(gs + XS2 + (g * 8 + s) * 768 + min(tid, 191) * 4);
    __syncwarp();
    mbar_wait(sb + S_WFULL + 48 + 8 * (w >> 1), 0);
    {
        const uint32_t po = sb + ST_WO + (48 * w + 12 * t) * 160 + 4 * g8;
#pragma unroll
        for (int s = 0; s < 3; s++)
#pragma unroll
            for (int m = 0; m < 5; m++) frag(Wo[m][s], po + 4 * s * 160 + 32 * m, 160);
    }
    __syncwarp();
    if (lane == 0) mbar_arrive(sb + S_RELW + 16);
    {
        const uint4 z = make_uint4(0, 0, 0, 0);
        const uint32_t c = (tid >> 6) & 1, cp = (tid >> 7) * COPY, k = (tid & 63) * 16;
        *reinterpret_cast<uint4*>(gx + pairL(RA, c, g) * 8192 + (i >> 2) * HALF + (i & 3) * 1024 + cp + k) = z;
        *reinterpret_cast<uint4*>(gx + pairL(RC, c, g) * 8192 + (i >> 2) * HALF + (i & 3) * 1024 + cp + k) = z;
        *reinterpret_cast<uint4*>(gx + pairL(RE, c, g) * 8192 + (i >> 2) * HALF + (i & 3) * 1024 + cp + k) = z;
        if ((tid & 31) < 24) *reinterpret_cast<uint4*>(gx + pairG((tid >> 5) & 1, c, i) * 8192 + (g >> 3) * HALF + (g & 7) * 512 + cp + (tid & 31) * 16) = z;
    }
    if (tid < 192) {
        int guard = 0;
        while (((or3(chk8(vs[0], 1), chk8(vs[1], 1), chk8(vs[2], 1)) | chk8(vs[3], 1) | chk8(vs[4], 1)) & 1) && ++guard < SPIN_LIMIT) {
#pragma unroll
            for (int b = 0; b < 5; b++)
#pragma unroll
                for (int s = 0; s < 8; s++) vs[b][s] = ldp32(srcS + b * 768 + s * 7680);
        }
        const uint32_t qpos = sb + S_QS + (tid >> 4) * 32 + ((tid & 7) >> 1) * 8 + ((tid >> 3) & 1) * 4 + (tid & 1) * 2;
#pragma unroll
        for (int b = 0; b < 4; b++) {
            sts_hi16(qpos + 384 * b, bfr(sum8(vs[b])));
        }
        stsf(sb + S_CSQ + 4 * tid, sum8(vs[4]));
    }
    if (tid < 192) stsf(sb + S_CSGU + 4 * tid, (chk8(cs2, 1) & 1) ? gather8<768>(gs + XS2 + g * 8 * 768 + tid * 4, 1) : sum8(cs2));
    bar_main();
    TSTAMP(2);

    uint32_t side;
    { int k = 0; while ((side = ldsvol(sb + S_SIDE)) == 0 && ++k < SPIN_LIMIT) {} }
    side = __shfl_sync(~0u, side & 1, 0) ^ 1;
    auto nearp = [&](uint32_t P) { return P * 8192 + ((side ^ __popc(P & PMASK)) & 1) * COPY; };
    const uint32_t td = __shfl_sync(~0u, tid, lane);
    const uint32_t wp = __shfl_sync(~0u, tid >> 5, 0);
    const uint32_t cc = wp >= 3;
#define IDS() uint32_t z_ = td; opaque(z_); const uint32_t ln = z_ & 31, q8 = ln >> 2, t4 = z_ & 3, n96 = z_ - 96 * cc, n80 = min(n96, 79u); (void)q8; (void)t4; (void)n80; (void)ln

    auto scores = [&](int b, auto pre, auto mid) {
        float s_own;
        {
            IDS();
            const uint32_t ka = sb + wp * SLOT + (ln & 15) * 128 + (((ln & 7) ^ (ln >> 4)) << 4);
            uint32_t kf[12][2][4];
            auto ldk = [&](int s) { ldsm4(kf[s][0], (ka ^ ((s & 3) * 32)) + (s >> 2) * 4096); ldsm4(kf[s][1], (ka ^ ((s & 3) * 32)) + (s >> 2) * 4096 + 2048); };
            const uint32_t qa = sb + S_QS + 384 * b + 8 * ln;
            pre(ldk, kf);
            const uint2 qlo = lds64(qa), qhi = lds64(qa + 256 - (q8 >= 4 ? 128 : 0));
            float acc[2][4] = {};
            auto qk = [&](int s) {
                const bool m = q8 == (s & 7);
                const uint32_t b0 = m ? (s < 8 ? qlo.x : qhi.x) : 0u, b1 = m ? (s < 8 ? qlo.y : qhi.y) : 0u;
                mmaA(acc[0], kf[s][0], b0, b1);
                mmaA(acc[1], kf[s][1], b0, b1);
            };
            constexpr int D = KPRE + KPRE2, R = 12 - D;
            ldk(D);
#pragma unroll
            for (int j = 0; j < (D > R ? D : R); j++) {
                if (j < D) qk(j);
                if (j + 1 < R) ldk(D + j + 1);
                if (j < R) qk(D + j);
            }
            const float v0 = acc[0][0] + acc[0][1], v1 = acc[0][2] + acc[0][3], v2 = acc[1][0] + acc[1][1], v3 = acc[1][2] + acc[1][3];
            const bool hi = t4 & 2, od = t4 & 1;
            const float u0 = (hi ? v2 : v0) + __shfl_xor_sync(~0u, hi ? v0 : v2, 2), u1 = (hi ? v3 : v1) + __shfl_xor_sync(~0u, hi ? v1 : v3, 2);
            s_own = (od ? u1 : u0) + __shfl_xor_sync(~0u, od ? u0 : u1, 1);
        }
        IDS();
        s_own = bfr(bfr(s_own) * 0.07216878364870322f);
        int key = __float_as_int(s_own);
        key ^= (key >> 31) & 0x7fffffff;
        key = __reduce_max_sync(~0u, key);
        key ^= (key >> 31) & 0x7fffffff;
        sts32_if(ln == 0, sb + S_WMAX + 4 * wp, key);
        mid();
        s_own *= LOG2E;
        bar_main();
        const uint4 m0 = lds128(sb + S_WMAX), m1 = lds128(sb + S_WMAX + 16);
        const float mx = fmaxf(fmaxf(fmaxf(asf(m0.x), asf(m0.y)), fmaxf(asf(m0.z), asf(m0.w))), fmaxf(fmaxf(asf(m1.x), asf(m1.y)), fmaxf(asf(m1.z), asf(m1.w))));
        sts_hi16(sb + S_PS + 64 * wp + (q8 >> 1) * 16 + (t4 & 1) * 8 + (t4 >> 1) * 4 + (q8 & 1) * 2, bfr(ex2(fmaf(mx, -LOG2E, s_own))));
        bar_main();
        return mx;
    };
    auto vaddr = [&](uint32_t (&voff)[3]) {
        IDS();
#pragma unroll
        for (int T = 0; T < 3; T++) {
            const uint32_t u = 3 * wp + T;
            voff[T] = sb + 8 * SLOT + (3 * ln + (u >> 3)) * 128 + (((u ^ (3 * ln + (u >> 3))) & 7) << 4);
        }
    };
    auto values = [&](uint32_t (&vf)[8][3][4], auto ldv, float mx, uint32_t col, uint32_t par) {
        IDS();
        const uint32_t pta = sb + S_PS + 16 * t4;
        float accA[3][4] = {}, accB[3][4] = {};
        uint4 pp[8];
        pp[0] = lds128(pta); pp[1] = lds128(pta + 64);
        const uint4 p = lds128(pta + 64 * q8);
        float lsum = ((bf_lo(p.x) + bf_hi(p.x)) + (bf_lo(p.y) + bf_hi(p.y))) + ((bf_lo(p.z) + bf_hi(p.z)) + (bf_lo(p.w) + bf_hi(p.w)));
#pragma unroll
        for (int s = 0; s < 8; s++) {
            if (s < 5) lsum += __shfl_xor_sync(~0u, lsum, 1 << s);
            if (s + 2 < 8) pp[s + 2] = lds128(pta + 64 * (s + 2));
#pragma unroll
            for (int T = 0; T < 3; T++) { mmaV(accA[T], pp[s], vf[s][T][0], vf[s][T][1]); mmaV(accB[T], pp[s], vf[s][T][2], vf[s][T][3]); }
            if (s < 3) ldv(s + 3);
            if (s == 4 || s == 5) ldv(s + 2);
        }
        char* pubA = gx + pairL(RA, col, g) * 8192 + (i >> 2) * HALF + (i & 3) * 1024 + (wp >> 1) * 256 + (wp & 1) * 96 + 8 * ln;
        const float a = sel4(q8, accA[0][0], accA[1][0], accA[2][0], mx) + sel4(q8, accB[0][2], accB[1][2], accB[2][2], 0.f);
        const float b = sel4(q8, accA[0][1], accA[1][1], accA[2][1], lsum) + sel4(q8, accB[0][3], accB[1][3], accB[2][3], 0.f);
        stp64_if(ln < 12 + (wp & 1), pubA, tagw(a, par), __float_as_uint(b));
    };

#pragma unroll 1
    for (int ch = 0; ch < 5; ch++) {
        const uint32_t par0 = (ch + 1) & 1, par1 = ch & 1;
        uint32_t voff[3], vf[8][3][4];
        CSTAMP(0);
        if (ch < 4) {
            if (ch > 0) {
                IDS();
                const char* polA = gx + nearp(pairL(RA, 1, g)) + (wp >> 2) * HALF + (wp & 3) * 256;
                hop_a(polA + 8 * min(ln, 23u), polA + 192, par1, sb + S_OS + 192 * wp + 4 * ln + 96, ln < 24, 25);
            }
            const float mx1 = scores(ch, [&](auto ldk, auto&) {
                mbar_wait(sb + S_FULL + 8 * wp, par1);
#pragma unroll
                for (int s = 0; s < KPRE + KPRE2; s++) ldk(s);
            }, [] {});
            TSTAMP(4 + 12 * ch);
            vaddr(voff);
            auto ldw = [&](int s) {
                mbar_wait(sb + S_FULL + 64 + 8 * s, par1);
#pragma unroll
                for (int T = 0; T < 3; T++) ldsm4t(vf[s][T], voff[T] + s * SLOT);
            };
            ldw(0); ldw(1); ldw(2);
            values(vf, ldw, mx1, 0, par0);
            TSTAMP(5 + 12 * ch);
            CSTAMP(5);
        }
        uint32_t oa, ra;
        {
            IDS();
            const uint32_t c = ch == 4;
            const char* polA = gx + nearp(pairL(RA, c, g)) + (wp >> 2) * HALF + (wp & 3) * 256;
            uint32_t osa = sb + S_OS + 192 * wp + 96 * c + 4 * ln;
            oa = sb + S_OS + 192 * wp + 96 * (q8 & 1) + 24 * t4; ra = sb + S_RED + 640 * wp + 320 * (t4 & 1) + 8 * q8;
            keep(osa); keep(oa); keep(ra);
            hop_a(polA + 8 * min(ln, 23u), polA + 192, c ? par1 : par0, osa, ln < 24, 5 * ch);
        }

        const bool has0 = ch < 4, has1 = ch > 0;
        const bool actc = wp < 6 && (cc ? has1 : has0);
        const uint32_t parc = cc ? par1 : par0;
        TSTAMP(6 + 12 * ch);
        CSTAMP(6);
        char* pubB;
        uint32_t rr;
        {
            IDS();
            pubB = gx + pairG(0, cc, i) * 8192 + (g >> 3) * HALF + (g & 7) * 512 + n80 * 4;
            rr = sb + S_RED + 320 * cc + 4 * n80;
            float acc[5][4] = {};
            const uint2 b0 = lds64(oa), b1 = lds64(oa + 8), b2 = lds64(oa + 16);
            keep(pubB); keep(rr);
#pragma unroll
            for (int m = 0; m < 5; m++) mmaA(acc[m], Wo[m][0], b0.x, b0.y);
#pragma unroll
            for (int m = 0; m < 5; m++) mmaA(acc[m], Wo[m][1], b1.x, b1.y);
#pragma unroll
            for (int m = 0; m < 5; m++) mmaA(acc[m], Wo[m][2], b2.x, b2.y);
#pragma unroll
            for (int m = 0; m < 5; m++) sts64_if(t4 < 2, ra + 64 * m, t4 ? acc[m][1] : acc[m][0], t4 ? acc[m][3] : acc[m][2]);
        }
        CSTAMP(7);
        bar_main();
        CSTAMP(8);
        float x1 = 0.f;
        uint32_t xtr, xqr;
        char* pubC;
        {
            IDS();
            if (actc) {
                uint32_t r[8];
#pragma unroll
                for (int s = 0; s < 8; s++) r[s] = lds32(rr + 640 * s);
                stp32_if(n96 < 80, pubB, sum8(r), parc);
                CSTAMP(9);
            }
            xtr = sb + S_XT + 160 * (q8 & 1) + 40 * t4; xqr = sb + S_XQ + 320 * min(q8, 2u) + 80 * t4;
            pubC = gx + pairL(RC, 0, g) * 8192 + (i >> 2) * HALF + (i & 3) * 1024 +
                   (wp < 6 ? (t4 & 1) * (32 * 8192) + (16 * wp + 8 * (t4 >> 1) + q8) * 8 : q8 < 2 ? q8 * (32 * 8192) + 768 : (t4 & 1) * (32 * 8192) + 776);
            keep(xtr); keep(xqr); keep(pubC);
            if (actc) {
                const char* polB = gx + nearp(pairG(0, cc, i)) + n80 * 4;
                uint32_t xqs = sb + S_XQ + 320 * cc + (n80 >> 2) * 16 + (n80 & 2) * 4 + 4 + (n80 & 1) * 2, xts = sb + S_XT + 160 * cc + 2 * n80;
                x1 = cc ? ldsf(sb + S_XCAR + 4 * n80) : bf_lo(lds16(sb + S_X0 + 160 * (ch & 3) + 2 * n80));
                keep(xqs); keep(xts); keep(x1);
                x1 = bfr(x1 + bfr(gather16(polB, parc, 5 * ch + 1)));
                CSTAMP(10);
                sts_hi16_if(n96 < 80, xts, x1);
                sts_hi16_if(n96 < 80, xqs, x1);
            }
        }
        bar_main();
        sts32_if(td == 255, sb + S_GATE, ch + 1);
        TSTAMP(7 + 12 * ch);
        CSTAMP(11);
        {
            IDS();
            uint2 b[5];
#pragma unroll
            for (int s = 0; s < 5; s++) b[s] = lds64(xtr + 8 * s);
            if (wp < 6) {
                float acc[2][2][4] = {};
#pragma unroll
                for (int s = 0; s < 5; s++) { mmaA(acc[0][s & 1], Wgu[0][s], b[s].x, b[s].y); mmaA(acc[1][s & 1], Wgu[1][s], b[s].x, b[s].y); }
                const float v0 = sel4(t4, acc[0][0][0], acc[0][0][1], acc[1][0][0], acc[1][0][1]) + sel4(t4, acc[0][1][0], acc[0][1][1], acc[1][1][0], acc[1][1][1]);
                const float v1 = sel4(t4, acc[0][0][2], acc[0][0][3], acc[1][0][2], acc[1][0][3]) + sel4(t4, acc[0][1][2], acc[0][1][3], acc[1][1][2], acc[1][1][3]);
                stp64_if((t4 & 1) ? has1 : has0, pubC, tagw(v0, (t4 & 1) ? par1 : par0), __float_as_uint(v1));
            } else if (wp == 6) {
                float a0[4] = {}, a1[4] = {};
                uint4 a[5];
#pragma unroll
                for (int s = 0; s < 5; s++) a[s] = lds128(xqr + 16 * s);
#pragma unroll
                for (int s = 0; s < 5; s++) mmaV((s & 1) ? a1 : a0, a[s], b[s].x, b[s].y);
                const uint32_t c = q8 < 2 ? q8 : (t4 & 1);
                stp64_if((c ? has1 : has0) && (q8 < 2 ? t4 == 0 : (q8 == 2 && t4 < 2)), pubC,
                         tagw(c ? a0[1] + a1[1] : a0[0] + a1[0], c ? par1 : par0), __float_as_uint(c ? a0[3] + a1[3] : a0[2] + a1[2]));
            }
        }
        CSTAMP(12);
        uint32_t Wd[6][4];
        uint32_t ha = 0;
        char* pubD = nullptr;
        if (wp < 6) {
            IDS();
            uint32_t wa = sb + S_WD + ((ln & 7) + 8 * (ln >> 4)) * 160 + (2 * min(wp, 4u) + ((ln >> 3) & 1)) * 16;
            ha = sb + S_HS + 192 * (q8 & 1) + 48 * t4;
            pubD = gx + pairG(1, t4 & 1, i) * 8192 + (g >> 3) * HALF + (g & 7) * 512 + (16 * wp + 8 * (t4 >> 1) + q8) * 4;
            uint32_t hsa = sb + S_HS + 192 * cc + ((n96 & 7) >> 1) * 48 + (n96 >> 4) * 8 + ((n96 >> 3) & 1) * 4 + (n96 & 1) * 2;
            keep(wa); keep(ha); keep(pubD); keep(hsa);
            float sx = 0.f, sq = 1.f, pg = 0.f, pu = 0.f;
            const uint2 cs = lds64(sb + S_CSGU + 8 * n96);
            if (actc) {
                const char* src = gx + nearp(pairL(RC, cc, g));
                const char* srcv = src + 8 * n96;
                uint2 v[8], st[8];
                int guard = 0;
                poll_delay<DELAY_L>();
                do {
#pragma unroll
                    for (int s = 0; s < 8; s++) st[s] = ldp64(src + 768 + (s >> 2) * HALF + (s & 3) * 1024);
#pragma unroll
                    for (int s = 0; s < 8; s++) v[s] = ldp64(srcv + (s >> 2) * HALF + (s & 3) * 1024);
                } while (((chk8(v, parc) | chk8(st, parc)) & 1) && ++guard < SPIN_LIMIT);
                CSTAMP(13);
                SWEEPS(5 * ch + 2, guard);
                sx = sum8x(st); sq = sum8y(st); pg = sum8x(v); pu = sum8y(v);
            }
            __syncwarp();
            if (ch == 0) mbar_wait(sb + S_WFULL + 80, 0);
#pragma unroll
            for (int s = 0; s < 6; s++) ldsm4t(Wd[s], wa + s * 2560);
            float mean, den; ln_stats(sx, sq, mean, den);
            const float rd = rcp(den);
            const float gt = bfr(fmaf(-mean, asf(cs.x), pg) * rd), up = bfr(fmaf(-mean, asf(cs.y), pu) * rd);
            const float h = bfr(bfr(gt * sigmoidf_(gt)) * up);
            sts_hi16(hsa, h);
            CSTAMP(14);
        } else {
#pragma unroll
            for (int s = 0; s < 6; s++) { Wd[s][0] = Wd[s][1] = Wd[s][2] = Wd[s][3] = 0; opaque(Wd[s][0]); opaque(Wd[s][1]); opaque(Wd[s][2]); opaque(Wd[s][3]); }
            if (wp == 6 ? has0 : has1) {
                IDS();
                const uint32_t par = wp == 6 ? par0 : par1;
                const char* src = gx + nearp(pairL(RC, wp - 6, g)) + 768;
                const float swr = ldsf(sb + S_SWR);
                uint2 v[8], st[8];
                int guard = 0;
                do {
#pragma unroll
                    for (int s = 0; s < 8; s++) { st[s] = ldp64(src + (s >> 2) * HALF + (s & 3) * 1024); v[s] = ldp64(src + 8 + (s >> 2) * HALF + (s & 3) * 1024); }
                } while (((chk8(v, par) | chk8(st, par)) & 1) && ++guard < SPIN_LIMIT);
                float mean, den; ln_stats(sum8x(st), sum8y(st), mean, den);
                const float r = bfr(fmaf(-mean, swr, sum8x(v)) * rcp(den));
                sts64_if(ln == 0, sb + S_STAT + 16 * (wp - 6), mean, den);
                sts32_if(ln == 0, sb + S_STAT + 16 * (wp - 6) + 8, __float_as_uint(bfr(sigmoidf_(r))));
            }
        }
        bar_main();
        TSTAMP(8 + 12 * ch);
        CSTAMP(15);
        if (wp < 5) {
            IDS();
            float a0[4] = {}, a1[4] = {}, a2[4] = {};
            const uint4 h0 = lds128(ha), h1 = lds128(ha + 16), h2 = lds128(ha + 32);
            mmaA(a0, Wd[0], h0.x, h0.y); mmaA(a1, Wd[2], h1.x, h1.y); mmaA(a2, Wd[4], h2.x, h2.y);
            mmaA(a0, Wd[1], h0.z, h0.w); mmaA(a1, Wd[3], h1.z, h1.w); mmaA(a2, Wd[5], h2.z, h2.w);
            stp32_if((t4 & 1) ? has1 : has0, pubD, (sel4(t4, a0[0], a0[1], a0[2], a0[3]) + sel4(t4, a1[0], a1[1], a1[2], a1[3])) + sel4(t4, a2[0], a2[1], a2[2], a2[3]),
                     (t4 & 1) ? par1 : par0);
        }
        CSTAMP(16);
        char* pubE;
        {
            IDS();
            pubE = gx + pairL(RE, 0, g) * 8192 + (i >> 2) * HALF + (i & 3) * 1024 +
                   (t4 < 3 ? (wp >> 2) * (32 * 8192) + 192 * (wp & 3) + 64 * t4 + 8 * q8 : (q8 & 1) * (32 * 8192) + 768);
            xtr = sb + S_XT + 40 * t4; xqr = sb + S_XQ + 80 * t4;
            keep(xtr); keep(xqr); keep(pubE);
            if (actc && (cc == 0 || g == 0)) {
                const char* polD = gx + nearp(pairG(1, cc, i)) + n80 * 4;
                const uint4 st = lds128(sb + S_STAT + 16 * cc);
                float lnx = bfr(__fdiv_rn(bfr(x1 - asf(st.x)), asf(st.y)));
                unsigned short* po = reinterpret_cast<unsigned short*>(P.out) + 640 * (ch - 1) + 80 * i + n80;
                uint32_t xqs = sb + S_XQ + (n80 >> 2) * 16 + (n80 & 2) * 4 + 4 + (n80 & 1) * 2, xts = sb + S_XT + 2 * n80, xca = sb + S_XCAR + 4 * n80;
                keep(lnx); keep(po); keep(xca); keep(xqs); keep(xts);
                const float y = bfr(bfr(gather16(polD, parc, 5 * ch + 3)) * asf(st.z));
                CSTAMP(17);
                const float x2 = bfr(x1 + bfr(lnx + y));
                if (cc) { if (n96 < 80) *po = (unsigned short)(__float_as_uint(x2) >> 16); }
                else {
                    sts_hi16_if(n96 < 80, xts, x2);
                    sts_hi16_if(n96 < 80, xqs, x2);
                    sts32_if(n96 < 80, xca, __float_as_uint(x2));
                }
            }
        }
        CSTAMP(18);
        if (!has0) break;
        bar_main();
        TSTAMP(9 + 12 * ch);
        CSTAMP(19);
        {
            IDS();
            float acc[4][4] = {};
            uint2 b[5];
#pragma unroll
            for (int s = 0; s < 5; s++) b[s] = lds64(xtr + 8 * s);
            if (wp == 7) {
#pragma unroll
                for (int s = 0; s < 5; s++) mmaV(acc[3], lds128(xqr + 16 * s), b[s].x, b[s].y);
            }
#pragma unroll
            for (int s = 0; s < 5; s++)
#pragma unroll
                for (int m = 0; m < 3; m++) mmaA(acc[m], Wq[m][s], b[s].x, b[s].y);
            const float v0 = sel4(t4, acc[0][0], acc[1][0], acc[2][0], acc[3][0]), v1 = sel4(t4, acc[0][2], acc[1][2], acc[2][2], acc[3][2]);
            stp64_if(t4 < 3 || (wp == 7 && q8 < 2), pubE, tagw(v0, par0), tagw(v1, par0));
        }
        CSTAMP(20);
        auto ldv = [&](int s) {
#pragma unroll
            for (int T = 0; T < 3; T++) ldsm4t(vf[s][T], voff[T] + s * SLOT);
        };
        const float mx2 = scores(ch, [&](auto ldk, auto& kf) {
#pragma unroll
            for (int s = 0; s < KPRE; s++) ldk(s);
            static_assert(KPRE >= 4, "the first K tile is released before q is known");
            const int m = 16 * ch + 16 + wp;
            const int sp = ldsvol(sb + S_SP);
            const uint32_t me = EARLY && m < sp && ((ldsvol(sb + S_DM + 4 * ((m >> 5) & 1)) >> (m & 31)) & 1);
            sts32_if((td & 31) == 0, sb + S_SELF + 4 * wp, 2 * me);
            auto head = [&] {
                if ((td & 31) == 0 && me) {
                    uint64_t pol;
                    asm volatile("createpolicy.fractional.L2::evict_first.b64 %0, 1.0;" : "=l"(pol));
                    const uint32_t dep = ((kf[0][0][0] | kf[0][1][0] | kf[1][0][0]) | (kf[1][1][0] | kf[2][0][0] | kf[2][1][0]) | kf[3][0][0] | kf[3][1][0]) & (sp >> 8);
                    load_k_head(M, sb, m, first_key() + dep, pol);
                }
                __syncwarp();
            };
            if (EARLY == 1) head();
            if (wp < 6) {
                const char* src = gx + nearp(pairL(RE, i >> 2, g));
                const char* srcv = src + 4 * td;
                const float cs = ldsf(sb + S_CSQ + 4 * td);
                uint32_t v[8]; uint2 st[8];
                int guard = 0;
                poll_delay<DELAY_E>();
                do {
#pragma unroll
                    for (int s = 0; s < 8; s++) st[s] = ldp64(src + 768 + (s >> 2) * HALF + (s & 3) * 1024);
#pragma unroll
                    for (int s = 0; s < 8; s++) v[s] = ldp32(srcv + (s >> 2) * HALF + (s & 3) * 1024);
                } while (((chk8(v, par0) | chk8(st, par0)) & 1) && ++guard < SPIN_LIMIT);
                CSTAMP(21);
                float mean, den; ln_stats(sum8x(st), sum8y(st), mean, den);
                const float q = bfr(fmaf(-mean, cs, sum8(v)) * rcp(den));
                sts_hi16(sb + S_QS + 384 * ch + (td >> 4) * 32 + ((td & 7) >> 1) * 8 + ((td >> 3) & 1) * 4 + (td & 1) * 2, q);
                SWEEPS(5 * ch + 4, guard);
                CSTAMP(22);
            }
            __syncwarp();
#pragma unroll
            for (int s = KPRE; s < KPRE + KPRE2; s++) ldk(s);
            if (EARLY == 2) head();
            bar_main();
            if (EARLY == 3) head();
            TSTAMP(10 + 12 * ch);
            CSTAMP(1);
        }, [&] {
            CSTAMP(2);
            if ((td & 31) == 0 && wp < NSELF && ldsvol(sb + S_SELF + 4 * wp)) {
                uint64_t pol;
                asm volatile("createpolicy.fractional.L2::evict_first.b64 %0, 1.0;" : "=l"(pol));
                load_k_rest(M, sb, 16 * ch + 16 + wp, first_key(), pol);
                stsvol(sb + S_SELF + 4 * wp, 1);
            }
            __syncwarp();
            arrive_if((td & 31) == 0, sb + S_RELK);
            vaddr(voff);
            ldv(0); ldv(1); ldv(2);
        });
        TSTAMP(14 + 12 * ch);
        CSTAMP(4);
        values(vf, ldv, mx2, 1, par0);
        __syncwarp();
        arrive_if((td & 31) == 0, sb + S_RELV);
        TSTAMP(15 + 12 * ch);
        CSTAMP(23);
    }
    TSTAMP(3);
}

typedef CUresult (*EncodeFn)(CUtensorMap*, CUtensorMapDataType, cuuint32_t, void*, const cuuint64_t*, const cuuint64_t*, const cuuint32_t*,
                             const cuuint32_t*, CUtensorMapInterleave, CUtensorMapSwizzle, CUtensorMapL2promotion, CUtensorMapFloatOOBfill);

void make_map(EncodeFn enc, CUtensorMap* m, const void* base, uint64_t cols, uint64_t rows, uint32_t box_cols, uint32_t box_rows, bool swizzle) {
    cuuint64_t dims[2] = {cols, rows};
    cuuint64_t strides[1] = {cols * 2};
    cuuint32_t box[2] = {box_cols, box_rows};
    cuuint32_t es[2] = {1, 1};
    enc(m, CU_TENSOR_MAP_DATA_TYPE_BFLOAT16, 2, const_cast<void*>(base), dims, strides, box, es, CU_TENSOR_MAP_INTERLEAVE_NONE,
        swizzle ? CU_TENSOR_MAP_SWIZZLE_128B : CU_TENSOR_MAP_SWIZZLE_NONE, swizzle ? CU_TENSOR_MAP_L2_PROMOTION_NONE : WPROMO, CU_TENSOR_MAP_FLOAT_OOB_FILL_NONE);
}

}

extern "C" void kernel_launch(void* const* d_in, const int* in_sizes, int n_in, void* d_out, int out_size) {
    (void)in_sizes; (void)n_in; (void)out_size;
    static EncodeFn enc = nullptr;
    if (!enc) {
        void* f = nullptr;
        cudaDriverEntryPointQueryResult q;
        cudaGetDriverEntryPoint("cuTensorMapEncodeTiled", &f, cudaEnableDefault, &q);
        enc = (EncodeFn)f;
        cudaFuncSetAttribute(fused_kernel, cudaFuncAttributeMaxDynamicSharedMemorySize, SMEM_BYTES);
    }
    Params P;
    P.x = (const __nv_bfloat16*)d_in[0]; P.k = (const __nv_bfloat16*)d_in[1]; P.v = (const __nv_bfloat16*)d_in[2];
    P.wr = (const __nv_bfloat16*)d_in[6];
    P.out = (__nv_bfloat16*)d_out;
    Maps M;
    make_map(enc, &M.k, P.k, 192, (uint64_t)4 * KV_BATCH_KEYS, 64, 32, true);
    make_map(enc, &M.v, P.v, 64, (uint64_t)12 * KV_BATCH_KEYS, 64, 96, true);
    make_map(enc, &M.wq, d_in[3], 6144, 640, 192, 40, false);
    make_map(enc, &M.wo, d_in[4], 640, 6144, 80, 96, false);
    make_map(enc, &M.wg, d_in[7], 1536, 640, 96, 80, false);
    make_map(enc, &M.wu, d_in[8], 1536, 640, 96, 80, false);
    make_map(enc, &M.wd, d_in[9], 640, 1536, 80, 96, false);
    fused_kernel<<<NCTA, NTHR, SMEM_BYTES, cudaStreamPerThread>>>(P, M);
}
```

```cpp
#include <cuda_runtime.h>
#include <cuda.h>
#include <cuda_bf16.h>
#include <stdint.h>

namespace {

constexpr int NCTA = 128;
constexpr int NTHR = 384;
constexpr int UNIT = 6144;
constexpr int SLOT = 12288;
#define TAU 4200
#define TAUW 4000
#define TMIN 2400
#define T_LEAD 0
#define WIN_W 3
#define WIN_S 4
#define WIN_U 8
#define RFR_ON 1
#define KRE_N1 0
#define KRE_TAU1 2500
#define RFR_TAU 6400
#define VPF 3
#define VPOS 3
#define KRE_GATE 0
#define KRE_TAU 4000
#define KRE_TAU3 KRE_TAU
#define HDEPTH 3
#define PV1PIPE 0
#define HOPA0 4
#define HOPA1 7
#define WPROMO CU_TENSOR_MAP_L2_PROMOTION_NONE
#define KPRE 2
#define KPRE2 1
#define DELAY_G 6
#define DELAY_L 5
#define DELAY_C 3
#define DELAY_D 6
#define DELAY_E 3
#define REG_LO "40"
#define REG_HI "232"
#define SPIN_LOG 17
constexpr int SPIN_LIMIT = 1 << SPIN_LOG;

__host__ __device__ constexpr uint32_t pairL(uint32_t region, uint32_t c, uint32_t g) { return (g & 1) | ((g >> 1) << 2) | (c << 5) | (region << 6); }
__host__ __device__ constexpr uint32_t pairG(uint32_t d, uint32_t c, uint32_t i) { return (i & 1) | ((i >> 1) << 2) | (d << 4) | (c << 5) | (3u << 6); }
constexpr uint32_t RA = 0, RC = 1, RE = 2, HALF = 16384, COPY = 4096, PMASK = 0x59;
constexpr uint32_t XS = 0;
constexpr uint32_t XS2 = XS + 128 * 7680;
constexpr uint32_t XSEND = XS2 + 128 * 768;
__device__ uint4 g_s[XSEND / 16];
__device__ uint4 g_x[(4u << 20) / 16];
#define SWEEPS(k, n) do {} while (0)

constexpr uint32_t S_WD = 16 * SLOT;
constexpr uint32_t S_DUMMY = S_WD + 15360;
constexpr uint32_t S_BAR = S_DUMMY + 4096;
constexpr uint32_t S_FV = S_BAR, S_FK = S_FV + 64, S_RING = S_FK + 64, S_DBAR = S_RING + 32, S_WFULL = S_DBAR + 32, S_QRDY = S_WFULL + 88;
constexpr uint32_t S_RELK = S_QRDY + 8, S_RELV = S_RELK + 8, S_RELR = S_RELV + 8, S_RELW = S_RELR + 8, S_SCO = S_RELW + 24;
constexpr uint32_t S_ZERO = S_SCO + 8;
constexpr uint32_t S_KP = S_SCO + 16, S_KF = S_KP + 8, S_AL = S_KF + 8;
constexpr uint32_t S_SIDE = S_AL + 4;
constexpr uint32_t S_GATE = S_SIDE + 4, S_SWR = S_GATE + 4;
constexpr uint32_t S_STAT = S_SWR + 4;
constexpr uint32_t S_XCAR = S_STAT + 32;
constexpr uint32_t S_CSQ = S_XCAR + 320;
constexpr uint32_t S_CSGU = S_CSQ + 768;
constexpr uint32_t S_RED = S_CSGU + 768;
constexpr uint32_t S_L0 = S_RED;
constexpr uint32_t S_OS = S_RED + 5120;
constexpr uint32_t S_PS = S_OS + 1536;
constexpr uint32_t PS_MAX = 512, PS_PASS = 544;
constexpr uint32_t S_QS = S_PS + 2 * PS_PASS;
constexpr uint32_t S_XB = S_QS + 2048;
constexpr uint32_t S_XA = S_XB + 768;
constexpr uint32_t S_HS = S_XA + 768;
constexpr uint32_t S_X0 = S_HS + 768;
constexpr int SMEM_BYTES = S_X0 + 640;
static_assert(SMEM_BYTES <= 232448 && S_STAT % 16 == 0 && S_RED % 16 == 0 && S_XB % 16 == 0 && S_HS % 16 == 0 && S_PS % 16 == 0 && S_QS % 16 == 0, "smem");
static_assert(S_SCO == S_BAR + 42 * 8 && S_RELK == S_BAR + 36 * 8, "barriers");
constexpr uint32_t ST_WQ = 2 * SLOT, ST_WG = 7 * SLOT, ST_WO = 11 * SLOT;

__device__ __forceinline__ uint32_t smem_u32(const void* p) { return (uint32_t)__cvta_generic_to_shared(p); }
__device__ __forceinline__ void mbar_init(uint32_t bar, uint32_t cnt) { asm volatile("mbarrier.init.shared::cta.b64 [%0], %1;" :: "r"(bar), "r"(cnt) : "memory"); }
__device__ __forceinline__ void mbar_expect(uint32_t bar, uint32_t bytes) { asm volatile("mbarrier.arrive.expect_tx.shared::cta.b64 _, [%0], %1;" :: "r"(bar), "r"(bytes) : "memory"); }
__device__ __forceinline__ void mbar_arrive(uint32_t bar) { asm volatile("mbarrier.arrive.shared::cta.b64 _, [%0];" :: "r"(bar) : "memory"); }
__device__ __forceinline__ bool mbar_try(uint32_t bar, uint32_t parity) {
    uint32_t ok;
    asm volatile("{\n .reg .pred p;\n mbarrier.try_wait.parity.shared::cta.b64 p, [%1], %2;\n selp.u32 %0, 1, 0, p;\n}" : "=r"(ok) : "r"(bar), "r"(parity) : "memory");
    return ok != 0;
}
__device__ __forceinline__ bool mbar_test(uint32_t bar, uint32_t parity) {
    uint32_t ok;
    asm volatile("{\n .reg .pred p;\n mbarrier.test_wait.parity.shared::cta.b64 p, [%1], %2;\n selp.u32 %0, 1, 0, p;\n}" : "=r"(ok) : "r"(bar), "r"(parity) : "memory");
    return ok != 0;
}
__device__ __forceinline__ void mbar_wait(uint32_t bar, uint32_t parity) {
    int n = 0;
    while (!mbar_try(bar, parity) && ++n < SPIN_LIMIT) {}
}
__device__ __forceinline__ unsigned long long gtime() { unsigned long long t; asm volatile("mov.u64 %0, %globaltimer;" : "=l"(t)); return t; }
__device__ __forceinline__ uint32_t gtime32() { uint32_t t; asm volatile("mov.u32 %0, %globaltimer_lo;" : "=r"(t)); return t; }
__device__ __forceinline__ void bar_main() { __syncwarp(); asm volatile("bar.sync 1, 256;" ::: "memory"); }

__device__ __forceinline__ void mma16816(float (&c)[4], uint32_t a0, uint32_t a1, uint32_t a2, uint32_t a3, uint32_t b0, uint32_t b1) {
    asm("mma.sync.aligned.m16n8k16.row.col.f32.bf16.bf16.f32 {%0,%1,%2,%3}, {%4,%5,%6,%7}, {%8,%9}, {%0,%1,%2,%3};"
        : "+f"(c[0]), "+f"(c[1]), "+f"(c[2]), "+f"(c[3]) : "r"(a0), "r"(a1), "r"(a2), "r"(a3), "r"(b0), "r"(b1));
}
__device__ __forceinline__ void mmaA(float (&c)[4], const uint32_t (&a)[4], uint32_t b0, uint32_t b1) { mma16816(c, a[0], a[1], a[2], a[3], b0, b1); }
__device__ __forceinline__ void mmaAv(float (&c)[4], const uint32_t (&a)[4], uint32_t b0, uint32_t b1) {
    asm volatile("mma.sync.aligned.m16n8k16.row.col.f32.bf16.bf16.f32 {%0,%1,%2,%3}, {%4,%5,%6,%7}, {%8,%9}, {%0,%1,%2,%3};"
        : "+f"(c[0]), "+f"(c[1]), "+f"(c[2]), "+f"(c[3]) : "r"(a[0]), "r"(a[1]), "r"(a[2]), "r"(a[3]), "r"(b0), "r"(b1) : "memory");
}
__device__ __forceinline__ void mma8(float (&c)[4], uint32_t a0, uint32_t a1, uint32_t b0) {
    asm("mma.sync.aligned.m16n8k8.row.col.f32.bf16.bf16.f32 {%0,%1,%2,%3}, {%4,%5}, {%6}, {%0,%1,%2,%3};"
        : "+f"(c[0]), "+f"(c[1]), "+f"(c[2]), "+f"(c[3]) : "r"(a0), "r"(a1), "r"(b0));
}
struct W80 { uint32_t a[2][4], c[2]; };
template <int N> __device__ __forceinline__ void mul80(float (&acc)[N][4], const W80 (&W)[N], const uint4& b, uint32_t b4) {
#pragma unroll
    for (int m = 0; m < N; m++) mmaA(acc[m], W[m].a[0], b.x, b.y);
#pragma unroll
    for (int m = 0; m < N; m++) mmaA(acc[m], W[m].a[1], b.z, b.w);
#pragma unroll
    for (int m = 0; m < N; m++) mma8(acc[m], W[m].c[0], W[m].c[1], b4);
}
__device__ __forceinline__ void ldsm2t(uint32_t (&r)[2], uint32_t addr) {
    asm volatile("ldmatrix.sync.aligned.m8n8.x2.trans.shared.b16 {%0,%1}, [%2];" : "=r"(r[0]), "=r"(r[1]) : "r"(addr) : "memory");
}
__device__ __forceinline__ void mmaV(float (&c)[4], const uint4& a, uint32_t b0, uint32_t b1) { mma16816(c, a.x, a.y, a.z, a.w, b0, b1); }
__device__ __forceinline__ void ldsm4(uint32_t (&r)[4], uint32_t addr) {
    asm volatile("ldmatrix.sync.aligned.m8n8.x4.shared.b16 {%0,%1,%2,%3}, [%4];" : "=r"(r[0]), "=r"(r[1]), "=r"(r[2]), "=r"(r[3]) : "r"(addr) : "memory");
}
__device__ __forceinline__ void ldsm4t(uint32_t (&r)[4], uint32_t addr) {
    asm volatile("ldmatrix.sync.aligned.m8n8.x4.trans.shared.b16 {%0,%1,%2,%3}, [%4];" : "=r"(r[0]), "=r"(r[1]), "=r"(r[2]), "=r"(r[3]) : "r"(addr) : "memory");
}
__device__ __forceinline__ uint32_t lds16(uint32_t a) { uint16_t v; asm volatile("ld.shared.u16 %0, [%1];" : "=h"(v) : "r"(a) : "memory"); return v; }
__device__ __forceinline__ uint32_t lds32(uint32_t a) { uint32_t v; asm volatile("ld.shared.u32 %0, [%1];" : "=r"(v) : "r"(a) : "memory"); return v; }
__device__ __forceinline__ float ldsf(uint32_t a) { return __uint_as_float(lds32(a)); }
__device__ __forceinline__ uint2 lds64(uint32_t a) { uint2 v; asm volatile("ld.shared.v2.u32 {%0,%1}, [%2];" : "=r"(v.x), "=r"(v.y) : "r"(a) : "memory"); return v; }
__device__ __forceinline__ uint4 lds128(uint32_t a) { uint4 v; asm volatile("ld.shared.v4.u32 {%0,%1,%2,%3}, [%4];" : "=r"(v.x), "=r"(v.y), "=r"(v.z), "=r"(v.w) : "r"(a) : "memory"); return v; }
__device__ __forceinline__ int ldsvol(uint32_t a) { int v; asm volatile("ld.volatile.shared.u32 %0, [%1];" : "=r"(v) : "r"(a) : "memory"); return v; }
__device__ __forceinline__ void stsvol(uint32_t a, int v) { asm volatile("st.volatile.shared.u32 [%0], %1;" :: "r"(a), "r"(v) : "memory"); }
__device__ __forceinline__ void sts_hi16(uint32_t a, float v) { asm volatile("{\n .reg .b16 lo, hi;\n mov.b32 {lo, hi}, %1;\n st.shared.u16 [%0], hi;\n}" :: "r"(a), "r"(__float_as_uint(v)) : "memory"); }
__device__ __forceinline__ void sts32(uint32_t a, uint32_t v) { asm volatile("st.shared.u32 [%0], %1;" :: "r"(a), "r"(v) : "memory"); }
__device__ __forceinline__ void stsf(uint32_t a, float v) { sts32(a, __float_as_uint(v)); }
__device__ __forceinline__ void sts64(uint32_t a, uint32_t x, uint32_t y) { asm volatile("st.shared.v2.u32 [%0], {%1,%2};" :: "r"(a), "r"(x), "r"(y) : "memory"); }

__device__ __forceinline__ void sts_hi16_if(bool p, uint32_t a, float v) {
    asm volatile("{\n .reg .pred p;\n .reg .b16 lo, hi;\n setp.ne.u32 p, %2, 0;\n mov.b32 {lo, hi}, %1;\n @p st.shared.u16 [%0], hi;\n}" :: "r"(a), "r"(__float_as_uint(v)), "r"((uint32_t)p) : "memory");
}
__device__ __forceinline__ void sts32_if(bool p, uint32_t a, uint32_t v) {
    asm volatile("{\n .reg .pred p;\n setp.ne.u32 p, %2, 0;\n @p st.shared.u32 [%0], %1;\n}" :: "r"(a), "r"(v), "r"((uint32_t)p) : "memory");
}
__device__ __forceinline__ void sts64_if(bool p, uint32_t a, float x, float y) {
    asm volatile("{\n .reg .pred p;\n setp.ne.u32 p, %3, 0;\n @p st.shared.v2.f32 [%0], {%1,%2};\n}" :: "r"(a), "f"(x), "f"(y), "r"((uint32_t)p) : "memory");
}
__device__ __forceinline__ void arrive_if(bool p, uint32_t bar) {
    asm volatile("{\n .reg .pred p;\n setp.ne.u32 p, %1, 0;\n @p mbarrier.arrive.shared::cta.b64 _, [%0];\n}" :: "r"(bar), "r"((uint32_t)p) : "memory");
}
__device__ __forceinline__ void opaque(uint32_t& v) { asm volatile("" : "+r"(v)); }
__device__ __forceinline__ void keep(uint32_t& v) { asm volatile("" : "+r"(v)); }
__device__ __forceinline__ void keep(float& v) { asm volatile("" : "+f"(v)); }
template <class T> __device__ __forceinline__ void keep(T*& v) { asm volatile("" : "+l"(v)); }

__device__ __forceinline__ uint32_t ldp32(const char* p) { uint32_t v; asm volatile("ld.relaxed.gpu.global.u32 %0, [%1];" : "=r"(v) : "l"(p) : "memory"); return v; }
__device__ __forceinline__ uint2 ldp64(const char* p) {
    uint2 v; asm volatile("{\n .reg .b64 d;\n ld.relaxed.gpu.global.b64 d, [%2];\n mov.b64 {%0,%1}, d;\n}" : "=r"(v.x), "=r"(v.y) : "l"(p) : "memory"); return v;
}
__device__ __forceinline__ uint32_t tagw(float f, uint32_t par) { return (__float_as_uint(f) & ~1u) | par; }
__device__ __forceinline__ void stp32(char* p, float a, uint32_t par) { asm volatile("st.relaxed.gpu.global.u32 [%0], %1;" :: "l"(p), "r"(tagw(a, par)) : "memory"); }
__device__ __forceinline__ void stp64(char* p, float a, float b, uint32_t par) {
    asm volatile("{\n .reg .b64 d;\n mov.b64 d, {%1,%2};\n st.relaxed.gpu.global.b64 [%0], d;\n}" :: "l"(p), "r"(tagw(a, par)), "r"(__float_as_uint(b)) : "memory");
}
__device__ __forceinline__ void stp32_if(bool p, char* d, float a, uint32_t par) {
    asm volatile("{\n .reg .pred p;\n setp.ne.u32 p, %2, 0;\n @p st.relaxed.gpu.global.u32 [%0], %1;\n @p st.relaxed.gpu.global.u32 [%0+4096], %1;\n}" :: "l"(d), "r"(tagw(a, par)), "r"((uint32_t)p) : "memory");
}
__device__ __forceinline__ void stp64_if(bool p, char* d, uint32_t lo, uint32_t hi) {
    asm volatile("{\n .reg .pred p;\n .reg .b64 d;\n setp.ne.u32 p, %3, 0;\n mov.b64 d, {%1,%2};\n @p st.relaxed.gpu.global.b64 [%0], d;\n @p st.relaxed.gpu.global.b64 [%0+4096], d;\n}" :: "l"(d), "r"(lo), "r"(hi), "r"((uint32_t)p) : "memory");
}
__device__ __forceinline__ uint32_t chk2(uint32_t a, uint32_t b, uint32_t par) { uint32_t r; asm("lop3.b32 %0, %1, %2, %3, 0x7E;" : "=r"(r) : "r"(a), "r"(b), "r"(par)); return r; }
__device__ __forceinline__ uint32_t or3(uint32_t a, uint32_t b, uint32_t c) { uint32_t r; asm("lop3.b32 %0, %1, %2, %3, 0xFE;" : "=r"(r) : "r"(a), "r"(b), "r"(c)); return r; }
__device__ __forceinline__ uint32_t chk8(const uint32_t (&v)[8], uint32_t par) { return or3(chk2(v[0], v[1], par), chk2(v[2], v[3], par), or3(chk2(v[4], v[5], par), chk2(v[6], v[7], par), 0)); }
__device__ __forceinline__ uint32_t chk8(const uint2 (&v)[8], uint32_t par) { return or3(chk2(v[0].x, v[1].x, par), chk2(v[2].x, v[3].x, par), or3(chk2(v[4].x, v[5].x, par), chk2(v[6].x, v[7].x, par), 0)); }
__device__ __forceinline__ uint32_t chk8y(const uint2 (&v)[8], uint32_t par) { return or3(chk2(v[0].y, v[1].y, par), chk2(v[2].y, v[3].y, par), or3(chk2(v[4].y, v[5].y, par), chk2(v[6].y, v[7].y, par), 0)); }
__device__ __forceinline__ uint32_t chk4(const uint2 (&v)[4], uint32_t par) { return or3(chk2(v[0].x, v[0].y, par), chk2(v[1].x, v[1].y, par), or3(chk2(v[2].x, v[2].y, par), chk2(v[3].x, v[3].y, par), 0)); }
__device__ __forceinline__ float asf(uint32_t v) { return __uint_as_float(v); }
__device__ __forceinline__ float sum8(const uint32_t (&v)[8]) { return ((asf(v[0]) + asf(v[1])) + (asf(v[2]) + asf(v[3]))) + ((asf(v[4]) + asf(v[5])) + (asf(v[6]) + asf(v[7]))); }
__device__ __forceinline__ float sum8x(const uint2 (&v)[8]) { return ((asf(v[0].x) + asf(v[1].x)) + (asf(v[2].x) + asf(v[3].x))) + ((asf(v[4].x) + asf(v[5].x)) + (asf(v[6].x) + asf(v[7].x))); }
__device__ __forceinline__ float sum8y(const uint2 (&v)[8]) { return ((asf(v[0].y) + asf(v[1].y)) + (asf(v[2].y) + asf(v[3].y))) + ((asf(v[4].y) + asf(v[5].y)) + (asf(v[6].y) + asf(v[7].y))); }

__device__ __forceinline__ uint32_t pack2(float lo, float hi) { uint32_t r; asm("cvt.rn.bf16x2.f32 %0, %1, %2;" : "=r"(r) : "f"(hi), "f"(lo)); return r; }
__device__ __forceinline__ float bfr(float x) { return __uint_as_float(pack2(0.0f, x)); }
__device__ __forceinline__ float ex2(float x) { float r; asm("ex2.approx.ftz.f32 %0, %1;" : "=f"(r) : "f"(x)); return r; }
__device__ __forceinline__ float rcp(float x) { float r; asm("rcp.approx.ftz.f32 %0, %1;" : "=f"(r) : "f"(x)); return r; }
__device__ __forceinline__ float sqrt_(float x) { float r; asm("sqrt.approx.ftz.f32 %0, %1;" : "=f"(r) : "f"(x)); return r; }
__device__ __forceinline__ float bf_lo(uint32_t v) { return __uint_as_float(v << 16); }
__device__ __forceinline__ float bf_hi(uint32_t v) { return __uint_as_float(v & 0xffff0000u); }
__device__ __forceinline__ float sel4(int k, float a, float b, float c, float d) { return (k & 2) ? ((k & 1) ? d : c) : ((k & 1) ? b : a); }
constexpr float LOG2E = 1.4426950408889634f;
constexpr uint32_t ONES = 0x3f803f80u;

__device__ __forceinline__ void ln_stats(float sum, float sq, float& mean, float& den) {
    const float m = sum * (1.0f / 640.0f);
    const float var = fmaxf(fmaf(sq, 1.0f / 640.0f, -m * m), 0.0f);
    mean = bfr(m);
    den = bfr(sqrt_(bfr(bfr(var) + 1e-5f)));
}
__device__ __forceinline__ float sigmoidf_(float x) { return rcp(1.0f + ex2(-x * LOG2E)); }

#define TSTAMP(k) do {} while (0)
#define TST(k) do {} while (0)

#define CSTAMP(k) do {} while (0)
template <int N> __device__ __forceinline__ uint32_t lag(uint32_t sb) {
    uint32_t z = 0;
#pragma unroll
    for (int k = 0; k < N; k++) z = ldsvol(sb + S_ZERO + z);
    return z;
}
__device__ __forceinline__ void warm_mma(uint32_t& a, uint32_t& b) {
    asm volatile("mma.sync.aligned.m16n8k8.row.col.f16.f16.f16.f16 {%0,%1}, {%0,%1}, {%0}, {%0,%1};" : "+r"(a), "+r"(b) :: "memory");
}
#define KWNS2 20
#define KWNS 200
template <int STRIDE>
__device__ __forceinline__ float gather8(const char* p, uint32_t par) {
    uint32_t v[8];
    int guard = 0;
    do {
#pragma unroll
        for (int s = 0; s < 8; s++) v[s] = ldp32(p + s * STRIDE);
    } while ((chk8(v, par) & 1) && ++guard < SPIN_LIMIT);
    return sum8(v);
}
__device__ __forceinline__ float gather16(const char* p, uint32_t par, int k) {
    uint32_t v[8], u[8];
    float r;
    int guard = 0;
    bool again;
    do {
#pragma unroll
        for (int s = 0; s < 8; s++) v[s] = ldp32(p + s * 512);
#pragma unroll
        for (int s = 0; s < 8; s++) u[s] = ldp32(p + HALF + s * 512);
        again = (chk8(v, par) | chk8(u, par)) & 1;
        r = sum8(v) + sum8(u);
        keep(r);
    } while (again && ++guard < SPIN_LIMIT);
    SWEEPS(k, guard);
    return r;
}

struct Params {
    const __nv_bfloat16 *x, *k, *v, *wr;
    __nv_bfloat16* out;
};
struct Maps { CUtensorMap k, v, wq, wo, wg, wu, wd; };

constexpr int KV_BATCH_KEYS = 32 * 4096;

__device__ __forceinline__ void tma2d(uint32_t dst, const CUtensorMap* m, int c0, int c1, uint32_t bar, uint32_t bytes, uint64_t pol) {
    asm volatile("{\n .reg .pred p;\n elect.sync _|p, 0xffffffff;\n"
                 " @p mbarrier.arrive.expect_tx.shared::cta.b64 _, [%2], %6;\n"
                 " @p cp.async.bulk.tensor.2d.shared::cluster.global.mbarrier::complete_tx::bytes.L2::cache_hint [%0], [%1, {%3, %4}], [%2], %5;\n}"
                 :: "r"(dst), "l"(m), "r"(bar), "r"(c0), "r"(c1), "l"(pol), "r"(bytes) : "memory");
}
__device__ __forceinline__ void scrap_copy(uint32_t dst, const char* src, uint32_t bar) {
    asm volatile("{\n .reg .pred p;\n elect.sync _|p, 0xffffffff;\n"
                 " @p mbarrier.arrive.expect_tx.shared::cta.b64 _, [%2], 12288;\n"
                 " @p cp.async.bulk.shared::cluster.global.mbarrier::complete_tx::bytes [%0], [%1], 4096, [%2];\n"
                 " @p cp.async.bulk.shared::cluster.global.mbarrier::complete_tx::bytes [%0], [%1+4096], 4096, [%2];\n"
                 " @p cp.async.bulk.shared::cluster.global.mbarrier::complete_tx::bytes [%0], [%1+8192], 4096, [%2];\n}"
                 :: "r"(dst), "l"(src), "r"(bar) : "memory");
}
__device__ __forceinline__ void prefetch_l2(const void* p, uint32_t bytes) {
    asm volatile("{\n .reg .pred p;\n elect.sync _|p, 0xffffffff;\n @p cp.async.bulk.prefetch.L2.global [%0], %1;\n}" :: "l"(p), "r"(bytes) : "memory");
}
__device__ __forceinline__ uint64_t pol_first() { uint64_t p; asm("createpolicy.fractional.L2::evict_first.b64 %0, 1.0;" : "=l"(p)); return p; }
__device__ __forceinline__ uint64_t pol_normal() { uint64_t p; asm("createpolicy.fractional.L2::evict_normal.b64 %0, 1.0;" : "=l"(p)); return p; }
__device__ __forceinline__ bool utest(uint32_t bar, uint32_t parity) { return __all_sync(~0u, mbar_test(bar, parity)); }
__device__ __forceinline__ void uwait(uint32_t bar, uint32_t parity) {
    int n = 0;
    while (!__all_sync(~0u, mbar_try(bar, parity)) && ++n < SPIN_LIMIT) {}
}
template <int A, int B, int CNT> __device__ __forceinline__ void init_bars(uint32_t sb) {
#pragma unroll 1
    for (int k = A; k < B; k++)
        asm volatile("{\n .reg .pred p;\n elect.sync _|p, 0xffffffff;\n @p mbarrier.init.shared::cta.b64 [%0], %1;\n}" :: "r"(sb + S_BAR + 8 * k), "n"(CNT) : "memory");
}
__device__ __forceinline__ int first_key() { return (blockIdx.x >> 2) * 4096 + 3072 + (blockIdx.x & 3) * 256; }
__device__ __forceinline__ void load_tile(const CUtensorMap* m, uint32_t dst, uint32_t bar, uint32_t bytes, int key, uint64_t pol) { tma2d(dst, m, 0, 3 * key, bar, bytes, pol); }
__device__ __forceinline__ const char* unit_ptr(const Params& P, int n) {
    return (const char*)((n & 16) ? P.v : P.k) + (size_t)(first_key() + (n >> 5) * KV_BATCH_KEYS + (n & 15) * 16) * 384;
}
#define LSTAMP(k) do {} while (0)

__device__ __forceinline__ uint32_t k_place(uint32_t b, uint32_t s) { return s + 2 + (s < 2 ? 0 : 6 * (b & 1)); }
__device__ __forceinline__ uint32_t v_place(uint32_t b, uint32_t s) { return s < 2 ? s : s + 8 - 6 * (b & 1); }
__device__ __forceinline__ void ring_load(const Maps& M, uint32_t sb, uint32_t n) {
    load_tile(&M.k, sb + (n & 3) * UNIT, sb + S_RING + 8 * (n & 3), UNIT, first_key() + (n >> 4) * KV_BATCH_KEYS + 16 * (n & 15), pol_normal());
}
__device__ __forceinline__ void place_load(const Maps& M, uint32_t sb, uint32_t n) {
    load_tile(&M.k, sb + k_place(n >> 4, (n >> 1) & 7) * SLOT + (n & 1) * UNIT, sb + S_FK + 4 * (n & 14), UNIT,
              first_key() + (n >> 4) * KV_BATCH_KEYS + 16 * (n & 15), pol_first());
}
__device__ __forceinline__ void v_load(const Maps& M, uint32_t sb, uint32_t b, uint32_t s) {
    load_tile(&M.v, sb + v_place(b, s) * SLOT, sb + S_FV + 8 * s, SLOT, first_key() + b * KV_BATCH_KEYS + 32 * s, pol_first());
}
__device__ __forceinline__ bool due(uint32_t t) { return __all_sync(~0u, (int)(gtime32() * 16 - t) >= 0); }
__device__ __forceinline__ bool reached(uint32_t a, int v) { return __all_sync(~0u, ldsvol(a) >= v); }

__device__ __forceinline__ void stream_warp(const Params& P, const Maps& M, uint32_t sb) {
    const uint64_t pol = pol_first();
    const int bid = blockIdx.x, g = bid >> 3, i = bid & 7;
    const uint32_t wf = sb + S_WFULL;
    uint32_t tn = __shfl_sync(~0u, gtime32(), 0) * 16 - T_LEAD;
    auto pace = [&](uint32_t dt) { int k = 0; while (!due(tn) && ++k < SPIN_LIMIT) {} tn += dt; };
#pragma unroll
    for (int k = 0; k < 10; k++) {
        if (k < 2) {
            if (k == 0) init_bars<24, 25, 1>(sb); else init_bars<25, 35, 1>(sb);
            asm volatile("fence.mbarrier_init.release.cluster;" ::: "memory");
            if (k == 1) { asm volatile("bar.arrive 2, %0;" :: "n"(NTHR) : "memory"); asm volatile("bar.sync 3, 128;" ::: "memory"); }
        }
        if (k >= WIN_W) uwait(wf + 8 * (k - WIN_W), 0);
        pace(TAUW * 5 / 2);
        if (k < 4) tma2d(sb + ST_WQ + 15360 * k, &M.wq, 384 * g + 192 * (k >> 1), 80 * i + 40 * (k & 1), wf + 8 * k, 15360, pol);
        else if (k < 6) tma2d(sb + ST_WG + 15360 * (k - 4), k == 4 ? &M.wg : &M.wu, 96 * g, 80 * i, wf + 8 * k, 15360, pol);
        else tma2d(sb + ST_WO + 15360 * (k - 6), &M.wo, 80 * i, 384 * g + 96 * (k - 6), wf + 8 * k, 15360, pol);
    }
#pragma unroll 1
    for (int n = 0; n < 16; n++) {
        if (n == 0 || n == 5 || n == 11) uwait(sb + S_RELW + (n == 0 ? 0 : n == 5 ? 8 : 16), 0);
        uwait(n < WIN_S ? wf + 8 * (10 - WIN_S + n) : sb + S_FV + 8 * ((n - WIN_S) ^ 8), 0);
        pace(2 * TAU);
        if (n < 8) { place_load(M, sb, 2 * n); place_load(M, sb, 2 * n + 1); }
        else v_load(M, sb, 0, n - 8);
        if (n == 7) { pace(TAUW * 5 / 2); tma2d(sb + S_WD, &M.wd, 80 * i, 96 * g, wf + 80, 15360, pol); }
    }
    int nd = 0;
    uint32_t q[4];
#pragma unroll
    for (int r = 0; r < 4; r++) q[r] = sb + S_FV + 8 * (7 - r);
    uint32_t td = tn;
#pragma unroll 1
    for (int b = 1; b < 4; b++) {
        const uint32_t pk = (b - 1) & 1;
        uint32_t fr = 0, pend = 0;
#pragma unroll 1
        for (int j = 0; j < 17; j++) {
            const int n = 16 * b + 2 * j;
            uint32_t now, st;
            int k = 0;
            while (true) {
                now = __shfl_sync(~0u, gtime32(), 0) * 16;
                const uint4 c = lds128(sb + S_KP);
                const uint32_t relr = mbar_test(sb + S_RELR, pk), relk = mbar_test(sb + S_RELK, pk), sco = mbar_test(sb + S_SCO, pk ^ 1);
                const uint32_t win = mbar_test(q[WIN_S - 1] & ~1u, q[WIN_S - 1] & 1) & ((int)c.y >= min(n + 2 - WIN_U, 16 * b + 16));
                st = __reduce_and_sync(~0u, relr * 0x300 + relk * 0xfc + (sco & relr) * 3 + win * 0x400 + ((int)c.z > n) * 0x800 + ((int)c.w > n) * 0x1000);
                fr |= st & 0x3ff;
#pragma unroll 1
                while (pend & fr) {
                    const uint32_t r = __ffs(pend & fr) - 1;
                    if (r < 8) v_load(M, sb, b, r); else { ring_load(M, sb, 16 * b + 2 * r - 16); ring_load(M, sb, 16 * b + 2 * r - 15); }
                    pend ^= 1u << r;
                }
                if ((j == 16 ? !pend : (st & 0x400) && (int)(now - td) >= 0) || ++k >= SPIN_LIMIT) break;
            }
            if (j == 16) break;
            tn += 2 * TAU;
            td = (int)(tn - now) > 2 * TMIN ? tn : now + 2 * TMIN;
            q[3] = q[2]; q[2] = q[1]; q[1] = q[0]; q[0] = sb + S_QRDY;
            const int s = j < 8 ? j + 8 : j < VPOS + 8 ? j - 6 : j < VPOS + 10 ? j - VPOS - 8 : j - 8;
            const char* src = unit_ptr(P, 32 * b + 2 * (s ^ 8));
            if (j < 8) {
                stsvol(sb + S_AL, n + 2);
                if ((fr >> s) & 1) { ring_load(M, sb, n); ring_load(M, sb, n + 1); }
                else {
                    if (!(st & 0x800)) prefetch_l2(src, UNIT);
                    if (!(st & 0x1000)) prefetch_l2(src + UNIT, UNIT);
                    pend |= (1u << s) & 0x300;
                }
            } else if ((fr >> s) & 1) { v_load(M, sb, b, s); q[0] = (sb + S_FV + 8 * s) | (pk ^ 1); }
            else {
                pend |= 1u << s;
                if (j >= VPF + 8) prefetch_l2(src, SLOT);
                else {
                    scrap_copy(sb + S_DUMMY, src, sb + S_DBAR + 8 * (nd & 3));
                    q[0] = (sb + S_DBAR + 8 * (nd & 3)) | ((nd >> 2) & 1);
                    nd++;
                }
            }
        }
    }
#pragma unroll 1
    for (int m = max(nd - 4, 0); m < nd; m++) uwait(sb + S_DBAR + 8 * (m & 3), (m >> 2) & 1);
}

template <class F>
__device__ __forceinline__ void probs(float v0, float v1, float v2, float v3, uint32_t ps, uint32_t src, uint32_t ln, F mid) {
    const uint32_t q8 = ln >> 2, t4 = ln & 3;
    const bool hi = t4 & 2, od = t4 & 1;
    const float u0 = (hi ? v2 : v0) + __shfl_xor_sync(~0u, hi ? v0 : v2, 2), u1 = (hi ? v3 : v1) + __shfl_xor_sync(~0u, hi ? v1 : v3, 2);
    float s = (od ? u1 : u0) + __shfl_xor_sync(~0u, od ? u0 : u1, 1);
    mid();
    s = bfr(bfr(s) * 0.07216878364870322f);
    int key = __float_as_int(s);
    key ^= (key >> 31) & 0x7fffffff;
    key = __reduce_max_sync(~0u, key);
    key ^= (key >> 31) & 0x7fffffff;
    const float ml = __int_as_float(key) * LOG2E;
    sts_hi16(ps + 64 * src + (q8 >> 1) * 16 + t4 * 4 + (q8 & 1) * 2, bfr(ex2(fmaf(s, LOG2E, -ml))));
    sts32_if(ln == 0, ps + PS_MAX + 4 * src, __float_as_uint(ml));
}
template <int H> __device__ __forceinline__ uint32_t b_pos(uint32_t e) { const uint32_t h = e >= H, k = e - H * h; return h * 192 + (k & 6) * 24 + (k >> 3) * 4 + (k & 1) * 2; }
__device__ __forceinline__ uint32_t a_pos(uint32_t e) { const uint32_t h = e >= 40, k = e - 40 * h; return (k & 6) * 24 + (k >> 3) * 8 + h * 4 + (k & 1) * 2; }
__device__ __forceinline__ uint32_t q_pos(uint32_t d) { return ((d >> 4) & 7) * 64 + (d & 6) * 8 + (d >> 7) * 8 + ((d >> 3) & 1) * 4 + (d & 1) * 2; }
__device__ __forceinline__ uint32_t k_off(uint32_t ln, uint32_t j) { const uint32_t r = 3 * (ln & 15) + j; return r * 128 + (((r & 7) ^ (ln >> 4)) << 4); }

#define HSTAMP(k) do {} while (0)
__device__ __forceinline__ void score_warp(const Params& P, const Maps& M, uint32_t sb, uint32_t h, uint32_t ln) {
    uwait(sb + S_QRDY, 0);
    float v0 = 0.f, v1 = 0.f;
    const uint32_t q8 = ln >> 2;
    const uint32_t k0 = k_off(ln, 0), k1 = k_off(ln, 1), k2 = k_off(ln, 2);
#pragma unroll 1
    for (uint32_t n = h; n < 64; n += 2) {
        HSTAMP(0);
        const uint4 q = lds128(sb + S_QS + 32 * (n & 48) + 16 * ln);
        const uint32_t ua = sb + (n >= 16 ? n & 3 : n + 4) * UNIT;
        uwait(n >= 16 ? sb + S_RING + 8 * (n & 3) : sb + S_FK + 8 * (n >> 1), n >= 16 ? (n >> 2) & 1 : 0);
        HSTAMP(1);
        stsvol(sb + S_KP + 4 * (n & 1), n + 1);
        float acc[2][4] = {};
        uint32_t kf[12][4];
        auto ld = [&](int s) { ldsm4(kf[s], (ua + (s < 4 ? k0 : s < 8 ? k1 : k2)) ^ (32 * (s & 3))); };
#pragma unroll
        for (int s = 0; s < HDEPTH; s++) ld(s);
#pragma unroll
        for (int s = 0; s < 12; s++) {
            __syncwarp();
            const bool m = q8 == (s & 7);
            mmaAv(acc[s & 1], kf[s], m ? (s < 8 ? q.x : q.z) : 0u, m ? (s < 8 ? q.y : q.w) : 0u);
            if (s + HDEPTH < 12) ld(s + HDEPTH);
        }
        HSTAMP(2);
        if (n >= 16 && (n & 12) != 12) {
            stsvol(sb + S_KF + 4 * (n & 1), n + 5);
            int k = 0;
            while (!reached(sb + S_AL, n + 5) && ++k < SPIN_LIMIT) {}
            ring_load(M, sb, n + 4);
        }
        HSTAMP(3);
        const float w0 = (acc[0][0] + acc[0][1]) + (acc[1][0] + acc[1][1]), w1 = (acc[0][2] + acc[0][3]) + (acc[1][2] + acc[1][3]);
        if (n & 2) probs(v0, v1, w0, w1, sb + S_PS, ((n & 12) >> 1) + (n & 1), ln, [] {});
        v0 = w0; v1 = w1;
        __syncwarp();
        arrive_if(ln == 0 && (n & 14) == 14, sb + S_SCO);
    }
}

__device__ __forceinline__ char* xwindow() { return reinterpret_cast<char*>((reinterpret_cast<uintptr_t>(g_x) + (2u << 20) - 1) & ~(uintptr_t)((2u << 20) - 1)); }

struct XPtr {
    uint32_t lo, hi;
    __device__ __forceinline__ explicit XPtr(char* p) : lo((uint32_t)(uintptr_t)p), hi((uint32_t)((uintptr_t)p >> 32)) {}
    __device__ __forceinline__ XPtr(uint32_t l, uint32_t h) : lo(l), hi(h) {}
    __device__ __forceinline__ XPtr operator+(uint32_t o) const { return XPtr(lo + o, hi); }
    __device__ __forceinline__ operator char*() const { uint64_t p; asm("mov.b64 %0, {%1, %2};" : "=l"(p) : "r"(lo), "r"(hi)); return (char*)p; }
};
__device__ __forceinline__ void keep(XPtr& v) { keep(v.lo); }

__device__ __forceinline__ void side_warp(uint32_t sb) {
    const uint32_t bid = blockIdx.x, g = bid >> 3, i = bid & 7, P = pairG(0, 0, i);
    char* p = xwindow() + P * 8192 + (g >> 3) * HALF + (g & 7) * 512 + 448;
    uint32_t best[2] = {~0u, ~0u};
    asm volatile("st.relaxed.gpu.global.b32 [%0], 1;" :: "l"(p) : "memory");
    asm volatile("st.relaxed.gpu.global.b32 [%0], 1;" :: "l"(p + COPY) : "memory");
#pragma unroll 1
    for (int r = 0; r < 64; r++) {
        if (r >= 4 && !(r & 1) && min(best[0], best[1]) < 380 && max(best[0], best[1]) > min(best[0], best[1]) + 80) break;
        uint32_t c0, c1, v;
        asm volatile("mov.u32 %0, %clock;" : "=r"(c0) :: "memory");
        asm volatile("atom.relaxed.gpu.global.exch.b32 %0, [%1], 0;" : "=r"(v) : "l"(p + (r & 1) * COPY) : "memory");
        asm volatile("{\n .reg .pred q;\n setp.eq.u32 q, %1, 0x13579bdf;\n mov.u32 %0, 0;\n @!q mov.u32 %0, %clock;\n}" : "=r"(c1) : "r"(v) : "memory");
        if (r & 1) best[1] = min(best[1], c1 - c0); else best[0] = min(best[0], c1 - c0);
    }
    stsvol(sb + S_SIDE, 1 + ((best[1] < best[0]) ^ (__popc(P & PMASK) & 1)));
}

__device__ __forceinline__ void look_a(uint2 (&v)[4], const char* src) {
#pragma unroll
    for (int s = 0; s < 4; s++) v[s] = ldp64(src + s * 1024);
}
__device__ __forceinline__ void hop_a(uint2 (&v)[4], const char* src, uint32_t par, uint32_t dst, bool st, int k) {
    int guard = 0;
    while (__any_sync(~0u, chk4(v, par) & 1) && ++guard < SPIN_LIMIT) look_a(v, src);
    const float M = fmaxf(fmaxf(asf(v[0].x), asf(v[1].x)), fmaxf(asf(v[2].x), asf(v[3].x)));
    float e[4];
#pragma unroll
    for (int s = 0; s < 4; s++) e[s] = ex2(asf(v[s].x) - M);
    const float rl = __shfl_sync(~0u, rcp(fmaf(e[0], asf(v[0].y), e[1] * asf(v[1].y)) + fmaf(e[2], asf(v[2].y), e[3] * asf(v[3].y))), 24);
#pragma unroll
    for (int s = 0; s < 4; s++) e[s] = __shfl_sync(~0u, e[s], 24);
    const float o0 = fmaf(e[0], asf(v[0].x), e[1] * asf(v[1].x)) + fmaf(e[2], asf(v[2].x), e[3] * asf(v[3].x));
    const float o1 = fmaf(e[0], asf(v[0].y), e[1] * asf(v[1].y)) + fmaf(e[2], asf(v[2].y), e[3] * asf(v[3].y));
    sts32_if(st, dst, pack2(o0 * rl, o1 * rl));
    SWEEPS(k, guard);
    __syncwarp();
}

__global__ void __launch_bounds__(NTHR, 1)
fused_kernel(const Params P, const __grid_constant__ Maps M) {
    extern __shared__ __align__(1024) unsigned char smem[];
    const uint32_t sb = smem_u32(smem);
    const int tid = threadIdx.x, bid = blockIdx.x;
    const int w = __shfl_sync(~0u, tid >> 5, 0), lane = tid & 31;

    if (w >= 8) {
        asm volatile("setmaxnreg.dec.sync.aligned.u32 " REG_LO ";");
        if (w == 8) {
            stream_warp(P, M, sb);
        } else {
            if (w == 9) { init_bars<0, 8, 1>(sb); init_bars<16, 20, 1>(sb); }
            else if (w == 10) { init_bars<8, 16, 2>(sb); init_bars<20, 24, 1>(sb); }
            else { init_bars<35, 36, 1>(sb); init_bars<36, 42, 8>(sb); init_bars<42, 43, 2>(sb); if (lane < 9) stsvol(sb + S_ZERO + 4 * lane, 0); }
            asm volatile("fence.mbarrier_init.release.cluster;" ::: "memory");
            asm volatile("bar.arrive 3, 128;" ::: "memory");
            asm volatile("bar.sync 2, %0;" :: "n"(NTHR) : "memory");
            if (w < 11) score_warp(P, M, sb, w - 9, lane);
            else {
                if (lane == 0) side_warp(sb);
                __syncwarp();
                uint32_t a = 0, b = 0;
                int k = 0;
                while (ldsvol(sb + S_GATE) == 0 && ++k < SPIN_LIMIT) { warm_mma(a, b); __nanosleep(KWNS); }
                uint4* d = reinterpret_cast<uint4*>(reinterpret_cast<char*>(g_s) + XS + bid * 7680) + lane;
                const uint4 z = make_uint4(0, 0, 0, 0);
#pragma unroll 1
                for (int u = 0; u < 15; u++) d[32 * u] = z;
                d = reinterpret_cast<uint4*>(reinterpret_cast<char*>(g_s) + XS2 + bid * 768) + lane;
                d[0] = z;
                if (lane < 16) d[32] = z;
                const uint32_t side = (ldsvol(sb + S_SIDE) & 1) ^ 1, g = bid >> 3, i = bid & 7;
                const XPtr gx(xwindow());
                auto nearp = [&](uint32_t pr) { return gx.lo + pr * 8192 + ((side ^ __popc(pr & PMASK)) & 1) * COPY; };
                const uint32_t own = (i >> 2) * HALF + (i & 3) * 1024 + (lane & 7) * 128;
                const uint32_t pAC = nearp(pairL(lane >> 4, (lane >> 3) & 1, g)) + own, pE = nearp(pairL(RE, (lane >> 3) & 1, g)) + own;
                const uint32_t pG = nearp(pairG((lane >> 2) & 1, (lane >> 3) & 1, i)) + min(lane & 3, 2) * 128;
                uint32_t tr = 0, tk = 0, ph = 0, src = g + (lane >> 4), seen = 0, n = 16;
                bool go = false, first = true;
                while (n < 64 && ++k < SPIN_LIMIT) {
                    const uint32_t now = __shfl_sync(~0u, gtime32(), 0) * 16;
                    if (!go && utest(sb + S_RELV, ((n >> 4) & 1) ^ 1) && utest(sb + S_FV + 8 * KRE_GATE, (n >> 4) & 1)) { go = true; tk = now; }
                    if (go && (int)(now - tk) >= 0) {
                        place_load(M, sb, n);
                        tk += n >= 48 ? KRE_TAU3 : (n & 15) < KRE_N1 ? KRE_TAU1 : KRE_TAU;
                        n++;
                        go = (n & 15) != 0;
                        if (!go) LSTAMP(63 + (n >> 3));
                    } else if (first || (int)(now - tr) >= 0) {
                        first = false;
                        tr = now + RFR_TAU;
                        b |= seen & a;
                        warm_mma(a, b);
                        if (RFR_ON) seen = ldp32(XPtr(ph == 0 ? pAC : ph == 1 && lane < 16 ? pE : pG + (src & 8) * (HALF / 8) + (src & 7) * 512, gx.hi));
                        src += ph == 0 ? 0 : ph == 1 ? 2 : 1;
                        ph = ph == 2 ? 0 : ph + 1;
                    } else __nanosleep(KWNS2);
                }
                while (ldsvol(sb + S_GATE) < 6 && ++k < SPIN_LIMIT) { warm_mma(a, b); __nanosleep(KWNS); }
                if (a | b) stsvol(sb + S_GATE, 6);
            }
        }
        return;
    }
    asm volatile("setmaxnreg.inc.sync.aligned.u32 " REG_HI ";");

    const int g = bid >> 3, i = bid & 7;
    const int g8 = lane >> 2, t = lane & 3;
    char* const gs = reinterpret_cast<char*>(g_s);
    const XPtr gx(xwindow());
    TSTAMP(0);

    W80 Wq[6], Wgu[3];
    uint32_t Wo[5][3][4];
    if (w < 4) {
        const uint32_t* xp = reinterpret_cast<const uint32_t*>(P.x + 640 * w);
        float sum = 0.f, sq = 0.f;
#pragma unroll
        for (int u = 0; u < 10; u++) { uint32_t v = xp[lane + 32 * u]; float a = bf_lo(v), b = bf_hi(v); sum += a + b; sq += a * a + b * b; }
#pragma unroll
        for (int o = 16; o > 0; o >>= 1) { sum += __shfl_xor_sync(~0u, sum, o); sq += __shfl_xor_sync(~0u, sq, o); }
        float mean, den; ln_stats(sum, sq, mean, den);
        if (lane < 20) {
            const uint2 v = reinterpret_cast<const uint2*>(P.x + 640 * w + 80 * i)[lane];
            sts64(sb + S_X0 + 160 * w + 8 * lane, v.x, v.y);
            sts32(sb + S_L0 + 384 * w + b_pos<40>(4 * lane), pack2(__fdiv_rn(bfr(bf_lo(v.x) - mean), den), __fdiv_rn(bfr(bf_hi(v.x) - mean), den)));
            sts32(sb + S_L0 + 384 * w + b_pos<40>(4 * lane + 2), pack2(__fdiv_rn(bfr(bf_lo(v.y) - mean), den), __fdiv_rn(bfr(bf_hi(v.y) - mean), den)));
        }
    } else if (w == 4) {
        const uint32_t* xp = reinterpret_cast<const uint32_t*>(P.wr);
        float sum = 0.f;
#pragma unroll
        for (int u = 0; u < 10; u++) { uint32_t v = xp[lane + 32 * u]; sum += bf_lo(v) + bf_hi(v); }
#pragma unroll
        for (int o = 16; o > 0; o >>= 1) sum += __shfl_xor_sync(~0u, sum, o);
        if (lane == 0) stsf(sb + S_SWR, sum);
        if (lane < 20) {
            const uint2 v = reinterpret_cast<const uint2*>(P.wr + 80 * i)[lane];
            sts32(sb + S_XA + 576 + a_pos(4 * lane), v.x); sts32(sb + S_XA + 576 + a_pos(4 * lane + 2), v.y);
            sts32(sb + S_XA + a_pos(4 * lane), ONES); sts32(sb + S_XA + a_pos(4 * lane + 2), ONES);
        }
    }
    asm volatile("bar.sync 2, %0;" :: "n"(NTHR) : "memory");
    auto frag = [](uint32_t (&a)[4], uint32_t p, int pitch) {
        const uint32_t r0 = lds32(p), r1 = lds32(p + pitch), r2 = lds32(p + 2 * pitch), r3 = lds32(p + 3 * pitch);
        a[0] = __byte_perm(r0, r1, 0x5410); a[1] = __byte_perm(r0, r1, 0x7632);
        a[2] = __byte_perm(r2, r3, 0x5410); a[3] = __byte_perm(r2, r3, 0x7632);
    };
    mbar_wait(sb + S_WFULL + 16 * (w >> 2), 0);
    mbar_wait(sb + S_WFULL + 16 * (w >> 2) + 8, 0);
    {
        const uint32_t p = sb + ST_WQ + (w >> 2) * 30720 + (2 * t) * 384 + (48 * (w & 3) + 2 * g8) * 2;
#pragma unroll
        for (int r = 0; r < 10; r++)
#pragma unroll
            for (int m = 0; m < 3; m++) {
                const uint32_t q = p + ((r & 1) * 40 + (r >> 1) * 8) * 384 + 32 * m, r0 = lds32(q), r1 = lds32(q + 384);
                (r < 8 ? Wq[2 * m].a[(r >> 2) & 1][r & 3] : Wq[2 * m].c[r & 1]) = __byte_perm(r0, r1, 0x5410);
                (r < 8 ? Wq[2 * m + 1].a[(r >> 2) & 1][r & 3] : Wq[2 * m + 1].c[r & 1]) = __byte_perm(r0, r1, 0x7632);
            }
    }
    __syncwarp();
    if (lane == 0) mbar_arrive(sb + S_RELW);
    TSTAMP(1);
    {
        char* d = gs + XS + bid * 7680 + (w >> 2) * 3840 + (48 * (w & 3) + 2 * g8) * 4;
        float acc[6][4] = {};
        mul80(acc, Wq, lds128(sb + S_L0 + 48 * lane), lds32(sb + S_L0 + 48 * lane + 16));
#pragma unroll
        for (int m = 0; m < 6; m++) stp32(d + t * 768 + 32 * (m & 6) + 4 * (m & 1), acc[m][0] + acc[m][3], 1);
        float sum[6][4] = {};
        mul80(sum, Wq, make_uint4(ONES, ONES, ONES, ONES), ONES);
        if (t == 0)
#pragma unroll
            for (int m = 0; m < 6; m++) stp32(d + 4 * 768 + 32 * (m & 6) + 4 * (m & 1), sum[m][0] + sum[m][3], 1);
    }
    mbar_wait(sb + S_WFULL + 32, 0);
    mbar_wait(sb + S_WFULL + 40, 0);
    const uint32_t oct = 3 * (w >> 1) + (w & 1), oct2 = 3 * (w >> 1) + 2;
    {
        const uint32_t p = sb + ST_WG + ((lane & 7) + 40 * ((lane >> 3) & 1) + 8 * (lane >> 4)) * 192;
#pragma unroll
        for (int T = 0; T < 3; T++) {
            const uint32_t q = p + (T < 2 ? T * 15360 + 16 * oct : (w & 1) * 15360 + 16 * oct2);
            ldsm4t(Wgu[T].a[0], q); ldsm4t(Wgu[T].a[1], q + 16 * 192); ldsm2t(Wgu[T].c, q + 32 * 192);
        }
        float sum[3][4] = {};
        mul80(sum, Wgu, make_uint4(ONES, ONES, ONES, ONES), ONES);
        if (t < 3) stp32(gs + XS2 + bid * 768 + (t < 2 ? 64 * oct + 4 * t : 64 * oct2 + 4 * (w & 1)) + 8 * g8,
                         sel4(t, sum[0][0] + sum[0][3], sum[1][0] + sum[1][3], sum[2][0] + sum[2][3], 0.f), 1);
    }
    __syncwarp();
    if (lane == 0) mbar_arrive(sb + S_RELW + 8);
    const char* srcS = gs + XS + g * 8 * 7680 + (i >> 2) * 3840 + min(tid, 191) * 4;
    uint32_t vs[5][8];
#pragma unroll
    for (int b = 0; b < 5; b++)
#pragma unroll
        for (int s = 0; s < 8; s++) vs[b][s] = ldp32(srcS + b * 768 + s * 7680);
    uint32_t cs2[8];
#pragma unroll
    for (int s = 0; s < 8; s++) cs2[s] = ldp32(gs + XS2 + (g * 8 + s) * 768 + min(tid, 191) * 4);
    __syncwarp();
    mbar_wait(sb + S_WFULL + 48 + 8 * (w >> 1), 0);
    {
        const uint32_t po = sb + ST_WO + (48 * w + 12 * t) * 160 + 4 * g8;
#pragma unroll
        for (int s = 0; s < 3; s++)
#pragma unroll
            for (int m = 0; m < 5; m++) frag(Wo[m][s], po + 4 * s * 160 + 32 * m, 160);
    }
    __syncwarp();
    if (lane == 0) mbar_arrive(sb + S_RELW + 16);
    {
        const uint4 z = make_uint4(0, 0, 0, 0);
        const uint32_t c = (tid >> 6) & 1, cp = (tid >> 7) * COPY, k = (tid & 63) * 16;
        *reinterpret_cast<uint4*>((char*)(gx + pairL(RA, c, g) * 8192 + (i >> 2) * HALF + (i & 3) * 1024 + cp + k)) = z;
        *reinterpret_cast<uint4*>((char*)(gx + pairL(RC, c, g) * 8192 + (i >> 2) * HALF + (i & 3) * 1024 + cp + k)) = z;
        *reinterpret_cast<uint4*>((char*)(gx + pairL(RE, c, g) * 8192 + (i >> 2) * HALF + (i & 3) * 1024 + cp + k)) = z;
        if ((tid & 31) < 24) *reinterpret_cast<uint4*>((char*)(gx + pairG((tid >> 5) & 1, c, i) * 8192 + (g >> 3) * HALF + (g & 7) * 512 + cp + (tid & 31) * 16)) = z;
    }
    if (tid < 192) {
        int guard = 0;
        while (((or3(chk8(vs[0], 1), chk8(vs[1], 1), chk8(vs[2], 1)) | chk8(vs[3], 1) | chk8(vs[4], 1)) & 1) && ++guard < SPIN_LIMIT) {
#pragma unroll
            for (int b = 0; b < 5; b++)
#pragma unroll
                for (int s = 0; s < 8; s++) vs[b][s] = ldp32(srcS + b * 768 + s * 7680);
        }
        const uint32_t qpos = sb + S_QS + q_pos(tid);
#pragma unroll
        for (int b = 0; b < 4; b++) {
            sts_hi16(qpos + 512 * b, bfr(sum8(vs[b])));
        }
        stsf(sb + S_CSQ + 4 * tid, sum8(vs[4]));
    }
    if (tid < 192) stsf(sb + S_CSGU + 4 * tid, (chk8(cs2, 1) & 1) ? gather8<768>(gs + XS2 + g * 8 * 768 + tid * 4, 1) : sum8(cs2));
    bar_main();
    arrive_if(tid == 0, sb + S_QRDY);
    TSTAMP(2);

    uint32_t side;
    { int k = 0; while ((side = ldsvol(sb + S_SIDE)) == 0 && ++k < SPIN_LIMIT) {} }
    side = __shfl_sync(~0u, side & 1, 0) ^ 1;
    auto nearp = [&](uint32_t P) { return P * 8192 + ((side ^ __popc(P & PMASK)) & 1) * COPY; };
    const uint32_t td = __shfl_sync(~0u, tid, lane);
    const uint32_t wp = __shfl_sync(~0u, tid >> 5, 0);
    const uint32_t cc = wp >= 3;
#define IDS() uint32_t z_ = td; opaque(z_); const uint32_t ln = z_ & 31, q8 = ln >> 2, t4 = z_ & 3, n96 = z_ - 96 * cc, n80 = min(n96, 79u); (void)q8; (void)t4; (void)n80; (void)ln

    auto vaddr = [&](uint32_t (&voff)[3]) {
        IDS();
        const uint32_t key3 = 3 * ((ln & 7) + 2 * (ln & 8) + ((ln >> 1) & 8));
#pragma unroll
        for (int T = 0; T < 3; T++) {
            const uint32_t u = 3 * wp + T, r = key3 + (u >> 3);
            voff[T] = r * 128 + (((u ^ r) & 7) << 4);
        }
    };
    auto values = [&](uint32_t (&vf)[8][3][4], auto step, uint32_t ps, uint32_t col, uint32_t par) {
        IDS();
        const uint4 p = lds128(ps + 16 * ln);
        const uint2 mp = lds64(ps + PS_MAX + 8 * t4);
        const float mq = ldsf(ps + PS_MAX + 4 * q8);
        float acc[3][4] = {};
        float M = fmaxf(asf(mp.x), asf(mp.y)), lsum = 0.f, f0 = 0.f, f1 = 0.f;
#pragma unroll
        for (int s = 0; s < 8; s++) {
            step(s);
            const bool m = (q8 >> 1) == (s >> 1);
            const uint32_t b0 = m ? ((s & 1) ? p.z : p.x) : 0u, b1 = m ? ((s & 1) ? p.w : p.y) : 0u;
#pragma unroll
            for (int T = 0; T < 3; T++) mmaA(acc[T], vf[s][T], b0, b1);
            if (s < 2) M = fmaxf(M, __shfl_xor_sync(~0u, M, 1 + s));
            if (s == 1) {
                f0 = ex2(asf(mp.x) - M); f1 = ex2(asf(mp.y) - M);
                lsum = (((bf_lo(p.x) + bf_hi(p.x)) + (bf_lo(p.y) + bf_hi(p.y))) + ((bf_lo(p.z) + bf_hi(p.z)) + (bf_lo(p.w) + bf_hi(p.w)))) * ex2(mq - M);
            }
            if (s >= 2 && s < 7) lsum += __shfl_xor_sync(~0u, lsum, 1 << (s - 2));
        }
        char* pubA = gx + pairL(RA, col, g) * 8192 + (i >> 2) * HALF + (i & 3) * 1024 + (wp >> 1) * 256 + (wp & 1) * 96 + 32 * t4 + 4 * q8;
        const float r0 = fmaf(f0, acc[0][0], f1 * acc[0][3]), r1 = fmaf(f0, acc[1][0], f1 * acc[1][3]), r2 = fmaf(f0, acc[2][0], f1 * acc[2][3]);
        const bool hi = t4 & 2, od = t4 & 1;
        const float u0 = (hi ? r2 : r0) + __shfl_xor_sync(~0u, hi ? r0 : r2, 2), u1 = r1 + __shfl_xor_sync(~0u, r1, 2);
        const float o = (od ? u1 : u0) + __shfl_xor_sync(~0u, od ? u0 : u1, 1);
        stp32_if(t4 < 3 || ((wp & 1) && q8 < 2), pubA, t4 < 3 ? o : q8 ? lsum : M, par);
    };

#pragma unroll 1
    for (int ch = 0; ch < 5; ch++) {
        const uint32_t par0 = (ch + 1) & 1, par1 = ch & 1;
        uint32_t voff[3], vf[8][3][4];
        CSTAMP(0);
        if (ch < 4) {
            vaddr(voff);
            mbar_wait(sb + S_SCO, par1);
            TST(0);
            auto ldw = [&](int s) {
                mbar_wait(sb + S_FV + 8 * s, par1);
#pragma unroll
                for (int T = 0; T < 3; T++) ldsm4t(vf[s][T], voff[T] + (sb + v_place(ch, s) * SLOT));
            };
            uint2 u[4];
            values(vf, [&](int s) {
                if (s == 0) { ldw(0); ldw(1); __syncwarp(); arrive_if((td & 31) == 0, sb + S_RELR); }
                if (s == HOPA0 || s == HOPA1) {
                    IDS();
                    const XPtr polA = gx + nearp(pairL(RA, 1, g)) + (wp >> 2) * HALF + (wp & 3) * 256 + 8 * min(ln, 24u);
                    if (s == HOPA0) look_a(u, polA);
                    if (s == HOPA1 && ch > 0) {
                        hop_a(u, polA, par1, sb + S_OS + 192 * wp + 4 * ln + 96, ln < 24, 25);
                    }
                }
                if (PV1PIPE) { if (s >= 1 && s < 6) ldw(s + 1); if (s == 7) ldw(7); }
                else if (s >= 2) ldw(s);
            }, sb + S_PS, 0, par0);
            TST(1);
            CSTAMP(5);
        } else {
#pragma unroll
            for (int s = 0; s < 24; s++) { vf[s / 12][(s / 4) % 3][s & 3] = 0; opaque(vf[s / 12][(s / 4) % 3][s & 3]); }
        }
        const bool has0 = ch < 4, has1 = ch > 0;
        const bool actc = wp < 6 && (cc ? has1 : has0);
        const uint32_t parc = cc ? par1 : par0;
        XPtr pubB = gx;
        uint32_t rr;
        {
            IDS();
            const uint32_t c = ch == 4;
            const XPtr polA = gx + nearp(pairL(RA, c, g)) + (wp >> 2) * HALF + (wp & 3) * 256 + 8 * min(ln, 24u) + lag<DELAY_L>(sb);
            uint2 v[4];
            look_a(v, polA);
            uint32_t osa = sb + S_OS + 192 * wp + 96 * c + 4 * ln;
            uint32_t oa = sb + S_OS + 192 * wp + 96 * (q8 & 1) + 24 * t4, ra = sb + S_RED + 640 * wp + 320 * (t4 & 1) + 8 * q8;
            pubB = gx + pairG(0, cc, i) * 8192 + (g >> 3) * HALF + (g & 7) * 512 + n80 * 4;
            rr = sb + S_RED + 320 * cc + 4 * n80;
            keep(osa); keep(oa); keep(ra); keep(pubB); keep(rr);
            hop_a(v, polA, c ? par1 : par0, osa, ln < 24, 5 * ch);
            TST(2);
            CSTAMP(6);
            float acc[5][4] = {};
            const uint2 b0 = lds64(oa), b1 = lds64(oa + 8), b2 = lds64(oa + 16);
#pragma unroll
            for (int m = 0; m < 5; m++) mmaA(acc[m], Wo[m][0], b0.x, b0.y);
#pragma unroll
            for (int m = 0; m < 5; m++) mmaA(acc[m], Wo[m][1], b1.x, b1.y);
#pragma unroll
            for (int m = 0; m < 5; m++) mmaA(acc[m], Wo[m][2], b2.x, b2.y);
#pragma unroll
            for (int m = 0; m < 5; m++) sts64_if(t4 < 2, ra + 64 * m, t4 ? acc[m][1] : acc[m][0], t4 ? acc[m][3] : acc[m][2]);
        }
        CSTAMP(7);
        bar_main();
        CSTAMP(8);
        float x1 = 0.f;
        uint32_t xr;
        XPtr pubC = gx, pubC2 = gx;
        {
            IDS();
            if (actc) {
                uint32_t r[8];
#pragma unroll
                for (int s = 0; s < 8; s++) r[s] = lds32(rr + 640 * s);
                stp32_if(n96 < 80, pubB, sum8(r), parc);
                CSTAMP(9);
            }
            xr = sb + S_XB + 48 * (ln & 15);
            pubC = gx + pairL(RC, 0, g) * 8192 + (i >> 2) * HALF + (i & 3) * 1024 + (t4 & 1) * (32 * 8192);
            pubC2 = pubC + ((t4 & 2) ? 64 * oct2 + 4 * (wp & 1) + 8 * q8 : 768 + 2 * ((q8 + 1) & 6));
            pubC = pubC + (64 * oct + 8 * q8);
            keep(xr); keep(pubC); keep(pubC2);
            if (actc) {
                const char* polB = gx + nearp(pairG(0, cc, i)) + n80 * 4 + lag<DELAY_G>(sb);
                uint32_t xas = sb + S_XA + 192 + 192 * cc + a_pos(n80), xbs = sb + S_XB + 384 * cc + b_pos<40>(n80);
                x1 = cc ? ldsf(sb + S_XCAR + 4 * n80) : bf_lo(lds16(sb + S_X0 + 160 * (ch & 3) + 2 * n80));
                keep(xas); keep(xbs); keep(x1);
                x1 = bfr(x1 + bfr(gather16(polB, parc, 5 * ch + 1)));
                CSTAMP(10);
                sts_hi16(xbs, x1);
                sts_hi16(xas, x1);
            }
        }
        bar_main();
        TST(3);
        CSTAMP(11);
        auto stats = [&](uint32_t xa, const uint4& b, uint32_t b4) {
            float a0[4] = {}, a1[4] = {};
            const uint4 p0 = lds128(xa), p1 = lds128(xa + 16);
            const uint2 p2 = lds64(xa + 32);
            mmaV(a0, p0, b.x, b.y); mmaV(a1, p1, b.z, b.w); mma8(a0, p2.x, p2.y, b4);
            return (a0[0] + a0[3]) + (a1[0] + a1[3]);
        };
        {
            IDS();
            const uint4 b = lds128(xr);
            const uint32_t b4 = lds32(xr + 16);
            float st = 0.f;
            if (wp == 7) st = stats(xr + (S_XA - S_XB), b, b4);
            float acc[3][4] = {};
            mul80(acc, Wgu, b, b4);
            const bool on = (t4 & 1) ? has1 : has0;
            const uint32_t par = (t4 & 1) ? par1 : par0;
            stp64_if(on && t4 < 2, pubC, tagw(acc[0][0] + acc[0][3], par), tagw(acc[1][0] + acc[1][3], par));
            stp32_if(on && (t4 >= 2 || (wp == 7 && q8 < 4 && q8 != 2 - t4)), pubC2, t4 >= 2 ? acc[2][0] + acc[2][3] : st, par);
        }
        sts32_if(td == 255, sb + S_GATE, ch + 1);
        CSTAMP(12);
        {
            IDS();
            const uint32_t wa = sb + S_WD + ((ln & 7) + 48 * ((ln >> 3) & 1) + 8 * (ln >> 4)) * 160 + (wp < 7 ? 16 * wp : 128);
            uint32_t ha = sb + S_HS + 48 * (ln & 15);
            XPtr pubD = gx + pairG(1, t4 & 1, i) * 8192 + (g >> 3) * HALF + (g & 7) * 512 + (wp < 7 ? 32 * wp : 256) + 16 * (t4 & 2) + 4 * q8;
            if (ch == 0) mbar_wait(sb + S_WFULL + 80, 0);
            auto down = [&](const uint32_t (&W)[3][4], const uint4& h0, const uint2& h1) {
                float a0[4] = {}, a1[4] = {}, a2[4] = {};
                mmaA(a0, W[0], h0.x, h0.y); mmaA(a1, W[1], h0.z, h0.w); mmaA(a2, W[2], h1.x, h1.y);
                return ((a0[0] + a0[3]) + (a1[0] + a1[3])) + (a2[0] + a2[3]);
            };
            if (wp < 6) {
                uint32_t Wd[3][4];
#pragma unroll
                for (int s = 0; s < 3; s++) ldsm4t(Wd[s], wa + s * 2560);
                uint32_t hsa = sb + S_HS + 384 * cc + b_pos<48>(n96);
                const uint2 cs = lds64(sb + S_CSGU + 8 * n96);
                keep(ha); keep(pubD); keep(hsa);
                if (actc) {
                    const XPtr src0 = gx + nearp(pairL(RC, cc, g)) + lag<DELAY_C>(sb);
                    const char* srcv = src0 + 8 * n96;
                    const char* src = src0 + (ln & 1) * HALF;
                    uint2 v[8], st[4];
                    float sx, sq, pg, pu;
                    int guard = 0;
                    bool again;
                    do {
#pragma unroll
                        for (int s = 0; s < 4; s++) st[s] = ldp64(src + 768 + s * 1024);
#pragma unroll
                        for (int s = 0; s < 8; s++) v[s] = ldp64(srcv + (s >> 2) * HALF + (s & 3) * 1024);
                        sx = (asf(st[0].x) + asf(st[1].x)) + (asf(st[2].x) + asf(st[3].x)); sq = (asf(st[0].y) + asf(st[1].y)) + (asf(st[2].y) + asf(st[3].y));
                        sx += __shfl_xor_sync(~0u, sx, 1); sq += __shfl_xor_sync(~0u, sq, 1);
                        again = __any_sync(~0u, or3(chk4(st, parc), chk8(v, parc), chk8y(v, parc)) & 1);
                        pg = sum8x(v); pu = sum8y(v);
                        keep(pg); keep(pu);
                    } while (again && ++guard < SPIN_LIMIT);
                    CSTAMP(13);
                    SWEEPS(5 * ch + 2, guard);
                    float mean, den; ln_stats(sx, sq, mean, den);
                    const float rd = rcp(den);
                    const float gt = bfr(fmaf(-mean, asf(cs.x), pg) * rd), up = bfr(fmaf(-mean, asf(cs.y), pu) * rd);
                    const float h = bfr(bfr(gt * sigmoidf_(gt)) * up);
                    sts_hi16(hsa, h);
                    CSTAMP(14);
                }
                bar_main();
                TST(4);
                CSTAMP(15);
                const uint4 h0 = lds128(ha);
                const uint2 h1 = lds64(ha + 16);
                stp32_if(t4 < 2 && (t4 ? has1 : has0), pubD, down(Wd, h0, h1), t4 ? par1 : par0);
            } else {
                uint32_t Wd[2][3][4];
#pragma unroll
                for (int s = 0; s < 6; s++) ldsm4t(Wd[s / 3][s % 3], wa + (s / 3) * 16 + (s % 3) * 2560);
                keep(ha); keep(pubD);
                if (wp == 6 ? has0 : has1) {
                    const uint32_t par = wp == 6 ? par0 : par1;
                    const char* src = gx + nearp(pairL(RC, wp - 6, g)) + 768 + (ln & 4) * (HALF / 4) + (ln & 3) * 1024 + 4 * min(ln >> 3, 2u) + lag<DELAY_C>(sb);
                    const float swr = ldsf(sb + S_SWR);
                    uint32_t v;
                    int guard = 0;
                    do v = ldp32(src); while (__any_sync(~0u, (v ^ par) & 1) && ++guard < SPIN_LIMIT);
                    float sx = asf(v);
                    sx += __shfl_xor_sync(~0u, sx, 1); sx += __shfl_xor_sync(~0u, sx, 2); sx += __shfl_xor_sync(~0u, sx, 4);
                    const float sq = __shfl_sync(~0u, sx, 8), xw = __shfl_sync(~0u, sx, 16);
                    float mean, den; ln_stats(sx, sq, mean, den);
                    const float r = bfr(fmaf(-mean, swr, xw) * rcp(den));
                    sts64_if(ln == 0, sb + S_STAT + 16 * (wp - 6), mean, den);
                    sts32_if(ln == 0, sb + S_STAT + 16 * (wp - 6) + 8, __float_as_uint(bfr(sigmoidf_(r))));
                }
                bar_main();
                const uint4 h0 = lds128(ha);
                const uint2 h1 = lds64(ha + 16);
                const float d0 = down(Wd[0], h0, h1), d1 = down(Wd[1], h0, h1);
                stp32_if((t4 & 1) ? has1 : has0, pubD, (t4 & 2) ? d1 : d0, (t4 & 1) ? par1 : par0);
            }
        }
        CSTAMP(16);
        XPtr pubE = gx;
        {
            IDS();
            pubE = gx + pairL(RE, 0, g) * 8192 + (i >> 2) * HALF + (i & 3) * 1024 +
                   (t4 < 3 ? (wp >> 2) * (32 * 8192) + 192 * (wp & 3) + 64 * t4 + 8 * q8 : (q8 >> 2) * (32 * 8192) + 768 + 4 * (q8 & 1));
            xr = sb + S_XB + 48 * (ln & 7);
            keep(xr); keep(pubE);
            if (actc && (cc == 0 || g == 0)) {
                const char* polD = gx + nearp(pairG(1, cc, i)) + n80 * 4 + lag<DELAY_D>(sb);
                const uint4 st = lds128(sb + S_STAT + 16 * cc);
                float lnx = bfr(__fdiv_rn(bfr(x1 - asf(st.x)), asf(st.y)));
                unsigned short* po = reinterpret_cast<unsigned short*>(P.out) + 640 * (ch - 1) + 80 * i + n80;
                uint32_t xas = sb + S_XA + 192 + a_pos(n80), xbs = sb + S_XB + b_pos<40>(n80), xca = sb + S_XCAR + 4 * n80;
                keep(lnx); keep(po); keep(xca); keep(xas); keep(xbs);
                const float y = bfr(bfr(gather16(polD, parc, 5 * ch + 3)) * asf(st.z));
                CSTAMP(17);
                const float x2 = bfr(x1 + bfr(lnx + y));
                if (cc) *po = (unsigned short)(__float_as_uint(x2) >> 16);
                else {
                    sts_hi16(xbs, x2);
                    sts_hi16(xas, x2);
                    stsf(xca, x2);
                }
            }
        }
        CSTAMP(18);
        if (!has0) break;
        bar_main();
        TST(5);
        CSTAMP(19);
        {
            IDS();
            const uint4 b = lds128(xr);
            const uint32_t b4 = lds32(xr + 16);
            if (wp == 7) stp32_if(t4 == 3 && !(q8 & 2), pubE, stats(xr + (S_XA - S_XB), b, b4), par0);
            float acc[6][4] = {};
            mul80(acc, Wq, b, b4);
            const float v0 = sel4(t4, acc[0][0] + acc[0][3], acc[2][0] + acc[2][3], acc[4][0] + acc[4][3], 0.f);
            const float v1 = sel4(t4, acc[1][0] + acc[1][3], acc[3][0] + acc[3][3], acc[5][0] + acc[5][3], 0.f);
            stp64_if(t4 < 3, pubE, tagw(v0, par0), tagw(v1, par0));
        }
        CSTAMP(20);
        {
            IDS();
            const uint32_t ua = sb + k_place(ch, wp & 6) * SLOT + (wp & 1) * UNIT;
            uint32_t kf[12][2][4];
            auto ldk = [&](int s) { const uint32_t a = (ua + k_off(ln, s >> 2)) ^ ((s & 3) * 32); ldsm4(kf[s][0], a); ldsm4(kf[s][1], a + SLOT); };
            mbar_wait(sb + S_FK + 8 * (wp & 6), par1); mbar_wait(sb + S_FK + 8 * (wp | 1), par1);
#pragma unroll
            for (int s = 0; s < KPRE; s++) ldk(s);
            if (wp < 6) {
                const XPtr src0 = gx + nearp(pairL(RE, i >> 2, g)) + lag<DELAY_E>(sb);
                const char* srcv = src0 + 4 * td;
                const char* src = src0 + (ln & 1) * HALF;
                const float cs = ldsf(sb + S_CSQ + 4 * td);
                uint32_t v[8]; uint2 st[4];
                float sx, sq, qs;
                int guard = 0;
                bool again;
                do {
#pragma unroll
                    for (int s = 0; s < 4; s++) st[s] = ldp64(src + 768 + s * 1024);
#pragma unroll
                    for (int s = 0; s < 8; s++) v[s] = ldp32(srcv + (s >> 2) * HALF + (s & 3) * 1024);
                    sx = (asf(st[0].x) + asf(st[1].x)) + (asf(st[2].x) + asf(st[3].x)); sq = (asf(st[0].y) + asf(st[1].y)) + (asf(st[2].y) + asf(st[3].y));
                    sx += __shfl_xor_sync(~0u, sx, 1); sq += __shfl_xor_sync(~0u, sq, 1);
                    again = __any_sync(~0u, (chk8(v, par0) | chk4(st, par0)) & 1);
                    qs = sum8(v);
                    keep(qs);
                } while (again && ++guard < SPIN_LIMIT);
                CSTAMP(21);
                float mean, den; ln_stats(sx, sq, mean, den);
                const float q = bfr(fmaf(-mean, cs, qs) * rcp(den));
                sts_hi16(sb + S_QS + 512 * ch + q_pos(td), q);
                SWEEPS(5 * ch + 4, guard);
                CSTAMP(22);
            }
            __syncwarp();
#pragma unroll
            for (int s = KPRE; s < KPRE + KPRE2; s++) ldk(s);
            bar_main();
            TST(6);
            CSTAMP(1);
            const uint4 q = lds128(sb + S_QS + 512 * ch + 16 * ln);
            float acc[2][4] = {};
            constexpr int D = KPRE + KPRE2;
#pragma unroll
            for (int s = 0; s < 12; s++) {
                const bool m = q8 == (s & 7);
                const uint32_t b0 = m ? (s < 8 ? q.x : q.z) : 0u, b1 = m ? (s < 8 ? q.y : q.w) : 0u;
                mmaA(acc[0], kf[s][0], b0, b1);
                mmaA(acc[1], kf[s][1], b0, b1);
                if (s + D < 12) ldk(s + D);
            }
            vaddr(voff);
            auto ldv = [&](int s) {
#pragma unroll
                for (int T = 0; T < 3; T++) ldsm4t(vf[s][T], voff[T] + (sb + v_place(ch, s) * SLOT));
            };
            ldv(2); ldv(3);
            probs(acc[0][0] + acc[0][1], acc[0][2] + acc[0][3], acc[1][0] + acc[1][1], acc[1][2] + acc[1][3], sb + S_PS + PS_PASS, wp, ln, [&] {
                CSTAMP(2);
                arrive_if(ln == 0, sb + S_RELK);
            });
            bar_main();
            TST(10);
            CSTAMP(4);
            values(vf, [&](int s) { if (s >= 1 && s < 5) ldv(s + 3); }, sb + S_PS + PS_PASS, 1, par0);
            arrive_if(ln == 0, sb + S_RELV);
        }
        TST(11);
        CSTAMP(23);
    }
    sts32_if(td == 255, sb + S_GATE, 6);
    TSTAMP(3);
}

typedef CUresult (*EncodeFn)(CUtensorMap*, CUtensorMapDataType, cuuint32_t, void*, const cuuint64_t*, const cuuint64_t*, const cuuint32_t*,
                             const cuuint32_t*, CUtensorMapInterleave, CUtensorMapSwizzle, CUtensorMapL2promotion, CUtensorMapFloatOOBfill);

void make_map(EncodeFn enc, CUtensorMap* m, const void* base, uint64_t cols, uint64_t rows, uint32_t box_cols, uint32_t box_rows, bool swizzle) {
    cuuint64_t dims[2] = {cols, rows};
    cuuint64_t strides[1] = {cols * 2};
    cuuint32_t box[2] = {box_cols, box_rows};
    cuuint32_t es[2] = {1, 1};
    enc(m, CU_TENSOR_MAP_DATA_TYPE_BFLOAT16, 2, const_cast<void*>(base), dims, strides, box, es, CU_TENSOR_MAP_INTERLEAVE_NONE,
        swizzle ? CU_TENSOR_MAP_SWIZZLE_128B : CU_TENSOR_MAP_SWIZZLE_NONE, swizzle ? CU_TENSOR_MAP_L2_PROMOTION_NONE : WPROMO, CU_TENSOR_MAP_FLOAT_OOB_FILL_NONE);
}

}

extern "C" void kernel_launch(void* const* d_in, const int* in_sizes, int n_in, void* d_out, int out_size) {
    (void)in_sizes; (void)n_in; (void)out_size;
    static EncodeFn enc = nullptr;
    if (!enc) {
        void* f = nullptr;
        cudaDriverEntryPointQueryResult q;
        cudaGetDriverEntryPoint("cuTensorMapEncodeTiled", &f, cudaEnableDefault, &q);
        enc = (EncodeFn)f;
        cudaFuncSetAttribute(fused_kernel, cudaFuncAttributeMaxDynamicSharedMemorySize, SMEM_BYTES);
    }
    Params P;
    P.x = (const __nv_bfloat16*)d_in[0]; P.k = (const __nv_bfloat16*)d_in[1]; P.v = (const __nv_bfloat16*)d_in[2];
    P.wr = (const __nv_bfloat16*)d_in[6];
    P.out = (__nv_bfloat16*)d_out;
    Maps M;
    make_map(enc, &M.k, P.k, 64, (uint64_t)12 * KV_BATCH_KEYS, 64, 48, true);
    make_map(enc, &M.v, P.v, 64, (uint64_t)12 * KV_BATCH_KEYS, 64, 96, true);
    make_map(enc, &M.wq, d_in[3], 6144, 640, 192, 40, false);
    make_map(enc, &M.wo, d_in[4], 640, 6144, 80, 96, false);
    make_map(enc, &M.wg, d_in[7], 1536, 640, 96, 80, false);
    make_map(enc, &M.wu, d_in[8], 1536, 640, 96, 80, false);
    make_map(enc, &M.wd, d_in[9], 640, 1536, 80, 96, false);
    fused_kernel<<<NCTA, NTHR, SMEM_BYTES, cudaStreamPerThread>>>(P, M);
}
```

```cpp
#include <cuda_runtime.h>
#include <cuda.h>
#include <cuda_bf16.h>
#include <stdint.h>
#include <type_traits>

namespace {

constexpr int NCTA = 128;
constexpr int NTHR = 384;
constexpr int UNIT = 6144;
constexpr int SLOT = 12288;
#define TAU 4100
#define TAUW 4000
#define TMIN 2400
#define T_LEAD 0
#define WIN_W 3
#define WIN_S 4
#define WIN_U 10
#define RFR_ON 1
#define KRE_N1 0
#define KRE_TAU1 2500
#define RFR_TAU 6400
#define VPF 5
#define KRE_GATE 0
#define KRE_GATE3 KRE_GATE
#define JFREE 16
#define TFREE 0
#define KRE_TAU 4000
#define KRE_TAU3 KRE_TAU
#define HDEPTH 3
#define SPEC 1
#define PV1PIPE 0
#define HOPA0 7
#define HOPA1 7
#define WPROMO CU_TENSOR_MAP_L2_PROMOTION_NONE
#define KPRE 1
#define KPRE2 2
#define DELAY_G 6
#define DELAY_L 5
#define DELAY_C 3
#define DELAY_D 6
#define DELAY_E 3
#define REG_LO "40"
#define REG_HI "232"
#define SPIN_LOG 17
constexpr int SPIN_LIMIT = 1 << SPIN_LOG;

__host__ __device__ constexpr uint32_t pairL(uint32_t region, uint32_t c, uint32_t g) { return (g & 1) | ((g >> 1) << 2) | (c << 5) | (region << 6); }
__host__ __device__ constexpr uint32_t pairG(uint32_t d, uint32_t c, uint32_t i) { return (i & 1) | ((i >> 1) << 2) | (d << 4) | (c << 5) | (3u << 6); }
constexpr uint32_t RA = 0, RC = 1, RE = 2, HALF = 16384, COPY = 4096, PMASK = 0x59;
constexpr uint32_t XS = 0;
constexpr uint32_t XS2 = XS + 128 * 7680;
constexpr uint32_t XSEND = XS2 + 128 * 768;
__device__ uint4 g_s[XSEND / 16];
__device__ uint4 g_x[(4u << 20) / 16];
#define SWEEPS(k, n) do {} while (0)

constexpr uint32_t S_WD = 16 * SLOT;
constexpr uint32_t S_DUMMY = S_WD + 15360;
constexpr uint32_t S_BAR = S_DUMMY + 4096;
constexpr uint32_t S_FV = S_BAR, S_FK = S_FV + 64, S_RING = S_FK + 64, S_DBAR = S_RING + 48, S_WFULL = S_DBAR + 32, S_QRDY = S_WFULL + 88;
constexpr uint32_t S_RELK = S_QRDY + 8, S_RELV = S_RELK + 8, S_RELR = S_RELV + 8, S_RELW = S_RELR + 8, S_SCO = S_RELW + 24;
constexpr uint32_t S_ZERO = S_SCO + 8;
constexpr uint32_t S_KF = S_SCO + 24;
constexpr uint32_t S_TOK = S_KF + 8;
constexpr uint32_t S_SIDE = S_TOK + 24, S_GATE = S_SIDE + 4;
constexpr uint32_t S_STAT = S_GATE + 4, S_SWR = S_STAT + 16;
constexpr uint32_t S_XCAR = S_STAT + 32;
constexpr uint32_t S_CSQ = S_XCAR + 320;
constexpr uint32_t S_CSGU = S_CSQ + 768;
constexpr uint32_t S_RED = S_CSGU + 768;
constexpr uint32_t S_L0 = S_RED;
constexpr uint32_t S_OS = S_RED + 5120;
constexpr uint32_t S_PS = S_OS + 1536;
constexpr uint32_t PS_MAX = 512, PS_PASS = 544;
constexpr uint32_t S_QS = S_PS + 2 * PS_PASS;
constexpr uint32_t S_XB = S_QS + 2048;
constexpr uint32_t S_XA = S_XB + 768;
constexpr uint32_t S_HS = S_XA + 768;
constexpr uint32_t S_X0 = S_HS + 768;
constexpr uint32_t S_SC = S_X0 + 640;
constexpr uint32_t S_TM = S_SC + 512;
constexpr int SMEM_BYTES = S_TM + 256;
static_assert(SMEM_BYTES <= 232448 && S_STAT % 16 == 0 && S_RED % 16 == 0 && S_XB % 16 == 0 && S_HS % 16 == 0 && S_PS % 16 == 0 && S_QS % 16 == 0, "smem");
static_assert(S_SCO == S_BAR + 44 * 8 && S_RELK == S_BAR + 38 * 8, "barriers");
constexpr uint32_t ST_WQ = 3 * SLOT, ST_WG = 8 * SLOT, ST_WO = 11 * SLOT;

__device__ __forceinline__ uint32_t smem_u32(const void* p) { return (uint32_t)__cvta_generic_to_shared(p); }
__device__ __forceinline__ void mbar_init(uint32_t bar, uint32_t cnt) { asm volatile("mbarrier.init.shared::cta.b64 [%0], %1;" :: "r"(bar), "r"(cnt) : "memory"); }
__device__ __forceinline__ void mbar_expect(uint32_t bar, uint32_t bytes) { asm volatile("mbarrier.arrive.expect_tx.shared::cta.b64 _, [%0], %1;" :: "r"(bar), "r"(bytes) : "memory"); }
__device__ __forceinline__ void mbar_arrive(uint32_t bar) { asm volatile("mbarrier.arrive.shared::cta.b64 _, [%0];" :: "r"(bar) : "memory"); }
__device__ __forceinline__ bool mbar_try(uint32_t bar, uint32_t parity) {
    uint32_t ok;
    asm volatile("{\n .reg .pred p;\n mbarrier.try_wait.parity.shared::cta.b64 p, [%1], %2;\n selp.u32 %0, 1, 0, p;\n}" : "=r"(ok) : "r"(bar), "r"(parity) : "memory");
    return ok != 0;
}
__device__ __forceinline__ bool mbar_test(uint32_t bar, uint32_t parity) {
    uint32_t ok;
    asm volatile("{\n .reg .pred p;\n mbarrier.test_wait.parity.shared::cta.b64 p, [%1], %2;\n selp.u32 %0, 1, 0, p;\n}" : "=r"(ok) : "r"(bar), "r"(parity) : "memory");
    return ok != 0;
}
__device__ __forceinline__ void mbar_wait(uint32_t bar, uint32_t parity) {
    int n = 0;
    while (!mbar_try(bar, parity) && ++n < SPIN_LIMIT) {}
}
__device__ __forceinline__ unsigned long long gtime() { unsigned long long t; asm volatile("mov.u64 %0, %globaltimer;" : "=l"(t)); return t; }
__device__ __forceinline__ uint32_t gtime32() { uint32_t t; asm volatile("mov.u32 %0, %globaltimer_lo;" : "=r"(t)); return t; }
__device__ __forceinline__ void bar_main() { __syncwarp(); asm volatile("bar.sync 1, 256;" ::: "memory"); }

__device__ __forceinline__ void mma16816(float (&c)[4], uint32_t a0, uint32_t a1, uint32_t a2, uint32_t a3, uint32_t b0, uint32_t b1) {
    asm("mma.sync.aligned.m16n8k16.row.col.f32.bf16.bf16.f32 {%0,%1,%2,%3}, {%4,%5,%6,%7}, {%8,%9}, {%0,%1,%2,%3};"
        : "+f"(c[0]), "+f"(c[1]), "+f"(c[2]), "+f"(c[3]) : "r"(a0), "r"(a1), "r"(a2), "r"(a3), "r"(b0), "r"(b1));
}
__device__ __forceinline__ void mmaA(float (&c)[4], const uint32_t (&a)[4], uint32_t b0, uint32_t b1) { mma16816(c, a[0], a[1], a[2], a[3], b0, b1); }
__device__ __forceinline__ void mmaAv(float (&c)[4], const uint32_t (&a)[4], uint32_t b0, uint32_t b1) {
    asm volatile("mma.sync.aligned.m16n8k16.row.col.f32.bf16.bf16.f32 {%0,%1,%2,%3}, {%4,%5,%6,%7}, {%8,%9}, {%0,%1,%2,%3};"
        : "+f"(c[0]), "+f"(c[1]), "+f"(c[2]), "+f"(c[3]) : "r"(a[0]), "r"(a[1]), "r"(a[2]), "r"(a[3]), "r"(b0), "r"(b1) : "memory");
}
__device__ __forceinline__ void mma8(float (&c)[4], uint32_t a0, uint32_t a1, uint32_t b0) {
    asm("mma.sync.aligned.m16n8k8.row.col.f32.bf16.bf16.f32 {%0,%1,%2,%3}, {%4,%5}, {%6}, {%0,%1,%2,%3};"
        : "+f"(c[0]), "+f"(c[1]), "+f"(c[2]), "+f"(c[3]) : "r"(a0), "r"(a1), "r"(b0));
}
struct W80 { uint32_t a[2][4], c[2]; };
template <int N> __device__ __forceinline__ void mul80(float (&acc)[N][4], const W80 (&W)[N], const uint4& b, uint32_t b4) {
#pragma unroll
    for (int m = 0; m < N; m++) mmaA(acc[m], W[m].a[0], b.x, b.y);
#pragma unroll
    for (int m = 0; m < N; m++) mmaA(acc[m], W[m].a[1], b.z, b.w);
#pragma unroll
    for (int m = 0; m < N; m++) mma8(acc[m], W[m].c[0], W[m].c[1], b4);
}
__device__ __forceinline__ void ldsm2t(uint32_t (&r)[2], uint32_t addr) {
    asm volatile("ldmatrix.sync.aligned.m8n8.x2.trans.shared.b16 {%0,%1}, [%2];" : "=r"(r[0]), "=r"(r[1]) : "r"(addr) : "memory");
}
__device__ __forceinline__ void mmaV(float (&c)[4], const uint4& a, uint32_t b0, uint32_t b1) { mma16816(c, a.x, a.y, a.z, a.w, b0, b1); }
__device__ __forceinline__ void ldsm4(uint32_t (&r)[4], uint32_t addr) {
    asm volatile("ldmatrix.sync.aligned.m8n8.x4.shared.b16 {%0,%1,%2,%3}, [%4];" : "=r"(r[0]), "=r"(r[1]), "=r"(r[2]), "=r"(r[3]) : "r"(addr) : "memory");
}
__device__ __forceinline__ void ldsm4t(uint32_t (&r)[4], uint32_t addr) {
    asm volatile("ldmatrix.sync.aligned.m8n8.x4.trans.shared.b16 {%0,%1,%2,%3}, [%4];" : "=r"(r[0]), "=r"(r[1]), "=r"(r[2]), "=r"(r[3]) : "r"(addr) : "memory");
}
__device__ __forceinline__ uint32_t lds16(uint32_t a) { uint16_t v; asm volatile("ld.shared.u16 %0, [%1];" : "=h"(v) : "r"(a) : "memory"); return v; }
__device__ __forceinline__ uint32_t lds32(uint32_t a) { uint32_t v; asm volatile("ld.shared.u32 %0, [%1];" : "=r"(v) : "r"(a) : "memory"); return v; }
__device__ __forceinline__ float ldsf(uint32_t a) { return __uint_as_float(lds32(a)); }
__device__ __forceinline__ uint2 lds64(uint32_t a) { uint2 v; asm volatile("ld.shared.v2.u32 {%0,%1}, [%2];" : "=r"(v.x), "=r"(v.y) : "r"(a) : "memory"); return v; }
__device__ __forceinline__ uint4 lds128(uint32_t a) { uint4 v; asm volatile("ld.shared.v4.u32 {%0,%1,%2,%3}, [%4];" : "=r"(v.x), "=r"(v.y), "=r"(v.z), "=r"(v.w) : "r"(a) : "memory"); return v; }
__device__ __forceinline__ int ldsvol(uint32_t a) { int v; asm volatile("ld.volatile.shared.u32 %0, [%1];" : "=r"(v) : "r"(a) : "memory"); return v; }
__device__ __forceinline__ void stsvol(uint32_t a, int v) { asm volatile("st.volatile.shared.u32 [%0], %1;" :: "r"(a), "r"(v) : "memory"); }
__device__ __forceinline__ void sts_hi16(uint32_t a, float v) { asm volatile("{\n .reg .b16 lo, hi;\n mov.b32 {lo, hi}, %1;\n st.shared.u16 [%0], hi;\n}" :: "r"(a), "r"(__float_as_uint(v)) : "memory"); }
__device__ __forceinline__ void sts32(uint32_t a, uint32_t v) { asm volatile("st.shared.u32 [%0], %1;" :: "r"(a), "r"(v) : "memory"); }
__device__ __forceinline__ void stsf(uint32_t a, float v) { sts32(a, __float_as_uint(v)); }
__device__ __forceinline__ void sts64(uint32_t a, uint32_t x, uint32_t y) { asm volatile("st.shared.v2.u32 [%0], {%1,%2};" :: "r"(a), "r"(x), "r"(y) : "memory"); }

__device__ __forceinline__ void sts_hi16_if(bool p, uint32_t a, float v) {
    asm volatile("{\n .reg .pred p;\n .reg .b16 lo, hi;\n setp.ne.u32 p, %2, 0;\n mov.b32 {lo, hi}, %1;\n @p st.shared.u16 [%0], hi;\n}" :: "r"(a), "r"(__float_as_uint(v)), "r"((uint32_t)p) : "memory");
}
__device__ __forceinline__ void sts32_if(bool p, uint32_t a, uint32_t v) {
    asm volatile("{\n .reg .pred p;\n setp.ne.u32 p, %2, 0;\n @p st.shared.u32 [%0], %1;\n}" :: "r"(a), "r"(v), "r"((uint32_t)p) : "memory");
}
__device__ __forceinline__ void sts64_if(bool p, uint32_t a, float x, float y) {
    asm volatile("{\n .reg .pred p;\n setp.ne.u32 p, %3, 0;\n @p st.shared.v2.f32 [%0], {%1,%2};\n}" :: "r"(a), "f"(x), "f"(y), "r"((uint32_t)p) : "memory");
}
__device__ __forceinline__ void arrive_if(bool p, uint32_t bar) {
    asm volatile("{\n .reg .pred p;\n setp.ne.u32 p, %1, 0;\n @p mbarrier.arrive.shared::cta.b64 _, [%0];\n}" :: "r"(bar), "r"((uint32_t)p) : "memory");
}
__device__ __forceinline__ void opaque(uint32_t& v) { asm volatile("" : "+r"(v)); }
__device__ __forceinline__ void keep(uint32_t& v) { asm volatile("" : "+r"(v)); }
__device__ __forceinline__ void keep(float& v) { asm volatile("" : "+f"(v)); }
template <class T> __device__ __forceinline__ void keep(T*& v) { asm volatile("" : "+l"(v)); }

__device__ __forceinline__ uint32_t ldp32(const char* p) { uint32_t v; asm volatile("ld.relaxed.gpu.global.u32 %0, [%1];" : "=r"(v) : "l"(p) : "memory"); return v; }
__device__ __forceinline__ uint2 ldp64(const char* p) {
    uint2 v; asm volatile("{\n .reg .b64 d;\n ld.relaxed.gpu.global.b64 d, [%2];\n mov.b64 {%0,%1}, d;\n}" : "=r"(v.x), "=r"(v.y) : "l"(p) : "memory"); return v;
}
__device__ __forceinline__ uint32_t tagw(float f, uint32_t par) { return (__float_as_uint(f) & ~1u) | par; }
__device__ __forceinline__ void stp32(char* p, float a, uint32_t par) { asm volatile("st.relaxed.gpu.global.u32 [%0], %1;" :: "l"(p), "r"(tagw(a, par)) : "memory"); }
__device__ __forceinline__ void stp64(char* p, float a, float b, uint32_t par) {
    asm volatile("{\n .reg .b64 d;\n mov.b64 d, {%1,%2};\n st.relaxed.gpu.global.b64 [%0], d;\n}" :: "l"(p), "r"(tagw(a, par)), "r"(__float_as_uint(b)) : "memory");
}
__device__ __forceinline__ void stp32_if(bool p, char* d, float a, uint32_t par) {
    asm volatile("{\n .reg .pred p;\n setp.ne.u32 p, %2, 0;\n @p st.relaxed.gpu.global.u32 [%0], %1;\n @p st.relaxed.gpu.global.u32 [%0+4096], %1;\n}" :: "l"(d), "r"(tagw(a, par)), "r"((uint32_t)p) : "memory");
}
__device__ __forceinline__ void stp64_if(bool p, char* d, uint32_t lo, uint32_t hi) {
    asm volatile("{\n .reg .pred p;\n .reg .b64 d;\n setp.ne.u32 p, %3, 0;\n mov.b64 d, {%1,%2};\n @p st.relaxed.gpu.global.b64 [%0], d;\n @p st.relaxed.gpu.global.b64 [%0+4096], d;\n}" :: "l"(d), "r"(lo), "r"(hi), "r"((uint32_t)p) : "memory");
}
__device__ __forceinline__ uint32_t chk2(uint32_t a, uint32_t b, uint32_t par) { uint32_t r; asm("lop3.b32 %0, %1, %2, %3, 0x7E;" : "=r"(r) : "r"(a), "r"(b), "r"(par)); return r; }
__device__ __forceinline__ uint32_t or3(uint32_t a, uint32_t b, uint32_t c) { uint32_t r; asm("lop3.b32 %0, %1, %2, %3, 0xFE;" : "=r"(r) : "r"(a), "r"(b), "r"(c)); return r; }
__device__ __forceinline__ uint32_t chk8(const uint32_t (&v)[8], uint32_t par) { return or3(chk2(v[0], v[1], par), chk2(v[2], v[3], par), or3(chk2(v[4], v[5], par), chk2(v[6], v[7], par), 0)); }
__device__ __forceinline__ uint32_t chk8(const uint2 (&v)[8], uint32_t par) { return or3(chk2(v[0].x, v[1].x, par), chk2(v[2].x, v[3].x, par), or3(chk2(v[4].x, v[5].x, par), chk2(v[6].x, v[7].x, par), 0)); }
__device__ __forceinline__ uint32_t chk8y(const uint2 (&v)[8], uint32_t par) { return or3(chk2(v[0].y, v[1].y, par), chk2(v[2].y, v[3].y, par), or3(chk2(v[4].y, v[5].y, par), chk2(v[6].y, v[7].y, par), 0)); }
__device__ __forceinline__ uint32_t chk4(const uint2 (&v)[4], uint32_t par) { return or3(chk2(v[0].x, v[0].y, par), chk2(v[1].x, v[1].y, par), or3(chk2(v[2].x, v[2].y, par), chk2(v[3].x, v[3].y, par), 0)); }
__device__ __forceinline__ float asf(uint32_t v) { return __uint_as_float(v); }
__device__ __forceinline__ float sum8(const uint32_t (&v)[8]) { return ((asf(v[0]) + asf(v[1])) + (asf(v[2]) + asf(v[3]))) + ((asf(v[4]) + asf(v[5])) + (asf(v[6]) + asf(v[7]))); }
__device__ __forceinline__ float sum8x(const uint2 (&v)[8]) { return ((asf(v[0].x) + asf(v[1].x)) + (asf(v[2].x) + asf(v[3].x))) + ((asf(v[4].x) + asf(v[5].x)) + (asf(v[6].x) + asf(v[7].x))); }
__device__ __forceinline__ float sum8y(const uint2 (&v)[8]) { return ((asf(v[0].y) + asf(v[1].y)) + (asf(v[2].y) + asf(v[3].y))) + ((asf(v[4].y) + asf(v[5].y)) + (asf(v[6].y) + asf(v[7].y))); }

__device__ __forceinline__ uint32_t pack2(float lo, float hi) { uint32_t r; asm("cvt.rn.bf16x2.f32 %0, %1, %2;" : "=r"(r) : "f"(hi), "f"(lo)); return r; }
__device__ __forceinline__ float bfr(float x) { return __uint_as_float(pack2(0.0f, x)); }
__device__ __forceinline__ float ex2(float x) { float r; asm("ex2.approx.ftz.f32 %0, %1;" : "=f"(r) : "f"(x)); return r; }
__device__ __forceinline__ float rcp(float x) { float r; asm("rcp.approx.ftz.f32 %0, %1;" : "=f"(r) : "f"(x)); return r; }
__device__ __forceinline__ float sqrt_(float x) { float r; asm("sqrt.approx.ftz.f32 %0, %1;" : "=f"(r) : "f"(x)); return r; }
__device__ __forceinline__ float bf_lo(uint32_t v) { return __uint_as_float(v << 16); }
__device__ __forceinline__ float bf_hi(uint32_t v) { return __uint_as_float(v & 0xffff0000u); }
__device__ __forceinline__ float sel4(int k, float a, float b, float c, float d) { return (k & 2) ? ((k & 1) ? d : c) : ((k & 1) ? b : a); }
constexpr float LOG2E = 1.4426950408889634f;
constexpr uint32_t ONES = 0x3f803f80u;

__device__ __forceinline__ void ln_stats(float sum, float sq, float& mean, float& den) {
    const float m = sum * (1.0f / 640.0f);
    const float var = fmaxf(fmaf(sq, 1.0f / 640.0f, -m * m), 0.0f);
    mean = bfr(m);
    den = bfr(sqrt_(bfr(bfr(var) + 1e-5f)));
}
__device__ __forceinline__ float sigmoidf_(float x) { return rcp(1.0f + ex2(-x * LOG2E)); }

#define TSTAMP(k) do {} while (0)
#define TST(k) do {} while (0)

#define CSTAMP(k) do {} while (0)
template <int N> __device__ __forceinline__ uint32_t lag(uint32_t sb) {
    uint32_t z = 0;
#pragma unroll
    for (int k = 0; k < N; k++) z = ldsvol(sb + S_ZERO + z);
    return z;
}
__device__ __forceinline__ void warm_mma(uint32_t& a, uint32_t& b) {
    asm volatile("mma.sync.aligned.m16n8k8.row.col.f16.f16.f16.f16 {%0,%1}, {%0,%1}, {%0}, {%0,%1};" : "+r"(a), "+r"(b) :: "memory");
}
#define KWNS2 20
#define KWNS 200
template <int STRIDE>
__device__ __forceinline__ float gather8(const char* p, uint32_t par) {
    uint32_t v[8];
    int guard = 0;
    do {
#pragma unroll
        for (int s = 0; s < 8; s++) v[s] = ldp32(p + s * STRIDE);
    } while ((chk8(v, par) & 1) && ++guard < SPIN_LIMIT);
    return sum8(v);
}
template <class F>
__device__ __forceinline__ float gather16(const char* p, uint32_t par, int k, F also) {
    uint32_t v[8], u[8];
    float r;
    int guard = 0;
    bool again;
    do {
#pragma unroll
        for (int s = 0; s < 8; s++) v[s] = ldp32(p + s * 512);
#pragma unroll
        for (int s = 0; s < 8; s++) u[s] = ldp32(p + HALF + s * 512);
        again = ((chk8(v, par) | chk8(u, par)) & 1) | also(((v[0] ^ par) & 1) * 8);
        r = sum8(v) + sum8(u);
        keep(r);
    } while (again && ++guard < SPIN_LIMIT);
    SWEEPS(k, guard);
    return r;
}

struct Params {
    const __nv_bfloat16 *x, *k, *v, *wr;
    __nv_bfloat16* out;
};
struct Maps { CUtensorMap k, v, wq, wo, wg, wu, wd; };

constexpr int KV_BATCH_KEYS = 32 * 4096;

__device__ __forceinline__ void tma2d(uint32_t dst, const CUtensorMap* m, int c0, int c1, uint32_t bar, uint32_t bytes, uint64_t pol) {
    asm volatile("{\n .reg .pred p;\n elect.sync _|p, 0xffffffff;\n"
                 " @p mbarrier.arrive.expect_tx.shared::cta.b64 _, [%2], %6;\n"
                 " @p cp.async.bulk.tensor.2d.shared::cluster.global.mbarrier::complete_tx::bytes.L2::cache_hint [%0], [%1, {%3, %4}], [%2], %5;\n}"
                 :: "r"(dst), "l"(m), "r"(bar), "r"(c0), "r"(c1), "l"(pol), "r"(bytes) : "memory");
}
__device__ __forceinline__ void scrap_copy(uint32_t dst, const char* src, uint32_t bar) {
    asm volatile("{\n .reg .pred p;\n elect.sync _|p, 0xffffffff;\n"
                 " @p mbarrier.arrive.expect_tx.shared::cta.b64 _, [%2], 12288;\n"
                 " @p cp.async.bulk.shared::cluster.global.mbarrier::complete_tx::bytes [%0], [%1], 4096, [%2];\n"
                 " @p cp.async.bulk.shared::cluster.global.mbarrier::complete_tx::bytes [%0], [%1+4096], 4096, [%2];\n"
                 " @p cp.async.bulk.shared::cluster.global.mbarrier::complete_tx::bytes [%0], [%1+8192], 4096, [%2];\n}"
                 :: "r"(dst), "l"(src), "r"(bar) : "memory");
}
__device__ __forceinline__ void prefetch_l2(const void* p, uint32_t bytes) {
    asm volatile("{\n .reg .pred p;\n elect.sync _|p, 0xffffffff;\n @p cp.async.bulk.prefetch.L2.global [%0], %1;\n}" :: "l"(p), "r"(bytes) : "memory");
}
__device__ __forceinline__ uint64_t pol_first() { uint64_t p; asm("createpolicy.fractional.L2::evict_first.b64 %0, 1.0;" : "=l"(p)); return p; }
__device__ __forceinline__ uint64_t pol_normal() { uint64_t p; asm("createpolicy.fractional.L2::evict_normal.b64 %0, 1.0;" : "=l"(p)); return p; }
__device__ __forceinline__ bool utest(uint32_t bar, uint32_t parity) { return __all_sync(~0u, mbar_test(bar, parity)); }
__device__ __forceinline__ void uwait(uint32_t bar, uint32_t parity) {
    int n = 0;
    while (!__all_sync(~0u, mbar_try(bar, parity)) && ++n < SPIN_LIMIT) {}
}
template <int A, int B, int CNT> __device__ __forceinline__ void init_bars(uint32_t sb) {
#pragma unroll 1
    for (int k = A; k < B; k++)
        asm volatile("{\n .reg .pred p;\n elect.sync _|p, 0xffffffff;\n @p mbarrier.init.shared::cta.b64 [%0], %1;\n}" :: "r"(sb + S_BAR + 8 * k), "n"(CNT) : "memory");
}
__device__ __forceinline__ int first_key() { return (blockIdx.x >> 2) * 4096 + 3072 + (blockIdx.x & 3) * 256; }
__device__ __forceinline__ void load_tile(const CUtensorMap* m, uint32_t dst, uint32_t bar, uint32_t bytes, int key, uint64_t pol) { tma2d(dst, m, 0, 3 * key, bar, bytes, pol); }
__device__ __forceinline__ const char* unit_ptr(const Params& P, int n) {
    return (const char*)((n & 16) ? P.v : P.k) + (size_t)(first_key() + (n >> 5) * KV_BATCH_KEYS + (n & 15) * 16) * 384;
}
#define LSTAMP(k) do {} while (0)

__device__ __forceinline__ uint32_t k_place(uint32_t b, uint32_t s) { return s + 3 + (s < 3 ? 0 : 5 * (b & 1)); }
__device__ __forceinline__ uint32_t v_place(uint32_t b, uint32_t s) { return s < 3 ? s : s + 8 - 5 * (b & 1); }
__device__ __forceinline__ uint32_t ring_pos(uint32_t n) { const uint32_t u = (n & 15) + 2; return u - (u >= 12 ? 12 : u >= 6 ? 6 : 0); }
__device__ __forceinline__ void ring_load(const Maps& M, uint32_t sb, uint32_t n, uint32_t pos) {
    load_tile(&M.k, sb + pos * UNIT, sb + S_RING + 8 * pos, UNIT, first_key() + (n >> 4) * KV_BATCH_KEYS + 16 * (n & 15), pol_normal());
}
__device__ __forceinline__ uint32_t token(bool p, uint32_t a) {
    uint32_t v;
    asm volatile("{\n .reg .pred p;\n setp.ne.u32 p, %2, 0;\n mov.u32 %0, 0;\n @p atom.shared.add.u32 %0, [%1], 1;\n}" : "=r"(v) : "r"(a), "r"((uint32_t)p) : "memory");
    return __ballot_sync(~0u, v & 1);
}
__device__ __forceinline__ void place_load(const Maps& M, uint32_t sb, uint32_t n) {
    load_tile(&M.k, sb + k_place(n >> 4, (n >> 1) & 7) * SLOT + (n & 1) * UNIT, sb + S_FK + 4 * (n & 14), UNIT,
              first_key() + (n >> 4) * KV_BATCH_KEYS + 16 * (n & 15), pol_first());
}
__device__ __forceinline__ void v_load(const Maps& M, uint32_t sb, uint32_t b, uint32_t s) {
    load_tile(&M.v, sb + v_place(b, s) * SLOT, sb + S_FV + 8 * s, SLOT, first_key() + b * KV_BATCH_KEYS + 32 * s, pol_first());
}
__device__ __forceinline__ bool due(uint32_t t) { return __all_sync(~0u, (int)(gtime32() * 16 - t) >= 0); }
__device__ __forceinline__ bool reached(uint32_t a, int v) { return __all_sync(~0u, ldsvol(a) >= v); }

__device__ __forceinline__ void stream_warp(const Params& P, const Maps& M, uint32_t sb, uint32_t lane) {
    const uint64_t pol = pol_first();
    const int bid = blockIdx.x, g = bid >> 3, i = bid & 7;
    const uint32_t wf = sb + S_WFULL;
    uint32_t tn = __shfl_sync(~0u, gtime32(), 0) * 16 - T_LEAD;
    auto pace = [&](uint32_t dt) { int k = 0; while (!due(tn) && ++k < SPIN_LIMIT) {} tn += dt; };
#pragma unroll
    for (int k = 0; k < 10; k++) {
        if (k < 2) {
            if (k == 0) init_bars<26, 27, 1>(sb); else init_bars<27, 37, 1>(sb);
            asm volatile("fence.mbarrier_init.release.cluster;" ::: "memory");
            if (k == 1) { asm volatile("bar.arrive 2, %0;" :: "n"(NTHR) : "memory"); asm volatile("bar.sync 3, 128;" ::: "memory"); }
        }
        if (k >= WIN_W) uwait(wf + 8 * (k - WIN_W), 0);
        pace(TAUW * 5 / 2);
        if (k < 4) tma2d(sb + ST_WQ + 15360 * k, &M.wq, 384 * g + 192 * (k >> 1), 80 * i + 40 * (k & 1), wf + 8 * k, 15360, pol);
        else if (k < 6) tma2d(sb + ST_WG + 15360 * (k - 4), k == 4 ? &M.wg : &M.wu, 96 * g, 80 * i, wf + 8 * k, 15360, pol);
        else tma2d(sb + ST_WO + 15360 * (k - 6), &M.wo, 80 * i, 384 * g + 96 * (k - 6), wf + 8 * k, 15360, pol);
    }
#pragma unroll 1
    for (int n = 0; n < 16; n++) {
        if (n == 0 || n == 5 || n == 11) uwait(sb + S_RELW + (n == 0 ? 0 : n == 5 ? 8 : 16), 0);
        uwait(n < WIN_S ? wf + 8 * (10 - WIN_S + n) : sb + S_FV + 8 * ((n - WIN_S) ^ 8), 0);
        pace(2 * TAU);
        if (n < 8) { place_load(M, sb, 2 * n); place_load(M, sb, 2 * n + 1); }
        else v_load(M, sb, 0, n - 8);
        if (n == 7) { pace(TAUW * 5 / 2); tma2d(sb + S_WD, &M.wd, 80 * i, 96 * g, wf + 80, 15360, pol); }
    }
    int nd = 0;
    uint32_t q[4];
#pragma unroll
    for (int r = 0; r < 4; r++) q[r] = sb + S_FV + 8 * (7 - r);
    uint32_t td = tn;
#pragma unroll 1
    for (int b = 1; b < 4; b++) {
        const uint32_t pk = (b - 1) & 1;
        uint32_t fr = 0, pend = 0;
#pragma unroll 1
        for (int j = 0; j < 17; j++) {
            const int n = 16 * b + 2 * j;
            uint32_t now, st;
            int k = 0;
            while (true) {
                now = __shfl_sync(~0u, gtime32(), 0) * 16;
                const uint2 c = lds64(sb + S_KF);
                const uint32_t rel = mbar_test(j < 8 ? sb + S_RELR : sb + S_RELK, pk);
                const int used = min((int)c.x + 1, (int)c.y) - 16 * b;
                static_assert(WIN_U <= 12, "a ring position has at most one token of the timetable");
                const uint32_t win = mbar_test(q[WIN_S - 1] & ~1u, q[WIN_S - 1] & 1) & (used >= min(2 * j + 2 - WIN_U, 16));
                st = __reduce_and_sync(~0u, (rel ? (j < 8 ? 0x700 : 0xf8) : 0) + (used >= 12) + (used >= 14) * 2 + (used >= 16) * 4 + win * 0x800);
                fr |= st & 0x7ff;
#pragma unroll 1
                while (pend & fr) {
                    const uint32_t r = __ffs(pend & fr) - 1;
                    if (r < 8) v_load(M, sb, b, r);
                    else { const uint32_t m = 16 * b + 2 * r - 16; ring_load(M, sb, m, ring_pos(m)); ring_load(M, sb, m + 1, ring_pos(m) + 1); }
                    pend ^= 1u << r;
                }
                if ((j == 16 ? !pend : (st & 0x800) && (int)(now - td) >= 0) || ++k >= SPIN_LIMIT) break;
            }
            if (j == 16) break;
            tn += 2 * TAU;
            td = (int)(tn - now) > 2 * TMIN ? tn : now + 2 * TMIN;
            if (b == 3 && j >= JFREE) td = now + TFREE;
            q[3] = q[2]; q[2] = q[1]; q[1] = q[0]; q[0] = sb + S_QRDY;
            const int s = j ^ 8;
            const char* src = unit_ptr(P, 32 * b + 2 * j);
            uint32_t mine = 0;
            if (j < 8) {
                const uint32_t pos = ring_pos(n);
                mine = j < 3 ? ((fr >> s) & 1) * 3 : token(lane < 2, sb + S_TOK + 4 * (pos + lane));
                if (mine & 1) ring_load(M, sb, n, pos); else prefetch_l2(src, UNIT);
                if (mine & 2) ring_load(M, sb, n + 1, pos + 1); else prefetch_l2(src + UNIT, UNIT);
                if (!mine) pend |= (1u << s) & 0x700;
            } else if ((fr >> s) & 1) { v_load(M, sb, b, s); q[0] = (sb + S_FV + 8 * s) | (pk ^ 1); }
            else {
                pend |= 1u << s;
                if (s < 3 || s >= VPF) prefetch_l2(src, SLOT);
                else {
                    scrap_copy(sb + S_DUMMY, src, sb + S_DBAR + 8 * (nd & 3));
                    q[0] = (sb + S_DBAR + 8 * (nd & 3)) | ((nd >> 2) & 1);
                    nd++;
                }
            }
        }
    }
#pragma unroll 1
    for (int m = max(nd - 4, 0); m < nd; m++) uwait(sb + S_DBAR + 8 * (m & 3), (m >> 2) & 1);
}

__device__ __forceinline__ float scaled(float s) { return bfr(bfr(s) * 0.07216878364870322f); }
__device__ __forceinline__ void probs(float s, uint32_t ps, uint32_t src, uint32_t ln) {
    const uint32_t q8 = ln >> 2, t4 = ln & 3;
    int key = __float_as_int(s);
    key ^= (key >> 31) & 0x7fffffff;
    key = __reduce_max_sync(~0u, key);
    key ^= (key >> 31) & 0x7fffffff;
    const float ml = __int_as_float(key) * LOG2E;
    sts_hi16(ps + 64 * src + (q8 >> 1) * 16 + t4 * 4 + (q8 & 1) * 2, bfr(ex2(fmaf(s, LOG2E, -ml))));
    sts32_if(ln == 0, ps + PS_MAX + 4 * src, __float_as_uint(ml));
}
template <int H> __device__ __forceinline__ uint32_t b_pos(uint32_t e) { const uint32_t h = e >= H, k = e - H * h; return h * 192 + (k & 6) * 24 + (k >> 3) * 4 + (k & 1) * 2; }
__device__ __forceinline__ uint32_t a_pos(uint32_t e) { const uint32_t h = e >= 40, k = e - 40 * h; return (k & 6) * 24 + (k >> 3) * 8 + h * 4 + (k & 1) * 2; }
__device__ __forceinline__ uint32_t q_pos(uint32_t d) { return ((d >> 4) & 7) * 64 + (d & 6) * 8 + (d >> 7) * 8 + ((d >> 3) & 1) * 4 + (d & 1) * 2; }
__device__ __forceinline__ uint32_t k_off(uint32_t ln, uint32_t j) { const uint32_t r = 3 * (ln & 15) + j; return r * 128 + (((r & 7) ^ (ln >> 4)) << 4); }

#define HSTAMP(k) do {} while (0)
__device__ __forceinline__ void score_warp(const Maps& M, uint32_t sb, uint32_t h, uint32_t ln) {
    uwait(sb + S_QRDY, 0);
    const uint32_t q8 = ln >> 2;
    const uint32_t k0 = k_off(ln, 0), k1 = k_off(ln, 1), k2 = k_off(ln, 2);
#pragma unroll 1
    for (uint32_t n = h; n < 64; n += 2) {
        HSTAMP(0);
        const uint4 q = lds128(sb + S_QS + 32 * (n & 48) + 16 * ln);
        const uint32_t pos = ring_pos(n), u = n & 15;
        const uint32_t ua = sb + (n >= 16 ? pos : n + 6) * UNIT;
        uwait(n >= 16 ? sb + S_RING + 8 * pos : sb + S_FK + 8 * (n >> 1), n < 16 ? 0 : pos < 2 ? u >= 6 : ((n >> 4) + (u < 6 || u >= 12)) & 1);
        HSTAMP(1);
        float acc[2][4] = {};
#pragma unroll
        for (int s = 0; s < 12; s++) {
            uint32_t kf[4];
            ldsm4(kf, (ua + (s < 4 ? k0 : s < 8 ? k1 : k2)) ^ (32 * (s & 3)));
            const bool m = q8 == (s & 7);
            mmaA(acc[s & 1], kf, m ? (s < 8 ? q.x : q.z) : 0u, m ? (s < 8 ? q.y : q.w) : 0u);
        }
        __syncwarp();
        HSTAMP(2);
        const uint32_t mine = token(ln == 0 && n >= 16 && u < 10, sb + S_TOK + 4 * pos);
        stsvol(sb + S_KF + 4 * (n & 1), n + 1);
        if (mine) ring_load(M, sb, n + 6, pos);
        HSTAMP(3);
        const float w0 = (acc[0][0] + acc[0][1]) + (acc[1][0] + acc[1][1]), w1 = (acc[0][2] + acc[0][3]) + (acc[1][2] + acc[1][3]);
        float s = ((ln & 1) ? w1 : w0) + __shfl_xor_sync(~0u, (ln & 1) ? w0 : w1, 1);
        s += __shfl_xor_sync(~0u, s, 2);
        sts_hi16(sb + S_SC + (((n & 12) >> 1) + (n & 1)) * 64 + (n & 2) * 2 + (ln & 29) * 2, scaled(s));
        __syncwarp();
        arrive_if(ln == 0 && (n & 14) == 14, sb + S_SCO);
    }
}

__device__ __forceinline__ char* xwindow() { return reinterpret_cast<char*>((reinterpret_cast<uintptr_t>(g_x) + (2u << 20) - 1) & ~(uintptr_t)((2u << 20) - 1)); }

struct XPtr {
    uint32_t lo, hi;
    __device__ __forceinline__ explicit XPtr(char* p) : lo((uint32_t)(uintptr_t)p), hi((uint32_t)((uintptr_t)p >> 32)) {}
    __device__ __forceinline__ XPtr(uint32_t l, uint32_t h) : lo(l), hi(h) {}
    __device__ __forceinline__ XPtr operator+(uint32_t o) const { return XPtr(lo + o, hi); }
    __device__ __forceinline__ operator char*() const { uint64_t p; asm("mov.b64 %0, {%1, %2};" : "=l"(p) : "r"(lo), "r"(hi)); return (char*)p; }
};
__device__ __forceinline__ void keep(XPtr& v) { keep(v.lo); }

__device__ __forceinline__ void side_warp(uint32_t sb) {
    const uint32_t bid = blockIdx.x, g = bid >> 3, i = bid & 7, P = pairG(0, 0, i);
    char* p = xwindow() + P * 8192 + (g >> 3) * HALF + (g & 7) * 512 + 448;
    uint32_t best[2] = {~0u, ~0u};
    asm volatile("st.relaxed.gpu.global.b32 [%0], 1;" :: "l"(p) : "memory");
    asm volatile("st.relaxed.gpu.global.b32 [%0], 1;" :: "l"(p + COPY) : "memory");
#pragma unroll 1
    for (int r = 0; r < 64; r++) {
        if (r >= 4 && !(r & 1) && min(best[0], best[1]) < 380 && max(best[0], best[1]) > min(best[0], best[1]) + 80) break;
        uint32_t c0, c1, v;
        asm volatile("mov.u32 %0, %clock;" : "=r"(c0) :: "memory");
        asm volatile("atom.relaxed.gpu.global.exch.b32 %0, [%1], 0;" : "=r"(v) : "l"(p + (r & 1) * COPY) : "memory");
        asm volatile("{\n .reg .pred q;\n setp.eq.u32 q, %1, 0x13579bdf;\n mov.u32 %0, 0;\n @!q mov.u32 %0, %clock;\n}" : "=r"(c1) : "r"(v) : "memory");
        if (r & 1) best[1] = min(best[1], c1 - c0); else best[0] = min(best[0], c1 - c0);
    }
    stsvol(sb + S_SIDE, 1 + ((best[1] < best[0]) ^ (__popc(P & PMASK) & 1)));
}

__device__ __forceinline__ void look_a(uint2 (&v)[4], const char* src) {
#pragma unroll
    for (int s = 0; s < 4; s++) v[s] = ldp64(src + s * 1024);
}
__device__ __forceinline__ void hop_a(uint2 (&v)[4], const char* src, uint32_t par, uint32_t dst, bool st, int k) {
    int guard = 0;
    while (__any_sync(~0u, chk4(v, par) & 1) && ++guard < SPIN_LIMIT) look_a(v, src);
    const float M = fmaxf(fmaxf(asf(v[0].x), asf(v[1].x)), fmaxf(asf(v[2].x), asf(v[3].x)));
    float e[4];
#pragma unroll
    for (int s = 0; s < 4; s++) e[s] = ex2(asf(v[s].x) - M);
    const float rl = __shfl_sync(~0u, rcp(fmaf(e[0], asf(v[0].y), e[1] * asf(v[1].y)) + fmaf(e[2], asf(v[2].y), e[3] * asf(v[3].y))), 24);
#pragma unroll
    for (int s = 0; s < 4; s++) e[s] = __shfl_sync(~0u, e[s], 24);
    const float o0 = fmaf(e[0], asf(v[0].x), e[1] * asf(v[1].x)) + fmaf(e[2], asf(v[2].x), e[3] * asf(v[3].x));
    const float o1 = fmaf(e[0], asf(v[0].y), e[1] * asf(v[1].y)) + fmaf(e[2], asf(v[2].y), e[3] * asf(v[3].y));
    sts32_if(st, dst, pack2(o0 * rl, o1 * rl));
    SWEEPS(k, guard);
    __syncwarp();
}

__global__ void __launch_bounds__(NTHR, 1)
fused_kernel(const Params P, const __grid_constant__ Maps M) {
    extern __shared__ __align__(1024) unsigned char smem[];
    const uint32_t sb = smem_u32(smem);
    const int tid = threadIdx.x, bid = blockIdx.x;
    const int w = __shfl_sync(~0u, tid >> 5, 0), lane = tid & 31;

    if (w >= 8) {
        asm volatile("setmaxnreg.dec.sync.aligned.u32 " REG_LO ";");
        if (w == 8) {
            stream_warp(P, M, sb, lane);
        } else {
            if (w == 9) { init_bars<0, 8, 1>(sb); init_bars<16, 22, 1>(sb); }
            else if (w == 10) { init_bars<8, 16, 2>(sb); init_bars<22, 26, 1>(sb); }
            else { init_bars<37, 38, 1>(sb); init_bars<38, 40, 8>(sb); init_bars<40, 41, 1>(sb); init_bars<41, 44, 8>(sb); init_bars<44, 45, 2>(sb); if (lane < 18) stsvol(sb + S_ZERO + 4 * lane, 0); }
            asm volatile("fence.mbarrier_init.release.cluster;" ::: "memory");
            asm volatile("bar.arrive 3, 128;" ::: "memory");
            asm volatile("bar.sync 2, %0;" :: "n"(NTHR) : "memory");
            if (w < 11) score_warp(M, sb, w - 9, lane);
            else {
                if (lane == 0) side_warp(sb);
                __syncwarp();
                uint32_t a = 0, b = 0;
                int k = 0;
                while (ldsvol(sb + S_GATE) == 0 && ++k < SPIN_LIMIT) { warm_mma(a, b); __nanosleep(KWNS); }
                uint4* d = reinterpret_cast<uint4*>(reinterpret_cast<char*>(g_s) + XS + bid * 7680) + lane;
                const uint4 z = make_uint4(0, 0, 0, 0);
#pragma unroll 1
                for (int u = 0; u < 15; u++) d[32 * u] = z;
                d = reinterpret_cast<uint4*>(reinterpret_cast<char*>(g_s) + XS2 + bid * 768) + lane;
                d[0] = z;
                if (lane < 16) d[32] = z;
                const uint32_t side = (ldsvol(sb + S_SIDE) & 1) ^ 1, g = bid >> 3, i = bid & 7;
                const XPtr gx(xwindow());
                auto nearp = [&](uint32_t pr) { return gx.lo + pr * 8192 + ((side ^ __popc(pr & PMASK)) & 1) * COPY; };
                const uint32_t own = (i >> 2) * HALF + (i & 3) * 1024 + (lane & 7) * 128;
                const uint32_t pAC = nearp(pairL(lane >> 4, (lane >> 3) & 1, g)) + own, pE = nearp(pairL(RE, (lane >> 3) & 1, g)) + own;
                const uint32_t pG = nearp(pairG((lane >> 2) & 1, (lane >> 3) & 1, i)) + min(lane & 3, 2) * 128;
                uint32_t tr = 0, tk = 0, ph = 0, src = g + (lane >> 4), seen = 0, n = 16;
                bool go = false, first = true;
                while (n < 64 && ++k < SPIN_LIMIT) {
                    const uint32_t now = __shfl_sync(~0u, gtime32(), 0) * 16;
                    if (!go && utest(sb + S_RELV, ((n >> 4) & 1) ^ 1) && utest(sb + S_FV + 8 * (n >= 48 ? KRE_GATE3 : KRE_GATE), (n >> 4) & 1)) { go = true; tk = now; }
                    if (go && (int)(now - tk) >= 0) {
                        place_load(M, sb, n);
                        tk += n >= 48 ? KRE_TAU3 : (n & 15) < KRE_N1 ? KRE_TAU1 : KRE_TAU;
                        n++;
                        go = (n & 15) != 0;
                        if (!go) LSTAMP(63 + (n >> 3));
                    } else if (first || (int)(now - tr) >= 0) {
                        first = false;
                        tr = now + RFR_TAU;
                        b |= seen & a;
                        warm_mma(a, b);
                        if (RFR_ON) seen = ldp32(XPtr(ph == 0 ? pAC : ph == 1 && lane < 16 ? pE : pG + (src & 8) * (HALF / 8) + (src & 7) * 512, gx.hi));
                        src += ph == 0 ? 0 : ph == 1 ? 2 : 1;
                        ph = ph == 2 ? 0 : ph + 1;
                    } else __nanosleep(KWNS2);
                }
                while (ldsvol(sb + S_GATE) < 6 && ++k < SPIN_LIMIT) { warm_mma(a, b); __nanosleep(KWNS); }
                if (a | b) stsvol(sb + S_GATE, 6);
            }
        }
        return;
    }
    asm volatile("setmaxnreg.inc.sync.aligned.u32 " REG_HI ";");

    const int g = bid >> 3, i = bid & 7;
    const int g8 = lane >> 2, t = lane & 3;
    char* const gs = reinterpret_cast<char*>(g_s);
    const XPtr gx(xwindow());

    W80 Wq[6], Wgu[3];
    uint32_t Wo[5][3][4];
    if (w < 4) {
        const uint32_t* xp = reinterpret_cast<const uint32_t*>(P.x + 640 * w);
        float sum = 0.f, sq = 0.f;
#pragma unroll
        for (int u = 0; u < 10; u++) { uint32_t v = xp[lane + 32 * u]; float a = bf_lo(v), b = bf_hi(v); sum += a + b; sq += a * a + b * b; }
#pragma unroll
        for (int o = 16; o > 0; o >>= 1) { sum += __shfl_xor_sync(~0u, sum, o); sq += __shfl_xor_sync(~0u, sq, o); }
        float mean, den; ln_stats(sum, sq, mean, den);
        if (lane < 20) {
            const uint2 v = reinterpret_cast<const uint2*>(P.x + 640 * w + 80 * i)[lane];
            sts64(sb + S_X0 + 160 * w + 8 * lane, v.x, v.y);
            sts32(sb + S_L0 + 384 * w + b_pos<40>(4 * lane), pack2(__fdiv_rn(bfr(bf_lo(v.x) - mean), den), __fdiv_rn(bfr(bf_hi(v.x) - mean), den)));
            sts32(sb + S_L0 + 384 * w + b_pos<40>(4 * lane + 2), pack2(__fdiv_rn(bfr(bf_lo(v.y) - mean), den), __fdiv_rn(bfr(bf_hi(v.y) - mean), den)));
        }
    } else if (w == 4) {
        const uint32_t* xp = reinterpret_cast<const uint32_t*>(P.wr);
        float sum = 0.f;
#pragma unroll
        for (int u = 0; u < 10; u++) { uint32_t v = xp[lane + 32 * u]; sum += bf_lo(v) + bf_hi(v); }
#pragma unroll
        for (int o = 16; o > 0; o >>= 1) sum += __shfl_xor_sync(~0u, sum, o);
        if (lane == 0) stsf(sb + S_SWR, sum);
        if (lane < 20) {
            const uint2 v = reinterpret_cast<const uint2*>(P.wr + 80 * i)[lane];
            sts32(sb + S_XA + 576 + a_pos(4 * lane), v.x); sts32(sb + S_XA + 576 + a_pos(4 * lane + 2), v.y);
            sts32(sb + S_XA + a_pos(4 * lane), ONES); sts32(sb + S_XA + a_pos(4 * lane + 2), ONES);
        }
    }
    asm volatile("bar.sync 2, %0;" :: "n"(NTHR) : "memory");
    auto frag = [](uint32_t (&a)[4], uint32_t p, int pitch) {
        const uint32_t r0 = lds32(p), r1 = lds32(p + pitch), r2 = lds32(p + 2 * pitch), r3 = lds32(p + 3 * pitch);
        a[0] = __byte_perm(r0, r1, 0x5410); a[1] = __byte_perm(r0, r1, 0x7632);
        a[2] = __byte_perm(r2, r3, 0x5410); a[3] = __byte_perm(r2, r3, 0x7632);
    };
    mbar_wait(sb + S_WFULL + 16 * (w >> 2), 0);
    mbar_wait(sb + S_WFULL + 16 * (w >> 2) + 8, 0);
    {
        const uint32_t p = sb + ST_WQ + (w >> 2) * 30720 + (2 * t) * 384 + (48 * (w & 3) + 2 * g8) * 2;
#pragma unroll
        for (int r = 0; r < 10; r++)
#pragma unroll
            for (int m = 0; m < 3; m++) {
                const uint32_t q = p + ((r & 1) * 40 + (r >> 1) * 8) * 384 + 32 * m, r0 = lds32(q), r1 = lds32(q + 384);
                (r < 8 ? Wq[2 * m].a[(r >> 2) & 1][r & 3] : Wq[2 * m].c[r & 1]) = __byte_perm(r0, r1, 0x5410);
                (r < 8 ? Wq[2 * m + 1].a[(r >> 2) & 1][r & 3] : Wq[2 * m + 1].c[r & 1]) = __byte_perm(r0, r1, 0x7632);
            }
    }
    __syncwarp();
    if (lane == 0) mbar_arrive(sb + S_RELW);
    TSTAMP(1);
    {
        char* d = gs + XS + bid * 7680 + (w >> 2) * 3840 + (48 * (w & 3) + 2 * g8) * 4;
        float acc[6][4] = {};
        mul80(acc, Wq, lds128(sb + S_L0 + 48 * lane), lds32(sb + S_L0 + 48 * lane + 16));
#pragma unroll
        for (int m = 0; m < 6; m++) stp32(d + t * 768 + 32 * (m & 6) + 4 * (m & 1), acc[m][0] + acc[m][3], 1);
        float sum[6][4] = {};
        mul80(sum, Wq, make_uint4(ONES, ONES, ONES, ONES), ONES);
        if (t == 0)
#pragma unroll
            for (int m = 0; m < 6; m++) stp32(d + 4 * 768 + 32 * (m & 6) + 4 * (m & 1), sum[m][0] + sum[m][3], 1);
    }
    mbar_wait(sb + S_WFULL + 32, 0);
    mbar_wait(sb + S_WFULL + 40, 0);
    const uint32_t oct = 3 * (w >> 1) + (w & 1), oct2 = 3 * (w >> 1) + 2;
    {
        const uint32_t p = sb + ST_WG + ((lane & 7) + 40 * ((lane >> 3) & 1) + 8 * (lane >> 4)) * 192;
#pragma unroll
        for (int T = 0; T < 3; T++) {
            const uint32_t q = p + (T < 2 ? T * 15360 + 16 * oct : (w & 1) * 15360 + 16 * oct2);
            ldsm4t(Wgu[T].a[0], q); ldsm4t(Wgu[T].a[1], q + 16 * 192); ldsm2t(Wgu[T].c, q + 32 * 192);
        }
        float sum[3][4] = {};
        mul80(sum, Wgu, make_uint4(ONES, ONES, ONES, ONES), ONES);
        if (t < 3) stp32(gs + XS2 + bid * 768 + (t < 2 ? 64 * oct + 4 * t : 64 * oct2 + 4 * (w & 1)) + 8 * g8,
                         sel4(t, sum[0][0] + sum[0][3], sum[1][0] + sum[1][3], sum[2][0] + sum[2][3], 0.f), 1);
    }
    __syncwarp();
    if (lane == 0) mbar_arrive(sb + S_RELW + 8);
    const char* srcS = gs + XS + g * 8 * 7680 + (i >> 2) * 3840 + min(tid, 191) * 4;
    uint32_t vs[5][8];
#pragma unroll
    for (int b = 0; b < 5; b++)
#pragma unroll
        for (int s = 0; s < 8; s++) vs[b][s] = ldp32(srcS + b * 768 + s * 7680);
    uint32_t cs2[8];
#pragma unroll
    for (int s = 0; s < 8; s++) cs2[s] = ldp32(gs + XS2 + (g * 8 + s) * 768 + min(tid, 191) * 4);
    __syncwarp();
    mbar_wait(sb + S_WFULL + 48 + 8 * (w >> 1), 0);
    {
        const uint32_t po = sb + ST_WO + (48 * w + 12 * t) * 160 + 4 * g8;
#pragma unroll
        for (int s = 0; s < 3; s++)
#pragma unroll
            for (int m = 0; m < 5; m++) frag(Wo[m][s], po + 4 * s * 160 + 32 * m, 160);
    }
    __syncwarp();
    if (lane == 0) mbar_arrive(sb + S_RELW + 16);
    {
        const uint4 z = make_uint4(0, 0, 0, 0);
        const uint32_t c = (tid >> 6) & 1, cp = (tid >> 7) * COPY, k = (tid & 63) * 16;
        *reinterpret_cast<uint4*>((char*)(gx + pairL(RA, c, g) * 8192 + (i >> 2) * HALF + (i & 3) * 1024 + cp + k)) = z;
        *reinterpret_cast<uint4*>((char*)(gx + pairL(RC, c, g) * 8192 + (i >> 2) * HALF + (i & 3) * 1024 + cp + k)) = z;
        *reinterpret_cast<uint4*>((char*)(gx + pairL(RE, c, g) * 8192 + (i >> 2) * HALF + (i & 3) * 1024 + cp + k)) = z;
        if ((tid & 31) < 24) *reinterpret_cast<uint4*>((char*)(gx + pairG((tid >> 5) & 1, c, i) * 8192 + (g >> 3) * HALF + (g & 7) * 512 + cp + (tid & 31) * 16)) = z;
    }
    if (tid < 192) {
        int guard = 0;
        while (((or3(chk8(vs[0], 1), chk8(vs[1], 1), chk8(vs[2], 1)) | chk8(vs[3], 1) | chk8(vs[4], 1)) & 1) && ++guard < SPIN_LIMIT) {
#pragma unroll
            for (int b = 0; b < 5; b++)
#pragma unroll
                for (int s = 0; s < 8; s++) vs[b][s] = ldp32(srcS + b * 768 + s * 7680);
        }
        const uint32_t qpos = sb + S_QS + q_pos(tid);
#pragma unroll
        for (int b = 0; b < 4; b++) {
            sts_hi16(qpos + 512 * b, bfr(sum8(vs[b])));
        }
        stsf(sb + S_CSQ + 4 * tid, sum8(vs[4]));
    }
    if (tid < 192) stsf(sb + S_CSGU + 4 * tid, (chk8(cs2, 1) & 1) ? gather8<768>(gs + XS2 + g * 8 * 768 + tid * 4, 1) : sum8(cs2));
    bar_main();
    arrive_if(tid == 0, sb + S_QRDY);
    TSTAMP(2);

    uint32_t side;
    { int k = 0; while ((side = ldsvol(sb + S_SIDE)) == 0 && ++k < SPIN_LIMIT) {} }
    side = __shfl_sync(~0u, side & 1, 0) ^ 1;
    auto nearp = [&](uint32_t P) { return P * 8192 + ((side ^ __popc(P & PMASK)) & 1) * COPY; };
    const uint32_t td = __shfl_sync(~0u, tid, lane);
    const uint32_t wp = __shfl_sync(~0u, tid >> 5, 0);
    const uint32_t cc = wp >= 3;
#define IDS() uint32_t z_ = td; opaque(z_); const uint32_t ln = z_ & 31, q8 = ln >> 2, t4 = z_ & 3, n96 = z_ - 96 * cc, n80 = min(n96, 79u); (void)q8; (void)t4; (void)n80; (void)ln

    auto vaddr = [&](uint32_t (&voff)[3]) {
        IDS();
        const uint32_t key3 = 3 * ((ln & 7) + 2 * (ln & 8) + ((ln >> 1) & 8));
#pragma unroll
        for (int T = 0; T < 3; T++) {
            const uint32_t u = 3 * wp + T, r = key3 + (u >> 3);
            voff[T] = r * 128 + (((u ^ r) & 7) << 4);
        }
    };
    auto values = [&](uint32_t (&vf)[8][3][4], auto step, uint32_t ps, uint32_t col, uint32_t par) {
        IDS();
        const uint4 p = lds128(ps + 16 * ln);
        const uint2 mp = lds64(ps + PS_MAX + 8 * t4);
        const float mq = ldsf(ps + PS_MAX + 4 * q8);
        float acc[3][4] = {};
        float M = fmaxf(asf(mp.x), asf(mp.y)), lsum = 0.f, f0 = 0.f, f1 = 0.f;
#pragma unroll
        for (int s = 0; s < 8; s++) {
            step(s);
            const bool m = (q8 >> 1) == (s >> 1);
            const uint32_t b0 = m ? ((s & 1) ? p.z : p.x) : 0u, b1 = m ? ((s & 1) ? p.w : p.y) : 0u;
#pragma unroll
            for (int T = 0; T < 3; T++) mmaA(acc[T], vf[s][T], b0, b1);
            if (s < 2) M = fmaxf(M, __shfl_xor_sync(~0u, M, 1 + s));
            if (s == 1) {
                f0 = ex2(asf(mp.x) - M); f1 = ex2(asf(mp.y) - M);
                lsum = (((bf_lo(p.x) + bf_hi(p.x)) + (bf_lo(p.y) + bf_hi(p.y))) + ((bf_lo(p.z) + bf_hi(p.z)) + (bf_lo(p.w) + bf_hi(p.w)))) * ex2(mq - M);
            }
            if (s >= 2 && s < 7) lsum += __shfl_xor_sync(~0u, lsum, 1 << (s - 2));
        }
        char* pubA = gx + pairL(RA, col, g) * 8192 + (i >> 2) * HALF + (i & 3) * 1024 + (wp >> 1) * 256 + (wp & 1) * 96 + 32 * t4 + 4 * q8;
        const float r0 = fmaf(f0, acc[0][0], f1 * acc[0][3]), r1 = fmaf(f0, acc[1][0], f1 * acc[1][3]), r2 = fmaf(f0, acc[2][0], f1 * acc[2][3]);
        const bool hi = t4 & 2, od = t4 & 1;
        const float u0 = (hi ? r2 : r0) + __shfl_xor_sync(~0u, hi ? r0 : r2, 2), u1 = r1 + __shfl_xor_sync(~0u, r1, 2);
        const float o = (od ? u1 : u0) + __shfl_xor_sync(~0u, od ? u0 : u1, 1);
        stp32_if(t4 < 3 || ((wp & 1) && q8 < 2), pubA, t4 < 3 ? o : q8 ? lsum : M, par);
    };

#pragma unroll 1
    for (int ch = 0; ch < 5; ch++) {
        const uint32_t par0 = (ch + 1) & 1, par1 = ch & 1;
        uint32_t voff[3], vf[8][3][4];
        CSTAMP(0);
        if (ch < 4) {
            vaddr(voff);
            mbar_wait(sb + S_SCO, par1);
            TST(0);
            auto ldw = [&](int s) {
                mbar_wait(sb + S_FV + 8 * s, par1);
#pragma unroll
                for (int T = 0; T < 3; T++) ldsm4t(vf[s][T], voff[T] + (sb + v_place(ch, s) * SLOT));
            };
            probs(bf_lo(lds16(sb + S_SC + 2 * td)), sb + S_PS, wp, td & 31);
            ldw(0); ldw(1); ldw(2);
            bar_main();
            arrive_if(td == 0, sb + S_RELR);
            uint2 u[4];
            values(vf, [&](int s) {
                if (s == HOPA0 || s == HOPA1) {
                    IDS();
                    const XPtr polA = gx + nearp(pairL(RA, 1, g)) + (wp >> 2) * HALF + (wp & 3) * 256 + 8 * min(ln, 24u);
                    if (s == HOPA0) look_a(u, polA);
                    if (s == HOPA1 && ch > 0) {
                        hop_a(u, polA, par1, sb + S_OS + 192 * wp + 4 * ln + 96, ln < 24, 25);
                    }
                }
                if (s >= 3) ldw(s);
            }, sb + S_PS, 0, par0);
            TST(1);
            CSTAMP(5);
        } else {
#pragma unroll
            for (int s = 0; s < 36; s++) { vf[s / 12][(s / 4) % 3][s & 3] = 0; opaque(vf[s / 12][(s / 4) % 3][s & 3]); }
        }
        const bool has0 = ch < 4, has1 = ch > 0;
        const bool actc = wp < 6 && (cc ? has1 : has0);
        const uint32_t parc = cc ? par1 : par0;
        const uint32_t pub0 = has0 ? par0 : 0;
        XPtr pubB = gx;
        uint32_t rr;
        {
            IDS();
            const uint32_t c = ch == 4;
            const XPtr polA = gx + nearp(pairL(RA, c, g)) + (wp >> 2) * HALF + (wp & 3) * 256 + 8 * min(ln, 24u) + lag<DELAY_L>(sb);
            uint2 v[4];
            look_a(v, polA);
            uint32_t osa = sb + S_OS + 192 * wp + 96 * c + 4 * ln;
            uint32_t oa = sb + S_OS + 192 * wp + 96 * (q8 & 1) + 24 * t4, ra = sb + S_RED + 640 * wp + 320 * (t4 & 1) + 8 * q8;
            pubB = gx + pairG(0, cc, i) * 8192 + (g >> 3) * HALF + (g & 7) * 512 + n80 * 4;
            rr = sb + S_RED + 320 * cc + 4 * n80;
            keep(osa); keep(oa); keep(ra); keep(pubB); keep(rr);
            hop_a(v, polA, c ? par1 : par0, osa, ln < 24, 5 * ch);
            TST(2);
            CSTAMP(6);
            float acc[5][4] = {};
            const uint2 b0 = lds64(oa), b1 = lds64(oa + 8), b2 = lds64(oa + 16);
#pragma unroll
            for (int m = 0; m < 5; m++) mmaA(acc[m], Wo[m][0], b0.x, b0.y);
#pragma unroll
            for (int m = 0; m < 5; m++) mmaA(acc[m], Wo[m][1], b1.x, b1.y);
#pragma unroll
            for (int m = 0; m < 5; m++) mmaA(acc[m], Wo[m][2], b2.x, b2.y);
#pragma unroll
            for (int m = 0; m < 5; m++) sts64_if(t4 < 2, ra + 64 * m, t4 ? acc[m][1] : acc[m][0], t4 ? acc[m][3] : acc[m][2]);
        }
        CSTAMP(7);
        bar_main();
        CSTAMP(8);
        float x1 = 0.f;
        uint32_t xr, fl;
        XPtr pubC = gx, pubC2 = gx;
        {
            IDS();
            if (actc) {
                uint32_t r[8];
#pragma unroll
                for (int s = 0; s < 8; s++) r[s] = lds32(rr + 640 * s);
                stp32_if(n96 < 80, pubB, sum8(r), parc);
                CSTAMP(9);
            }
            xr = sb + S_XB + 48 * (ln & 15);
            pubC = gx + pairL(RC, 0, g) * 8192 + (i >> 2) * HALF + (i & 3) * 1024 + (t4 & 1) * (32 * 8192);
            pubC2 = pubC + ((t4 & 2) ? 192 * (wp >> 1) + 128 + 4 * (wp & 1) + 8 * q8 : 768 + 2 * ((q8 + 1) & 6));
            pubC = pubC + (192 * (wp >> 1) + 64 * (wp & 1) + 8 * q8);
            fl = ((t4 & 1) ? par1 : pub0) | (t4 >= 2 || (wp == 7 && q8 < 4 && q8 != 2 - t4) ? 2 : 0);
            keep(xr); keep(pubC); keep(pubC2); keep(fl);
            if (actc) {
                const char* polB = gx + nearp(pairG(0, cc, i)) + n80 * 4 + lag<DELAY_G>(sb);
                uint32_t xas = sb + S_XA + 192 + 192 * cc + a_pos(n80), xbs = sb + S_XB + 384 * cc + b_pos<40>(n80);
                x1 = cc ? ldsf(sb + S_XCAR + 4 * n80) : bf_lo(lds16(sb + S_X0 + 160 * (ch & 3) + 2 * n80));
                keep(xas); keep(xbs); keep(x1);
                x1 = bfr(x1 + bfr(gather16(polB, parc, 5 * ch + 1, [](uint32_t) { return false; })));
                CSTAMP(10);
                sts_hi16(xbs, x1);
                sts_hi16(xas, x1);
            }
        }
        bar_main();
        TST(3);
        CSTAMP(11);
        auto stats = [&](uint32_t xa, const uint4& b, uint32_t b4) {
            float a[4] = {};
            const uint4 p0 = lds128(xa), p1 = lds128(xa + 16);
            const uint2 p2 = lds64(xa + 32);
            mmaV(a, p0, b.x, b.y); mmaV(a, p1, b.z, b.w); mma8(a, p2.x, p2.y, b4);
            return a[0] + a[3];
        };
        {
            auto gate_up = [&](auto with_stats) {
                const uint4 b = lds128(xr);
                const uint32_t b4 = lds32(xr + 16);
                float acc[3][4] = {}, st = 0.f;
                if (with_stats.value) st = stats(xr + (S_XA - S_XB), b, b4);
                mul80(acc, Wgu, b, b4);
                stp64_if(!(td & 2), pubC, tagw(acc[0][0] + acc[0][3], fl & 1), tagw(acc[1][0] + acc[1][3], fl & 1));
                stp32_if(fl & 2, pubC2, !with_stats.value || (td & 2) ? acc[2][0] + acc[2][3] : st, fl & 1);
            };
            if (wp == 7) gate_up(std::true_type()); else gate_up(std::false_type());
        }
        sts32_if(td == 255, sb + S_GATE, ch + 1);
        CSTAMP(12);
        float mean = 0.f, den = 1.f;
        {
            IDS();
            const uint32_t wa = sb + S_WD + ((ln & 7) + 48 * ((ln >> 3) & 1) + 8 * (ln >> 4)) * 160 + (wp < 7 ? 16 * wp : 128);
            uint32_t ha = sb + S_HS + 48 * (ln & 15);
            XPtr pubD = gx + pairG(1, t4 & 1, i) * 8192 + (g >> 3) * HALF + (g & 7) * 512 + (wp < 7 ? 32 * wp : 256) + 16 * (t4 & 2) + 4 * q8;
            if (ch == 0) mbar_wait(sb + S_WFULL + 80, 0);
            auto down = [&](const uint32_t (&W)[3][4], const uint4& h0, const uint2& h1) {
                float a0[4] = {}, a1[4] = {}, a2[4] = {};
                mmaA(a0, W[0], h0.x, h0.y); mmaA(a1, W[1], h0.z, h0.w); mmaA(a2, W[2], h1.x, h1.y);
                return ((a0[0] + a0[3]) + (a1[0] + a1[3])) + (a2[0] + a2[3]);
            };
            if (wp < 6) {
                uint32_t Wd[3][4];
                auto ldd = [&] {
#pragma unroll
                    for (int s = 0; s < 3; s++) ldsm4t(Wd[s], wa + s * 2560);
                };
                uint32_t hsa = sb + S_HS + 384 * cc + b_pos<48>(n96);
                keep(ha); keep(pubD); keep(hsa);
                if (actc) {
                    const XPtr src0 = gx + nearp(pairL(RC, cc, g)) + lag<DELAY_C>(sb);
                    const char* srcv = src0 + 8 * n96;
                    const char* src = src0 + (ln & 1) * HALF;
                    uint2 v[8], st[4];
                    float sx, sq, pg, pu, rd;
                    uint2 cs;
                    int guard = 0;
                    bool again;
                    do {
#pragma unroll
                        for (int s = 0; s < 4; s++) st[s] = ldp64(src + 768 + s * 1024);
#pragma unroll
                        for (int s = 0; s < 8; s++) v[s] = ldp64(srcv + (s >> 2) * HALF + (s & 3) * 1024);
                        sx = (asf(st[0].x) + asf(st[1].x)) + (asf(st[2].x) + asf(st[3].x)); sq = (asf(st[0].y) + asf(st[1].y)) + (asf(st[2].y) + asf(st[3].y));
                        sx += __shfl_xor_sync(~0u, sx, 1); sq += __shfl_xor_sync(~0u, sq, 1);
                        cs = lds64(sb + S_CSGU - 768 * cc + 8 * td);
                        again = __any_sync(~0u, or3(chk4(st, parc), chk8(v, parc), chk8y(v, parc)) & 1);
                        pg = sum8x(v); pu = sum8y(v);
                        if (SPEC) { ln_stats(sx, sq, mean, den); rd = rcp(den); keep(mean); keep(rd); }
                        keep(pg); keep(pu);
                    } while (again && ++guard < SPIN_LIMIT);
                    CSTAMP(13);
                    ldd();
                    SWEEPS(5 * ch + 2, guard);
                    if (!SPEC) { ln_stats(sx, sq, mean, den); rd = rcp(den); }
                    const float gt = bfr(fmaf(-mean, asf(cs.x), pg) * rd), up = bfr(fmaf(-mean, asf(cs.y), pu) * rd);
                    const float h = bfr(bfr(gt * sigmoidf_(gt)) * up);
                    sts_hi16(hsa, h);
                    CSTAMP(14);
                } else ldd();
                bar_main();
                TST(4);
                CSTAMP(15);
                const uint4 h0 = lds128(ha);
                const uint2 h1 = lds64(ha + 16);
                stp32_if(!(td & 2), pubD, down(Wd, h0, h1), fl & 1);
            } else {
                uint32_t Wd[2][3][4];
#pragma unroll
                for (int s = 0; s < 6; s++) ldsm4t(Wd[s / 3][s % 3], wa + (s / 3) * 16 + (s % 3) * 2560);
                keep(ha); keep(pubD);
                uint32_t v = 0;
                if (wp == 6 ? has0 : has1) {
                    const uint32_t par = wp == 6 ? par0 : par1;
                    const char* src = gx + nearp(pairL(RC, wp - 6, g)) + 768 + (ln & 4) * (HALF / 4) + (ln & 3) * 1024 + 4 * min(ln >> 3, 2u) + lag<DELAY_C>(sb);
                    int guard = 0;
                    do v = ldp32(src); while (__any_sync(~0u, (v ^ par) & 1) && ++guard < SPIN_LIMIT);
                }
                bar_main();
                const uint4 h0 = lds128(ha);
                const uint2 h1 = lds64(ha + 16);
                const float d0 = down(Wd[0], h0, h1), d1 = down(Wd[1], h0, h1);
                stp32_if(true, pubD, (td & 2) ? d1 : d0, fl & 1);
                if (wp == 6 ? has0 : has1) {
                    float sx = asf(v);
                    sx += __shfl_xor_sync(~0u, sx, 1); sx += __shfl_xor_sync(~0u, sx, 2); sx += __shfl_xor_sync(~0u, sx, 4);
                    const float sq = __shfl_sync(~0u, sx, 8), xw = __shfl_sync(~0u, sx, 16);
                    ln_stats(sx, sq, mean, den);
                    const float r = bfr(fmaf(-mean, ldsf(sb + S_SWR), xw) * rcp(den));
                    sts32_if(ln == 0, sb + S_STAT + 4 * (wp - 6), __float_as_uint(bfr(sigmoidf_(r))) | (ch + 1));
                }
            }
        }
        CSTAMP(16);
        XPtr pubE = gx;
        {
            IDS();
            pubE = gx + pairL(RE, 0, g) * 8192 + (i >> 2) * HALF + (i & 3) * 1024 +
                   (t4 < 3 ? (wp >> 2) * (32 * 8192) + 192 * (wp & 3) + 64 * t4 + 8 * q8 : (q8 >> 2) * (32 * 8192) + 768 + 4 * (q8 & 1));
            xr = sb + S_XB + 48 * (ln & 7);
            keep(xr); keep(pubE);
            if (actc && (cc == 0 || g == 0)) {
                const char* polD = gx + nearp(pairG(1, cc, i)) + n80 * 4 + lag<DELAY_D>(sb);
                float lnx = bfr(__fdiv_rn(bfr(x1 - mean), den));
                unsigned short* po = reinterpret_cast<unsigned short*>(P.out) + 640 * (ch - 1) + 80 * i + n80;
                uint32_t xas = sb + S_XA + 192 + a_pos(n80), xbs = sb + S_XB + b_pos<40>(n80), xca = sb + S_XCAR + 4 * n80;
                keep(lnx); keep(po); keep(xca); keep(xas); keep(xbs);
                uint32_t gate;
                const float dn = gather16(polD, parc, 5 * ch + 3, [&](uint32_t z) { gate = ldsvol(sb + S_STAT + 4 * cc + z); return (gate & 7) != ch + 1; });
                const float y = bfr(bfr(dn) * bf_hi(gate));
                CSTAMP(17);
                const float x2 = bfr(x1 + bfr(lnx + y));
                if (cc) *po = (unsigned short)(__float_as_uint(x2) >> 16);
                else {
                    sts_hi16(xbs, x2);
                    sts_hi16(xas, x2);
                    stsf(xca, x2);
                }
            }
        }
        CSTAMP(18);
        if (!has0) break;
        bar_main();
        TST(5);
        CSTAMP(19);
        {
            auto qproj = [&](auto with_stats) {
                const uint32_t t4 = td & 3;
                const uint4 b = lds128(xr);
                const uint32_t b4 = lds32(xr + 16);
                if (with_stats.value) stp32_if((td & 11) == 3, pubE, stats(xr + (S_XA - S_XB), b, b4), par0);
                float acc[6][4] = {};
                mul80(acc, Wq, b, b4);
                const float v0 = sel4(t4, acc[0][0] + acc[0][3], acc[2][0] + acc[2][3], acc[4][0] + acc[4][3], acc[4][0] + acc[4][3]);
                const float v1 = sel4(t4, acc[1][0] + acc[1][3], acc[3][0] + acc[3][3], acc[5][0] + acc[5][3], acc[5][0] + acc[5][3]);
                stp64_if(t4 < 3, pubE, tagw(v0, par0), tagw(v1, par0));
            };
            if (wp == 7) qproj(std::true_type()); else qproj(std::false_type());
        }
        CSTAMP(20);
        {
            IDS();
            const uint32_t ua = sb + k_place(ch, wp & 6) * SLOT + (wp & 1) * UNIT, ub = (k_place(ch, wp | 1) - k_place(ch, wp & 6)) * SLOT;
            uint32_t kf[12][2][4];
            auto ldk = [&](int s) { const uint32_t a = (ua + k_off(ln, s >> 2)) ^ ((s & 3) * 32); ldsm4(kf[s][0], a); ldsm4(kf[s][1], a + ub); };
            mbar_wait(sb + S_FK + 8 * (wp & 6), par1); mbar_wait(sb + S_FK + 8 * (wp | 1), par1);
#pragma unroll
            for (int s = 0; s < KPRE; s++) ldk(s);
            if (wp < 6) {
                const XPtr src0 = gx + nearp(pairL(RE, i >> 2, g)) + lag<DELAY_E>(sb);
                const char* srcv = src0 + 4 * td;
                const char* src = src0 + (ln & 1) * HALF;
                uint32_t v[8]; uint2 st[4];
                float sx, sq, qs, rd, cs;
                int guard = 0;
                bool again;
                do {
#pragma unroll
                    for (int s = 0; s < 4; s++) st[s] = ldp64(src + 768 + s * 1024);
#pragma unroll
                    for (int s = 0; s < 8; s++) v[s] = ldp32(srcv + (s >> 2) * HALF + (s & 3) * 1024);
                    sx = (asf(st[0].x) + asf(st[1].x)) + (asf(st[2].x) + asf(st[3].x)); sq = (asf(st[0].y) + asf(st[1].y)) + (asf(st[2].y) + asf(st[3].y));
                    sx += __shfl_xor_sync(~0u, sx, 1); sq += __shfl_xor_sync(~0u, sq, 1);
                    cs = ldsf(sb + S_CSQ + 4 * td);
                    again = __any_sync(~0u, (chk8(v, par0) | chk4(st, par0)) & 1);
                    qs = sum8(v);
                    if (SPEC) { ln_stats(sx, sq, mean, den); rd = rcp(den); keep(mean); keep(rd); }
                    keep(qs);
                } while (again && ++guard < SPIN_LIMIT);
                CSTAMP(21);
                if (!SPEC) { ln_stats(sx, sq, mean, den); rd = rcp(den); }
                const float q = bfr(fmaf(-mean, cs, qs) * rd);
                sts_hi16(sb + S_QS + 512 * ch + q_pos(td), q);
                SWEEPS(5 * ch + 4, guard);
                CSTAMP(22);
            }
            __syncwarp();
#pragma unroll
            for (int s = KPRE; s < KPRE + KPRE2; s++) ldk(s);
            bar_main();
            TST(6);
            CSTAMP(1);
            const uint4 q = lds128(sb + S_QS + 512 * ch + 16 * ln);
            float acc[2][4] = {};
            constexpr int D = KPRE + KPRE2;
#pragma unroll
            for (int s = 0; s < 12; s++) {
                const bool m = q8 == (s & 7);
                const uint32_t b0 = m ? (s < 8 ? q.x : q.z) : 0u, b1 = m ? (s < 8 ? q.y : q.w) : 0u;
                mmaA(acc[0], kf[s][0], b0, b1);
                mmaA(acc[1], kf[s][1], b0, b1);
                if (s + D < 12) ldk(s + D);
            }
            vaddr(voff);
            auto ldv = [&](int s) {
#pragma unroll
                for (int T = 0; T < 3; T++) ldsm4t(vf[s][T], voff[T] + (sb + v_place(ch, s) * SLOT));
            };
            ldv(3);
            {
                const float v0 = acc[0][0] + acc[0][1], v1 = acc[0][2] + acc[0][3], v2 = acc[1][0] + acc[1][1], v3 = acc[1][2] + acc[1][3];
                const bool hi = t4 & 2, od = t4 & 1;
                const float u0 = (hi ? v2 : v0) + __shfl_xor_sync(~0u, hi ? v0 : v2, 2), u1 = (hi ? v3 : v1) + __shfl_xor_sync(~0u, hi ? v1 : v3, 2);
                const float s = (od ? u1 : u0) + __shfl_xor_sync(~0u, od ? u0 : u1, 1);
                CSTAMP(2);
                arrive_if(ln == 0, sb + S_RELK);
                probs(scaled(s), sb + S_PS + PS_PASS, wp, ln);
            }
            bar_main();
            TST(10);
            CSTAMP(4);
            values(vf, [&](int s) { if (s >= 1 && s < 5) ldv(s + 3); }, sb + S_PS + PS_PASS, 1, par0);
            arrive_if(ln == 0, sb + S_RELV);
        }
        TST(11);
        CSTAMP(23);
    }
    sts32_if(td == 255, sb + S_GATE, 6);
    TSTAMP(3);
}

typedef CUresult (*EncodeFn)(CUtensorMap*, CUtensorMapDataType, cuuint32_t, void*, const cuuint64_t*, const cuuint64_t*, const cuuint32_t*,
                             const cuuint32_t*, CUtensorMapInterleave, CUtensorMapSwizzle, CUtensorMapL2promotion, CUtensorMapFloatOOBfill);

void make_map(EncodeFn enc, CUtensorMap* m, const void* base, uint64_t cols, uint64_t rows, uint32_t box_cols, uint32_t box_rows, bool swizzle) {
    cuuint64_t dims[2] = {cols, rows};
    cuuint64_t strides[1] = {cols * 2};
    cuuint32_t box[2] = {box_cols, box_rows};
    cuuint32_t es[2] = {1, 1};
    enc(m, CU_TENSOR_MAP_DATA_TYPE_BFLOAT16, 2, const_cast<void*>(base), dims, strides, box, es, CU_TENSOR_MAP_INTERLEAVE_NONE,
        swizzle ? CU_TENSOR_MAP_SWIZZLE_128B : CU_TENSOR_MAP_SWIZZLE_NONE, swizzle ? CU_TENSOR_MAP_L2_PROMOTION_NONE : WPROMO, CU_TENSOR_MAP_FLOAT_OOB_FILL_NONE);
}

}

extern "C" void kernel_launch(void* const* d_in, const int* in_sizes, int n_in, void* d_out, int out_size) {
    (void)in_sizes; (void)n_in; (void)out_size;
    static EncodeFn enc = nullptr;
    if (!enc) {
        void* f = nullptr;
        cudaDriverEntryPointQueryResult q;
        cudaGetDriverEntryPoint("cuTensorMapEncodeTiled", &f, cudaEnableDefault, &q);
        enc = (EncodeFn)f;
        cudaFuncSetAttribute(fused_kernel, cudaFuncAttributeMaxDynamicSharedMemorySize, SMEM_BYTES);
    }
    Params P;
    P.x = (const __nv_bfloat16*)d_in[0]; P.k = (const __nv_bfloat16*)d_in[1]; P.v = (const __nv_bfloat16*)d_in[2];
    P.wr = (const __nv_bfloat16*)d_in[6];
    P.out = (__nv_bfloat16*)d_out;
    Maps M;
    make_map(enc, &M.k, P.k, 64, (uint64_t)12 * KV_BATCH_KEYS, 64, 48, true);
    make_map(enc, &M.v, P.v, 64, (uint64_t)12 * KV_BATCH_KEYS, 64, 96, true);
    make_map(enc, &M.wq, d_in[3], 6144, 640, 192, 40, false);
    make_map(enc, &M.wo, d_in[4], 640, 6144, 80, 96, false);
    make_map(enc, &M.wg, d_in[7], 1536, 640, 96, 80, false);
    make_map(enc, &M.wu, d_in[8], 1536, 640, 96, 80, false);
    make_map(enc, &M.wd, d_in[9], 640, 1536, 80, 96, false);
    fused_kernel<<<NCTA, NTHR, SMEM_BYTES, cudaStreamPerThread>>>(P, M);
}
```

```cpp
#include <cuda_runtime.h>
#include <cuda.h>
#include <cuda_bf16.h>
#include <stdint.h>
#include <type_traits>

namespace {

constexpr int NCTA = 128;
constexpr int NTHR = 384;
constexpr int UNIT = 6144;
constexpr int SLOT = 12288;
#define TAU 4100
#define TAUW 4000
#define TMIN 2400
#define T_LEAD 0
#define WIN_W 3
#define WIN_S 4
#define WIN_U 10
#define RFR_ON 1
#define KRE_N1 0
#define KRE_TAU1 2500
#define RFR_TAU 6400
#define VPF 5
#define KRE_GATE 0
#define KRE_GATE3 KRE_GATE
#define JFREE 16
#define TFREE 0
#define KRE_TAU 4000
#define KRE_TAU3 KRE_TAU
#define HDEPTH 3
#define SPEC 1
#define PV1PIPE 0
#define HOPA0 7
#define HOPA1 7
#define WPROMO CU_TENSOR_MAP_L2_PROMOTION_NONE
#define KPRE 1
#define KPRE2 2
#define DELAY_G 6
#define DELAY_L 5
#define DELAY_C 3
#define DELAY_D 6
#define DELAY_E 3
#define REG_LO "40"
#define REG_HI "232"
#define SPIN_LOG 17
constexpr int SPIN_LIMIT = 1 << SPIN_LOG;

__host__ __device__ constexpr uint32_t pairL(uint32_t region, uint32_t c, uint32_t g) { return (g & 1) | ((g >> 1) << 2) | (c << 5) | (region << 6); }
__host__ __device__ constexpr uint32_t pairG(uint32_t d, uint32_t c, uint32_t i) { return (i & 1) | ((i >> 1) << 2) | (d << 4) | (c << 5) | (3u << 6); }
constexpr uint32_t RA = 0, RC = 1, RE = 2, HALF = 16384, COPY = 4096, PMASK = 0x59;
constexpr uint32_t XS = 0;
constexpr uint32_t XS2 = XS + 128 * 7680;
constexpr uint32_t XSEND = XS2 + 128 * 768;
__device__ uint4 g_s[XSEND / 16];
__device__ uint4 g_x[(4u << 20) / 16];
#define SWEEPS(k, n) do {} while (0)

constexpr uint32_t S_WD = 16 * SLOT;
constexpr uint32_t S_DUMMY = S_WD + 15360;
constexpr uint32_t S_BAR = S_DUMMY + 4096;
constexpr uint32_t S_FV = S_BAR, S_FK = S_FV + 64, S_RING = S_FK + 64, S_DBAR = S_RING + 48, S_WFULL = S_DBAR + 32, S_QRDY = S_WFULL + 88;
constexpr uint32_t S_RELK = S_QRDY + 8, S_RELV = S_RELK + 8, S_RELR = S_RELV + 8, S_RELW = S_RELR + 8, S_SCO = S_RELW + 24;
constexpr uint32_t S_ZERO = S_SCO + 8;
constexpr uint32_t S_KF = S_SCO + 24;
constexpr uint32_t S_TOK = S_KF + 8;
constexpr uint32_t S_SIDE = S_TOK + 24, S_GATE = S_SIDE + 4;
constexpr uint32_t S_STAT = S_GATE + 4, S_SWR = S_STAT + 16;
constexpr uint32_t S_XCAR = S_STAT + 32;
constexpr uint32_t S_CSQ = S_XCAR + 320;
constexpr uint32_t S_CSGU = S_CSQ + 768;
constexpr uint32_t S_RED = S_CSGU + 768;
constexpr uint32_t S_L0 = S_RED;
constexpr uint32_t S_OS = S_RED + 5120;
constexpr uint32_t S_PS = S_OS + 1536;
constexpr uint32_t PS_MAX = 512, PS_PASS = 544;
constexpr uint32_t S_QS = S_PS + 2 * PS_PASS;
constexpr uint32_t S_XB = S_QS + 2048;
constexpr uint32_t S_XA = S_XB + 768;
constexpr uint32_t S_HS = S_XA + 768;
constexpr uint32_t S_X0 = S_HS + 768;
constexpr uint32_t S_SC = S_X0 + 640;
constexpr uint32_t S_TM = S_SC + 512;
constexpr int SMEM_BYTES = S_TM + 256;
static_assert(SMEM_BYTES <= 232448 && S_STAT % 16 == 0 && S_RED % 16 == 0 && S_XB % 16 == 0 && S_HS % 16 == 0 && S_PS % 16 == 0 && S_QS % 16 == 0, "smem");
static_assert(S_SCO == S_BAR + 44 * 8 && S_RELK == S_BAR + 38 * 8, "barriers");
constexpr uint32_t ST_WQ = 3 * SLOT, ST_WG = 8 * SLOT, ST_WO = 11 * SLOT;

__device__ __forceinline__ uint32_t smem_u32(const void* p) { return (uint32_t)__cvta_generic_to_shared(p); }
__device__ __forceinline__ void mbar_init(uint32_t bar, uint32_t cnt) { asm volatile("mbarrier.init.shared::cta.b64 [%0], %1;" :: "r"(bar), "r"(cnt) : "memory"); }
__device__ __forceinline__ void mbar_expect(uint32_t bar, uint32_t bytes) { asm volatile("mbarrier.arrive.expect_tx.shared::cta.b64 _, [%0], %1;" :: "r"(bar), "r"(bytes) : "memory"); }
__device__ __forceinline__ void mbar_arrive(uint32_t bar) { asm volatile("mbarrier.arrive.shared::cta.b64 _, [%0];" :: "r"(bar) : "memory"); }
__device__ __forceinline__ bool mbar_try(uint32_t bar, uint32_t parity) {
    uint32_t ok;
    asm volatile("{\n .reg .pred p;\n mbarrier.try_wait.parity.shared::cta.b64 p, [%1], %2;\n selp.u32 %0, 1, 0, p;\n}" : "=r"(ok) : "r"(bar), "r"(parity) : "memory");
    return ok != 0;
}
__device__ __forceinline__ bool mbar_test(uint32_t bar, uint32_t parity) {
    uint32_t ok;
    asm volatile("{\n .reg .pred p;\n mbarrier.test_wait.parity.shared::cta.b64 p, [%1], %2;\n selp.u32 %0, 1, 0, p;\n}" : "=r"(ok) : "r"(bar), "r"(parity) : "memory");
    return ok != 0;
}
__device__ __forceinline__ void mbar_wait(uint32_t bar, uint32_t parity) {
    int n = 0;
    while (!mbar_try(bar, parity) && ++n < SPIN_LIMIT) {}
}
__device__ __forceinline__ unsigned long long gtime() { unsigned long long t; asm volatile("mov.u64 %0, %globaltimer;" : "=l"(t)); return t; }
__device__ __forceinline__ uint32_t gtime32() { uint32_t t; asm volatile("mov.u32 %0, %globaltimer_lo;" : "=r"(t)); return t; }
__device__ __forceinline__ void bar_main() { __syncwarp(); asm volatile("bar.sync 1, 256;" ::: "memory"); }

__device__ __forceinline__ void mma16816(float (&c)[4], uint32_t a0, uint32_t a1, uint32_t a2, uint32_t a3, uint32_t b0, uint32_t b1) {
    asm("mma.sync.aligned.m16n8k16.row.col.f32.bf16.bf16.f32 {%0,%1,%2,%3}, {%4,%5,%6,%7}, {%8,%9}, {%0,%1,%2,%3};"
        : "+f"(c[0]), "+f"(c[1]), "+f"(c[2]), "+f"(c[3]) : "r"(a0), "r"(a1), "r"(a2), "r"(a3), "r"(b0), "r"(b1));
}
__device__ __forceinline__ void mmaA(float (&c)[4], const uint32_t (&a)[4], uint32_t b0, uint32_t b1) { mma16816(c, a[0], a[1], a[2], a[3], b0, b1); }
__device__ __forceinline__ void mmaAv(float (&c)[4], const uint32_t (&a)[4], uint32_t b0, uint32_t b1) {
    asm volatile("mma.sync.aligned.m16n8k16.row.col.f32.bf16.bf16.f32 {%0,%1,%2,%3}, {%4,%5,%6,%7}, {%8,%9}, {%0,%1,%2,%3};"
        : "+f"(c[0]), "+f"(c[1]), "+f"(c[2]), "+f"(c[3]) : "r"(a[0]), "r"(a[1]), "r"(a[2]), "r"(a[3]), "r"(b0), "r"(b1) : "memory");
}
__device__ __forceinline__ void mma8(float (&c)[4], uint32_t a0, uint32_t a1, uint32_t b0) {
    asm("mma.sync.aligned.m16n8k8.row.col.f32.bf16.bf16.f32 {%0,%1,%2,%3}, {%4,%5}, {%6}, {%0,%1,%2,%3};"
        : "+f"(c[0]), "+f"(c[1]), "+f"(c[2]), "+f"(c[3]) : "r"(a0), "r"(a1), "r"(b0));
}
struct W80 { uint32_t a[2][4], c[2]; };
template <int N> __device__ __forceinline__ void mul80(float (&acc)[N][4], const W80 (&W)[N], const uint4& b, uint32_t b4) {
#pragma unroll
    for (int m = 0; m < N; m++) mmaA(acc[m], W[m].a[0], b.x, b.y);
#pragma unroll
    for (int m = 0; m < N; m++) mmaA(acc[m], W[m].a[1], b.z, b.w);
#pragma unroll
    for (int m = 0; m < N; m++) mma8(acc[m], W[m].c[0], W[m].c[1], b4);
}
__device__ __forceinline__ void ldsm2t(uint32_t (&r)[2], uint32_t addr) {
    asm volatile("ldmatrix.sync.aligned.m8n8.x2.trans.shared.b16 {%0,%1}, [%2];" : "=r"(r[0]), "=r"(r[1]) : "r"(addr) : "memory");
}
__device__ __forceinline__ void mmaV(float (&c)[4], const uint4& a, uint32_t b0, uint32_t b1) { mma16816(c, a.x, a.y, a.z, a.w, b0, b1); }
__device__ __forceinline__ void ldsm4(uint32_t (&r)[4], uint32_t addr) {
    asm volatile("ldmatrix.sync.aligned.m8n8.x4.shared.b16 {%0,%1,%2,%3}, [%4];" : "=r"(r[0]), "=r"(r[1]), "=r"(r[2]), "=r"(r[3]) : "r"(addr) : "memory");
}
__device__ __forceinline__ void ldsm4t(uint32_t (&r)[4], uint32_t addr) {
    asm volatile("ldmatrix.sync.aligned.m8n8.x4.trans.shared.b16 {%0,%1,%2,%3}, [%4];" : "=r"(r[0]), "=r"(r[1]), "=r"(r[2]), "=r"(r[3]) : "r"(addr) : "memory");
}
__device__ __forceinline__ uint32_t lds16(uint32_t a) { uint16_t v; asm volatile("ld.shared.u16 %0, [%1];" : "=h"(v) : "r"(a) : "memory"); return v; }
__device__ __forceinline__ uint32_t lds32(uint32_t a) { uint32_t v; asm volatile("ld.shared.u32 %0, [%1];" : "=r"(v) : "r"(a) : "memory"); return v; }
__device__ __forceinline__ float ldsf(uint32_t a) { return __uint_as_float(lds32(a)); }
__device__ __forceinline__ uint2 lds64(uint32_t a) { uint2 v; asm volatile("ld.shared.v2.u32 {%0,%1}, [%2];" : "=r"(v.x), "=r"(v.y) : "r"(a) : "memory"); return v; }
__device__ __forceinline__ uint4 lds128(uint32_t a) { uint4 v; asm volatile("ld.shared.v4.u32 {%0,%1,%2,%3}, [%4];" : "=r"(v.x), "=r"(v.y), "=r"(v.z), "=r"(v.w) : "r"(a) : "memory"); return v; }
__device__ __forceinline__ int ldsvol(uint32_t a) { int v; asm volatile("ld.volatile.shared.u32 %0, [%1];" : "=r"(v) : "r"(a) : "memory"); return v; }
__device__ __forceinline__ void stsvol(uint32_t a, int v) { asm volatile("st.volatile.shared.u32 [%0], %1;" :: "r"(a), "r"(v) : "memory"); }
__device__ __forceinline__ void sts_hi16(uint32_t a, float v) { asm volatile("{\n .reg .b16 lo, hi;\n mov.b32 {lo, hi}, %1;\n st.shared.u16 [%0], hi;\n}" :: "r"(a), "r"(__float_as_uint(v)) : "memory"); }
__device__ __forceinline__ void sts32(uint32_t a, uint32_t v) { asm volatile("st.shared.u32 [%0], %1;" :: "r"(a), "r"(v) : "memory"); }
__device__ __forceinline__ void stsf(uint32_t a, float v) { sts32(a, __float_as_uint(v)); }
__device__ __forceinline__ void sts64(uint32_t a, uint32_t x, uint32_t y) { asm volatile("st.shared.v2.u32 [%0], {%1,%2};" :: "r"(a), "r"(x), "r"(y) : "memory"); }

__device__ __forceinline__ void sts_hi16_if(bool p, uint32_t a, float v) {
    asm volatile("{\n .reg .pred p;\n .reg .b16 lo, hi;\n setp.ne.u32 p, %2, 0;\n mov.b32 {lo, hi}, %1;\n @p st.shared.u16 [%0], hi;\n}" :: "r"(a), "r"(__float_as_uint(v)), "r"((uint32_t)p) : "memory");
}
__device__ __forceinline__ void sts32_if(bool p, uint32_t a, uint32_t v) {
    asm volatile("{\n .reg .pred p;\n setp.ne.u32 p, %2, 0;\n @p st.shared.u32 [%0], %1;\n}" :: "r"(a), "r"(v), "r"((uint32_t)p) : "memory");
}
__device__ __forceinline__ void sts64_if(bool p, uint32_t a, float x, float y) {
    asm volatile("{\n .reg .pred p;\n setp.ne.u32 p, %3, 0;\n @p st.shared.v2.f32 [%0], {%1,%2};\n}" :: "r"(a), "f"(x), "f"(y), "r"((uint32_t)p) : "memory");
}
__device__ __forceinline__ void arrive_if(bool p, uint32_t bar) {
    asm volatile("{\n .reg .pred p;\n setp.ne.u32 p, %1, 0;\n @p mbarrier.arrive.shared::cta.b64 _, [%0];\n}" :: "r"(bar), "r"((uint32_t)p) : "memory");
}
__device__ __forceinline__ void opaque(uint32_t& v) { asm volatile("" : "+r"(v)); }
__device__ __forceinline__ void keep(uint32_t& v) { asm volatile("" : "+r"(v)); }
__device__ __forceinline__ void keep(float& v) { asm volatile("" : "+f"(v)); }
template <class T> __device__ __forceinline__ void keep(T*& v) { asm volatile("" : "+l"(v)); }

__device__ __forceinline__ uint32_t ldp32(const char* p) { uint32_t v; asm volatile("ld.relaxed.gpu.global.u32 %0, [%1];" : "=r"(v) : "l"(p) : "memory"); return v; }
__device__ __forceinline__ uint2 ldp64(const char* p) {
    uint2 v; asm volatile("{\n .reg .b64 d;\n ld.relaxed.gpu.global.b64 d, [%2];\n mov.b64 {%0,%1}, d;\n}" : "=r"(v.x), "=r"(v.y) : "l"(p) : "memory"); return v;
}
__device__ __forceinline__ uint32_t tagw(float f, uint32_t par) { return (__float_as_uint(f) & ~1u) | par; }
__device__ __forceinline__ void stp32(char* p, float a, uint32_t par) { asm volatile("st.relaxed.gpu.global.u32 [%0], %1;" :: "l"(p), "r"(tagw(a, par)) : "memory"); }
__device__ __forceinline__ void stp64(char* p, float a, float b, uint32_t par) {
    asm volatile("{\n .reg .b64 d;\n mov.b64 d, {%1,%2};\n st.relaxed.gpu.global.b64 [%0], d;\n}" :: "l"(p), "r"(tagw(a, par)), "r"(__float_as_uint(b)) : "memory");
}
__device__ __forceinline__ void stp32_if(bool p, char* d, float a, uint32_t par) {
    asm volatile("{\n .reg .pred p;\n setp.ne.u32 p, %2, 0;\n @p st.relaxed.gpu.global.u32 [%0], %1;\n @p st.relaxed.gpu.global.u32 [%0+4096], %1;\n}" :: "l"(d), "r"(tagw(a, par)), "r"((uint32_t)p) : "memory");
}
__device__ __forceinline__ void stp64_if(bool p, char* d, uint32_t lo, uint32_t hi) {
    asm volatile("{\n .reg .pred p;\n .reg .b64 d;\n setp.ne.u32 p, %3, 0;\n mov.b64 d, {%1,%2};\n @p st.relaxed.gpu.global.b64 [%0], d;\n @p st.relaxed.gpu.global.b64 [%0+4096], d;\n}" :: "l"(d), "r"(lo), "r"(hi), "r"((uint32_t)p) : "memory");
}
__device__ __forceinline__ uint32_t chk2(uint32_t a, uint32_t b, uint32_t par) { uint32_t r; asm("lop3.b32 %0, %1, %2, %3, 0x7E;" : "=r"(r) : "r"(a), "r"(b), "r"(par)); return r; }
__device__ __forceinline__ uint32_t or3(uint32_t a, uint32_t b, uint32_t c) { uint32_t r; asm("lop3.b32 %0, %1, %2, %3, 0xFE;" : "=r"(r) : "r"(a), "r"(b), "r"(c)); return r; }
__device__ __forceinline__ uint32_t chk8(const uint32_t (&v)[8], uint32_t par) { return or3(chk2(v[0], v[1], par), chk2(v[2], v[3], par), or3(chk2(v[4], v[5], par), chk2(v[6], v[7], par), 0)); }
__device__ __forceinline__ uint32_t chk8(const uint2 (&v)[8], uint32_t par) { return or3(chk2(v[0].x, v[1].x, par), chk2(v[2].x, v[3].x, par), or3(chk2(v[4].x, v[5].x, par), chk2(v[6].x, v[7].x, par), 0)); }
__device__ __forceinline__ uint32_t chk8y(const uint2 (&v)[8], uint32_t par) { return or3(chk2(v[0].y, v[1].y, par), chk2(v[2].y, v[3].y, par), or3(chk2(v[4].y, v[5].y, par), chk2(v[6].y, v[7].y, par), 0)); }
__device__ __forceinline__ uint32_t chk4(const uint2 (&v)[4], uint32_t par) { return or3(chk2(v[0].x, v[0].y, par), chk2(v[1].x, v[1].y, par), or3(chk2(v[2].x, v[2].y, par), chk2(v[3].x, v[3].y, par), 0)); }
__device__ __forceinline__ float asf(uint32_t v) { return __uint_as_float(v); }
__device__ __forceinline__ float sum8(const uint32_t (&v)[8]) { return ((asf(v[0]) + asf(v[1])) + (asf(v[2]) + asf(v[3]))) + ((asf(v[4]) + asf(v[5])) + (asf(v[6]) + asf(v[7]))); }
__device__ __forceinline__ float sum8x(const uint2 (&v)[8]) { return ((asf(v[0].x) + asf(v[1].x)) + (asf(v[2].x) + asf(v[3].x))) + ((asf(v[4].x) + asf(v[5].x)) + (asf(v[6].x) + asf(v[7].x))); }
__device__ __forceinline__ float sum8y(const uint2 (&v)[8]) { return ((asf(v[0].y) + asf(v[1].y)) + (asf(v[2].y) + asf(v[3].y))) + ((asf(v[4].y) + asf(v[5].y)) + (asf(v[6].y) + asf(v[7].y))); }

__device__ __forceinline__ uint32_t pack2(float lo, float hi) { uint32_t r; asm("cvt.rn.bf16x2.f32 %0, %1, %2;" : "=r"(r) : "f"(hi), "f"(lo)); return r; }
__device__ __forceinline__ float bfr(float x) { return __uint_as_float(pack2(0.0f, x)); }
__device__ __forceinline__ float ex2(float x) { float r; asm("ex2.approx.ftz.f32 %0, %1;" : "=f"(r) : "f"(x)); return r; }
__device__ __forceinline__ float rcp(float x) { float r; asm("rcp.approx.ftz.f32 %0, %1;" : "=f"(r) : "f"(x)); return r; }
__device__ __forceinline__ float sqrt_(float x) { float r; asm("sqrt.approx.ftz.f32 %0, %1;" : "=f"(r) : "f"(x)); return r; }
__device__ __forceinline__ float bf_lo(uint32_t v) { return __uint_as_float(v << 16); }
__device__ __forceinline__ float bf_hi(uint32_t v) { return __uint_as_float(v & 0xffff0000u); }
__device__ __forceinline__ float sel4(int k, float a, float b, float c, float d) { return (k & 2) ? ((k & 1) ? d : c) : ((k & 1) ? b : a); }
constexpr float LOG2E = 1.4426950408889634f;
constexpr uint32_t ONES = 0x3f803f80u;

__device__ __forceinline__ void ln_stats(float sum, float sq, float& mean, float& den) {
    const float m = sum * (1.0f / 640.0f);
    const float var = fmaxf(fmaf(sq, 1.0f / 640.0f, -m * m), 0.0f);
    mean = bfr(m);
    den = bfr(sqrt_(bfr(bfr(var) + 1e-5f)));
}
__device__ __forceinline__ float sigmoidf_(float x) { return rcp(1.0f + ex2(-x * LOG2E)); }

#define TSTAMP(k) do {} while (0)
#define TST(k) do {} while (0)

#define CSTAMP(k) do {} while (0)
template <int N> __device__ __forceinline__ uint32_t lag(uint32_t sb) {
    uint32_t z = 0;
#pragma unroll
    for (int k = 0; k < N; k++) z = ldsvol(sb + S_ZERO + z);
    return z;
}
__device__ __forceinline__ void warm_mma(uint32_t& a, uint32_t& b) {
    asm volatile("mma.sync.aligned.m16n8k8.row.col.f16.f16.f16.f16 {%0,%1}, {%0,%1}, {%0}, {%0,%1};" : "+r"(a), "+r"(b) :: "memory");
}
#define KWNS2 20
#define KWNS 200
template <int STRIDE>
__device__ __forceinline__ float gather8(const char* p, uint32_t par) {
    uint32_t v[8];
    int guard = 0;
    do {
#pragma unroll
        for (int s = 0; s < 8; s++) v[s] = ldp32(p + s * STRIDE);
    } while ((chk8(v, par) & 1) && ++guard < SPIN_LIMIT);
    return sum8(v);
}
template <class F>
__device__ __forceinline__ float gather16(const char* p, uint32_t par, int k, F also) {
    uint32_t v[8], u[8];
    float r;
    int guard = 0;
    bool again;
    do {
#pragma unroll
        for (int s = 0; s < 8; s++) v[s] = ldp32(p + s * 512);
#pragma unroll
        for (int s = 0; s < 8; s++) u[s] = ldp32(p + HALF + s * 512);
        again = ((chk8(v, par) | chk8(u, par)) & 1) | also(((v[0] ^ par) & 1) * 8);
        r = sum8(v) + sum8(u);
        keep(r);
    } while (again && ++guard < SPIN_LIMIT);
    SWEEPS(k, guard);
    return r;
}

struct Params {
    const __nv_bfloat16 *x, *k, *v, *wr;
    __nv_bfloat16* out;
};
struct Maps { CUtensorMap k, v, wq, wo, wg, wu, wd; };

constexpr int KV_BATCH_KEYS = 32 * 4096;

__device__ __forceinline__ void tma2d(uint32_t dst, const CUtensorMap* m, int c0, int c1, uint32_t bar, uint32_t bytes, uint64_t pol) {
    asm volatile("{\n .reg .pred p;\n elect.sync _|p, 0xffffffff;\n"
                 " @p mbarrier.arrive.expect_tx.shared::cta.b64 _, [%2], %6;\n"
                 " @p cp.async.bulk.tensor.2d.shared::cluster.global.mbarrier::complete_tx::bytes.L2::cache_hint [%0], [%1, {%3, %4}], [%2], %5;\n}"
                 :: "r"(dst), "l"(m), "r"(bar), "r"(c0), "r"(c1), "l"(pol), "r"(bytes) : "memory");
}
__device__ __forceinline__ void scrap_copy(uint32_t dst, const char* src, uint32_t bar) {
    asm volatile("{\n .reg .pred p;\n elect.sync _|p, 0xffffffff;\n"
                 " @p mbarrier.arrive.expect_tx.shared::cta.b64 _, [%2], 12288;\n"
                 " @p cp.async.bulk.shared::cluster.global.mbarrier::complete_tx::bytes [%0], [%1], 4096, [%2];\n"
                 " @p cp.async.bulk.shared::cluster.global.mbarrier::complete_tx::bytes [%0], [%1+4096], 4096, [%2];\n"
                 " @p cp.async.bulk.shared::cluster.global.mbarrier::complete_tx::bytes [%0], [%1+8192], 4096, [%2];\n}"
                 :: "r"(dst), "l"(src), "r"(bar) : "memory");
}
__device__ __forceinline__ void prefetch_l2(const void* p, uint32_t bytes) {
    asm volatile("{\n .reg .pred p;\n elect.sync _|p, 0xffffffff;\n @p cp.async.bulk.prefetch.L2.global [%0], %1;\n}" :: "l"(p), "r"(bytes) : "memory");
}
__device__ __forceinline__ uint64_t pol_first() { uint64_t p; asm("createpolicy.fractional.L2::evict_first.b64 %0, 1.0;" : "=l"(p)); return p; }
__device__ __forceinline__ uint64_t pol_normal() { uint64_t p; asm("createpolicy.fractional.L2::evict_normal.b64 %0, 1.0;" : "=l"(p)); return p; }
__device__ __forceinline__ bool utest(uint32_t bar, uint32_t parity) { return __all_sync(~0u, mbar_test(bar, parity)); }
__device__ __forceinline__ void uwait(uint32_t bar, uint32_t parity) {
    int n = 0;
    while (!__all_sync(~0u, mbar_try(bar, parity)) && ++n < SPIN_LIMIT) {}
}
template <int A, int B, int CNT> __device__ __forceinline__ void init_bars(uint32_t sb) {
#pragma unroll 1
    for (int k = A; k < B; k++)
        asm volatile("{\n .reg .pred p;\n elect.sync _|p, 0xffffffff;\n @p mbarrier.init.shared::cta.b64 [%0], %1;\n}" :: "r"(sb + S_BAR + 8 * k), "n"(CNT) : "memory");
}
__device__ __forceinline__ int first_key() { return (blockIdx.x >> 2) * 4096 + 3072 + (blockIdx.x & 3) * 256; }
__device__ __forceinline__ void load_tile(const CUtensorMap* m, uint32_t dst, uint32_t bar, uint32_t bytes, int key, uint64_t pol) { tma2d(dst, m, 0, 3 * key, bar, bytes, pol); }
__device__ __forceinline__ const char* unit_ptr(const Params& P, int n) {
    return (const char*)((n & 16) ? P.v : P.k) + (size_t)(first_key() + (n >> 5) * KV_BATCH_KEYS + (n & 15) * 16) * 384;
}
#define LSTAMP(k) do {} while (0)

__device__ __forceinline__ uint32_t k_place(uint32_t b, uint32_t s) { return s + 3 + (s < 3 ? 0 : 5 * (b & 1)); }
__device__ __forceinline__ uint32_t v_place(uint32_t b, uint32_t s) { return s < 3 ? s : s + 8 - 5 * (b & 1); }
__device__ __forceinline__ uint32_t ring_pos(uint32_t n) { const uint32_t u = (n & 15) + 2; return u - (u >= 12 ? 12 : u >= 6 ? 6 : 0); }
__device__ __forceinline__ void ring_load(const Maps& M, uint32_t sb, uint32_t n, uint32_t pos) {
    load_tile(&M.k, sb + pos * UNIT, sb + S_RING + 8 * pos, UNIT, first_key() + (n >> 4) * KV_BATCH_KEYS + 16 * (n & 15), pol_normal());
}
__device__ __forceinline__ uint32_t token(bool p, uint32_t a, uint32_t n) {
    uint32_t v;
    asm volatile("{\n .reg .pred p;\n setp.ne.u32 p, %2, 0;\n mov.u32 %0, 0;\n @p atom.shared.exch.b32 %0, [%1], %3;\n}" : "=r"(v) : "r"(a), "r"((uint32_t)p), "r"(n) : "memory");
    return v;
}
__device__ __forceinline__ void place_load(const Maps& M, uint32_t sb, uint32_t n) {
    load_tile(&M.k, sb + k_place(n >> 4, (n >> 1) & 7) * SLOT + (n & 1) * UNIT, sb + S_FK + 4 * (n & 14), UNIT,
              first_key() + (n >> 4) * KV_BATCH_KEYS + 16 * (n & 15), pol_first());
}
__device__ __forceinline__ void v_load(const Maps& M, uint32_t sb, uint32_t b, uint32_t s) {
    load_tile(&M.v, sb + v_place(b, s) * SLOT, sb + S_FV + 8 * s, SLOT, first_key() + b * KV_BATCH_KEYS + 32 * s, pol_first());
}
__device__ __forceinline__ bool due(uint32_t t) { return __all_sync(~0u, (int)(gtime32() * 16 - t) >= 0); }
__device__ __forceinline__ bool reached(uint32_t a, int v) { return __all_sync(~0u, ldsvol(a) >= v); }

__device__ __forceinline__ void stream_warp(const Params& P, const Maps& M, uint32_t sb, uint32_t lane) {
    const uint64_t pol = pol_first();
    const int bid = blockIdx.x, g = bid >> 3, i = bid & 7;
    const uint32_t wf = sb + S_WFULL;
    uint32_t tn = __shfl_sync(~0u, gtime32(), 0) * 16 - T_LEAD;
    auto pace = [&](uint32_t dt) { int k = 0; while (!due(tn) && ++k < SPIN_LIMIT) {} tn += dt; };
#pragma unroll
    for (int k = 0; k < 10; k++) {
        if (k < 2) {
            if (k == 0) init_bars<26, 27, 1>(sb); else init_bars<27, 37, 1>(sb);
            asm volatile("fence.mbarrier_init.release.cluster;" ::: "memory");
            if (k == 1) { asm volatile("bar.arrive 2, %0;" :: "n"(NTHR) : "memory"); asm volatile("bar.sync 3, 128;" ::: "memory"); }
        }
        if (k >= WIN_W) uwait(wf + 8 * (k - WIN_W), 0);
        pace(TAUW * 5 / 2);
        if (k < 4) tma2d(sb + ST_WQ + 15360 * k, &M.wq, 384 * g + 192 * (k >> 1), 80 * i + 40 * (k & 1), wf + 8 * k, 15360, pol);
        else if (k < 6) tma2d(sb + ST_WG + 15360 * (k - 4), k == 4 ? &M.wg : &M.wu, 96 * g, 80 * i, wf + 8 * k, 15360, pol);
        else tma2d(sb + ST_WO + 15360 * (k - 6), &M.wo, 80 * i, 384 * g + 96 * (k - 6), wf + 8 * k, 15360, pol);
    }
#pragma unroll 1
    for (int n = 0; n < 16; n++) {
        if (n == 0 || n == 5 || n == 11) uwait(sb + S_RELW + (n == 0 ? 0 : n == 5 ? 8 : 16), 0);
        uwait(n < WIN_S ? wf + 8 * (10 - WIN_S + n) : sb + S_FV + 8 * ((n - WIN_S) ^ 8), 0);
        pace(2 * TAU);
        if (n < 8) { place_load(M, sb, 2 * n); place_load(M, sb, 2 * n + 1); }
        else v_load(M, sb, 0, n - 8);
        if (n == 7) { pace(TAUW * 5 / 2); tma2d(sb + S_WD, &M.wd, 80 * i, 96 * g, wf + 80, 15360, pol); }
    }
    int nd = 0;
    uint32_t q[4];
#pragma unroll
    for (int r = 0; r < 4; r++) q[r] = sb + S_FV + 8 * (7 - r);
    uint32_t td = tn;
#pragma unroll 1
    for (int b = 1; b < 4; b++) {
        const uint32_t pk = (b - 1) & 1;
        uint32_t fr = 0, pend = 0;
#pragma unroll 1
        for (int j = 0; j < 17; j++) {
            const int n = 16 * b + 2 * j;
            uint32_t now, st;
            int k = 0;
            while (true) {
                now = __shfl_sync(~0u, gtime32(), 0) * 16;
                const uint2 c = lds64(sb + S_KF);
                const uint32_t rel = mbar_test(j < 8 ? sb + S_RELR : sb + S_RELK, pk);
                const int used = min((int)c.x + 1, (int)c.y) - 16 * b;
                static_assert(WIN_U <= 12, "a ring position has at most one token of the timetable");
                const uint32_t win = mbar_test(q[WIN_S - 1] & ~1u, q[WIN_S - 1] & 1) & (used >= min(2 * j + 2 - WIN_U, 16));
                st = __reduce_and_sync(~0u, (rel ? (j < 8 ? 0x700 : 0xf8) : 0) + (used >= 12) + (used >= 14) * 2 + (used >= 16) * 4 + win * 0x800);
                fr |= st & 0x7ff;
#pragma unroll 1
                while (pend & fr) {
                    const uint32_t r = __ffs(pend & fr) - 1;
                    if (r < 8) v_load(M, sb, b, r);
                    else { const uint32_t m = 16 * b + 2 * r - 16; ring_load(M, sb, m, ring_pos(m)); ring_load(M, sb, m + 1, ring_pos(m) + 1); }
                    pend ^= 1u << r;
                }
                if ((j == 16 ? !pend : (st & 0x800) && (int)(now - td) >= 0) || ++k >= SPIN_LIMIT) break;
            }
            if (j == 16) break;
            tn += 2 * TAU;
            td = (int)(tn - now) > 2 * TMIN ? tn : now + 2 * TMIN;
            if (b == 3 && j >= JFREE) td = now + TFREE;
            q[3] = q[2]; q[2] = q[1]; q[1] = q[0]; q[0] = sb + S_QRDY;
            const int s = j ^ 8;
            const char* src = unit_ptr(P, 32 * b + 2 * j);
            uint32_t mine = 0;
            if (j < 8) {
                const uint32_t pos = ring_pos(n);
                mine = j < 3 ? ((fr >> s) & 1) * 3 : __ballot_sync(~0u, token(lane < 2, sb + S_TOK + 4 * (pos + lane), n + lane) == n + lane);
                if (mine & 1) ring_load(M, sb, n, pos); else prefetch_l2(src, UNIT);
                if (mine & 2) ring_load(M, sb, n + 1, pos + 1); else prefetch_l2(src + UNIT, UNIT);
                if (!mine) pend |= (1u << s) & 0x700;
            } else if ((fr >> s) & 1) { v_load(M, sb, b, s); q[0] = (sb + S_FV + 8 * s) | (pk ^ 1); }
            else {
                pend |= 1u << s;
                if (s < 3 || s >= VPF) prefetch_l2(src, SLOT);
                else {
                    scrap_copy(sb + S_DUMMY, src, sb + S_DBAR + 8 * (nd & 3));
                    q[0] = (sb + S_DBAR + 8 * (nd & 3)) | ((nd >> 2) & 1);
                    nd++;
                }
            }
        }
    }
#pragma unroll 1
    for (int m = max(nd - 4, 0); m < nd; m++) uwait(sb + S_DBAR + 8 * (m & 3), (m >> 2) & 1);
}

__device__ __forceinline__ float scaled(float s) { return bfr(bfr(s) * 0.07216878364870322f); }
__device__ __forceinline__ void probs(float s, uint32_t ps, uint32_t src, uint32_t ln) {
    const uint32_t q8 = ln >> 2, t4 = ln & 3;
    int key = __float_as_int(s);
    key ^= (key >> 31) & 0x7fffffff;
    key = __reduce_max_sync(~0u, key);
    key ^= (key >> 31) & 0x7fffffff;
    const float ml = __int_as_float(key) * LOG2E;
    sts_hi16(ps + 64 * src + (q8 >> 1) * 16 + t4 * 4 + (q8 & 1) * 2, bfr(ex2(fmaf(s, LOG2E, -ml))));
    sts32_if(ln == 0, ps + PS_MAX + 4 * src, __float_as_uint(ml));
}
template <int H> __device__ __forceinline__ uint32_t b_pos(uint32_t e) { const uint32_t h = e >= H, k = e - H * h; return h * 192 + (k & 6) * 24 + (k >> 3) * 4 + (k & 1) * 2; }
__device__ __forceinline__ uint32_t a_pos(uint32_t e) { const uint32_t h = e >= 40, k = e - 40 * h; return (k & 6) * 24 + (k >> 3) * 8 + h * 4 + (k & 1) * 2; }
__device__ __forceinline__ uint32_t q_pos(uint32_t d) { return ((d >> 4) & 7) * 64 + (d & 6) * 8 + (d >> 7) * 8 + ((d >> 3) & 1) * 4 + (d & 1) * 2; }
__device__ __forceinline__ uint32_t k_off(uint32_t ln, uint32_t j) { const uint32_t r = 3 * (ln & 15) + j; return r * 128 + (((r & 7) ^ (ln >> 4)) << 4); }

#define HSTAMP(k) do {} while (0)
__device__ __forceinline__ void score_warp(const Maps& M, uint32_t sb, uint32_t h, uint32_t ln) {
    uwait(sb + S_QRDY, 0);
    const uint32_t q8 = ln >> 2;
    const uint32_t k0 = k_off(ln, 0), k1 = k_off(ln, 1), k2 = k_off(ln, 2);
    const uint64_t pol = pol_normal();
    uint32_t pos = h + 6, bar = sb + S_FK, par = 0, phases = 0;
    uint4 q = lds128(sb + S_QS + 16 * ln);
#pragma unroll 1
    for (uint32_t n = h; n < 64; n += 2) {
        HSTAMP(0);
        const uint32_t ua = sb + pos * UNIT;
        if (!__all_sync(~0u, mbar_try(bar, par))) uwait(bar, par);
        HSTAMP(1);
        float acc[2][4] = {};
        uint32_t mine = 0;
#pragma unroll
        for (int s = 0; s < 12; s++) {
            uint32_t kf[4];
            ldsm4(kf, (ua + (s < 4 ? k0 : s < 8 ? k1 : k2)) ^ (32 * (s & 3)));
            if (s == 11) {
                __syncwarp();
                mine = token(ln == 0 && n >= 16 && (n & 15) < 10, sb + S_TOK + 4 * pos, n + 6);
                stsvol(sb + S_KF + 4 * h, n + 1);
            }
            const bool m = q8 == (s & 7);
            mmaA(acc[s & 1], kf, m ? (s < 8 ? q.x : q.z) : 0u, m ? (s < 8 ? q.y : q.w) : 0u);
        }
        const int row = 3 * (first_key() + (n >> 4) * KV_BATCH_KEYS + 16 * (n & 15) + 96);
        const uint32_t bar0 = bar;
        const bool last = (n & 14) == 14;
        pos = last ? h + 2 : n >= 16 && pos >= 4 ? h : pos + 2;
        bar = n >= 14 ? sb + S_RING + 8 * pos : bar + 8;
        par = n >= 14 ? (phases >> pos) & 1 : 0;
        phases ^= n >= 14 ? 1u << pos : 0;
        const float w0 = (acc[0][0] + acc[0][1]) + (acc[1][0] + acc[1][1]), w1 = (acc[0][2] + acc[0][3]) + (acc[1][2] + acc[1][3]);
        HSTAMP(2);
        if (__any_sync(~0u, mine == n + 6)) tma2d(ua, &M.k, 0, row, bar0, UNIT, pol);
        HSTAMP(3);
        float s = ((ln & 1) ? w1 : w0) + __shfl_xor_sync(~0u, (ln & 1) ? w0 : w1, 1);
        s += __shfl_xor_sync(~0u, s, 2);
        sts_hi16(sb + S_SC + (((n & 12) >> 1) + h) * 64 + (n & 2) * 2 + (ln & 29) * 2, scaled(s));
        if (last) {
            __syncwarp();
            arrive_if(ln == 0, sb + S_SCO);
            q = lds128(sb + S_QS + 32 * ((n + 2) & 48) + 16 * ln);
        }
    }
}

__device__ __forceinline__ char* xwindow() { return reinterpret_cast<char*>((reinterpret_cast<uintptr_t>(g_x) + (2u << 20) - 1) & ~(uintptr_t)((2u << 20) - 1)); }

struct XPtr {
    uint32_t lo, hi;
    __device__ __forceinline__ explicit XPtr(char* p) : lo((uint32_t)(uintptr_t)p), hi((uint32_t)((uintptr_t)p >> 32)) {}
    __device__ __forceinline__ XPtr(uint32_t l, uint32_t h) : lo(l), hi(h) {}
    __device__ __forceinline__ XPtr operator+(uint32_t o) const { return XPtr(lo + o, hi); }
    __device__ __forceinline__ operator char*() const { uint64_t p; asm("mov.b64 %0, {%1, %2};" : "=l"(p) : "r"(lo), "r"(hi)); return (char*)p; }
};
__device__ __forceinline__ void keep(XPtr& v) { keep(v.lo); }

__device__ __forceinline__ void side_warp(uint32_t sb) {
    const uint32_t bid = blockIdx.x, g = bid >> 3, i = bid & 7, P = pairG(0, 0, i);
    char* p = xwindow() + P * 8192 + (g >> 3) * HALF + (g & 7) * 512 + 448;
    uint32_t best[2] = {~0u, ~0u};
    asm volatile("st.relaxed.gpu.global.b32 [%0], 1;" :: "l"(p) : "memory");
    asm volatile("st.relaxed.gpu.global.b32 [%0], 1;" :: "l"(p + COPY) : "memory");
#pragma unroll 1
    for (int r = 0; r < 64; r++) {
        if (r >= 4 && !(r & 1) && min(best[0], best[1]) < 380 && max(best[0], best[1]) > min(best[0], best[1]) + 80) break;
        uint32_t c0, c1, v;
        asm volatile("mov.u32 %0, %clock;" : "=r"(c0) :: "memory");
        asm volatile("atom.relaxed.gpu.global.exch.b32 %0, [%1], 0;" : "=r"(v) : "l"(p + (r & 1) * COPY) : "memory");
        asm volatile("{\n .reg .pred q;\n setp.eq.u32 q, %1, 0x13579bdf;\n mov.u32 %0, 0;\n @!q mov.u32 %0, %clock;\n}" : "=r"(c1) : "r"(v) : "memory");
        if (r & 1) best[1] = min(best[1], c1 - c0); else best[0] = min(best[0], c1 - c0);
    }
    stsvol(sb + S_SIDE, 1 + ((best[1] < best[0]) ^ (__popc(P & PMASK) & 1)));
}

__device__ __forceinline__ void look_a(uint2 (&v)[4], const char* src) {
#pragma unroll
    for (int s = 0; s < 4; s++) v[s] = ldp64(src + s * 1024);
}
__device__ __forceinline__ void hop_a(uint2 (&v)[4], const char* src, uint32_t par, uint32_t dst, bool st, int k) {
    int guard = 0;
    while (__any_sync(~0u, chk4(v, par) & 1) && ++guard < SPIN_LIMIT) look_a(v, src);
    const float M = fmaxf(fmaxf(asf(v[0].x), asf(v[1].x)), fmaxf(asf(v[2].x), asf(v[3].x)));
    float e[4];
#pragma unroll
    for (int s = 0; s < 4; s++) e[s] = ex2(asf(v[s].x) - M);
    const float rl = __shfl_sync(~0u, rcp(fmaf(e[0], asf(v[0].y), e[1] * asf(v[1].y)) + fmaf(e[2], asf(v[2].y), e[3] * asf(v[3].y))), 24);
#pragma unroll
    for (int s = 0; s < 4; s++) e[s] = __shfl_sync(~0u, e[s], 24);
    const float o0 = fmaf(e[0], asf(v[0].x), e[1] * asf(v[1].x)) + fmaf(e[2], asf(v[2].x), e[3] * asf(v[3].x));
    const float o1 = fmaf(e[0], asf(v[0].y), e[1] * asf(v[1].y)) + fmaf(e[2], asf(v[2].y), e[3] * asf(v[3].y));
    sts32_if(st, dst, pack2(o0 * rl, o1 * rl));
    SWEEPS(k, guard);
    __syncwarp();
}

__global__ void __launch_bounds__(NTHR, 1)
fused_kernel(const Params P, const __grid_constant__ Maps M) {
    extern __shared__ __align__(1024) unsigned char smem[];
    const uint32_t sb = smem_u32(smem);
    const int tid = threadIdx.x, bid = blockIdx.x;
    const int w = __shfl_sync(~0u, tid >> 5, 0), lane = tid & 31;

    if (w >= 8) {
        asm volatile("setmaxnreg.dec.sync.aligned.u32 " REG_LO ";");
        if (w == 8) {
            stream_warp(P, M, sb, lane);
        } else {
            if (w == 9) { init_bars<0, 8, 1>(sb); init_bars<16, 22, 1>(sb); }
            else if (w == 10) { init_bars<8, 16, 2>(sb); init_bars<22, 26, 1>(sb); }
            else { init_bars<37, 38, 1>(sb); init_bars<38, 40, 8>(sb); init_bars<40, 41, 1>(sb); init_bars<41, 44, 8>(sb); init_bars<44, 45, 2>(sb); if (lane < 18) stsvol(sb + S_ZERO + 4 * lane, 0); }
            asm volatile("fence.mbarrier_init.release.cluster;" ::: "memory");
            asm volatile("bar.arrive 3, 128;" ::: "memory");
            asm volatile("bar.sync 2, %0;" :: "n"(NTHR) : "memory");
            if (w < 11) score_warp(M, sb, w - 9, lane);
            else {
                if (lane == 0) side_warp(sb);
                __syncwarp();
                uint32_t a = 0, b = 0;
                int k = 0;
                while (ldsvol(sb + S_GATE) == 0 && ++k < SPIN_LIMIT) { warm_mma(a, b); __nanosleep(KWNS); }
                uint4* d = reinterpret_cast<uint4*>(reinterpret_cast<char*>(g_s) + XS + bid * 7680) + lane;
                const uint4 z = make_uint4(0, 0, 0, 0);
#pragma unroll 1
                for (int u = 0; u < 15; u++) d[32 * u] = z;
                d = reinterpret_cast<uint4*>(reinterpret_cast<char*>(g_s) + XS2 + bid * 768) + lane;
                d[0] = z;
                if (lane < 16) d[32] = z;
                const uint32_t side = (ldsvol(sb + S_SIDE) & 1) ^ 1, g = bid >> 3, i = bid & 7;
                const XPtr gx(xwindow());
                auto nearp = [&](uint32_t pr) { return gx.lo + pr * 8192 + ((side ^ __popc(pr & PMASK)) & 1) * COPY; };
                const uint32_t own = (i >> 2) * HALF + (i & 3) * 1024 + (lane & 7) * 128;
                const uint32_t pAC = nearp(pairL(lane >> 4, (lane >> 3) & 1, g)) + own, pE = nearp(pairL(RE, (lane >> 3) & 1, g)) + own;
                const uint32_t pG = nearp(pairG((lane >> 2) & 1, (lane >> 3) & 1, i)) + min(lane & 3, 2) * 128;
                uint32_t tr = 0, tk = 0, ph = 0, src = g + (lane >> 4), seen = 0, n = 16;
                bool go = false, first = true;
                while (n < 64 && ++k < SPIN_LIMIT) {
                    const uint32_t now = __shfl_sync(~0u, gtime32(), 0) * 16;
                    if (!go && utest(sb + S_RELV, ((n >> 4) & 1) ^ 1) && utest(sb + S_FV + 8 * (n >= 48 ? KRE_GATE3 : KRE_GATE), (n >> 4) & 1)) { go = true; tk = now; }
                    if (go && (int)(now - tk) >= 0) {
                        place_load(M, sb, n);
                        tk += n >= 48 ? KRE_TAU3 : (n & 15) < KRE_N1 ? KRE_TAU1 : KRE_TAU;
                        n++;
                        go = (n & 15) != 0;
                        if (!go) LSTAMP(63 + (n >> 3));
                    } else if (first || (int)(now - tr) >= 0) {
                        first = false;
                        tr = now + RFR_TAU;
                        b |= seen & a;
                        warm_mma(a, b);
                        if (RFR_ON) seen = ldp32(XPtr(ph == 0 ? pAC : ph == 1 && lane < 16 ? pE : pG + (src & 8) * (HALF / 8) + (src & 7) * 512, gx.hi));
                        src += ph == 0 ? 0 : ph == 1 ? 2 : 1;
                        ph = ph == 2 ? 0 : ph + 1;
                    } else __nanosleep(KWNS2);
                }
                while (ldsvol(sb + S_GATE) < 6 && ++k < SPIN_LIMIT) { warm_mma(a, b); __nanosleep(KWNS); }
                if (a | b) stsvol(sb + S_GATE, 6);
            }
        }
        return;
    }
    asm volatile("setmaxnreg.inc.sync.aligned.u32 " REG_HI ";");

    const int g = bid >> 3, i = bid & 7;
    const int g8 = lane >> 2, t = lane & 3;
    char* const gs = reinterpret_cast<char*>(g_s);
    const XPtr gx(xwindow());

    W80 Wq[6], Wgu[3];
    uint32_t Wo[5][3][4];
    if (w < 4) {
        const uint32_t* xp = reinterpret_cast<const uint32_t*>(P.x + 640 * w);
        float sum = 0.f, sq = 0.f;
#pragma unroll
        for (int u = 0; u < 10; u++) { uint32_t v = xp[lane + 32 * u]; float a = bf_lo(v), b = bf_hi(v); sum += a + b; sq += a * a + b * b; }
#pragma unroll
        for (int o = 16; o > 0; o >>= 1) { sum += __shfl_xor_sync(~0u, sum, o); sq += __shfl_xor_sync(~0u, sq, o); }
        float mean, den; ln_stats(sum, sq, mean, den);
        if (lane < 20) {
            const uint2 v = reinterpret_cast<const uint2*>(P.x + 640 * w + 80 * i)[lane];
            sts64(sb + S_X0 + 160 * w + 8 * lane, v.x, v.y);
            sts32(sb + S_L0 + 384 * w + b_pos<40>(4 * lane), pack2(__fdiv_rn(bfr(bf_lo(v.x) - mean), den), __fdiv_rn(bfr(bf_hi(v.x) - mean), den)));
            sts32(sb + S_L0 + 384 * w + b_pos<40>(4 * lane + 2), pack2(__fdiv_rn(bfr(bf_lo(v.y) - mean), den), __fdiv_rn(bfr(bf_hi(v.y) - mean), den)));
        }
    } else if (w == 4) {
        const uint32_t* xp = reinterpret_cast<const uint32_t*>(P.wr);
        float sum = 0.f;
#pragma unroll
        for (int u = 0; u < 10; u++) { uint32_t v = xp[lane + 32 * u]; sum += bf_lo(v) + bf_hi(v); }
#pragma unroll
        for (int o = 16; o > 0; o >>= 1) sum += __shfl_xor_sync(~0u, sum, o);
        if (lane == 0) stsf(sb + S_SWR, sum);
        if (lane < 20) {
            const uint2 v = reinterpret_cast<const uint2*>(P.wr + 80 * i)[lane];
            sts32(sb + S_XA + 576 + a_pos(4 * lane), v.x); sts32(sb + S_XA + 576 + a_pos(4 * lane + 2), v.y);
            sts32(sb + S_XA + a_pos(4 * lane), ONES); sts32(sb + S_XA + a_pos(4 * lane + 2), ONES);
        }
    }
    asm volatile("bar.sync 2, %0;" :: "n"(NTHR) : "memory");
    auto frag = [](uint32_t (&a)[4], uint32_t p, int pitch) {
        const uint32_t r0 = lds32(p), r1 = lds32(p + pitch), r2 = lds32(p + 2 * pitch), r3 = lds32(p + 3 * pitch);
        a[0] = __byte_perm(r0, r1, 0x5410); a[1] = __byte_perm(r0, r1, 0x7632);
        a[2] = __byte_perm(r2, r3, 0x5410); a[3] = __byte_perm(r2, r3, 0x7632);
    };
    mbar_wait(sb + S_WFULL + 16 * (w >> 2), 0);
    mbar_wait(sb + S_WFULL + 16 * (w >> 2) + 8, 0);
    {
        const uint32_t p = sb + ST_WQ + (w >> 2) * 30720 + (2 * t) * 384 + (48 * (w & 3) + 2 * g8) * 2;
#pragma unroll
        for (int r = 0; r < 10; r++)
#pragma unroll
            for (int m = 0; m < 3; m++) {
                const uint32_t q = p + ((r & 1) * 40 + (r >> 1) * 8) * 384 + 32 * m, r0 = lds32(q), r1 = lds32(q + 384);
                (r < 8 ? Wq[2 * m].a[(r >> 2) & 1][r & 3] : Wq[2 * m].c[r & 1]) = __byte_perm(r0, r1, 0x5410);
                (r < 8 ? Wq[2 * m + 1].a[(r >> 2) & 1][r & 3] : Wq[2 * m + 1].c[r & 1]) = __byte_perm(r0, r1, 0x7632);
            }
    }
    __syncwarp();
    if (lane == 0) mbar_arrive(sb + S_RELW);
    TSTAMP(1);
    {
        char* d = gs + XS + bid * 7680 + (w >> 2) * 3840 + (48 * (w & 3) + 2 * g8) * 4;
        float acc[6][4] = {};
        mul80(acc, Wq, lds128(sb + S_L0 + 48 * lane), lds32(sb + S_L0 + 48 * lane + 16));
#pragma unroll
        for (int m = 0; m < 6; m++) stp32(d + t * 768 + 32 * (m & 6) + 4 * (m & 1), acc[m][0] + acc[m][3], 1);
        float sum[6][4] = {};
        mul80(sum, Wq, make_uint4(ONES, ONES, ONES, ONES), ONES);
        if (t == 0)
#pragma unroll
            for (int m = 0; m < 6; m++) stp32(d + 4 * 768 + 32 * (m & 6) + 4 * (m & 1), sum[m][0] + sum[m][3], 1);
    }
    mbar_wait(sb + S_WFULL + 32, 0);
    mbar_wait(sb + S_WFULL + 40, 0);
    const uint32_t oct = 3 * (w >> 1) + (w & 1), oct2 = 3 * (w >> 1) + 2;
    {
        const uint32_t p = sb + ST_WG + ((lane & 7) + 40 * ((lane >> 3) & 1) + 8 * (lane >> 4)) * 192;
#pragma unroll
        for (int T = 0; T < 3; T++) {
            const uint32_t q = p + (T < 2 ? T * 15360 + 16 * oct : (w & 1) * 15360 + 16 * oct2);
            ldsm4t(Wgu[T].a[0], q); ldsm4t(Wgu[T].a[1], q + 16 * 192); ldsm2t(Wgu[T].c, q + 32 * 192);
        }
        float sum[3][4] = {};
        mul80(sum, Wgu, make_uint4(ONES, ONES, ONES, ONES), ONES);
        if (t < 3) stp32(gs + XS2 + bid * 768 + (t < 2 ? 64 * oct + 4 * t : 64 * oct2 + 4 * (w & 1)) + 8 * g8,
                         sel4(t, sum[0][0] + sum[0][3], sum[1][0] + sum[1][3], sum[2][0] + sum[2][3], 0.f), 1);
    }
    __syncwarp();
    if (lane == 0) mbar_arrive(sb + S_RELW + 8);
    const char* srcS = gs + XS + g * 8 * 7680 + (i >> 2) * 3840 + min(tid, 191) * 4;
    uint32_t vs[5][8];
#pragma unroll
    for (int b = 0; b < 5; b++)
#pragma unroll
        for (int s = 0; s < 8; s++) vs[b][s] = ldp32(srcS + b * 768 + s * 7680);
    uint32_t cs2[8];
#pragma unroll
    for (int s = 0; s < 8; s++) cs2[s] = ldp32(gs + XS2 + (g * 8 + s) * 768 + min(tid, 191) * 4);
    __syncwarp();
    mbar_wait(sb + S_WFULL + 48 + 8 * (w >> 1), 0);
    {
        const uint32_t po = sb + ST_WO + (48 * w + 12 * t) * 160 + 4 * g8;
#pragma unroll
        for (int s = 0; s < 3; s++)
#pragma unroll
            for (int m = 0; m < 5; m++) frag(Wo[m][s], po + 4 * s * 160 + 32 * m, 160);
    }
    __syncwarp();
    if (lane == 0) mbar_arrive(sb + S_RELW + 16);
    {
        const uint4 z = make_uint4(0, 0, 0, 0);
        const uint32_t c = (tid >> 6) & 1, cp = (tid >> 7) * COPY, k = (tid & 63) * 16;
        *reinterpret_cast<uint4*>((char*)(gx + pairL(RA, c, g) * 8192 + (i >> 2) * HALF + (i & 3) * 1024 + cp + k)) = z;
        *reinterpret_cast<uint4*>((char*)(gx + pairL(RC, c, g) * 8192 + (i >> 2) * HALF + (i & 3) * 1024 + cp + k)) = z;
        *reinterpret_cast<uint4*>((char*)(gx + pairL(RE, c, g) * 8192 + (i >> 2) * HALF + (i & 3) * 1024 + cp + k)) = z;
        if ((tid & 31) < 24) *reinterpret_cast<uint4*>((char*)(gx + pairG((tid >> 5) & 1, c, i) * 8192 + (g >> 3) * HALF + (g & 7) * 512 + cp + (tid & 31) * 16)) = z;
    }
    if (tid < 192) {
        int guard = 0;
        while (((or3(chk8(vs[0], 1), chk8(vs[1], 1), chk8(vs[2], 1)) | chk8(vs[3], 1) | chk8(vs[4], 1)) & 1) && ++guard < SPIN_LIMIT) {
#pragma unroll
            for (int b = 0; b < 5; b++)
#pragma unroll
                for (int s = 0; s < 8; s++) vs[b][s] = ldp32(srcS + b * 768 + s * 7680);
        }
        const uint32_t qpos = sb + S_QS + q_pos(tid);
#pragma unroll
        for (int b = 0; b < 4; b++) {
            sts_hi16(qpos + 512 * b, bfr(sum8(vs[b])));
        }
        stsf(sb + S_CSQ + 4 * tid, sum8(vs[4]));
    }
    if (tid < 192) stsf(sb + S_CSGU + 4 * tid, (chk8(cs2, 1) & 1) ? gather8<768>(gs + XS2 + g * 8 * 768 + tid * 4, 1) : sum8(cs2));
    bar_main();
    arrive_if(tid == 0, sb + S_QRDY);
    TSTAMP(2);

    uint32_t side;
    { int k = 0; while ((side = ldsvol(sb + S_SIDE)) == 0 && ++k < SPIN_LIMIT) {} }
    side = __shfl_sync(~0u, side & 1, 0) ^ 1;
    auto nearp = [&](uint32_t P) { return P * 8192 + ((side ^ __popc(P & PMASK)) & 1) * COPY; };
    const uint32_t td = __shfl_sync(~0u, tid, lane);
    const uint32_t wp = __shfl_sync(~0u, tid >> 5, 0);
    const uint32_t cc = wp >= 3;
#define IDS() uint32_t z_ = td; opaque(z_); const uint32_t ln = z_ & 31, q8 = ln >> 2, t4 = z_ & 3, n96 = z_ - 96 * cc, n80 = min(n96, 79u); (void)q8; (void)t4; (void)n80; (void)ln

    auto vaddr = [&](uint32_t (&voff)[3]) {
        IDS();
        const uint32_t key3 = 3 * ((ln & 7) + 2 * (ln & 8) + ((ln >> 1) & 8));
#pragma unroll
        for (int T = 0; T < 3; T++) {
            const uint32_t u = 3 * wp + T, r = key3 + (u >> 3);
            voff[T] = r * 128 + (((u ^ r) & 7) << 4);
        }
    };
    auto values = [&](uint32_t (&vf)[8][3][4], auto step, uint32_t ps, uint32_t col, uint32_t par) {
        IDS();
        const uint4 p = lds128(ps + 16 * ln);
        const uint2 mp = lds64(ps + PS_MAX + 8 * t4);
        const float mq = ldsf(ps + PS_MAX + 4 * q8);
        float acc[3][4] = {};
        float M = fmaxf(asf(mp.x), asf(mp.y)), lsum = 0.f, f0 = 0.f, f1 = 0.f;
#pragma unroll
        for (int s = 0; s < 8; s++) {
            step(s);
            const bool m = (q8 >> 1) == (s >> 1);
            const uint32_t b0 = m ? ((s & 1) ? p.z : p.x) : 0u, b1 = m ? ((s & 1) ? p.w : p.y) : 0u;
#pragma unroll
            for (int T = 0; T < 3; T++) mmaA(acc[T], vf[s][T], b0, b1);
            if (s < 2) M = fmaxf(M, __shfl_xor_sync(~0u, M, 1 + s));
            if (s == 1) {
                f0 = ex2(asf(mp.x) - M); f1 = ex2(asf(mp.y) - M);
                lsum = (((bf_lo(p.x) + bf_hi(p.x)) + (bf_lo(p.y) + bf_hi(p.y))) + ((bf_lo(p.z) + bf_hi(p.z)) + (bf_lo(p.w) + bf_hi(p.w)))) * ex2(mq - M);
            }
            if (s >= 2 && s < 7) lsum += __shfl_xor_sync(~0u, lsum, 1 << (s - 2));
        }
        char* pubA = gx + pairL(RA, col, g) * 8192 + (i >> 2) * HALF + (i & 3) * 1024 + (wp >> 1) * 256 + (wp & 1) * 96 + 32 * t4 + 4 * q8;
        const float r0 = fmaf(f0, acc[0][0], f1 * acc[0][3]), r1 = fmaf(f0, acc[1][0], f1 * acc[1][3]), r2 = fmaf(f0, acc[2][0], f1 * acc[2][3]);
        const bool hi = t4 & 2, od = t4 & 1;
        const float u0 = (hi ? r2 : r0) + __shfl_xor_sync(~0u, hi ? r0 : r2, 2), u1 = r1 + __shfl_xor_sync(~0u, r1, 2);
        const float o = (od ? u1 : u0) + __shfl_xor_sync(~0u, od ? u0 : u1, 1);
        stp32_if(t4 < 3 || ((wp & 1) && q8 < 2), pubA, t4 < 3 ? o : q8 ? lsum : M, par);
    };

#pragma unroll 1
    for (int ch = 0; ch < 5; ch++) {
        const uint32_t par0 = (ch + 1) & 1, par1 = ch & 1;
        uint32_t voff[3], vf[8][3][4];
        CSTAMP(0);
        if (ch < 4) {
            vaddr(voff);
            mbar_wait(sb + S_SCO, par1);
            TST(0);
            auto ldw = [&](int s) {
                mbar_wait(sb + S_FV + 8 * s, par1);
#pragma unroll
                for (int T = 0; T < 3; T++) ldsm4t(vf[s][T], voff[T] + (sb + v_place(ch, s) * SLOT));
            };
            probs(bf_lo(lds16(sb + S_SC + 2 * td)), sb + S_PS, wp, td & 31);
            ldw(0); ldw(1); ldw(2);
            bar_main();
            arrive_if(td == 0, sb + S_RELR);
            uint2 u[4];
            values(vf, [&](int s) {
                if (s == HOPA0 || s == HOPA1) {
                    IDS();
                    const XPtr polA = gx + nearp(pairL(RA, 1, g)) + (wp >> 2) * HALF + (wp & 3) * 256 + 8 * min(ln, 24u);
                    if (s == HOPA0) look_a(u, polA);
                    if (s == HOPA1 && ch > 0) {
                        hop_a(u, polA, par1, sb + S_OS + 192 * wp + 4 * ln + 96, ln < 24, 25);
                    }
                }
                if (s >= 3) ldw(s);
            }, sb + S_PS, 0, par0);
            TST(1);
            CSTAMP(5);
        } else {
#pragma unroll
            for (int s = 0; s < 36; s++) { vf[s / 12][(s / 4) % 3][s & 3] = 0; opaque(vf[s / 12][(s / 4) % 3][s & 3]); }
        }
        const bool has0 = ch < 4, has1 = ch > 0;
        const bool actc = wp < 6 && (cc ? has1 : has0);
        const uint32_t parc = cc ? par1 : par0;
        const uint32_t pub0 = has0 ? par0 : 0;
        XPtr pubB = gx;
        uint32_t rr;
        {
            IDS();
            const uint32_t c = ch == 4;
            const XPtr polA = gx + nearp(pairL(RA, c, g)) + (wp >> 2) * HALF + (wp & 3) * 256 + 8 * min(ln, 24u) + lag<DELAY_L>(sb);
            uint2 v[4];
            look_a(v, polA);
            uint32_t osa = sb + S_OS + 192 * wp + 96 * c + 4 * ln;
            uint32_t oa = sb + S_OS + 192 * wp + 96 * (q8 & 1) + 24 * t4, ra = sb + S_RED + 640 * wp + 320 * (t4 & 1) + 8 * q8;
            pubB = gx + pairG(0, cc, i) * 8192 + (g >> 3) * HALF + (g & 7) * 512 + n80 * 4;
            rr = sb + S_RED + 320 * cc + 4 * n80;
            keep(osa); keep(oa); keep(ra); keep(pubB); keep(rr);
            hop_a(v, polA, c ? par1 : par0, osa, ln < 24, 5 * ch);
            TST(2);
            CSTAMP(6);
            float acc[5][4] = {};
            const uint2 b0 = lds64(oa), b1 = lds64(oa + 8), b2 = lds64(oa + 16);
#pragma unroll
            for (int m = 0; m < 5; m++) mmaA(acc[m], Wo[m][0], b0.x, b0.y);
#pragma unroll
            for (int m = 0; m < 5; m++) mmaA(acc[m], Wo[m][1], b1.x, b1.y);
#pragma unroll
            for (int m = 0; m < 5; m++) mmaA(acc[m], Wo[m][2], b2.x, b2.y);
#pragma unroll
            for (int m = 0; m < 5; m++) sts64_if(t4 < 2, ra + 64 * m, t4 ? acc[m][1] : acc[m][0], t4 ? acc[m][3] : acc[m][2]);
        }
        CSTAMP(7);
        bar_main();
        CSTAMP(8);
        float x1 = 0.f;
        uint32_t xr, fl;
        XPtr pubC = gx, pubC2 = gx;
        {
            IDS();
            if (actc) {
                uint32_t r[8];
#pragma unroll
                for (int s = 0; s < 8; s++) r[s] = lds32(rr + 640 * s);
                stp32_if(n96 < 80, pubB, sum8(r), parc);
                CSTAMP(9);
            }
            xr = sb + S_XB + 48 * (ln & 15);
            pubC = gx + pairL(RC, 0, g) * 8192 + (i >> 2) * HALF + (i & 3) * 1024 + (t4 & 1) * (32 * 8192);
            pubC2 = pubC + ((t4 & 2) ? 192 * (wp >> 1) + 128 + 4 * (wp & 1) + 8 * q8 : 768 + 2 * ((q8 + 1) & 6));
            pubC = pubC + (192 * (wp >> 1) + 64 * (wp & 1) + 8 * q8);
            fl = ((t4 & 1) ? par1 : pub0) | (t4 >= 2 || (wp == 7 && q8 < 4 && q8 != 2 - t4) ? 2 : 0);
            keep(xr); keep(pubC); keep(pubC2); keep(fl);
            if (actc) {
                const char* polB = gx + nearp(pairG(0, cc, i)) + n80 * 4 + lag<DELAY_G>(sb);
                uint32_t xas = sb + S_XA + 192 + 192 * cc + a_pos(n80), xbs = sb + S_XB + 384 * cc + b_pos<40>(n80);
                x1 = cc ? ldsf(sb + S_XCAR + 4 * n80) : bf_lo(lds16(sb + S_X0 + 160 * (ch & 3) + 2 * n80));
                keep(xas); keep(xbs); keep(x1);
                x1 = bfr(x1 + bfr(gather16(polB, parc, 5 * ch + 1, [](uint32_t) { return false; })));
                CSTAMP(10);
                sts_hi16(xbs, x1);
                sts_hi16(xas, x1);
            }
        }
        bar_main();
        TST(3);
        CSTAMP(11);
        auto stats = [&](uint32_t xa, const uint4& b, uint32_t b4) {
            float a[4] = {};
            const uint4 p0 = lds128(xa), p1 = lds128(xa + 16);
            const uint2 p2 = lds64(xa + 32);
            mmaV(a, p0, b.x, b.y); mmaV(a, p1, b.z, b.w); mma8(a, p2.x, p2.y, b4);
            return a[0] + a[3];
        };
        {
            auto gate_up = [&](auto with_stats) {
                const uint4 b = lds128(xr);
                const uint32_t b4 = lds32(xr + 16);
                float acc[3][4] = {}, st = 0.f;
                if (with_stats.value) st = stats(xr + (S_XA - S_XB), b, b4);
                mul80(acc, Wgu, b, b4);
                stp64_if(!(td & 2), pubC, tagw(acc[0][0] + acc[0][3], fl & 1), tagw(acc[1][0] + acc[1][3], fl & 1));
                stp32_if(fl & 2, pubC2, !with_stats.value || (td & 2) ? acc[2][0] + acc[2][3] : st, fl & 1);
            };
            if (wp == 7) gate_up(std::true_type()); else gate_up(std::false_type());
        }
        sts32_if(td == 255, sb + S_GATE, ch + 1);
        CSTAMP(12);
        float mean = 0.f, den = 1.f;
        {
            IDS();
            const uint32_t wa = sb + S_WD + ((ln & 7) + 48 * ((ln >> 3) & 1) + 8 * (ln >> 4)) * 160 + (wp < 7 ? 16 * wp : 128);
            uint32_t ha = sb + S_HS + 48 * (ln & 15);
            XPtr pubD = gx + pairG(1, t4 & 1, i) * 8192 + (g >> 3) * HALF + (g & 7) * 512 + (wp < 7 ? 32 * wp : 256) + 16 * (t4 & 2) + 4 * q8;
            if (ch == 0) mbar_wait(sb + S_WFULL + 80, 0);
            auto down = [&](const uint32_t (&W)[3][4], const uint4& h0, const uint2& h1) {
                float a0[4] = {}, a1[4] = {}, a2[4] = {};
                mmaA(a0, W[0], h0.x, h0.y); mmaA(a1, W[1], h0.z, h0.w); mmaA(a2, W[2], h1.x, h1.y);
                return ((a0[0] + a0[3]) + (a1[0] + a1[3])) + (a2[0] + a2[3]);
            };
            if (wp < 6) {
                uint32_t Wd[3][4];
                auto ldd = [&] {
#pragma unroll
                    for (int s = 0; s < 3; s++) ldsm4t(Wd[s], wa + s * 2560);
                };
                uint32_t hsa = sb + S_HS + 384 * cc + b_pos<48>(n96);
                keep(ha); keep(pubD); keep(hsa);
                if (actc) {
                    const XPtr src0 = gx + nearp(pairL(RC, cc, g)) + lag<DELAY_C>(sb);
                    const char* srcv = src0 + 8 * n96;
                    const char* src = src0 + (ln & 1) * HALF;
                    uint2 v[8], st[4];
                    float sx, sq, pg, pu, rd;
                    uint2 cs;
                    int guard = 0;
                    bool again;
                    do {
#pragma unroll
                        for (int s = 0; s < 4; s++) st[s] = ldp64(src + 768 + s * 1024);
#pragma unroll
                        for (int s = 0; s < 8; s++) v[s] = ldp64(srcv + (s >> 2) * HALF + (s & 3) * 1024);
                        sx = (asf(st[0].x) + asf(st[1].x)) + (asf(st[2].x) + asf(st[3].x)); sq = (asf(st[0].y) + asf(st[1].y)) + (asf(st[2].y) + asf(st[3].y));
                        sx += __shfl_xor_sync(~0u, sx, 1); sq += __shfl_xor_sync(~0u, sq, 1);
                        cs = lds64(sb + S_CSGU - 768 * cc + 8 * td);
                        again = __any_sync(~0u, or3(chk4(st, parc), chk8(v, parc), chk8y(v, parc)) & 1);
                        pg = sum8x(v); pu = sum8y(v);
                        if (SPEC) { ln_stats(sx, sq, mean, den); rd = rcp(den); keep(mean); keep(rd); }
                        keep(pg); keep(pu);
                    } while (again && ++guard < SPIN_LIMIT);
                    CSTAMP(13);
                    ldd();
                    SWEEPS(5 * ch + 2, guard);
                    if (!SPEC) { ln_stats(sx, sq, mean, den); rd = rcp(den); }
                    const float gt = bfr(fmaf(-mean, asf(cs.x), pg) * rd), up = bfr(fmaf(-mean, asf(cs.y), pu) * rd);
                    const float h = bfr(bfr(gt * sigmoidf_(gt)) * up);
                    sts_hi16(hsa, h);
                    CSTAMP(14);
                } else ldd();
                bar_main();
                TST(4);
                CSTAMP(15);
                const uint4 h0 = lds128(ha);
                const uint2 h1 = lds64(ha + 16);
                stp32_if(!(td & 2), pubD, down(Wd, h0, h1), fl & 1);
            } else {
                uint32_t Wd[2][3][4];
#pragma unroll
                for (int s = 0; s < 6; s++) ldsm4t(Wd[s / 3][s % 3], wa + (s / 3) * 16 + (s % 3) * 2560);
                keep(ha); keep(pubD);
                uint32_t v = 0;
                if (wp == 6 ? has0 : has1) {
                    const uint32_t par = wp == 6 ? par0 : par1;
                    const char* src = gx + nearp(pairL(RC, wp - 6, g)) + 768 + (ln & 4) * (HALF / 4) + (ln & 3) * 1024 + 4 * min(ln >> 3, 2u) + lag<DELAY_C>(sb);
                    int guard = 0;
                    do v = ldp32(src); while (__any_sync(~0u, (v ^ par) & 1) && ++guard < SPIN_LIMIT);
                }
                bar_main();
                const uint4 h0 = lds128(ha);
                const uint2 h1 = lds64(ha + 16);
                const float d0 = down(Wd[0], h0, h1), d1 = down(Wd[1], h0, h1);
                stp32_if(true, pubD, (td & 2) ? d1 : d0, fl & 1);
                if (wp == 6 ? has0 : has1) {
                    float sx = asf(v);
                    sx += __shfl_xor_sync(~0u, sx, 1); sx += __shfl_xor_sync(~0u, sx, 2); sx += __shfl_xor_sync(~0u, sx, 4);
                    const float sq = __shfl_sync(~0u, sx, 8), xw = __shfl_sync(~0u, sx, 16);
                    ln_stats(sx, sq, mean, den);
                    const float r = bfr(fmaf(-mean, ldsf(sb + S_SWR), xw) * rcp(den));
                    sts32_if(ln == 0, sb + S_STAT + 4 * (wp - 6), __float_as_uint(bfr(sigmoidf_(r))) | (ch + 1));
                }
            }
        }
        CSTAMP(16);
        XPtr pubE = gx;
        {
            IDS();
            pubE = gx + pairL(RE, 0, g) * 8192 + (i >> 2) * HALF + (i & 3) * 1024 +
                   (t4 < 3 ? (wp >> 2) * (32 * 8192) + 192 * (wp & 3) + 64 * t4 + 8 * q8 : (q8 >> 2) * (32 * 8192) + 768 + 4 * (q8 & 1));
            xr = sb + S_XB + 48 * (ln & 7);
            keep(xr); keep(pubE);
            if (actc && (cc == 0 || g == 0)) {
                const char* polD = gx + nearp(pairG(1, cc, i)) + n80 * 4 + lag<DELAY_D>(sb);
                float lnx = bfr(__fdiv_rn(bfr(x1 - mean), den));
                unsigned short* po = reinterpret_cast<unsigned short*>(P.out) + 640 * (ch - 1) + 80 * i + n80;
                uint32_t xas = sb + S_XA + 192 + a_pos(n80), xbs = sb + S_XB + b_pos<40>(n80), xca = sb + S_XCAR + 4 * n80;
                keep(lnx); keep(po); keep(xca); keep(xas); keep(xbs);
                uint32_t gate;
                const float dn = gather16(polD, parc, 5 * ch + 3, [&](uint32_t z) { gate = ldsvol(sb + S_STAT + 4 * cc + z); return (gate & 7) != ch + 1; });
                const float y = bfr(bfr(dn) * bf_hi(gate));
                CSTAMP(17);
                const float x2 = bfr(x1 + bfr(lnx + y));
                if (cc) *po = (unsigned short)(__float_as_uint(x2) >> 16);
                else {
                    sts_hi16(xbs, x2);
                    sts_hi16(xas, x2);
                    stsf(xca, x2);
                }
            }
        }
        CSTAMP(18);
        if (!has0) break;
        bar_main();
        TST(5);
        CSTAMP(19);
        {
            auto qproj = [&](auto with_stats) {
                const uint32_t t4 = td & 3;
                const uint4 b = lds128(xr);
                const uint32_t b4 = lds32(xr + 16);
                if (with_stats.value) stp32_if((td & 11) == 3, pubE, stats(xr + (S_XA - S_XB), b, b4), par0);
                float acc[6][4] = {};
                mul80(acc, Wq, b, b4);
                const float v0 = sel4(t4, acc[0][0] + acc[0][3], acc[2][0] + acc[2][3], acc[4][0] + acc[4][3], acc[4][0] + acc[4][3]);
                const float v1 = sel4(t4, acc[1][0] + acc[1][3], acc[3][0] + acc[3][3], acc[5][0] + acc[5][3], acc[5][0] + acc[5][3]);
                stp64_if(t4 < 3, pubE, tagw(v0, par0), tagw(v1, par0));
            };
            if (wp == 7) qproj(std::true_type()); else qproj(std::false_type());
        }
        CSTAMP(20);
        {
            IDS();
            const uint32_t ua = sb + k_place(ch, wp & 6) * SLOT + (wp & 1) * UNIT, ub = (k_place(ch, wp | 1) - k_place(ch, wp & 6)) * SLOT;
            uint32_t kf[12][2][4];
            auto ldk = [&](int s) { const uint32_t a = (ua + k_off(ln, s >> 2)) ^ ((s & 3) * 32); ldsm4(kf[s][0], a); ldsm4(kf[s][1], a + ub); };
            mbar_wait(sb + S_FK + 8 * (wp & 6), par1); mbar_wait(sb + S_FK + 8 * (wp | 1), par1);
#pragma unroll
            for (int s = 0; s < KPRE; s++) ldk(s);
            if (wp < 6) {
                const XPtr src0 = gx + nearp(pairL(RE, i >> 2, g)) + lag<DELAY_E>(sb);
                const char* srcv = src0 + 4 * td;
                const char* src = src0 + (ln & 1) * HALF;
                uint32_t v[8]; uint2 st[4];
                float sx, sq, qs, rd, cs;
                int guard = 0;
                bool again;
                do {
#pragma unroll
                    for (int s = 0; s < 4; s++) st[s] = ldp64(src + 768 + s * 1024);
#pragma unroll
                    for (int s = 0; s < 8; s++) v[s] = ldp32(srcv + (s >> 2) * HALF + (s & 3) * 1024);
                    sx = (asf(st[0].x) + asf(st[1].x)) + (asf(st[2].x) + asf(st[3].x)); sq = (asf(st[0].y) + asf(st[1].y)) + (asf(st[2].y) + asf(st[3].y));
                    sx += __shfl_xor_sync(~0u, sx, 1); sq += __shfl_xor_sync(~0u, sq, 1);
                    cs = ldsf(sb + S_CSQ + 4 * td);
                    again = __any_sync(~0u, (chk8(v, par0) | chk4(st, par0)) & 1);
                    qs = sum8(v);
                    if (SPEC) { ln_stats(sx, sq, mean, den); rd = rcp(den); keep(mean); keep(rd); }
                    keep(qs);
                } while (again && ++guard < SPIN_LIMIT);
                CSTAMP(21);
                if (!SPEC) { ln_stats(sx, sq, mean, den); rd = rcp(den); }
                const float q = bfr(fmaf(-mean, cs, qs) * rd);
                sts_hi16(sb + S_QS + 512 * ch + q_pos(td), q);
                SWEEPS(5 * ch + 4, guard);
                CSTAMP(22);
            }
            __syncwarp();
#pragma unroll
            for (int s = KPRE; s < KPRE + KPRE2; s++) ldk(s);
            bar_main();
            TST(6);
            CSTAMP(1);
            const uint4 q = lds128(sb + S_QS + 512 * ch + 16 * ln);
            float acc[2][4] = {};
            constexpr int D = KPRE + KPRE2;
#pragma unroll
            for (int s = 0; s < 12; s++) {
                const bool m = q8 == (s & 7);
                const uint32_t b0 = m ? (s < 8 ? q.x : q.z) : 0u, b1 = m ? (s < 8 ? q.y : q.w) : 0u;
                mmaA(acc[0], kf[s][0], b0, b1);
                mmaA(acc[1], kf[s][1], b0, b1);
                if (s + D < 12) ldk(s + D);
            }
            vaddr(voff);
            auto ldv = [&](int s) {
#pragma unroll
                for (int T = 0; T < 3; T++) ldsm4t(vf[s][T], voff[T] + (sb + v_place(ch, s) * SLOT));
            };
            ldv(3);
            {
                const float v0 = acc[0][0] + acc[0][1], v1 = acc[0][2] + acc[0][3], v2 = acc[1][0] + acc[1][1], v3 = acc[1][2] + acc[1][3];
                const bool hi = t4 & 2, od = t4 & 1;
                const float u0 = (hi ? v2 : v0) + __shfl_xor_sync(~0u, hi ? v0 : v2, 2), u1 = (hi ? v3 : v1) + __shfl_xor_sync(~0u, hi ? v1 : v3, 2);
                const float s = (od ? u1 : u0) + __shfl_xor_sync(~0u, od ? u0 : u1, 1);
                CSTAMP(2);
                arrive_if(ln == 0, sb + S_RELK);
                probs(scaled(s), sb + S_PS + PS_PASS, wp, ln);
            }
            bar_main();
            TST(10);
            CSTAMP(4);
            values(vf, [&](int s) { if (s >= 1 && s < 5) ldv(s + 3); }, sb + S_PS + PS_PASS, 1, par0);
            arrive_if(ln == 0, sb + S_RELV);
        }
        TST(11);
        CSTAMP(23);
    }
    sts32_if(td == 255, sb + S_GATE, 6);
    TSTAMP(3);
}

typedef CUresult (*EncodeFn)(CUtensorMap*, CUtensorMapDataType, cuuint32_t, void*, const cuuint64_t*, const cuuint64_t*, const cuuint32_t*,
                             const cuuint32_t*, CUtensorMapInterleave, CUtensorMapSwizzle, CUtensorMapL2promotion, CUtensorMapFloatOOBfill);

void make_map(EncodeFn enc, CUtensorMap* m, const void* base, uint64_t cols, uint64_t rows, uint32_t box_cols, uint32_t box_rows, bool swizzle) {
    cuuint64_t dims[2] = {cols, rows};
    cuuint64_t strides[1] = {cols * 2};
    cuuint32_t box[2] = {box_cols, box_rows};
    cuuint32_t es[2] = {1, 1};
    enc(m, CU_TENSOR_MAP_DATA_TYPE_BFLOAT16, 2, const_cast<void*>(base), dims, strides, box, es, CU_TENSOR_MAP_INTERLEAVE_NONE,
        swizzle ? CU_TENSOR_MAP_SWIZZLE_128B : CU_TENSOR_MAP_SWIZZLE_NONE, swizzle ? CU_TENSOR_MAP_L2_PROMOTION_NONE : WPROMO, CU_TENSOR_MAP_FLOAT_OOB_FILL_NONE);
}

}

extern "C" void kernel_launch(void* const* d_in, const int* in_sizes, int n_in, void* d_out, int out_size) {
    (void)in_sizes; (void)n_in; (void)out_size;
    static EncodeFn enc = nullptr;
    if (!enc) {
        void* f = nullptr;
        cudaDriverEntryPointQueryResult q;
        cudaGetDriverEntryPoint("cuTensorMapEncodeTiled", &f, cudaEnableDefault, &q);
        enc = (EncodeFn)f;
        cudaFuncSetAttribute(fused_kernel, cudaFuncAttributeMaxDynamicSharedMemorySize, SMEM_BYTES);
    }
    Params P;
    P.x = (const __nv_bfloat16*)d_in[0]; P.k = (const __nv_bfloat16*)d_in[1]; P.v = (const __nv_bfloat16*)d_in[2];
    P.wr = (const __nv_bfloat16*)d_in[6];
    P.out = (__nv_bfloat16*)d_out;
    Maps M;
    make_map(enc, &M.k, P.k, 64, (uint64_t)12 * KV_BATCH_KEYS, 64, 48, true);
    make_map(enc, &M.v, P.v, 64, (uint64_t)12 * KV_BATCH_KEYS, 64, 96, true);
    make_map(enc, &M.wq, d_in[3], 6144, 640, 192, 40, false);
    make_map(enc, &M.wo, d_in[4], 640, 6144, 80, 96, false);
    make_map(enc, &M.wg, d_in[7], 1536, 640, 96, 80, false);
    make_map(enc, &M.wu, d_in[8], 1536, 640, 96, 80, false);
    make_map(enc, &M.wd, d_in[9], 640, 1536, 80, 96, false);
    fused_kernel<<<NCTA, NTHR, SMEM_BYTES, cudaStreamPerThread>>>(P, M);
}
```

```cpp
#include <cuda_runtime.h>
#include <cuda.h>
#include <cuda_bf16.h>
#include <stdint.h>
#include <type_traits>

namespace {

constexpr int NCTA = 128;
constexpr int NTHR = 384;
constexpr int UNIT = 6144;
constexpr int SLOT = 12288;
#define TAU 4100
#define TAUW 4000
#define TAU0 4000
#define PF0 2
#define PFMAP 1
#define ZPOS 1
#define LOOK1 0
#define LOOK2 0
#define TMIN 2400
#define T_LEAD 0
#define WIN_W 3
#define WIN_S 4
#define WIN_U 10
#define RFR_ON 1
#define KRE_N1 0
#define KRE_TAU1 2500
#define RFR_TAU 6400
#define VPF 5
#define KRE_GATE 0
#define KRE_GATE3 KRE_GATE
#define JFREE 16
#define TFREE 0
#define KRE_TAU 4000
#define KRE_TAU3 KRE_TAU
#define HDEPTH 3
#define SPEC 1
#define PV1PIPE 0
#define HOPA0 6
#define HOPA1 6
#define WPROMO CU_TENSOR_MAP_L2_PROMOTION_NONE
#define KPRE 1
#define KPRE2 2
#define DELAY_G 6
#define DELAY_L 5
#define DELAY_C 3
#define DELAY_D 6
#define DELAY_E 3
#define REG_LO "40"
#define REG_HI "232"
#define SPIN_LOG 17
constexpr int SPIN_LIMIT = 1 << SPIN_LOG;

__host__ __device__ constexpr uint32_t pairL(uint32_t region, uint32_t c, uint32_t g) { return (g & 1) | ((g >> 1) << 2) | (c << 5) | (region << 6); }
__host__ __device__ constexpr uint32_t pairG(uint32_t d, uint32_t c, uint32_t i) { return (i & 1) | ((i >> 1) << 2) | (d << 4) | (c << 5) | (3u << 6); }
constexpr uint32_t RA = 0, RC = 1, RE = 2, HALF = 16384, COPY = 4096, PMASK = 0x59;
constexpr uint32_t XS = 0;
constexpr uint32_t XS2 = XS + 128 * 7680;
constexpr uint32_t XSEND = XS2 + 128 * 768;
__device__ uint4 g_s[XSEND / 16];
__device__ uint4 g_x[(4u << 20) / 16];
#define SWEEPS(k, n) do {} while (0)

constexpr uint32_t S_WD = 16 * SLOT;
constexpr uint32_t S_DUMMY = S_WD + 15360;
constexpr uint32_t S_BAR = S_DUMMY + 4096;
constexpr uint32_t S_FV = S_BAR, S_FK = S_FV + 64, S_RING = S_FK + 64, S_DBAR = S_RING + 48, S_WFULL = S_DBAR + 32, S_QRDY = S_WFULL + 88;
constexpr uint32_t S_RELK = S_QRDY + 8, S_RELV = S_RELK + 8, S_RELR = S_RELV + 8, S_RELW = S_RELR + 8, S_SCO = S_RELW + 24;
constexpr uint32_t S_ZERO = S_SCO + 8;
constexpr uint32_t S_KF = S_SCO + 24;
constexpr uint32_t S_TOK = S_KF + 8;
constexpr uint32_t S_SIDE = S_TOK + 24, S_GATE = S_SIDE + 4;
constexpr uint32_t S_STAT = S_GATE + 4, S_SWR = S_STAT + 16;
constexpr uint32_t S_XCAR = S_STAT + 32;
constexpr uint32_t S_CSQ = S_XCAR + 320;
constexpr uint32_t S_CSGU = S_CSQ + 768;
constexpr uint32_t S_RED = S_CSGU + 768;
constexpr uint32_t S_L0 = S_RED;
constexpr uint32_t S_OS = S_RED + 5120;
constexpr uint32_t S_PS = S_OS + 1536;
constexpr uint32_t PS_MAX = 512, PS_PASS = 544;
constexpr uint32_t S_QS = S_PS + 2 * PS_PASS;
constexpr uint32_t S_XB = S_QS + 2048;
constexpr uint32_t S_XA = S_XB + 768;
constexpr uint32_t S_HS = S_XA + 768;
constexpr uint32_t S_X0 = S_HS + 768;
constexpr uint32_t S_SC = S_X0 + 640;
constexpr uint32_t S_TM = S_SC + 512;
constexpr int SMEM_BYTES = S_TM + 256;
static_assert(SMEM_BYTES <= 232448 && S_STAT % 16 == 0 && S_RED % 16 == 0 && S_XB % 16 == 0 && S_HS % 16 == 0 && S_PS % 16 == 0 && S_QS % 16 == 0, "smem");
static_assert(S_SCO == S_BAR + 44 * 8 && S_RELK == S_BAR + 38 * 8, "barriers");
constexpr uint32_t ST_WQ = 3 * SLOT, ST_WG = 8 * SLOT, ST_WO = 11 * SLOT;

__device__ __forceinline__ uint32_t smem_u32(const void* p) { return (uint32_t)__cvta_generic_to_shared(p); }
__device__ __forceinline__ void mbar_init(uint32_t bar, uint32_t cnt) { asm volatile("mbarrier.init.shared::cta.b64 [%0], %1;" :: "r"(bar), "r"(cnt) : "memory"); }
__device__ __forceinline__ void mbar_expect(uint32_t bar, uint32_t bytes) { asm volatile("mbarrier.arrive.expect_tx.shared::cta.b64 _, [%0], %1;" :: "r"(bar), "r"(bytes) : "memory"); }
__device__ __forceinline__ void mbar_arrive(uint32_t bar) { asm volatile("mbarrier.arrive.shared::cta.b64 _, [%0];" :: "r"(bar) : "memory"); }
__device__ __forceinline__ bool mbar_try(uint32_t bar, uint32_t parity) {
    uint32_t ok;
    asm volatile("{\n .reg .pred p;\n mbarrier.try_wait.parity.shared::cta.b64 p, [%1], %2;\n selp.u32 %0, 1, 0, p;\n}" : "=r"(ok) : "r"(bar), "r"(parity) : "memory");
    return ok != 0;
}
__device__ __forceinline__ bool mbar_test(uint32_t bar, uint32_t parity) {
    uint32_t ok;
    asm volatile("{\n .reg .pred p;\n mbarrier.test_wait.parity.shared::cta.b64 p, [%1], %2;\n selp.u32 %0, 1, 0, p;\n}" : "=r"(ok) : "r"(bar), "r"(parity) : "memory");
    return ok != 0;
}
__device__ __forceinline__ void mbar_wait(uint32_t bar, uint32_t parity) {
    int n = 0;
    while (!mbar_try(bar, parity) && ++n < SPIN_LIMIT) {}
}
__device__ __forceinline__ unsigned long long gtime() { unsigned long long t; asm volatile("mov.u64 %0, %globaltimer;" : "=l"(t)); return t; }
__device__ __forceinline__ uint32_t gtime32() { uint32_t t; asm volatile("mov.u32 %0, %globaltimer_lo;" : "=r"(t)); return t; }
__device__ __forceinline__ void bar_main() { __syncwarp(); asm volatile("bar.sync 1, 256;" ::: "memory"); }

__device__ __forceinline__ void mma16816(float (&c)[4], uint32_t a0, uint32_t a1, uint32_t a2, uint32_t a3, uint32_t b0, uint32_t b1) {
    asm("mma.sync.aligned.m16n8k16.row.col.f32.bf16.bf16.f32 {%0,%1,%2,%3}, {%4,%5,%6,%7}, {%8,%9}, {%0,%1,%2,%3};"
        : "+f"(c[0]), "+f"(c[1]), "+f"(c[2]), "+f"(c[3]) : "r"(a0), "r"(a1), "r"(a2), "r"(a3), "r"(b0), "r"(b1));
}
__device__ __forceinline__ void mmaA(float (&c)[4], const uint32_t (&a)[4], uint32_t b0, uint32_t b1) { mma16816(c, a[0], a[1], a[2], a[3], b0, b1); }
__device__ __forceinline__ void mmaAv(float (&c)[4], const uint32_t (&a)[4], uint32_t b0, uint32_t b1) {
    asm volatile("mma.sync.aligned.m16n8k16.row.col.f32.bf16.bf16.f32 {%0,%1,%2,%3}, {%4,%5,%6,%7}, {%8,%9}, {%0,%1,%2,%3};"
        : "+f"(c[0]), "+f"(c[1]), "+f"(c[2]), "+f"(c[3]) : "r"(a[0]), "r"(a[1]), "r"(a[2]), "r"(a[3]), "r"(b0), "r"(b1) : "memory");
}
__device__ __forceinline__ void mma8(float (&c)[4], uint32_t a0, uint32_t a1, uint32_t b0) {
    asm("mma.sync.aligned.m16n8k8.row.col.f32.bf16.bf16.f32 {%0,%1,%2,%3}, {%4,%5}, {%6}, {%0,%1,%2,%3};"
        : "+f"(c[0]), "+f"(c[1]), "+f"(c[2]), "+f"(c[3]) : "r"(a0), "r"(a1), "r"(b0));
}
struct W80 { uint32_t a[2][4], c[2]; };
template <int N> __device__ __forceinline__ void mul80(float (&acc)[N][4], const W80 (&W)[N], const uint4& b, uint32_t b4) {
#pragma unroll
    for (int m = 0; m < N; m++) mmaA(acc[m], W[m].a[0], b.x, b.y);
#pragma unroll
    for (int m = 0; m < N; m++) mmaA(acc[m], W[m].a[1], b.z, b.w);
#pragma unroll
    for (int m = 0; m < N; m++) mma8(acc[m], W[m].c[0], W[m].c[1], b4);
}
__device__ __forceinline__ void ldsm2t(uint32_t (&r)[2], uint32_t addr) {
    asm volatile("ldmatrix.sync.aligned.m8n8.x2.trans.shared.b16 {%0,%1}, [%2];" : "=r"(r[0]), "=r"(r[1]) : "r"(addr) : "memory");
}
__device__ __forceinline__ void mmaV(float (&c)[4], const uint4& a, uint32_t b0, uint32_t b1) { mma16816(c, a.x, a.y, a.z, a.w, b0, b1); }
__device__ __forceinline__ void ldsm4(uint32_t (&r)[4], uint32_t addr) {
    asm volatile("ldmatrix.sync.aligned.m8n8.x4.shared.b16 {%0,%1,%2,%3}, [%4];" : "=r"(r[0]), "=r"(r[1]), "=r"(r[2]), "=r"(r[3]) : "r"(addr) : "memory");
}
__device__ __forceinline__ void ldsm4t(uint32_t (&r)[4], uint32_t addr) {
    asm volatile("ldmatrix.sync.aligned.m8n8.x4.trans.shared.b16 {%0,%1,%2,%3}, [%4];" : "=r"(r[0]), "=r"(r[1]), "=r"(r[2]), "=r"(r[3]) : "r"(addr) : "memory");
}
__device__ __forceinline__ uint32_t lds16(uint32_t a) { uint16_t v; asm volatile("ld.shared.u16 %0, [%1];" : "=h"(v) : "r"(a) : "memory"); return v; }
__device__ __forceinline__ uint32_t lds32(uint32_t a) { uint32_t v; asm volatile("ld.shared.u32 %0, [%1];" : "=r"(v) : "r"(a) : "memory"); return v; }
__device__ __forceinline__ float ldsf(uint32_t a) { return __uint_as_float(lds32(a)); }
__device__ __forceinline__ uint2 lds64(uint32_t a) { uint2 v; asm volatile("ld.shared.v2.u32 {%0,%1}, [%2];" : "=r"(v.x), "=r"(v.y) : "r"(a) : "memory"); return v; }
__device__ __forceinline__ uint4 lds128(uint32_t a) { uint4 v; asm volatile("ld.shared.v4.u32 {%0,%1,%2,%3}, [%4];" : "=r"(v.x), "=r"(v.y), "=r"(v.z), "=r"(v.w) : "r"(a) : "memory"); return v; }
__device__ __forceinline__ int ldsvol(uint32_t a) { int v; asm volatile("ld.volatile.shared.u32 %0, [%1];" : "=r"(v) : "r"(a) : "memory"); return v; }
__device__ __forceinline__ void stsvol(uint32_t a, int v) { asm volatile("st.volatile.shared.u32 [%0], %1;" :: "r"(a), "r"(v) : "memory"); }
__device__ __forceinline__ void sts_hi16(uint32_t a, float v) { asm volatile("{\n .reg .b16 lo, hi;\n mov.b32 {lo, hi}, %1;\n st.shared.u16 [%0], hi;\n}" :: "r"(a), "r"(__float_as_uint(v)) : "memory"); }
__device__ __forceinline__ void sts32(uint32_t a, uint32_t v) { asm volatile("st.shared.u32 [%0], %1;" :: "r"(a), "r"(v) : "memory"); }
__device__ __forceinline__ void stsf(uint32_t a, float v) { sts32(a, __float_as_uint(v)); }
__device__ __forceinline__ void sts64(uint32_t a, uint32_t x, uint32_t y) { asm volatile("st.shared.v2.u32 [%0], {%1,%2};" :: "r"(a), "r"(x), "r"(y) : "memory"); }

__device__ __forceinline__ void sts_hi16_if(bool p, uint32_t a, float v) {
    asm volatile("{\n .reg .pred p;\n .reg .b16 lo, hi;\n setp.ne.u32 p, %2, 0;\n mov.b32 {lo, hi}, %1;\n @p st.shared.u16 [%0], hi;\n}" :: "r"(a), "r"(__float_as_uint(v)), "r"((uint32_t)p) : "memory");
}
__device__ __forceinline__ void sts32_if(bool p, uint32_t a, uint32_t v) {
    asm volatile("{\n .reg .pred p;\n setp.ne.u32 p, %2, 0;\n @p st.shared.u32 [%0], %1;\n}" :: "r"(a), "r"(v), "r"((uint32_t)p) : "memory");
}
__device__ __forceinline__ void sts64_if(bool p, uint32_t a, float x, float y) {
    asm volatile("{\n .reg .pred p;\n setp.ne.u32 p, %3, 0;\n @p st.shared.v2.f32 [%0], {%1,%2};\n}" :: "r"(a), "f"(x), "f"(y), "r"((uint32_t)p) : "memory");
}
__device__ __forceinline__ void arrive_if(bool p, uint32_t bar) {
    asm volatile("{\n .reg .pred p;\n setp.ne.u32 p, %1, 0;\n @p mbarrier.arrive.shared::cta.b64 _, [%0];\n}" :: "r"(bar), "r"((uint32_t)p) : "memory");
}
__device__ __forceinline__ void opaque(uint32_t& v) { asm volatile("" : "+r"(v)); }
__device__ __forceinline__ void keep(uint32_t& v) { asm volatile("" : "+r"(v)); }
__device__ __forceinline__ void keep(float& v) { asm volatile("" : "+f"(v)); }
template <class T> __device__ __forceinline__ void keep(T*& v) { asm volatile("" : "+l"(v)); }

__device__ __forceinline__ uint32_t ldp32(const char* p) { uint32_t v; asm volatile("ld.relaxed.gpu.global.u32 %0, [%1];" : "=r"(v) : "l"(p) : "memory"); return v; }
__device__ __forceinline__ uint2 ldp64(const char* p) {
    uint2 v; asm volatile("{\n .reg .b64 d;\n ld.relaxed.gpu.global.b64 d, [%2];\n mov.b64 {%0,%1}, d;\n}" : "=r"(v.x), "=r"(v.y) : "l"(p) : "memory"); return v;
}
__device__ __forceinline__ uint32_t tagw(float f, uint32_t par) { return (__float_as_uint(f) & ~1u) | par; }
__device__ __forceinline__ void stp32(char* p, float a, uint32_t par) { asm volatile("st.relaxed.gpu.global.u32 [%0], %1;" :: "l"(p), "r"(tagw(a, par)) : "memory"); }
__device__ __forceinline__ void stp64(char* p, float a, float b, uint32_t par) {
    asm volatile("{\n .reg .b64 d;\n mov.b64 d, {%1,%2};\n st.relaxed.gpu.global.b64 [%0], d;\n}" :: "l"(p), "r"(tagw(a, par)), "r"(tagw(b, par)) : "memory");
}
__device__ __forceinline__ void stp32_if(bool p, char* d, float a, uint32_t par) {
    asm volatile("{\n .reg .pred p;\n setp.ne.u32 p, %2, 0;\n @p st.relaxed.gpu.global.u32 [%0], %1;\n @p st.relaxed.gpu.global.u32 [%0+4096], %1;\n}" :: "l"(d), "r"(tagw(a, par)), "r"((uint32_t)p) : "memory");
}
__device__ __forceinline__ void stp64_if(bool p, char* d, uint32_t lo, uint32_t hi) {
    asm volatile("{\n .reg .pred p;\n .reg .b64 d;\n setp.ne.u32 p, %3, 0;\n mov.b64 d, {%1,%2};\n @p st.relaxed.gpu.global.b64 [%0], d;\n @p st.relaxed.gpu.global.b64 [%0+4096], d;\n}" :: "l"(d), "r"(lo), "r"(hi), "r"((uint32_t)p) : "memory");
}
__device__ __forceinline__ uint32_t chk2(uint32_t a, uint32_t b, uint32_t par) { uint32_t r; asm("lop3.b32 %0, %1, %2, %3, 0x7E;" : "=r"(r) : "r"(a), "r"(b), "r"(par)); return r; }
__device__ __forceinline__ uint32_t or3(uint32_t a, uint32_t b, uint32_t c) { uint32_t r; asm("lop3.b32 %0, %1, %2, %3, 0xFE;" : "=r"(r) : "r"(a), "r"(b), "r"(c)); return r; }
__device__ __forceinline__ uint32_t chk8(const uint32_t (&v)[8], uint32_t par) { return or3(chk2(v[0], v[1], par), chk2(v[2], v[3], par), or3(chk2(v[4], v[5], par), chk2(v[6], v[7], par), 0)); }
__device__ __forceinline__ uint32_t chk8(const uint2 (&v)[8], uint32_t par) { return or3(chk2(v[0].x, v[1].x, par), chk2(v[2].x, v[3].x, par), or3(chk2(v[4].x, v[5].x, par), chk2(v[6].x, v[7].x, par), 0)); }
__device__ __forceinline__ uint32_t chk8y(const uint2 (&v)[8], uint32_t par) { return or3(chk2(v[0].y, v[1].y, par), chk2(v[2].y, v[3].y, par), or3(chk2(v[4].y, v[5].y, par), chk2(v[6].y, v[7].y, par), 0)); }
__device__ __forceinline__ uint32_t chk4(const uint2 (&v)[4], uint32_t par) { return or3(chk2(v[0].x, v[0].y, par), chk2(v[1].x, v[1].y, par), or3(chk2(v[2].x, v[2].y, par), chk2(v[3].x, v[3].y, par), 0)); }
__device__ __forceinline__ float asf(uint32_t v) { return __uint_as_float(v); }
__device__ __forceinline__ float sum8(const uint32_t (&v)[8]) { return ((asf(v[0]) + asf(v[1])) + (asf(v[2]) + asf(v[3]))) + ((asf(v[4]) + asf(v[5])) + (asf(v[6]) + asf(v[7]))); }
__device__ __forceinline__ float sum8x(const uint2 (&v)[8]) { return ((asf(v[0].x) + asf(v[1].x)) + (asf(v[2].x) + asf(v[3].x))) + ((asf(v[4].x) + asf(v[5].x)) + (asf(v[6].x) + asf(v[7].x))); }
__device__ __forceinline__ float sum8y(const uint2 (&v)[8]) { return ((asf(v[0].y) + asf(v[1].y)) + (asf(v[2].y) + asf(v[3].y))) + ((asf(v[4].y) + asf(v[5].y)) + (asf(v[6].y) + asf(v[7].y))); }

__device__ __forceinline__ uint32_t pack2(float lo, float hi) { uint32_t r; asm("cvt.rn.bf16x2.f32 %0, %1, %2;" : "=r"(r) : "f"(hi), "f"(lo)); return r; }
__device__ __forceinline__ float bfr(float x) { return __uint_as_float(pack2(0.0f, x)); }
__device__ __forceinline__ float ex2(float x) { float r; asm("ex2.approx.ftz.f32 %0, %1;" : "=f"(r) : "f"(x)); return r; }
__device__ __forceinline__ float rcp(float x) { float r; asm("rcp.approx.ftz.f32 %0, %1;" : "=f"(r) : "f"(x)); return r; }
__device__ __forceinline__ float sqrt_(float x) { float r; asm("sqrt.approx.ftz.f32 %0, %1;" : "=f"(r) : "f"(x)); return r; }
__device__ __forceinline__ float bf_lo(uint32_t v) { return __uint_as_float(v << 16); }
__device__ __forceinline__ float bf_hi(uint32_t v) { return __uint_as_float(v & 0xffff0000u); }
__device__ __forceinline__ float sel4(int k, float a, float b, float c, float d) { return (k & 2) ? ((k & 1) ? d : c) : ((k & 1) ? b : a); }
constexpr float LOG2E = 1.4426950408889634f;
constexpr uint32_t ONES = 0x3f803f80u;

__device__ __forceinline__ void ln_stats(float sum, float sq, float& mean, float& den) {
    const float m = sum * (1.0f / 640.0f);
    const float var = fmaxf(fmaf(sq, 1.0f / 640.0f, -m * m), 0.0f);
    mean = bfr(m);
    den = bfr(sqrt_(bfr(bfr(var) + 1e-5f)));
}
__device__ __forceinline__ float sigmoidf_(float x) { return rcp(1.0f + ex2(-x * LOG2E)); }

#define TSTAMP(k) do {} while (0)
#define TST(k) do {} while (0)

#define CSTAMP(k) do {} while (0)
template <int N> __device__ __forceinline__ uint32_t lag(uint32_t sb) {
    uint32_t z = 0;
#pragma unroll
    for (int k = 0; k < N; k++) z = ldsvol(sb + S_ZERO + z);
    return z;
}
__device__ __forceinline__ void warm_mma(uint32_t& a, uint32_t& b) {
    asm volatile("mma.sync.aligned.m16n8k8.row.col.f16.f16.f16.f16 {%0,%1}, {%0,%1}, {%0}, {%0,%1};" : "+r"(a), "+r"(b) :: "memory");
}
#define KWNS2 20
#define KWNS 200
template <int STRIDE>
__device__ __forceinline__ float gather8(const char* p, uint32_t par) {
    uint32_t v[8];
    int guard = 0;
    do {
#pragma unroll
        for (int s = 0; s < 8; s++) v[s] = ldp32(p + s * STRIDE);
    } while ((chk8(v, par) & 1) && ++guard < SPIN_LIMIT);
    return sum8(v);
}
template <class F>
__device__ __forceinline__ float gather16(const char* p, uint32_t par, int k, F also) {
    uint32_t v[8], u[8];
    float r;
    int guard = 0;
    bool again;
    do {
#pragma unroll
        for (int s = 0; s < 8; s++) v[s] = ldp32(p + s * 512);
#pragma unroll
        for (int s = 0; s < 8; s++) u[s] = ldp32(p + HALF + s * 512);
        again = ((chk8(v, par) | chk8(u, par)) & 1) | also(((v[0] ^ par) & 1) * 8);
        r = sum8(v) + sum8(u);
        keep(r);
    } while (again && ++guard < SPIN_LIMIT);
    SWEEPS(k, guard);
    return r;
}

struct Params {
    const __nv_bfloat16 *x, *k, *v, *wr;
    __nv_bfloat16* out;
};
struct Maps { CUtensorMap k, v, wq, wo, wg, wu, wd; };

constexpr int KV_BATCH_KEYS = 32 * 4096;

__device__ __forceinline__ void tma2d(uint32_t dst, const CUtensorMap* m, int c0, int c1, uint32_t bar, uint32_t bytes, uint64_t pol) {
    asm volatile("{\n .reg .pred p;\n elect.sync _|p, 0xffffffff;\n"
                 " @p mbarrier.arrive.expect_tx.shared::cta.b64 _, [%2], %6;\n"
                 " @p cp.async.bulk.tensor.2d.shared::cluster.global.mbarrier::complete_tx::bytes.L2::cache_hint [%0], [%1, {%3, %4}], [%2], %5;\n}"
                 :: "r"(dst), "l"(m), "r"(bar), "r"(c0), "r"(c1), "l"(pol), "r"(bytes) : "memory");
}
__device__ __forceinline__ void scrap_copy(uint32_t dst, const char* src, uint32_t bar) {
    asm volatile("{\n .reg .pred p;\n elect.sync _|p, 0xffffffff;\n"
                 " @p mbarrier.arrive.expect_tx.shared::cta.b64 _, [%2], 12288;\n"
                 " @p cp.async.bulk.shared::cluster.global.mbarrier::complete_tx::bytes [%0], [%1], 4096, [%2];\n"
                 " @p cp.async.bulk.shared::cluster.global.mbarrier::complete_tx::bytes [%0], [%1+4096], 4096, [%2];\n"
                 " @p cp.async.bulk.shared::cluster.global.mbarrier::complete_tx::bytes [%0], [%1+8192], 4096, [%2];\n}"
                 :: "r"(dst), "l"(src), "r"(bar) : "memory");
}
__device__ __forceinline__ void prefetch_l2(const void* p, uint32_t bytes) {
    asm volatile("{\n .reg .pred p;\n elect.sync _|p, 0xffffffff;\n @p cp.async.bulk.prefetch.L2.global [%0], %1;\n}" :: "l"(p), "r"(bytes) : "memory");
}
__device__ __forceinline__ uint64_t pol_first() { uint64_t p; asm("createpolicy.fractional.L2::evict_first.b64 %0, 1.0;" : "=l"(p)); return p; }
__device__ __forceinline__ uint64_t pol_normal() { uint64_t p; asm("createpolicy.fractional.L2::evict_normal.b64 %0, 1.0;" : "=l"(p)); return p; }
__device__ __forceinline__ bool utest(uint32_t bar, uint32_t parity) { return __all_sync(~0u, mbar_test(bar, parity)); }
__device__ __forceinline__ void uwait(uint32_t bar, uint32_t parity) {
    int n = 0;
    while (!__all_sync(~0u, mbar_try(bar, parity)) && ++n < SPIN_LIMIT) {}
}
template <int A, int B, int CNT> __device__ __forceinline__ void init_bars(uint32_t sb) {
#pragma unroll 1
    for (int k = A; k < B; k++)
        asm volatile("{\n .reg .pred p;\n elect.sync _|p, 0xffffffff;\n @p mbarrier.init.shared::cta.b64 [%0], %1;\n}" :: "r"(sb + S_BAR + 8 * k), "n"(CNT) : "memory");
}
__device__ __forceinline__ int first_key() { return (blockIdx.x >> 2) * 4096 + 3072 + (blockIdx.x & 3) * 256; }
__device__ __forceinline__ void load_tile(const CUtensorMap* m, uint32_t dst, uint32_t bar, uint32_t bytes, int key, uint64_t pol) { tma2d(dst, m, 0, 3 * key, bar, bytes, pol); }
__device__ __forceinline__ const char* unit_ptr(const Params& P, int n) {
    return (const char*)((n & 16) ? P.v : P.k) + (size_t)(first_key() + (n >> 5) * KV_BATCH_KEYS + (n & 15) * 16) * 384;
}
#define LSTAMP(k) do {} while (0)

__device__ __forceinline__ uint32_t k_place(uint32_t b, uint32_t s) { return s + 3 + (s < 3 ? 0 : 5 * (b & 1)); }
__device__ __forceinline__ uint32_t v_place(uint32_t b, uint32_t s) { return s < 3 ? s : s + 8 - 5 * (b & 1); }
__device__ __forceinline__ uint32_t ring_pos(uint32_t n) { const uint32_t u = (n & 15) + 2; return u - (u >= 12 ? 12 : u >= 6 ? 6 : 0); }
__device__ __forceinline__ void ring_load(const Maps& M, uint32_t sb, uint32_t n, uint32_t pos) {
    load_tile(&M.k, sb + pos * UNIT, sb + S_RING + 8 * pos, UNIT, first_key() + (n >> 4) * KV_BATCH_KEYS + 16 * (n & 15), pol_normal());
}
__device__ __forceinline__ uint32_t token(bool p, uint32_t a, uint32_t n) {
    uint32_t v;
    asm volatile("{\n .reg .pred p;\n setp.ne.u32 p, %2, 0;\n mov.u32 %0, 0;\n @p atom.shared.exch.b32 %0, [%1], %3;\n}" : "=r"(v) : "r"(a), "r"((uint32_t)p), "r"(n) : "memory");
    return v;
}
__device__ __forceinline__ void place_load(const Maps& M, uint32_t sb, uint32_t n) {
    load_tile(&M.k, sb + k_place(n >> 4, (n >> 1) & 7) * SLOT + (n & 1) * UNIT, sb + S_FK + 4 * (n & 14), UNIT,
              first_key() + (n >> 4) * KV_BATCH_KEYS + 16 * (n & 15), pol_first());
}
__device__ __forceinline__ void v_load(const Maps& M, uint32_t sb, uint32_t b, uint32_t s) {
    load_tile(&M.v, sb + v_place(b, s) * SLOT, sb + S_FV + 8 * s, SLOT, first_key() + b * KV_BATCH_KEYS + 32 * s, pol_first());
}
__device__ __forceinline__ bool due(uint32_t t) { return __all_sync(~0u, (int)(gtime32() * 16 - t) >= 0); }
__device__ __forceinline__ bool reached(uint32_t a, int v) { return __all_sync(~0u, ldsvol(a) >= v); }

__device__ __forceinline__ void stream_warp(const Params& P, const Maps& M, uint32_t sb, uint32_t lane) {
    const uint64_t pol = pol_first();
    const int bid = blockIdx.x, g = bid >> 3, i = bid & 7;
    const uint32_t wf = sb + S_WFULL;
    if (PF0 > 0) prefetch_l2(unit_ptr(P, 0), PF0 * UNIT);
    uint32_t tn = __shfl_sync(~0u, gtime32(), 0) * 16 - T_LEAD;
    auto pace = [&](uint32_t dt) { int k = 0; while (!due(tn) && ++k < SPIN_LIMIT) {} tn += dt; };
#pragma unroll
    for (int k = 0; k < 10; k++) {
        if (k < 2) {
            if (k == 0) init_bars<26, 27, 1>(sb); else init_bars<27, 37, 1>(sb);
            asm volatile("fence.mbarrier_init.release.cluster;" ::: "memory");
            if (k == 1) { asm volatile("bar.arrive 2, %0;" :: "n"(NTHR) : "memory"); asm volatile("bar.sync 3, 128;" ::: "memory"); }
        }
        if (k >= WIN_W) uwait(wf + 8 * (k - WIN_W), 0);
        pace(TAUW * 5 / 2);
        if (k < 4) tma2d(sb + ST_WQ + 15360 * k, &M.wq, 384 * g + 192 * (k >> 1), 80 * i + 40 * (k & 1), wf + 8 * k, 15360, pol);
        else if (k < 6) tma2d(sb + ST_WG + 15360 * (k - 4), k == 4 ? &M.wg : &M.wu, 96 * g, 80 * i, wf + 8 * k, 15360, pol);
        else tma2d(sb + ST_WO + 15360 * (k - 6), &M.wo, 80 * i, 384 * g + 96 * (k - 6), wf + 8 * k, 15360, pol);
    }
#pragma unroll 1
    for (int n = 0; n < 16; n++) {
        if (n == 0 || n == 5 || n == 11) uwait(sb + S_RELW + (n == 0 ? 0 : n == 5 ? 8 : 16), 0);
        uwait(n < WIN_S ? wf + 8 * (10 - WIN_S + n) : sb + S_FV + 8 * ((n - WIN_S) ^ 8), 0);
        pace(max(min(2 * n + 2 - PF0, 2), 0) * TAU0);
        if (n < 8) { place_load(M, sb, 2 * n); place_load(M, sb, 2 * n + 1); }
        else v_load(M, sb, 0, n - 8);
        if (n == 7) { pace(TAUW * 5 / 2); tma2d(sb + S_WD, &M.wd, 80 * i, 96 * g, wf + 80, 15360, pol); }
    }
    int nd = 0;
    uint32_t q[4];
#pragma unroll
    for (int r = 0; r < 4; r++) q[r] = sb + S_FV + 8 * (7 - r);
    uint32_t td = tn;
#pragma unroll 1
    for (int b = 1; b < 4; b++) {
        const uint32_t pk = (b - 1) & 1;
        uint32_t fr = 0, pend = 0;
#pragma unroll 1
        for (int j = 0; j < 17; j++) {
            const int n = 16 * b + 2 * j;
            uint32_t now, st;
            int k = 0;
            while (true) {
                now = __shfl_sync(~0u, gtime32(), 0) * 16;
                const uint2 c = lds64(sb + S_KF);
                const uint32_t rel = mbar_test(j < 8 ? sb + S_RELR : sb + S_RELK, pk);
                const int used = min((int)c.x + 1, (int)c.y) - 16 * b;
                static_assert(WIN_U <= 12, "a ring position has at most one token of the timetable");
                const uint32_t win = mbar_test(q[WIN_S - 1] & ~1u, q[WIN_S - 1] & 1) & (used >= min(2 * j + 2 - WIN_U, 16));
                st = __reduce_and_sync(~0u, (rel ? (j < 8 ? 0x700 : 0xf8) : 0) + (used >= 12) + (used >= 14) * 2 + (used >= 16) * 4 + win * 0x800);
                fr |= st & 0x7ff;
#pragma unroll 1
                while (pend & fr) {
                    const uint32_t r = __ffs(pend & fr) - 1;
                    if (r < 8) v_load(M, sb, b, r);
                    else { const uint32_t m = 16 * b + 2 * r - 16; ring_load(M, sb, m, ring_pos(m)); ring_load(M, sb, m + 1, ring_pos(m) + 1); }
                    pend ^= 1u << r;
                }
                if ((j == 16 ? !pend : (st & 0x800) && (int)(now - td) >= 0) || ++k >= SPIN_LIMIT) break;
            }
            if (j == 16) break;
            tn += 2 * TAU;
            td = (int)(tn - now) > 2 * TMIN ? tn : now + 2 * TMIN;
            if (b == 3 && j >= JFREE) td = now + TFREE;
            q[3] = q[2]; q[2] = q[1]; q[1] = q[0]; q[0] = sb + S_QRDY;
            const int s = j ^ 8;
            const char* src = unit_ptr(P, 32 * b + 2 * j);
            uint32_t mine = 0;
            if (j < 8) {
                const uint32_t pos = ring_pos(n);
                mine = j < 3 ? ((fr >> s) & 1) * 3 : __ballot_sync(~0u, token(lane < 2, sb + S_TOK + 4 * (pos + lane), n + lane) == n + lane);
                if (mine & 1) ring_load(M, sb, n, pos); else prefetch_l2(src, UNIT);
                if (mine & 2) ring_load(M, sb, n + 1, pos + 1); else prefetch_l2(src + UNIT, UNIT);
                if (!mine) pend |= (1u << s) & 0x700;
            } else if ((fr >> s) & 1) { v_load(M, sb, b, s); q[0] = (sb + S_FV + 8 * s) | (pk ^ 1); }
            else {
                pend |= 1u << s;
                if (s < 3 || s >= VPF) prefetch_l2(src, SLOT);
                else {
                    scrap_copy(sb + S_DUMMY, src, sb + S_DBAR + 8 * (nd & 3));
                    q[0] = (sb + S_DBAR + 8 * (nd & 3)) | ((nd >> 2) & 1);
                    nd++;
                }
            }
        }
    }
#pragma unroll 1
    for (int m = max(nd - 4, 0); m < nd; m++) uwait(sb + S_DBAR + 8 * (m & 3), (m >> 2) & 1);
}

__device__ __forceinline__ float scaled(float s) { return bfr(bfr(s) * 0.07216878364870322f); }
__device__ __forceinline__ void probs(float s, uint32_t ps, uint32_t src, uint32_t ln) {
    const uint32_t q8 = ln >> 2, t4 = ln & 3;
    int key = __float_as_int(s);
    key ^= (key >> 31) & 0x7fffffff;
    key = __reduce_max_sync(~0u, key);
    key ^= (key >> 31) & 0x7fffffff;
    const float ml = __int_as_float(key) * LOG2E;
    sts_hi16(ps + 64 * src + (q8 >> 1) * 16 + t4 * 4 + (q8 & 1) * 2, bfr(ex2(fmaf(s, LOG2E, -ml))));
    sts32_if(ln == 0, ps + PS_MAX + 4 * src, __float_as_uint(ml));
}
template <int H> __device__ __forceinline__ uint32_t b_pos(uint32_t e) { const uint32_t h = e >= H, k = e - H * h; return h * 192 + (k & 6) * 24 + (k >> 3) * 4 + (k & 1) * 2; }
__device__ __forceinline__ uint32_t a_pos(uint32_t e) { const uint32_t h = e >= 40, k = e - 40 * h; return (k & 6) * 24 + (k >> 3) * 8 + h * 4 + (k & 1) * 2; }
__device__ __forceinline__ uint32_t q_pos(uint32_t d) { return ((d >> 4) & 7) * 64 + (d & 6) * 8 + (d >> 7) * 8 + ((d >> 3) & 1) * 4 + (d & 1) * 2; }
__device__ __forceinline__ uint32_t k_off(uint32_t ln, uint32_t j) { const uint32_t r = 3 * (ln & 15) + j; return r * 128 + (((r & 7) ^ (ln >> 4)) << 4); }

#define HSTAMP(k) do {} while (0)
__device__ __forceinline__ void score_warp(const Maps& M, uint32_t sb, uint32_t h, uint32_t ln) {
    uwait(sb + S_QRDY, 0);
    const uint32_t q8 = ln >> 2;
    const uint32_t k0 = k_off(ln, 0), k1 = k_off(ln, 1), k2 = k_off(ln, 2);
    const uint64_t pol = pol_normal();
    uint32_t pos = h + 6, bar = sb + S_FK, par = 0, phases = 0;
    uint4 q = lds128(sb + S_QS + 16 * ln);
#pragma unroll 1
    for (uint32_t n = h; n < 64; n += 2) {
        HSTAMP(0);
        const uint32_t ua = sb + pos * UNIT;
        if (!__all_sync(~0u, mbar_try(bar, par))) uwait(bar, par);
        HSTAMP(1);
        float acc[2][4] = {};
        uint32_t mine = 0;
#pragma unroll
        for (int s = 0; s < 12; s++) {
            uint32_t kf[4];
            ldsm4(kf, (ua + (s < 4 ? k0 : s < 8 ? k1 : k2)) ^ (32 * (s & 3)));
            if (s == 11) {
                __syncwarp();
                mine = token(ln == 0 && n >= 16 && (n & 15) < 10, sb + S_TOK + 4 * pos, n + 6);
                stsvol(sb + S_KF + 4 * h, n + 1);
            }
            const bool m = q8 == (s & 7);
            mmaA(acc[s & 1], kf, m ? (s < 8 ? q.x : q.z) : 0u, m ? (s < 8 ? q.y : q.w) : 0u);
        }
        const int row = 3 * (first_key() + (n >> 4) * KV_BATCH_KEYS + 16 * (n & 15) + 96);
        const uint32_t bar0 = bar;
        const bool last = (n & 14) == 14;
        pos = last ? h + 2 : n >= 16 && pos >= 4 ? h : pos + 2;
        bar = n >= 14 ? sb + S_RING + 8 * pos : bar + 8;
        par = n >= 14 ? (phases >> pos) & 1 : 0;
        phases ^= n >= 14 ? 1u << pos : 0;
        const float w0 = (acc[0][0] + acc[0][1]) + (acc[1][0] + acc[1][1]), w1 = (acc[0][2] + acc[0][3]) + (acc[1][2] + acc[1][3]);
        HSTAMP(2);
        if (__any_sync(~0u, mine == n + 6)) tma2d(ua, &M.k, 0, row, bar0, UNIT, pol);
        HSTAMP(3);
        float s = ((ln & 1) ? w1 : w0) + __shfl_xor_sync(~0u, (ln & 1) ? w0 : w1, 1);
        s += __shfl_xor_sync(~0u, s, 2);
        sts_hi16(sb + S_SC + (((n & 12) >> 1) + h) * 64 + (n & 2) * 2 + (ln & 29) * 2, scaled(s));
        if (last) {
            __syncwarp();
            arrive_if(ln == 0, sb + S_SCO);
            q = lds128(sb + S_QS + 32 * ((n + 2) & 48) + 16 * ln);
        }
    }
}

__device__ __forceinline__ char* xwindow() { return reinterpret_cast<char*>((reinterpret_cast<uintptr_t>(g_x) + (2u << 20) - 1) & ~(uintptr_t)((2u << 20) - 1)); }

struct XPtr {
    uint32_t lo, hi;
    __device__ __forceinline__ explicit XPtr(char* p) : lo((uint32_t)(uintptr_t)p), hi((uint32_t)((uintptr_t)p >> 32)) {}
    __device__ __forceinline__ XPtr(uint32_t l, uint32_t h) : lo(l), hi(h) {}
    __device__ __forceinline__ XPtr operator+(uint32_t o) const { return XPtr(lo + o, hi); }
    __device__ __forceinline__ operator char*() const { uint64_t p; asm("mov.b64 %0, {%1, %2};" : "=l"(p) : "r"(lo), "r"(hi)); return (char*)p; }
};
__device__ __forceinline__ void keep(XPtr& v) { keep(v.lo); }

__device__ __forceinline__ void side_warp(uint32_t sb) {
    const uint32_t bid = blockIdx.x, g = bid >> 3, i = bid & 7, P = pairG(0, 0, i);
    char* p = xwindow() + P * 8192 + (g >> 3) * HALF + (g & 7) * 512 + 448;
    uint32_t best[2] = {~0u, ~0u};
    asm volatile("st.relaxed.gpu.global.b32 [%0], 1;" :: "l"(p) : "memory");
    asm volatile("st.relaxed.gpu.global.b32 [%0], 1;" :: "l"(p + COPY) : "memory");
#pragma unroll 1
    for (int r = 0; r < 64; r++) {
        if (r >= 4 && !(r & 1) && min(best[0], best[1]) < 380 && max(best[0], best[1]) > min(best[0], best[1]) + 80) break;
        uint32_t c0, c1, v;
        asm volatile("mov.u32 %0, %clock;" : "=r"(c0) :: "memory");
        asm volatile("atom.relaxed.gpu.global.exch.b32 %0, [%1], 0;" : "=r"(v) : "l"(p + (r & 1) * COPY) : "memory");
        asm volatile("{\n .reg .pred q;\n setp.eq.u32 q, %1, 0x13579bdf;\n mov.u32 %0, 0;\n @!q mov.u32 %0, %clock;\n}" : "=r"(c1) : "r"(v) : "memory");
        if (r & 1) best[1] = min(best[1], c1 - c0); else best[0] = min(best[0], c1 - c0);
    }
    stsvol(sb + S_SIDE, 1 + ((best[1] < best[0]) ^ (__popc(P & PMASK) & 1)));
}

__device__ __forceinline__ void look_a(uint2 (&v)[4], const char* src) {
#pragma unroll
    for (int s = 0; s < 4; s++) v[s] = ldp64(src + s * 1024);
}
__device__ __forceinline__ void hop_a(uint2 (&v)[4], const char* src, uint32_t par, uint32_t dst, bool st, int k) {
    int guard = 0;
    while (__any_sync(~0u, chk4(v, par) & 1) && ++guard < SPIN_LIMIT) look_a(v, src);
    const float M = fmaxf(fmaxf(asf(v[0].x), asf(v[1].x)), fmaxf(asf(v[2].x), asf(v[3].x)));
    float e[4];
#pragma unroll
    for (int s = 0; s < 4; s++) e[s] = ex2(asf(v[s].x) - M);
    const float rl = __shfl_sync(~0u, rcp(fmaf(e[0], asf(v[0].y), e[1] * asf(v[1].y)) + fmaf(e[2], asf(v[2].y), e[3] * asf(v[3].y))), 24);
#pragma unroll
    for (int s = 0; s < 4; s++) e[s] = __shfl_sync(~0u, e[s], 24);
    const float o0 = fmaf(e[0], asf(v[0].x), e[1] * asf(v[1].x)) + fmaf(e[2], asf(v[2].x), e[3] * asf(v[3].x));
    const float o1 = fmaf(e[0], asf(v[0].y), e[1] * asf(v[1].y)) + fmaf(e[2], asf(v[2].y), e[3] * asf(v[3].y));
    sts32_if(st, dst, pack2(o0 * rl, o1 * rl));
    SWEEPS(k, guard);
    __syncwarp();
}

__global__ void __launch_bounds__(NTHR, 1)
fused_kernel(const Params P, const __grid_constant__ Maps M) {
    extern __shared__ __align__(1024) unsigned char smem[];
    const uint32_t sb = smem_u32(smem);
    const int tid = threadIdx.x, bid = blockIdx.x;
    const int w = __shfl_sync(~0u, tid >> 5, 0), lane = tid & 31;

    if (w >= 8) {
        asm volatile("setmaxnreg.dec.sync.aligned.u32 " REG_LO ";");
        if (w == 8) {
            stream_warp(P, M, sb, lane);
        } else {
            if (PFMAP && w == 11 && lane < 7) asm volatile("prefetch.tensormap [%0];" :: "l"(&M.k + lane) : "memory");
            if (w == 9) { init_bars<0, 8, 1>(sb); init_bars<16, 22, 1>(sb); }
            else if (w == 10) { init_bars<8, 16, 2>(sb); init_bars<22, 26, 1>(sb); }
            else { init_bars<37, 38, 1>(sb); init_bars<38, 40, 8>(sb); init_bars<40, 41, 1>(sb); init_bars<41, 44, 8>(sb); init_bars<44, 45, 2>(sb); if (lane < 18) stsvol(sb + S_ZERO + 4 * lane, 0); }
            asm volatile("fence.mbarrier_init.release.cluster;" ::: "memory");
            asm volatile("bar.arrive 3, 128;" ::: "memory");
            asm volatile("bar.sync 2, %0;" :: "n"(NTHR) : "memory");
            if (w < 11) score_warp(M, sb, w - 9, lane);
            else {
                if (lane == 0) side_warp(sb);
                __syncwarp();
                uint32_t a = 0, b = 0;
                int k = 0;
                while (ldsvol(sb + S_GATE) == 0 && ++k < SPIN_LIMIT) { warm_mma(a, b); __nanosleep(KWNS); }
                uint4* d = reinterpret_cast<uint4*>(reinterpret_cast<char*>(g_s) + XS + bid * 7680) + lane;
                const uint4 z = make_uint4(0, 0, 0, 0);
#pragma unroll 1
                for (int u = 0; u < 15; u++) d[32 * u] = z;
                d = reinterpret_cast<uint4*>(reinterpret_cast<char*>(g_s) + XS2 + bid * 768) + lane;
                d[0] = z;
                if (lane < 16) d[32] = z;
                const uint32_t side = (ldsvol(sb + S_SIDE) & 1) ^ 1, g = bid >> 3, i = bid & 7;
                const XPtr gx(xwindow());
                auto nearp = [&](uint32_t pr) { return gx.lo + pr * 8192 + ((side ^ __popc(pr & PMASK)) & 1) * COPY; };
                const uint32_t own = (i >> 2) * HALF + (i & 3) * 1024 + (lane & 7) * 128;
                const uint32_t pAC = nearp(pairL(lane >> 4, (lane >> 3) & 1, g)) + own, pE = nearp(pairL(RE, (lane >> 3) & 1, g)) + own;
                const uint32_t pG = nearp(pairG((lane >> 2) & 1, (lane >> 3) & 1, i)) + min(lane & 3, 2) * 128;
                uint32_t tr = 0, tk = 0, ph = 0, src = g + (lane >> 4), seen = 0, n = 16;
                bool go = false, first = true;
                while (n < 64 && ++k < SPIN_LIMIT) {
                    const uint32_t now = __shfl_sync(~0u, gtime32(), 0) * 16;
                    if (!go && utest(sb + S_RELV, ((n >> 4) & 1) ^ 1) && utest(sb + S_FV + 8 * (n >= 48 ? KRE_GATE3 : KRE_GATE), (n >> 4) & 1)) { go = true; tk = now; }
                    if (go && (int)(now - tk) >= 0) {
                        place_load(M, sb, n);
                        tk += n >= 48 ? KRE_TAU3 : (n & 15) < KRE_N1 ? KRE_TAU1 : KRE_TAU;
                        n++;
                        go = (n & 15) != 0;
                        if (!go) LSTAMP(63 + (n >> 3));
                    } else if (first || (int)(now - tr) >= 0) {
                        first = false;
                        tr = now + RFR_TAU;
                        b |= seen & a;
                        warm_mma(a, b);
                        if (RFR_ON) seen = ldp32(XPtr(ph == 0 ? pAC : ph == 1 && lane < 16 ? pE : pG + (src & 8) * (HALF / 8) + (src & 7) * 512, gx.hi));
                        src += ph == 0 ? 0 : ph == 1 ? 2 : 1;
                        ph = ph == 2 ? 0 : ph + 1;
                    } else __nanosleep(KWNS2);
                }
                while (ldsvol(sb + S_GATE) < 6 && ++k < SPIN_LIMIT) { warm_mma(a, b); __nanosleep(KWNS); }
                if (a | b) stsvol(sb + S_GATE, 6);
            }
        }
        return;
    }
    asm volatile("setmaxnreg.inc.sync.aligned.u32 " REG_HI ";");

    const int g = bid >> 3, i = bid & 7;
    const int g8 = lane >> 2, t = lane & 3;
    char* const gs = reinterpret_cast<char*>(g_s);
    const XPtr gx(xwindow());

    auto zero_words = [&] {
        const uint4 z = make_uint4(0, 0, 0, 0);
        const uint32_t c = (tid >> 6) & 1, cp = (tid >> 7) * COPY, k = (tid & 63) * 16;
        *reinterpret_cast<uint4*>((char*)(gx + pairL(RA, c, g) * 8192 + (i >> 2) * HALF + (i & 3) * 1024 + cp + k)) = z;
        *reinterpret_cast<uint4*>((char*)(gx + pairL(RC, c, g) * 8192 + (i >> 2) * HALF + (i & 3) * 1024 + cp + k)) = z;
        *reinterpret_cast<uint4*>((char*)(gx + pairL(RE, c, g) * 8192 + (i >> 2) * HALF + (i & 3) * 1024 + cp + k)) = z;
        if ((tid & 31) < 24) *reinterpret_cast<uint4*>((char*)(gx + pairG((tid >> 5) & 1, c, i) * 8192 + (g >> 3) * HALF + (g & 7) * 512 + cp + (tid & 31) * 16)) = z;
    };
    if (ZPOS == 0) zero_words();
    W80 Wq[6], Wgu[3];
    uint32_t Wo[5][3][4];
    if (w < 4) {
        const uint32_t* xp = reinterpret_cast<const uint32_t*>(P.x + 640 * w);
        float sum = 0.f, sq = 0.f;
#pragma unroll
        for (int u = 0; u < 10; u++) { uint32_t v = xp[lane + 32 * u]; float a = bf_lo(v), b = bf_hi(v); sum += a + b; sq += a * a + b * b; }
#pragma unroll
        for (int o = 16; o > 0; o >>= 1) { sum += __shfl_xor_sync(~0u, sum, o); sq += __shfl_xor_sync(~0u, sq, o); }
        float mean, den; ln_stats(sum, sq, mean, den);
        if (lane < 20) {
            const uint2 v = reinterpret_cast<const uint2*>(P.x + 640 * w + 80 * i)[lane];
            sts64(sb + S_X0 + 160 * w + 8 * lane, v.x, v.y);
            sts32(sb + S_L0 + 384 * w + b_pos<40>(4 * lane), pack2(__fdiv_rn(bfr(bf_lo(v.x) - mean), den), __fdiv_rn(bfr(bf_hi(v.x) - mean), den)));
            sts32(sb + S_L0 + 384 * w + b_pos<40>(4 * lane + 2), pack2(__fdiv_rn(bfr(bf_lo(v.y) - mean), den), __fdiv_rn(bfr(bf_hi(v.y) - mean), den)));
        }
    } else if (w == 4) {
        const uint32_t* xp = reinterpret_cast<const uint32_t*>(P.wr);
        float sum = 0.f;
#pragma unroll
        for (int u = 0; u < 10; u++) { uint32_t v = xp[lane + 32 * u]; sum += bf_lo(v) + bf_hi(v); }
#pragma unroll
        for (int o = 16; o > 0; o >>= 1) sum += __shfl_xor_sync(~0u, sum, o);
        if (lane == 0) stsf(sb + S_SWR, sum);
        if (lane < 20) {
            const uint2 v = reinterpret_cast<const uint2*>(P.wr + 80 * i)[lane];
            sts32(sb + S_XA + 576 + a_pos(4 * lane), v.x); sts32(sb + S_XA + 576 + a_pos(4 * lane + 2), v.y);
            sts32(sb + S_XA + a_pos(4 * lane), ONES); sts32(sb + S_XA + a_pos(4 * lane + 2), ONES);
        }
    }
    asm volatile("bar.sync 2, %0;" :: "n"(NTHR) : "memory");
    auto frag = [](uint32_t (&a)[4], uint32_t p, int pitch) {
        const uint32_t r0 = lds32(p), r1 = lds32(p + pitch), r2 = lds32(p + 2 * pitch), r3 = lds32(p + 3 * pitch);
        a[0] = __byte_perm(r0, r1, 0x5410); a[1] = __byte_perm(r0, r1, 0x7632);
        a[2] = __byte_perm(r2, r3, 0x5410); a[3] = __byte_perm(r2, r3, 0x7632);
    };
    mbar_wait(sb + S_WFULL + 16 * (w >> 2), 0);
    mbar_wait(sb + S_WFULL + 16 * (w >> 2) + 8, 0);
    {
        const uint32_t p = sb + ST_WQ + (w >> 2) * 30720 + (2 * t) * 384 + (48 * (w & 3) + 2 * g8) * 2;
#pragma unroll
        for (int r = 0; r < 10; r++)
#pragma unroll
            for (int m = 0; m < 3; m++) {
                const uint32_t q = p + ((r & 1) * 40 + (r >> 1) * 8) * 384 + 32 * m, r0 = lds32(q), r1 = lds32(q + 384);
                (r < 8 ? Wq[2 * m].a[(r >> 2) & 1][r & 3] : Wq[2 * m].c[r & 1]) = __byte_perm(r0, r1, 0x5410);
                (r < 8 ? Wq[2 * m + 1].a[(r >> 2) & 1][r & 3] : Wq[2 * m + 1].c[r & 1]) = __byte_perm(r0, r1, 0x7632);
            }
    }
    __syncwarp();
    if (lane == 0) mbar_arrive(sb + S_RELW);
    TSTAMP(1);
    {
        char* d = gs + XS + bid * 7680 + (w >> 2) * 3840 + (48 * (w & 3) + 2 * g8) * 4;
        float acc[6][4] = {};
        mul80(acc, Wq, lds128(sb + S_L0 + 48 * lane), lds32(sb + S_L0 + 48 * lane + 16));
#pragma unroll
        for (int m = 0; m < 6; m += 2) stp64(d + t * 768 + 32 * m, acc[m][0] + acc[m][3], acc[m + 1][0] + acc[m + 1][3], 1);
        float sum[6][4] = {};
        mul80(sum, Wq, make_uint4(ONES, ONES, ONES, ONES), ONES);
        if (t == 0)
#pragma unroll
            for (int m = 0; m < 6; m += 2) stp64(d + 4 * 768 + 32 * m, sum[m][0] + sum[m][3], sum[m + 1][0] + sum[m + 1][3], 1);
    }
    mbar_wait(sb + S_WFULL + 32, 0);
    mbar_wait(sb + S_WFULL + 40, 0);
    const uint32_t oct = 3 * (w >> 1) + (w & 1), oct2 = 3 * (w >> 1) + 2;
    {
        const uint32_t p = sb + ST_WG + ((lane & 7) + 40 * ((lane >> 3) & 1) + 8 * (lane >> 4)) * 192;
#pragma unroll
        for (int T = 0; T < 3; T++) {
            const uint32_t q = p + (T < 2 ? T * 15360 + 16 * oct : (w & 1) * 15360 + 16 * oct2);
            ldsm4t(Wgu[T].a[0], q); ldsm4t(Wgu[T].a[1], q + 16 * 192); ldsm2t(Wgu[T].c, q + 32 * 192);
        }
        float sum[3][4] = {};
        mul80(sum, Wgu, make_uint4(ONES, ONES, ONES, ONES), ONES);
        if (t < 3) stp32(gs + XS2 + bid * 768 + (t < 2 ? 64 * oct + 4 * t : 64 * oct2 + 4 * (w & 1)) + 8 * g8,
                         sel4(t, sum[0][0] + sum[0][3], sum[1][0] + sum[1][3], sum[2][0] + sum[2][3], 0.f), 1);
    }
    __syncwarp();
    if (lane == 0) mbar_arrive(sb + S_RELW + 8);
    const char* srcS = gs + XS + g * 8 * 7680 + (i >> 2) * 3840 + min(tid, 191) * 4;
    uint32_t vs[5][8];
#pragma unroll
    for (int b = 0; b < 5; b++)
#pragma unroll
        for (int s = 0; s < 8; s++) vs[b][s] = LOOK1 ? ldp32(srcS + b * 768 + s * 7680) : 0;
    uint32_t cs2[8];
#pragma unroll
    for (int s = 0; s < 8; s++) cs2[s] = LOOK2 ? ldp32(gs + XS2 + (g * 8 + s) * 768 + min(tid, 191) * 4) : 0;
    __syncwarp();
    mbar_wait(sb + S_WFULL + 48 + 8 * (w >> 1), 0);
    {
        const uint32_t po = sb + ST_WO + (48 * w + 12 * t) * 160 + 4 * g8;
#pragma unroll
        for (int s = 0; s < 3; s++)
#pragma unroll
            for (int m = 0; m < 5; m++) frag(Wo[m][s], po + 4 * s * 160 + 32 * m, 160);
    }
    __syncwarp();
    if (lane == 0) mbar_arrive(sb + S_RELW + 16);
    if (ZPOS == 1) zero_words();
    if (tid < 192) {
        int guard = 0;
        while (((or3(chk8(vs[0], 1), chk8(vs[1], 1), chk8(vs[2], 1)) | chk8(vs[3], 1) | chk8(vs[4], 1)) & 1) && ++guard < SPIN_LIMIT) {
#pragma unroll
            for (int b = 0; b < 5; b++)
#pragma unroll
                for (int s = 0; s < 8; s++) vs[b][s] = ldp32(srcS + b * 768 + s * 7680);
        }
        const uint32_t qpos = sb + S_QS + q_pos(tid);
#pragma unroll
        for (int b = 0; b < 4; b++) {
            sts_hi16(qpos + 512 * b, bfr(sum8(vs[b])));
        }
        stsf(sb + S_CSQ + 4 * tid, sum8(vs[4]));
    }
    if (tid < 192) stsf(sb + S_CSGU + 4 * tid, (chk8(cs2, 1) & 1) ? gather8<768>(gs + XS2 + g * 8 * 768 + tid * 4, 1) : sum8(cs2));
    bar_main();
    arrive_if(tid == 0, sb + S_QRDY);
    if (ZPOS == 2) zero_words();
    TSTAMP(2);

    uint32_t side;
    { int k = 0; while ((side = ldsvol(sb + S_SIDE)) == 0 && ++k < SPIN_LIMIT) {} }
    side = __shfl_sync(~0u, side & 1, 0) ^ 1;
    auto nearp = [&](uint32_t P) { return P * 8192 + ((side ^ __popc(P & PMASK)) & 1) * COPY; };
    const uint32_t td = __shfl_sync(~0u, tid, lane);
    const uint32_t wp = __shfl_sync(~0u, tid >> 5, 0);
    const uint32_t cc = wp >= 3;
#define IDS() uint32_t z_ = td; opaque(z_); const uint32_t ln = z_ & 31, q8 = ln >> 2, t4 = z_ & 3, n96 = z_ - 96 * cc, n80 = min(n96, 79u); (void)q8; (void)t4; (void)n80; (void)ln

    auto vaddr = [&](uint32_t (&voff)[3]) {
        IDS();
        const uint32_t key3 = 3 * ((ln & 7) + 2 * (ln & 8) + ((ln >> 1) & 8));
#pragma unroll
        for (int T = 0; T < 3; T++) {
            const uint32_t u = 3 * wp + T, r = key3 + (u >> 3);
            voff[T] = r * 128 + (((u ^ r) & 7) << 4);
        }
    };
    auto values = [&](uint32_t (&vf)[8][3][4], auto step, uint32_t ps, uint32_t col, uint32_t par) {
        IDS();
        const uint4 p = lds128(ps + 16 * ln);
        const uint2 mp = lds64(ps + PS_MAX + 8 * t4);
        const float mq = ldsf(ps + PS_MAX + 4 * q8);
        float acc[3][4] = {};
        float M = fmaxf(asf(mp.x), asf(mp.y)), lsum = 0.f, f0 = 0.f, f1 = 0.f;
#pragma unroll
        for (int s = 0; s < 8; s++) {
            step(s);
            const bool m = (q8 >> 1) == (s >> 1);
            const uint32_t b0 = m ? ((s & 1) ? p.z : p.x) : 0u, b1 = m ? ((s & 1) ? p.w : p.y) : 0u;
#pragma unroll
            for (int T = 0; T < 3; T++) mmaA(acc[T], vf[s][T], b0, b1);
            if (s < 2) M = fmaxf(M, __shfl_xor_sync(~0u, M, 1 + s));
            if (s == 1) {
                f0 = ex2(asf(mp.x) - M); f1 = ex2(asf(mp.y) - M);
                lsum = (((bf_lo(p.x) + bf_hi(p.x)) + (bf_lo(p.y) + bf_hi(p.y))) + ((bf_lo(p.z) + bf_hi(p.z)) + (bf_lo(p.w) + bf_hi(p.w)))) * ex2(mq - M);
            }
            if (s >= 2 && s < 7) lsum += __shfl_xor_sync(~0u, lsum, 1 << (s - 2));
        }
        char* pubA = gx + pairL(RA, col, g) * 8192 + (i >> 2) * HALF + (i & 3) * 1024 + (wp >> 1) * 256 + (wp & 1) * 96 + 32 * t4 + 4 * q8;
        const float r0 = fmaf(f0, acc[0][0], f1 * acc[0][3]), r1 = fmaf(f0, acc[1][0], f1 * acc[1][3]), r2 = fmaf(f0, acc[2][0], f1 * acc[2][3]);
        const bool hi = t4 & 2, od = t4 & 1;
        const float u0 = (hi ? r2 : r0) + __shfl_xor_sync(~0u, hi ? r0 : r2, 2), u1 = r1 + __shfl_xor_sync(~0u, r1, 2);
        const float o = (od ? u1 : u0) + __shfl_xor_sync(~0u, od ? u0 : u1, 1);
        stp32_if(t4 < 3 || ((wp & 1) && q8 < 2), pubA, t4 < 3 ? o : q8 ? lsum : M, par);
    };

#pragma unroll 1
    for (int ch = 0; ch < 5; ch++) {
        const uint32_t par0 = (ch + 1) & 1, par1 = ch & 1;
        uint32_t voff[3], vf[8][3][4];
        CSTAMP(0);
        if (ch < 4) {
            vaddr(voff);
            mbar_wait(sb + S_SCO, par1);
            TST(0);
            auto ldw = [&](int s) {
                mbar_wait(sb + S_FV + 8 * s, par1);
#pragma unroll
                for (int T = 0; T < 3; T++) ldsm4t(vf[s][T], voff[T] + (sb + v_place(ch, s) * SLOT));
            };
            probs(bf_lo(lds16(sb + S_SC + 2 * td)), sb + S_PS, wp, td & 31);
            ldw(0); ldw(1); ldw(2);
            bar_main();
            arrive_if(td == 0, sb + S_RELR);
            uint2 u[4];
            values(vf, [&](int s) {
                if (s == HOPA0 || s == HOPA1) {
                    IDS();
                    const XPtr polA = gx + nearp(pairL(RA, 1, g)) + (wp >> 2) * HALF + (wp & 3) * 256 + 8 * min(ln, 24u);
                    if (s == HOPA0) look_a(u, polA);
                    if (s == HOPA1 && ch > 0) {
                        hop_a(u, polA, par1, sb + S_OS + 192 * wp + 4 * ln + 96, ln < 24, 25);
                    }
                }
                if (s >= 3) ldw(s);
            }, sb + S_PS, 0, par0);
            TST(1);
            CSTAMP(5);
        } else {
#pragma unroll
            for (int s = 0; s < 36; s++) { vf[s / 12][(s / 4) % 3][s & 3] = 0; opaque(vf[s / 12][(s / 4) % 3][s & 3]); }
        }
        const bool has0 = ch < 4, has1 = ch > 0;
        const bool actc = wp < 6 && (cc ? has1 : has0);
        const uint32_t parc = cc ? par1 : par0;
        const uint32_t pub0 = has0 ? par0 : 0;
        XPtr pubB = gx;
        uint32_t rr;
        {
            IDS();
            const uint32_t c = ch == 4;
            const XPtr polA = gx + nearp(pairL(RA, c, g)) + (wp >> 2) * HALF + (wp & 3) * 256 + 8 * min(ln, 24u) + lag<DELAY_L>(sb);
            uint2 v[4];
            look_a(v, polA);
            uint32_t osa = sb + S_OS + 192 * wp + 96 * c + 4 * ln;
            uint32_t oa = sb + S_OS + 192 * wp + 96 * (q8 & 1) + 24 * t4, ra = sb + S_RED + 640 * wp + 320 * (t4 & 1) + 8 * q8;
            pubB = gx + pairG(0, cc, i) * 8192 + (g >> 3) * HALF + (g & 7) * 512 + n80 * 4;
            rr = sb + S_RED + 320 * cc + 4 * n80;
            keep(osa); keep(oa); keep(ra); keep(pubB); keep(rr);
            hop_a(v, polA, c ? par1 : par0, osa, ln < 24, 5 * ch);
            TST(2);
            CSTAMP(6);
            float acc[5][4] = {};
            const uint2 b0 = lds64(oa), b1 = lds64(oa + 8), b2 = lds64(oa + 16);
#pragma unroll
            for (int m = 0; m < 5; m++) mmaA(acc[m], Wo[m][0], b0.x, b0.y);
#pragma unroll
            for (int m = 0; m < 5; m++) mmaA(acc[m], Wo[m][1], b1.x, b1.y);
#pragma unroll
            for (int m = 0; m < 5; m++) mmaA(acc[m], Wo[m][2], b2.x, b2.y);
#pragma unroll
            for (int m = 0; m < 5; m++) sts64_if(t4 < 2, ra + 64 * m, t4 ? acc[m][1] : acc[m][0], t4 ? acc[m][3] : acc[m][2]);
        }
        CSTAMP(7);
        bar_main();
        CSTAMP(8);
        float x1 = 0.f;
        uint32_t xr, fl;
        XPtr pubC = gx, pubC2 = gx;
        {
            IDS();
            if (actc) {
                uint32_t r[8];
#pragma unroll
                for (int s = 0; s < 8; s++) r[s] = lds32(rr + 640 * s);
                stp32_if(n96 < 80, pubB, sum8(r), parc);
                CSTAMP(9);
            }
            xr = sb + S_XB + 48 * (ln & 15);
            pubC = gx + pairL(RC, 0, g) * 8192 + (i >> 2) * HALF + (i & 3) * 1024 + (t4 & 1) * (32 * 8192);
            pubC2 = pubC + ((t4 & 2) ? 192 * (wp >> 1) + 128 + 4 * (wp & 1) + 8 * q8 : 768 + 2 * ((q8 + 1) & 6));
            pubC = pubC + (192 * (wp >> 1) + 64 * (wp & 1) + 8 * q8);
            fl = ((t4 & 1) ? par1 : pub0) | (t4 >= 2 || (wp == 7 && q8 < 4 && q8 != 2 - t4) ? 2 : 0);
            keep(xr); keep(pubC); keep(pubC2); keep(fl);
            if (actc) {
                const char* polB = gx + nearp(pairG(0, cc, i)) + n80 * 4 + lag<DELAY_G>(sb);
                uint32_t xas = sb + S_XA + 192 + 192 * cc + a_pos(n80), xbs = sb + S_XB + 384 * cc + b_pos<40>(n80);
                x1 = cc ? ldsf(sb + S_XCAR + 4 * n80) : bf_lo(lds16(sb + S_X0 + 160 * (ch & 3) + 2 * n80));
                keep(xas); keep(xbs); keep(x1);
                x1 = bfr(x1 + bfr(gather16(polB, parc, 5 * ch + 1, [](uint32_t) { return false; })));
                CSTAMP(10);
                sts_hi16(xbs, x1);
                sts_hi16(xas, x1);
            }
        }
        bar_main();
        TST(3);
        CSTAMP(11);
        auto stats = [&](uint32_t xa, const uint4& b, uint32_t b4) {
            float a[4] = {};
            const uint4 p0 = lds128(xa), p1 = lds128(xa + 16);
            const uint2 p2 = lds64(xa + 32);
            mmaV(a, p0, b.x, b.y); mmaV(a, p1, b.z, b.w); mma8(a, p2.x, p2.y, b4);
            return a[0] + a[3];
        };
        {
            auto gate_up = [&](auto with_stats) {
                const uint4 b = lds128(xr);
                const uint32_t b4 = lds32(xr + 16);
                float acc[3][4] = {}, st = 0.f;
                if (with_stats.value) st = stats(xr + (S_XA - S_XB), b, b4);
                mul80(acc, Wgu, b, b4);
                stp64_if(!(td & 2), pubC, tagw(acc[0][0] + acc[0][3], fl & 1), tagw(acc[1][0] + acc[1][3], fl & 1));
                stp32_if(fl & 2, pubC2, !with_stats.value || (td & 2) ? acc[2][0] + acc[2][3] : st, fl & 1);
            };
            if (wp == 7) gate_up(std::true_type()); else gate_up(std::false_type());
        }
        sts32_if(td == 255, sb + S_GATE, ch + 1);
        CSTAMP(12);
        float mean = 0.f, den = 1.f;
        {
            IDS();
            const uint32_t wa = sb + S_WD + ((ln & 7) + 48 * ((ln >> 3) & 1) + 8 * (ln >> 4)) * 160 + (wp < 7 ? 16 * wp : 128);
            uint32_t ha = sb + S_HS + 48 * (ln & 15);
            XPtr pubD = gx + pairG(1, t4 & 1, i) * 8192 + (g >> 3) * HALF + (g & 7) * 512 + (wp < 7 ? 32 * wp : 256) + 16 * (t4 & 2) + 4 * q8;
            if (ch == 0) mbar_wait(sb + S_WFULL + 80, 0);
            auto down = [&](const uint32_t (&W)[3][4], const uint4& h0, const uint2& h1) {
                float a0[4] = {}, a1[4] = {}, a2[4] = {};
                mmaA(a0, W[0], h0.x, h0.y); mmaA(a1, W[1], h0.z, h0.w); mmaA(a2, W[2], h1.x, h1.y);
                return ((a0[0] + a0[3]) + (a1[0] + a1[3])) + (a2[0] + a2[3]);
            };
            if (wp < 6) {
                uint32_t Wd[3][4];
                auto ldd = [&] {
#pragma unroll
                    for (int s = 0; s < 3; s++) ldsm4t(Wd[s], wa + s * 2560);
                };
                uint32_t hsa = sb + S_HS + 384 * cc + b_pos<48>(n96);
                keep(ha); keep(pubD); keep(hsa);
                if (actc) {
                    const XPtr src0 = gx + nearp(pairL(RC, cc, g)) + lag<DELAY_C>(sb);
                    const char* srcv = src0 + 8 * n96;
                    const char* src = src0 + (ln & 1) * HALF;
                    uint2 v[8], st[4];
                    float sx, sq, pg, pu, rd;
                    uint2 cs;
                    int guard = 0;
                    bool again;
                    do {
#pragma unroll
                        for (int s = 0; s < 4; s++) st[s] = ldp64(src + 768 + s * 1024);
#pragma unroll
                        for (int s = 0; s < 8; s++) v[s] = ldp64(srcv + (s >> 2) * HALF + (s & 3) * 1024);
                        sx = (asf(st[0].x) + asf(st[1].x)) + (asf(st[2].x) + asf(st[3].x)); sq = (asf(st[0].y) + asf(st[1].y)) + (asf(st[2].y) + asf(st[3].y));
                        sx += __shfl_xor_sync(~0u, sx, 1); sq += __shfl_xor_sync(~0u, sq, 1);
                        cs = lds64(sb + S_CSGU - 768 * cc + 8 * td);
                        again = __any_sync(~0u, or3(chk4(st, parc), chk8(v, parc), chk8y(v, parc)) & 1);
                        pg = sum8x(v); pu = sum8y(v);
                        if (SPEC) { ln_stats(sx, sq, mean, den); rd = rcp(den); keep(mean); keep(rd); }
                        keep(pg); keep(pu);
                    } while (again && ++guard < SPIN_LIMIT);
                    CSTAMP(13);
                    ldd();
                    SWEEPS(5 * ch + 2, guard);
                    if (!SPEC) { ln_stats(sx, sq, mean, den); rd = rcp(den); }
                    const float gt = bfr(fmaf(-mean, asf(cs.x), pg) * rd), up = bfr(fmaf(-mean, asf(cs.y), pu) * rd);
                    const float h = bfr(bfr(gt * sigmoidf_(gt)) * up);
                    sts_hi16(hsa, h);
                    CSTAMP(14);
                } else ldd();
                bar_main();
                TST(4);
                CSTAMP(15);
                const uint4 h0 = lds128(ha);
                const uint2 h1 = lds64(ha + 16);
                stp32_if(!(td & 2), pubD, down(Wd, h0, h1), fl & 1);
            } else {
                uint32_t Wd[2][3][4];
#pragma unroll
                for (int s = 0; s < 6; s++) ldsm4t(Wd[s / 3][s % 3], wa + (s / 3) * 16 + (s % 3) * 2560);
                keep(ha); keep(pubD);
                uint32_t v = 0;
                if (wp == 6 ? has0 : has1) {
                    const uint32_t par = wp == 6 ? par0 : par1;
                    const char* src = gx + nearp(pairL(RC, wp - 6, g)) + 768 + (ln & 4) * (HALF / 4) + (ln & 3) * 1024 + 4 * min(ln >> 3, 2u) + lag<DELAY_C>(sb);
                    int guard = 0;
                    do v = ldp32(src); while (__any_sync(~0u, (v ^ par) & 1) && ++guard < SPIN_LIMIT);
                }
                bar_main();
                const uint4 h0 = lds128(ha);
                const uint2 h1 = lds64(ha + 16);
                const float d0 = down(Wd[0], h0, h1), d1 = down(Wd[1], h0, h1);
                stp32_if(true, pubD, (td & 2) ? d1 : d0, fl & 1);
                if (wp == 6 ? has0 : has1) {
                    float sx = asf(v);
                    sx += __shfl_xor_sync(~0u, sx, 1); sx += __shfl_xor_sync(~0u, sx, 2); sx += __shfl_xor_sync(~0u, sx, 4);
                    const float sq = __shfl_sync(~0u, sx, 8), xw = __shfl_sync(~0u, sx, 16);
                    ln_stats(sx, sq, mean, den);
                    const float r = bfr(fmaf(-mean, ldsf(sb + S_SWR), xw) * rcp(den));
                    sts32_if(ln == 0, sb + S_STAT + 4 * (wp - 6), __float_as_uint(bfr(sigmoidf_(r))) | (ch + 1));
                }
            }
        }
        CSTAMP(16);
        XPtr pubE = gx;
        {
            IDS();
            pubE = gx + pairL(RE, 0, g) * 8192 + (i >> 2) * HALF + (i & 3) * 1024 +
                   (t4 < 3 ? (wp >> 2) * (32 * 8192) + 192 * (wp & 3) + 64 * t4 + 8 * q8 : (q8 >> 2) * (32 * 8192) + 768 + 4 * (q8 & 1));
            xr = sb + S_XB + 48 * (ln & 7);
            keep(xr); keep(pubE);
            if (actc && (cc == 0 || g == 0)) {
                const char* polD = gx + nearp(pairG(1, cc, i)) + n80 * 4 + lag<DELAY_D>(sb);
                float lnx = bfr(__fdiv_rn(bfr(x1 - mean), den));
                unsigned short* po = reinterpret_cast<unsigned short*>(P.out) + 640 * (ch - 1) + 80 * i + n80;
                uint32_t xas = sb + S_XA + 192 + a_pos(n80), xbs = sb + S_XB + b_pos<40>(n80), xca = sb + S_XCAR + 4 * n80;
                keep(lnx); keep(po); keep(xca); keep(xas); keep(xbs);
                uint32_t gate;
                const float dn = gather16(polD, parc, 5 * ch + 3, [&](uint32_t z) { gate = ldsvol(sb + S_STAT + 4 * cc + z); return (gate & 7) != ch + 1; });
                const float y = bfr(bfr(dn) * bf_hi(gate));
                CSTAMP(17);
                const float x2 = bfr(x1 + bfr(lnx + y));
                if (cc) *po = (unsigned short)(__float_as_uint(x2) >> 16);
                else {
                    sts_hi16(xbs, x2);
                    sts_hi16(xas, x2);
                    stsf(xca, x2);
                }
            }
        }
        CSTAMP(18);
        if (!has0) break;
        bar_main();
        TST(5);
        CSTAMP(19);
        {
            auto qproj = [&](auto with_stats) {
                const uint32_t t4 = td & 3;
                const uint4 b = lds128(xr);
                const uint32_t b4 = lds32(xr + 16);
                if (with_stats.value) stp32_if((td & 11) == 3, pubE, stats(xr + (S_XA - S_XB), b, b4), par0);
                float acc[6][4] = {};
                mul80(acc, Wq, b, b4);
                const float v0 = sel4(t4, acc[0][0] + acc[0][3], acc[2][0] + acc[2][3], acc[4][0] + acc[4][3], acc[4][0] + acc[4][3]);
                const float v1 = sel4(t4, acc[1][0] + acc[1][3], acc[3][0] + acc[3][3], acc[5][0] + acc[5][3], acc[5][0] + acc[5][3]);
                stp64_if(t4 < 3, pubE, tagw(v0, par0), tagw(v1, par0));
            };
            if (wp == 7) qproj(std::true_type()); else qproj(std::false_type());
        }
        CSTAMP(20);
        {
            IDS();
            const uint32_t ua = sb + k_place(ch, wp & 6) * SLOT + (wp & 1) * UNIT, ub = (k_place(ch, wp | 1) - k_place(ch, wp & 6)) * SLOT;
            uint32_t kf[12][2][4];
            auto ldk = [&](int s) { const uint32_t a = (ua + k_off(ln, s >> 2)) ^ ((s & 3) * 32); ldsm4(kf[s][0], a); ldsm4(kf[s][1], a + ub); };
            mbar_wait(sb + S_FK + 8 * (wp & 6), par1); mbar_wait(sb + S_FK + 8 * (wp | 1), par1);
#pragma unroll
            for (int s = 0; s < KPRE; s++) ldk(s);
            if (wp < 6) {
                const XPtr src0 = gx + nearp(pairL(RE, i >> 2, g)) + lag<DELAY_E>(sb);
                const char* srcv = src0 + 4 * td;
                const char* src = src0 + (ln & 1) * HALF;
                uint32_t v[8]; uint2 st[4];
                float sx, sq, qs, rd, cs;
                int guard = 0;
                bool again;
                do {
#pragma unroll
                    for (int s = 0; s < 4; s++) st[s] = ldp64(src + 768 + s * 1024);
#pragma unroll
                    for (int s = 0; s < 8; s++) v[s] = ldp32(srcv + (s >> 2) * HALF + (s & 3) * 1024);
                    sx = (asf(st[0].x) + asf(st[1].x)) + (asf(st[2].x) + asf(st[3].x)); sq = (asf(st[0].y) + asf(st[1].y)) + (asf(st[2].y) + asf(st[3].y));
                    sx += __shfl_xor_sync(~0u, sx, 1); sq += __shfl_xor_sync(~0u, sq, 1);
                    cs = ldsf(sb + S_CSQ + 4 * td);
                    again = __any_sync(~0u, (chk8(v, par0) | chk4(st, par0)) & 1);
                    qs = sum8(v);
                    if (SPEC) { ln_stats(sx, sq, mean, den); rd = rcp(den); keep(mean); keep(rd); }
                    keep(qs);
                } while (again && ++guard < SPIN_LIMIT);
                CSTAMP(21);
                if (!SPEC) { ln_stats(sx, sq, mean, den); rd = rcp(den); }
                const float q = bfr(fmaf(-mean, cs, qs) * rd);
                sts_hi16(sb + S_QS + 512 * ch + q_pos(td), q);
                SWEEPS(5 * ch + 4, guard);
                CSTAMP(22);
            }
            __syncwarp();
#pragma unroll
            for (int s = KPRE; s < KPRE + KPRE2; s++) ldk(s);
            bar_main();
            TST(6);
            CSTAMP(1);
            const uint4 q = lds128(sb + S_QS + 512 * ch + 16 * ln);
            float acc[2][4] = {};
            constexpr int D = KPRE + KPRE2;
#pragma unroll
            for (int s = 0; s < 12; s++) {
                const bool m = q8 == (s & 7);
                const uint32_t b0 = m ? (s < 8 ? q.x : q.z) : 0u, b1 = m ? (s < 8 ? q.y : q.w) : 0u;
                mmaA(acc[0], kf[s][0], b0, b1);
                mmaA(acc[1], kf[s][1], b0, b1);
                if (s + D < 12) ldk(s + D);
            }
            vaddr(voff);
            auto ldv = [&](int s) {
#pragma unroll
                for (int T = 0; T < 3; T++) ldsm4t(vf[s][T], voff[T] + (sb + v_place(ch, s) * SLOT));
            };
            ldv(3);
            {
                const float v0 = acc[0][0] + acc[0][1], v1 = acc[0][2] + acc[0][3], v2 = acc[1][0] + acc[1][1], v3 = acc[1][2] + acc[1][3];
                const bool hi = t4 & 2, od = t4 & 1;
                const float u0 = (hi ? v2 : v0) + __shfl_xor_sync(~0u, hi ? v0 : v2, 2), u1 = (hi ? v3 : v1) + __shfl_xor_sync(~0u, hi ? v1 : v3, 2);
                const float s = (od ? u1 : u0) + __shfl_xor_sync(~0u, od ? u0 : u1, 1);
                CSTAMP(2);
                arrive_if(ln == 0, sb + S_RELK);
                probs(scaled(s), sb + S_PS + PS_PASS, wp, ln);
            }
            bar_main();
            TST(10);
            CSTAMP(4);
            values(vf, [&](int s) { if (s >= 1 && s < 5) ldv(s + 3); }, sb + S_PS + PS_PASS, 1, par0);
            arrive_if(ln == 0, sb + S_RELV);
        }
        TST(11);
        CSTAMP(23);
    }
    sts32_if(td == 255, sb + S_GATE, 6);
    TSTAMP(3);
}

typedef CUresult (*EncodeFn)(CUtensorMap*, CUtensorMapDataType, cuuint32_t, void*, const cuuint64_t*, const cuuint64_t*, const cuuint32_t*,
                             const cuuint32_t*, CUtensorMapInterleave, CUtensorMapSwizzle, CUtensorMapL2promotion, CUtensorMapFloatOOBfill);

void make_map(EncodeFn enc, CUtensorMap* m, const void* base, uint64_t cols, uint64_t rows, uint32_t box_cols, uint32_t box_rows, bool swizzle) {
    cuuint64_t dims[2] = {cols, rows};
    cuuint64_t strides[1] = {cols * 2};
    cuuint32_t box[2] = {box_cols, box_rows};
    cuuint32_t es[2] = {1, 1};
    enc(m, CU_TENSOR_MAP_DATA_TYPE_BFLOAT16, 2, const_cast<void*>(base), dims, strides, box, es, CU_TENSOR_MAP_INTERLEAVE_NONE,
        swizzle ? CU_TENSOR_MAP_SWIZZLE_128B : CU_TENSOR_MAP_SWIZZLE_NONE, swizzle ? CU_TENSOR_MAP_L2_PROMOTION_NONE : WPROMO, CU_TENSOR_MAP_FLOAT_OOB_FILL_NONE);
}

}

extern "C" void kernel_launch(void* const* d_in, const int* in_sizes, int n_in, void* d_out, int out_size) {
    (void)in_sizes; (void)n_in; (void)out_size;
    static EncodeFn enc = nullptr;
    if (!enc) {
        void* f = nullptr;
        cudaDriverEntryPointQueryResult q;
        cudaGetDriverEntryPoint("cuTensorMapEncodeTiled", &f, cudaEnableDefault, &q);
        enc = (EncodeFn)f;
        cudaFuncSetAttribute(fused_kernel, cudaFuncAttributeMaxDynamicSharedMemorySize, SMEM_BYTES);
    }
    Params P;
    P.x = (const __nv_bfloat16*)d_in[0]; P.k = (const __nv_bfloat16*)d_in[1]; P.v = (const __nv_bfloat16*)d_in[2];
    P.wr = (const __nv_bfloat16*)d_in[6];
    P.out = (__nv_bfloat16*)d_out;
    Maps M;
    make_map(enc, &M.k, P.k, 64, (uint64_t)12 * KV_BATCH_KEYS, 64, 48, true);
    make_map(enc, &M.v, P.v, 64, (uint64_t)12 * KV_BATCH_KEYS, 64, 96, true);
    make_map(enc, &M.wq, d_in[3], 6144, 640, 192, 40, false);
    make_map(enc, &M.wo, d_in[4], 640, 6144, 80, 96, false);
    make_map(enc, &M.wg, d_in[7], 1536, 640, 96, 80, false);
    make_map(enc, &M.wu, d_in[8], 1536, 640, 96, 80, false);
    make_map(enc, &M.wd, d_in[9], 640, 1536, 80, 96, false);
    fused_kernel<<<NCTA, NTHR, SMEM_BYTES, cudaStreamPerThread>>>(P, M);
}
```

```cpp
#include <cuda_runtime.h>
#include <cuda.h>
#include <cuda_bf16.h>
#include <stdint.h>
#include <type_traits>

namespace {

constexpr int NCTA = 128;
constexpr int NTHR = 384;
constexpr int UNIT = 6144;
constexpr int SLOT = 12288;
#define TAU 4100
#define TAUW 4000
#define TAU0 4000
#define PF0 2
#define PFMAP 1
#define ZPOS 1
#define LOOK1 0
#define LOOK2 0
#define SLACK 8000
#define SLACK0 SLACK
#define TMIN 2400
#define T_LEAD 0
#define WIN_W 3
#define WIN_S 4
#define WIN_U 10
#define RFR_ON 1
#define KRE_N1 0
#define KRE_TAU1 2500
#define RFR_TAU 6400
#define VPF 5
#define KRE_GATE 0
#define KRE_GATE3 KRE_GATE
#define JFREE 16
#define TFREE 0
#define KRE_TAU 4000
#define KRE_TAU3 KRE_TAU
#define HDEPTH 3
#define LAST0 0
#define LAST1 4
#define LAST2 3
#define FSTEP 4
#define SPEC 1
#define PV1PIPE 0
#define HOPA0 6
#define HOPA1 6
#define WPROMO CU_TENSOR_MAP_L2_PROMOTION_NONE
#define KPRE 1
#define KPRE2 3
#define DELAY_G 6
#define DELAY_L 5
#define DELAY_C 3
#define DELAY_D 6
#define DELAY_E 3
#define REG_LO "40"
#define REG_HI "232"
#define SPIN_LOG 17
constexpr int SPIN_LIMIT = 1 << SPIN_LOG;

__host__ __device__ constexpr uint32_t pairL(uint32_t region, uint32_t c, uint32_t g) { return (g & 1) | ((g >> 1) << 2) | (c << 5) | (region << 6); }
__host__ __device__ constexpr uint32_t pairG(uint32_t d, uint32_t c, uint32_t i) { return (i & 1) | ((i >> 1) << 2) | (d << 4) | (c << 5) | (3u << 6); }
constexpr uint32_t RA = 0, RC = 1, RE = 2, HALF = 16384, COPY = 4096, PMASK = 0x59;
constexpr uint32_t XS = 0;
constexpr uint32_t XS2 = XS + 128 * 7680;
constexpr uint32_t XSEND = XS2 + 128 * 768;
__device__ uint4 g_s[XSEND / 16];
__device__ uint4 g_x[(4u << 20) / 16];
#define SWEEPS(k, n) do {} while (0)

constexpr uint32_t S_WD = 16 * SLOT;
constexpr uint32_t S_DUMMY = S_WD + 15360;
constexpr uint32_t S_BAR = S_DUMMY + 4096;
constexpr uint32_t S_FV = S_BAR, S_FK = S_FV + 64, S_RING = S_FK + 64, S_DBAR = S_RING + 48, S_WFULL = S_DBAR + 32, S_QRDY = S_WFULL + 88;
constexpr uint32_t S_RELK = S_QRDY + 8, S_RELV = S_RELK + 8, S_RELR = S_RELV + 8, S_RELW = S_RELR + 8, S_SCO = S_RELW + 24;
constexpr uint32_t S_ZERO = S_SCO + 8;
constexpr uint32_t S_KF = S_SCO + 24;
constexpr uint32_t S_TOK = S_KF + 8;
constexpr uint32_t S_SIDE = S_TOK + 24, S_GATE = S_SIDE + 4;
constexpr uint32_t S_STAT = S_GATE + 4, S_SWR = S_STAT + 16;
constexpr uint32_t S_XCAR = S_STAT + 32;
constexpr uint32_t S_CSQ = S_XCAR + 320;
constexpr uint32_t S_CSGU = S_CSQ + 768;
constexpr uint32_t S_RED = S_CSGU + 768;
constexpr uint32_t S_L0 = S_RED;
constexpr uint32_t S_OS = S_RED + 5120;
constexpr uint32_t S_PS = S_OS + 1536;
constexpr uint32_t PS_MAX = 512, PS_PASS = 544;
constexpr uint32_t S_QS = S_PS + 2 * PS_PASS;
constexpr uint32_t S_XB = S_QS + 1536;
constexpr uint32_t S_XA = S_XB + 768;
constexpr uint32_t S_HS = S_XA + 768;
constexpr uint32_t S_X0 = S_HS + 768;
constexpr uint32_t S_SC = S_X0 + 640;
constexpr uint32_t S_TM = S_SC + 512;
constexpr int SMEM_BYTES = S_TM + 256;
static_assert(SMEM_BYTES <= 232448 && S_STAT % 16 == 0 && S_RED % 16 == 0 && S_XB % 16 == 0 && S_HS % 16 == 0 && S_PS % 16 == 0 && S_QS % 16 == 0, "smem");
static_assert(S_SCO == S_BAR + 44 * 8 && S_RELK == S_BAR + 38 * 8, "barriers");
constexpr uint32_t ST_WQ = 3 * SLOT, ST_WG = 8 * SLOT, ST_WO = 11 * SLOT;

__device__ __forceinline__ uint32_t smem_u32(const void* p) { return (uint32_t)__cvta_generic_to_shared(p); }
__device__ __forceinline__ void mbar_init(uint32_t bar, uint32_t cnt) { asm volatile("mbarrier.init.shared::cta.b64 [%0], %1;" :: "r"(bar), "r"(cnt) : "memory"); }
__device__ __forceinline__ void mbar_expect(uint32_t bar, uint32_t bytes) { asm volatile("mbarrier.arrive.expect_tx.shared::cta.b64 _, [%0], %1;" :: "r"(bar), "r"(bytes) : "memory"); }
__device__ __forceinline__ void mbar_arrive(uint32_t bar) { asm volatile("mbarrier.arrive.shared::cta.b64 _, [%0];" :: "r"(bar) : "memory"); }
__device__ __forceinline__ bool mbar_try(uint32_t bar, uint32_t parity) {
    uint32_t ok;
    asm volatile("{\n .reg .pred p;\n mbarrier.try_wait.parity.shared::cta.b64 p, [%1], %2;\n selp.u32 %0, 1, 0, p;\n}" : "=r"(ok) : "r"(bar), "r"(parity) : "memory");
    return ok != 0;
}
__device__ __forceinline__ bool mbar_test(uint32_t bar, uint32_t parity) {
    uint32_t ok;
    asm volatile("{\n .reg .pred p;\n mbarrier.test_wait.parity.shared::cta.b64 p, [%1], %2;\n selp.u32 %0, 1, 0, p;\n}" : "=r"(ok) : "r"(bar), "r"(parity) : "memory");
    return ok != 0;
}
__device__ __forceinline__ void mbar_wait(uint32_t bar, uint32_t parity) {
    int n = 0;
    while (!mbar_try(bar, parity) && ++n < SPIN_LIMIT) {}
}
__device__ __forceinline__ unsigned long long gtime() { unsigned long long t; asm volatile("mov.u64 %0, %globaltimer;" : "=l"(t)); return t; }
__device__ __forceinline__ uint32_t gtime32() { uint32_t t; asm volatile("mov.u32 %0, %globaltimer_lo;" : "=r"(t)); return t; }
__device__ __forceinline__ void bar_main() { asm volatile("bar.sync 1, 256;" ::: "memory"); }

__device__ __forceinline__ void mma16816(float (&c)[4], uint32_t a0, uint32_t a1, uint32_t a2, uint32_t a3, uint32_t b0, uint32_t b1) {
    asm("mma.sync.aligned.m16n8k16.row.col.f32.bf16.bf16.f32 {%0,%1,%2,%3}, {%4,%5,%6,%7}, {%8,%9}, {%0,%1,%2,%3};"
        : "+f"(c[0]), "+f"(c[1]), "+f"(c[2]), "+f"(c[3]) : "r"(a0), "r"(a1), "r"(a2), "r"(a3), "r"(b0), "r"(b1));
}
__device__ __forceinline__ void mmaA(float (&c)[4], const uint32_t (&a)[4], uint32_t b0, uint32_t b1) { mma16816(c, a[0], a[1], a[2], a[3], b0, b1); }
__device__ __forceinline__ void mmaAv(float (&c)[4], const uint32_t (&a)[4], uint32_t b0, uint32_t b1) {
    asm volatile("mma.sync.aligned.m16n8k16.row.col.f32.bf16.bf16.f32 {%0,%1,%2,%3}, {%4,%5,%6,%7}, {%8,%9}, {%0,%1,%2,%3};"
        : "+f"(c[0]), "+f"(c[1]), "+f"(c[2]), "+f"(c[3]) : "r"(a[0]), "r"(a[1]), "r"(a[2]), "r"(a[3]), "r"(b0), "r"(b1) : "memory");
}
__device__ __forceinline__ void mma8(float (&c)[4], uint32_t a0, uint32_t a1, uint32_t b0) {
    asm("mma.sync.aligned.m16n8k8.row.col.f32.bf16.bf16.f32 {%0,%1,%2,%3}, {%4,%5}, {%6}, {%0,%1,%2,%3};"
        : "+f"(c[0]), "+f"(c[1]), "+f"(c[2]), "+f"(c[3]) : "r"(a0), "r"(a1), "r"(b0));
}
struct W80 { uint32_t a[2][4], c[2]; };
template <int N> __device__ __forceinline__ void mul80(float (&acc)[N][4], const W80 (&W)[N], const uint4& b, uint32_t b4) {
#pragma unroll
    for (int m = 0; m < N; m++) mmaA(acc[m], W[m].a[0], b.x, b.y);
#pragma unroll
    for (int m = 0; m < N; m++) mmaA(acc[m], W[m].a[1], b.z, b.w);
#pragma unroll
    for (int m = 0; m < N; m++) mma8(acc[m], W[m].c[0], W[m].c[1], b4);
}
__device__ __forceinline__ void ldsm2t(uint32_t (&r)[2], uint32_t addr) {
    asm volatile("ldmatrix.sync.aligned.m8n8.x2.trans.shared.b16 {%0,%1}, [%2];" : "=r"(r[0]), "=r"(r[1]) : "r"(addr) : "memory");
}
__device__ __forceinline__ void mmaV(float (&c)[4], const uint4& a, uint32_t b0, uint32_t b1) { mma16816(c, a.x, a.y, a.z, a.w, b0, b1); }
__device__ __forceinline__ void ldsm4(uint32_t (&r)[4], uint32_t addr) {
    asm volatile("ldmatrix.sync.aligned.m8n8.x4.shared.b16 {%0,%1,%2,%3}, [%4];" : "=r"(r[0]), "=r"(r[1]), "=r"(r[2]), "=r"(r[3]) : "r"(addr) : "memory");
}
__device__ __forceinline__ void ldsm4t(uint32_t (&r)[4], uint32_t addr) {
    asm volatile("ldmatrix.sync.aligned.m8n8.x4.trans.shared.b16 {%0,%1,%2,%3}, [%4];" : "=r"(r[0]), "=r"(r[1]), "=r"(r[2]), "=r"(r[3]) : "r"(addr) : "memory");
}
__device__ __forceinline__ uint32_t lds16(uint32_t a) { uint16_t v; asm volatile("ld.shared.u16 %0, [%1];" : "=h"(v) : "r"(a) : "memory"); return v; }
__device__ __forceinline__ uint32_t lds32(uint32_t a) { uint32_t v; asm volatile("ld.shared.u32 %0, [%1];" : "=r"(v) : "r"(a) : "memory"); return v; }
__device__ __forceinline__ float ldsf(uint32_t a) { return __uint_as_float(lds32(a)); }
__device__ __forceinline__ uint2 lds64(uint32_t a) { uint2 v; asm volatile("ld.shared.v2.u32 {%0,%1}, [%2];" : "=r"(v.x), "=r"(v.y) : "r"(a) : "memory"); return v; }
__device__ __forceinline__ uint4 lds128(uint32_t a) { uint4 v; asm volatile("ld.shared.v4.u32 {%0,%1,%2,%3}, [%4];" : "=r"(v.x), "=r"(v.y), "=r"(v.z), "=r"(v.w) : "r"(a) : "memory"); return v; }
__device__ __forceinline__ int ldsvol(uint32_t a) { int v; asm volatile("ld.volatile.shared.u32 %0, [%1];" : "=r"(v) : "r"(a) : "memory"); return v; }
__device__ __forceinline__ void stsvol(uint32_t a, int v) { asm volatile("st.volatile.shared.u32 [%0], %1;" :: "r"(a), "r"(v) : "memory"); }
__device__ __forceinline__ void sts_hi16(uint32_t a, float v) { asm volatile("{\n .reg .b16 lo, hi;\n mov.b32 {lo, hi}, %1;\n st.shared.u16 [%0], hi;\n}" :: "r"(a), "r"(__float_as_uint(v)) : "memory"); }
__device__ __forceinline__ void sts16(uint32_t a, uint32_t v) { asm volatile("st.shared.u16 [%0], %1;" :: "r"(a), "r"(v) : "memory"); }
__device__ __forceinline__ void sts32(uint32_t a, uint32_t v) { asm volatile("st.shared.u32 [%0], %1;" :: "r"(a), "r"(v) : "memory"); }
__device__ __forceinline__ void stsf(uint32_t a, float v) { sts32(a, __float_as_uint(v)); }
__device__ __forceinline__ void sts64(uint32_t a, uint32_t x, uint32_t y) { asm volatile("st.shared.v2.u32 [%0], {%1,%2};" :: "r"(a), "r"(x), "r"(y) : "memory"); }

__device__ __forceinline__ void sts_hi16_if(bool p, uint32_t a, float v) {
    asm volatile("{\n .reg .pred p;\n .reg .b16 lo, hi;\n setp.ne.u32 p, %2, 0;\n mov.b32 {lo, hi}, %1;\n @p st.shared.u16 [%0], hi;\n}" :: "r"(a), "r"(__float_as_uint(v)), "r"((uint32_t)p) : "memory");
}
__device__ __forceinline__ void sts32_if(bool p, uint32_t a, uint32_t v) {
    asm volatile("{\n .reg .pred p;\n setp.ne.u32 p, %2, 0;\n @p st.shared.u32 [%0], %1;\n}" :: "r"(a), "r"(v), "r"((uint32_t)p) : "memory");
}
__device__ __forceinline__ void sts64_if(bool p, uint32_t a, float x, float y) {
    asm volatile("{\n .reg .pred p;\n setp.ne.u32 p, %3, 0;\n @p st.shared.v2.f32 [%0], {%1,%2};\n}" :: "r"(a), "f"(x), "f"(y), "r"((uint32_t)p) : "memory");
}
__device__ __forceinline__ void arrive_if(bool p, uint32_t bar) {
    asm volatile("{\n .reg .pred p;\n setp.ne.u32 p, %1, 0;\n @p mbarrier.arrive.shared::cta.b64 _, [%0];\n}" :: "r"(bar), "r"((uint32_t)p) : "memory");
}
__device__ __forceinline__ void opaque(uint32_t& v) { asm volatile("" : "+r"(v)); }
__device__ __forceinline__ void keep(uint32_t& v) { asm volatile("" : "+r"(v)); }
__device__ __forceinline__ void keep(float& v) { asm volatile("" : "+f"(v)); }
template <class T> __device__ __forceinline__ void keep(T*& v) { asm volatile("" : "+l"(v)); }

__device__ __forceinline__ uint32_t ldp32(const char* p) { uint32_t v; asm volatile("ld.relaxed.gpu.global.u32 %0, [%1];" : "=r"(v) : "l"(p) : "memory"); return v; }
__device__ __forceinline__ uint2 ldp64(const char* p) {
    uint2 v; asm volatile("{\n .reg .b64 d;\n ld.relaxed.gpu.global.b64 d, [%2];\n mov.b64 {%0,%1}, d;\n}" : "=r"(v.x), "=r"(v.y) : "l"(p) : "memory"); return v;
}
__device__ __forceinline__ uint32_t tagw(float f, uint32_t par) { return (__float_as_uint(f) & ~1u) | par; }
__device__ __forceinline__ void stp32(char* p, float a, uint32_t par) { asm volatile("st.relaxed.gpu.global.u32 [%0], %1;" :: "l"(p), "r"(tagw(a, par)) : "memory"); }
__device__ __forceinline__ void stp64(char* p, float a, float b, uint32_t par) {
    asm volatile("{\n .reg .b64 d;\n mov.b64 d, {%1,%2};\n st.relaxed.gpu.global.b64 [%0], d;\n}" :: "l"(p), "r"(tagw(a, par)), "r"(tagw(b, par)) : "memory");
}
__device__ __forceinline__ void stp32_if(bool p, char* d, float a, uint32_t par) {
    asm volatile("{\n .reg .pred p;\n setp.ne.u32 p, %2, 0;\n @p st.relaxed.gpu.global.u32 [%0], %1;\n @p st.relaxed.gpu.global.u32 [%0+4096], %1;\n}" :: "l"(d), "r"(tagw(a, par)), "r"((uint32_t)p) : "memory");
}
__device__ __forceinline__ void stp64_if(bool p, char* d, uint32_t lo, uint32_t hi) {
    asm volatile("{\n .reg .pred p;\n .reg .b64 d;\n setp.ne.u32 p, %3, 0;\n mov.b64 d, {%1,%2};\n @p st.relaxed.gpu.global.b64 [%0], d;\n @p st.relaxed.gpu.global.b64 [%0+4096], d;\n}" :: "l"(d), "r"(lo), "r"(hi), "r"((uint32_t)p) : "memory");
}
__device__ __forceinline__ uint32_t chk2(uint32_t a, uint32_t b, uint32_t par) { uint32_t r; asm("lop3.b32 %0, %1, %2, %3, 0x7E;" : "=r"(r) : "r"(a), "r"(b), "r"(par)); return r; }
__device__ __forceinline__ uint32_t or3(uint32_t a, uint32_t b, uint32_t c) { uint32_t r; asm("lop3.b32 %0, %1, %2, %3, 0xFE;" : "=r"(r) : "r"(a), "r"(b), "r"(c)); return r; }
__device__ __forceinline__ uint32_t chk8(const uint32_t (&v)[8], uint32_t par) { return or3(chk2(v[0], v[1], par), chk2(v[2], v[3], par), or3(chk2(v[4], v[5], par), chk2(v[6], v[7], par), 0)); }
__device__ __forceinline__ uint32_t chk8(const uint2 (&v)[8], uint32_t par) { return or3(chk2(v[0].x, v[1].x, par), chk2(v[2].x, v[3].x, par), or3(chk2(v[4].x, v[5].x, par), chk2(v[6].x, v[7].x, par), 0)); }
__device__ __forceinline__ uint32_t chk8y(const uint2 (&v)[8], uint32_t par) { return or3(chk2(v[0].y, v[1].y, par), chk2(v[2].y, v[3].y, par), or3(chk2(v[4].y, v[5].y, par), chk2(v[6].y, v[7].y, par), 0)); }
__device__ __forceinline__ uint32_t chk4(const uint2 (&v)[4], uint32_t par) { return or3(chk2(v[0].x, v[0].y, par), chk2(v[1].x, v[1].y, par), or3(chk2(v[2].x, v[2].y, par), chk2(v[3].x, v[3].y, par), 0)); }
__device__ __forceinline__ float asf(uint32_t v) { return __uint_as_float(v); }
__device__ __forceinline__ float sum8(const uint32_t (&v)[8]) { return ((asf(v[0]) + asf(v[1])) + (asf(v[2]) + asf(v[3]))) + ((asf(v[4]) + asf(v[5])) + (asf(v[6]) + asf(v[7]))); }
__device__ __forceinline__ float sum8x(const uint2 (&v)[8]) { return ((asf(v[0].x) + asf(v[1].x)) + (asf(v[2].x) + asf(v[3].x))) + ((asf(v[4].x) + asf(v[5].x)) + (asf(v[6].x) + asf(v[7].x))); }
__device__ __forceinline__ float sum8y(const uint2 (&v)[8]) { return ((asf(v[0].y) + asf(v[1].y)) + (asf(v[2].y) + asf(v[3].y))) + ((asf(v[4].y) + asf(v[5].y)) + (asf(v[6].y) + asf(v[7].y))); }

__device__ __forceinline__ uint32_t pack2(float lo, float hi) { uint32_t r; asm("cvt.rn.bf16x2.f32 %0, %1, %2;" : "=r"(r) : "f"(hi), "f"(lo)); return r; }
__device__ __forceinline__ float bfr(float x) { return __uint_as_float(pack2(0.0f, x)); }
__device__ __forceinline__ float ex2(float x) { float r; asm("ex2.approx.ftz.f32 %0, %1;" : "=f"(r) : "f"(x)); return r; }
__device__ __forceinline__ float rcp(float x) { float r; asm("rcp.approx.ftz.f32 %0, %1;" : "=f"(r) : "f"(x)); return r; }
__device__ __forceinline__ float sqrt_(float x) { float r; asm("sqrt.approx.ftz.f32 %0, %1;" : "=f"(r) : "f"(x)); return r; }
__device__ __forceinline__ float bf_lo(uint32_t v) { return __uint_as_float(v << 16); }
__device__ __forceinline__ float bf_hi(uint32_t v) { return __uint_as_float(v & 0xffff0000u); }
__device__ __forceinline__ float sel4(int k, float a, float b, float c, float d) { return (k & 2) ? ((k & 1) ? d : c) : ((k & 1) ? b : a); }
constexpr float LOG2E = 1.4426950408889634f;
constexpr uint32_t ONES = 0x3f803f80u;

__device__ __forceinline__ void ln_stats(float sum, float sq, float& mean, float& den) {
    const float m = sum * (1.0f / 640.0f);
    const float var = fmaxf(fmaf(sq, 1.0f / 640.0f, -m * m), 0.0f);
    mean = bfr(m);
    den = bfr(sqrt_(bfr(bfr(var) + 1e-5f)));
}
__device__ __forceinline__ float sigmoidf_(float x) { return rcp(1.0f + ex2(-x * LOG2E)); }

#define TSTAMP(k) do {} while (0)
#define TST(k) do {} while (0)

#define CSTAMP(k) do {} while (0)
template <int N> __device__ __forceinline__ uint32_t lag(uint32_t sb) {
    uint32_t z = 0;
#pragma unroll
    for (int k = 0; k < N; k++) z = ldsvol(sb + S_ZERO + z);
    return z;
}
__device__ __forceinline__ void warm_mma(uint32_t& a, uint32_t& b) {
    asm volatile("mma.sync.aligned.m16n8k8.row.col.f16.f16.f16.f16 {%0,%1}, {%0,%1}, {%0}, {%0,%1};" : "+r"(a), "+r"(b) :: "memory");
}
#define KWNS2 20
#define KWNS 200
template <int STRIDE>
__device__ __forceinline__ float gather8(const char* p, uint32_t par) {
    uint32_t v[8];
    int guard = 0;
    do {
#pragma unroll
        for (int s = 0; s < 8; s++) v[s] = ldp32(p + s * STRIDE);
    } while ((chk8(v, par) & 1) && ++guard < SPIN_LIMIT);
    return sum8(v);
}
template <class F>
__device__ __forceinline__ void gather16(const char* p, uint32_t par, int k, F use) {
    uint32_t v[8], u[8];
    int guard = 0;
    bool again;
    do {
#pragma unroll
        for (int s = 0; s < 8; s++) v[s] = ldp32(p + s * 512);
#pragma unroll
        for (int s = 0; s < 8; s++) u[s] = ldp32(p + HALF + s * 512);
        const uint32_t stale = use(sum8(v) + sum8(u), ((v[0] ^ par) & 1) * 8);
        again = __any_sync(~0u, (or3(chk8(v, par), chk8(u, par), stale) & 1) != 0);
    } while (again & (++guard < SPIN_LIMIT));
    SWEEPS(k, guard - 1);
}

struct Params {
    const __nv_bfloat16 *x, *k, *v, *wr;
    __nv_bfloat16* out;
};
struct Maps { CUtensorMap k, v, wq, wo, wg, wu, wd; };

constexpr int KV_BATCH_KEYS = 32 * 4096;

__device__ __forceinline__ void tma2d(uint32_t dst, const CUtensorMap* m, int c0, int c1, uint32_t bar, uint32_t bytes, uint64_t pol) {
    asm volatile("{\n .reg .pred p;\n elect.sync _|p, 0xffffffff;\n"
                 " @p mbarrier.arrive.expect_tx.shared::cta.b64 _, [%2], %6;\n"
                 " @p cp.async.bulk.tensor.2d.shared::cluster.global.mbarrier::complete_tx::bytes.L2::cache_hint [%0], [%1, {%3, %4}], [%2], %5;\n}"
                 :: "r"(dst), "l"(m), "r"(bar), "r"(c0), "r"(c1), "l"(pol), "r"(bytes) : "memory");
}
__device__ __forceinline__ void scrap_copy(uint32_t dst, const char* src, uint32_t bar) {
    asm volatile("{\n .reg .pred p;\n elect.sync _|p, 0xffffffff;\n"
                 " @p mbarrier.arrive.expect_tx.shared::cta.b64 _, [%2], 12288;\n"
                 " @p cp.async.bulk.shared::cluster.global.mbarrier::complete_tx::bytes [%0], [%1], 4096, [%2];\n"
                 " @p cp.async.bulk.shared::cluster.global.mbarrier::complete_tx::bytes [%0], [%1+4096], 4096, [%2];\n"
                 " @p cp.async.bulk.shared::cluster.global.mbarrier::complete_tx::bytes [%0], [%1+8192], 4096, [%2];\n}"
                 :: "r"(dst), "l"(src), "r"(bar) : "memory");
}
__device__ __forceinline__ void prefetch_l2(const void* p, uint32_t bytes) {
    asm volatile("{\n .reg .pred p;\n elect.sync _|p, 0xffffffff;\n @p cp.async.bulk.prefetch.L2.global [%0], %1;\n}" :: "l"(p), "r"(bytes) : "memory");
}
__device__ __forceinline__ uint64_t pol_first() { uint64_t p; asm("createpolicy.fractional.L2::evict_first.b64 %0, 1.0;" : "=l"(p)); return p; }
__device__ __forceinline__ uint64_t pol_normal() { uint64_t p; asm("createpolicy.fractional.L2::evict_normal.b64 %0, 1.0;" : "=l"(p)); return p; }
__device__ __forceinline__ bool utest(uint32_t bar, uint32_t parity) { return __all_sync(~0u, mbar_test(bar, parity)); }
__device__ __forceinline__ void uwait(uint32_t bar, uint32_t parity) {
    int n = 0;
    while (!__all_sync(~0u, mbar_try(bar, parity)) && ++n < SPIN_LIMIT) {}
}
template <int A, int B, int CNT> __device__ __forceinline__ void init_bars(uint32_t sb) {
#pragma unroll 1
    for (int k = A; k < B; k++)
        asm volatile("{\n .reg .pred p;\n elect.sync _|p, 0xffffffff;\n @p mbarrier.init.shared::cta.b64 [%0], %1;\n}" :: "r"(sb + S_BAR + 8 * k), "n"(CNT) : "memory");
}
__device__ __forceinline__ int first_key() { return (blockIdx.x >> 2) * 4096 + 3072 + (blockIdx.x & 3) * 256; }
__device__ __forceinline__ void load_tile(const CUtensorMap* m, uint32_t dst, uint32_t bar, uint32_t bytes, int key, uint64_t pol) { tma2d(dst, m, 0, 3 * key, bar, bytes, pol); }
__device__ __forceinline__ const char* unit_ptr(const Params& P, int n) {
    return (const char*)((n & 16) ? P.v : P.k) + (size_t)(first_key() + (n >> 5) * KV_BATCH_KEYS + (n & 15) * 16) * 384;
}
#define LSTAMP(k) do {} while (0)

__device__ __forceinline__ uint32_t k_place(uint32_t b, uint32_t s) { return s + 3 + 5 * (b & 1); }
__device__ __forceinline__ uint32_t v_place(uint32_t b, uint32_t s) { return s < 3 ? s : s + 8 - 8 * (b & 1); }
__device__ __forceinline__ void k_load(const Maps& M, uint32_t dst, uint32_t bar, int key8, uint64_t pol) {
    asm volatile("{\n .reg .pred p;\n elect.sync _|p, 0xffffffff;\n"
                 " @p mbarrier.arrive.expect_tx.shared::cta.b64 _, [%2], 6144;\n"
                 " @p cp.async.bulk.tensor.4d.shared::cluster.global.mbarrier::complete_tx::bytes.L2::cache_hint [%0], [%1, {0, 0, 0, %3}], [%2], %4;\n}"
                 :: "r"(dst), "l"(&M.k), "r"(bar), "r"(key8), "l"(pol) : "memory");
}
__device__ __forceinline__ int unit_key8(uint32_t n) { return first_key() / 8 + (n >> 4) * (KV_BATCH_KEYS / 8) + 2 * (n & 15); }
__device__ __forceinline__ uint32_t ring_pos(uint32_t n) { const uint32_t u = (n & 15) + 2; return u - (u >= 12 ? 12 : u >= 6 ? 6 : 0); }
__device__ __forceinline__ void ring_load(const Maps& M, uint32_t sb, uint32_t n, uint32_t pos) {
    k_load(M, sb + pos * UNIT, sb + S_RING + 8 * pos, unit_key8(n), pol_normal());
}
__device__ __forceinline__ uint32_t token(bool p, uint32_t a, uint32_t n) {
    uint32_t v;
    asm volatile("{\n .reg .pred p;\n setp.ne.u32 p, %2, 0;\n mov.u32 %0, 0;\n @p atom.shared.exch.b32 %0, [%1], %3;\n}" : "=r"(v) : "r"(a), "r"((uint32_t)p), "r"(n) : "memory");
    return v;
}
__device__ __forceinline__ void place_load(const Maps& M, uint32_t sb, uint32_t n) {
    k_load(M, sb + k_place(n >> 4, 0) * SLOT + (n & 15) * UNIT, sb + S_FK + 4 * (n & 14), unit_key8(n), pol_first());
}
__device__ __forceinline__ void v_load(const Maps& M, uint32_t sb, uint32_t b, uint32_t s) {
    load_tile(&M.v, sb + v_place(b, s) * SLOT, sb + S_FV + 8 * s, SLOT, first_key() + b * KV_BATCH_KEYS + 32 * s, pol_first());
}
__device__ __forceinline__ bool due(uint32_t t) { return __all_sync(~0u, (int)(gtime32() * 16 - t) >= 0); }
__device__ __forceinline__ bool reached(uint32_t a, int v) { return __all_sync(~0u, ldsvol(a) >= v); }

__device__ __forceinline__ void stream_warp(const Params& P, const Maps& M, uint32_t sb, uint32_t lane) {
    const uint64_t pol = pol_first();
    const int bid = blockIdx.x, g = bid >> 3, i = bid & 7;
    const uint32_t wf = sb + S_WFULL;
    if (PF0 > 0) prefetch_l2(unit_ptr(P, 0), PF0 * UNIT);
    uint32_t tn = __shfl_sync(~0u, gtime32(), 0) * 16 - T_LEAD;
    auto pace = [&](uint32_t dt) {
        int k = 0;
        uint32_t now;
        do now = __shfl_sync(~0u, gtime32(), 0) * 16; while ((int)(now - tn) < 0 && ++k < SPIN_LIMIT);
        if ((int)(now - tn) > SLACK0) tn = now - SLACK0;
        tn += dt;
    };
#pragma unroll
    for (int k = 0; k < 10; k++) {
        if (k < 2) {
            if (k == 0) init_bars<26, 27, 1>(sb); else init_bars<27, 37, 1>(sb);
            asm volatile("fence.mbarrier_init.release.cluster;" ::: "memory");
            if (k == 1) { asm volatile("bar.arrive 2, %0;" :: "n"(NTHR) : "memory"); asm volatile("bar.sync 3, 128;" ::: "memory"); }
        }
        if (k >= WIN_W) uwait(wf + 8 * (k - WIN_W), 0);
        pace(TAUW * 5 / 2);
        if (k < 4) tma2d(sb + ST_WQ + 15360 * k, &M.wq, 384 * g + 192 * (k >> 1), 80 * i + 40 * (k & 1), wf + 8 * k, 15360, pol);
        else if (k < 6) tma2d(sb + ST_WG + 15360 * (k - 4), k == 4 ? &M.wg : &M.wu, 96 * g, 80 * i, wf + 8 * k, 15360, pol);
        else tma2d(sb + ST_WO + 15360 * (k - 6), &M.wo, 80 * i, 384 * g + 96 * (k - 6), wf + 8 * k, 15360, pol);
    }
#pragma unroll 1
    for (int n = 0; n < 16; n++) {
        if (n == 0 || n == 5 || n == 11) uwait(sb + S_RELW + (n == 0 ? 0 : n == 5 ? 8 : 16), 0);
        uwait(n < WIN_S ? wf + 8 * (10 - WIN_S + n) : sb + S_FV + 8 * ((n - WIN_S) ^ 8), 0);
        pace(max(min(2 * n + 2 - PF0, 2), 0) * TAU0);
        if (n < 8) { place_load(M, sb, 2 * n); place_load(M, sb, 2 * n + 1); }
        else v_load(M, sb, 0, n - 8);
        if (n == 7) { pace(TAUW * 5 / 2); tma2d(sb + S_WD, &M.wd, 80 * i, 96 * g, wf + 80, 15360, pol); }
    }
    int nd = 0;
    uint32_t q[4];
#pragma unroll
    for (int r = 0; r < 4; r++) q[r] = sb + S_FV + 8 * (7 - r);
    uint32_t td = tn;
#pragma unroll 1
    for (int b = 1; b < 4; b++) {
        const uint32_t pk = (b - 1) & 1;
        uint32_t fr = 0, pend = 0;
#pragma unroll 1
        for (int j = 0; j < 17; j++) {
            const int n = 16 * b + 2 * j;
            uint32_t now, st;
            int k = 0;
            while (true) {
                now = __shfl_sync(~0u, gtime32(), 0) * 16;
                const uint2 c = lds64(sb + S_KF);
                const uint32_t rel = mbar_test(j < 8 ? sb + S_RELR : sb + S_RELK, pk);
                const int used = min((int)c.x + 1, (int)c.y) - 16 * b;
                static_assert(WIN_U <= 12, "a ring position has at most one token of the timetable");
                const uint32_t win = mbar_test(q[WIN_S - 1] & ~1u, q[WIN_S - 1] & 1) & (used >= min(2 * j + 2 - WIN_U, 16));
                st = __reduce_and_sync(~0u, (rel ? (j < 8 ? 0x700 : 0xf8) : 0) + (used >= 12) + (used >= 14) * 2 + (used >= 16) * 4 + win * 0x800);
                fr |= st & 0x7ff;
#pragma unroll 1
                while (pend & fr) {
                    const uint32_t r = __ffs(pend & fr) - 1;
                    if (r < 8) v_load(M, sb, b, r);
                    else { const uint32_t m = 16 * b + 2 * r - 16; ring_load(M, sb, m, ring_pos(m)); ring_load(M, sb, m + 1, ring_pos(m) + 1); }
                    pend ^= 1u << r;
                }
                if ((j == 16 ? !pend : (st & 0x800) && (int)(now - td) >= 0) || ++k >= SPIN_LIMIT) break;
            }
            if (j == 16) break;
            if ((int)(now - tn) > SLACK) tn = now - SLACK;
            tn += 2 * TAU;
            td = (int)(tn - now) > 2 * TMIN ? tn : now + 2 * TMIN;
            if (b == 3 && j >= JFREE) td = now + TFREE;
            q[3] = q[2]; q[2] = q[1]; q[1] = q[0]; q[0] = sb + S_QRDY;
            const int s = j ^ 8;
            const char* src = unit_ptr(P, 32 * b + 2 * j);
            uint32_t mine = 0;
            if (j < 8) {
                const uint32_t pos = ring_pos(n);
                mine = j < 3 ? ((fr >> s) & 1) * 3 : __ballot_sync(~0u, token(lane < 2, sb + S_TOK + 4 * (pos + lane), n + lane) == n + lane);
                if (mine & 1) ring_load(M, sb, n, pos); else prefetch_l2(src, UNIT);
                if (mine & 2) ring_load(M, sb, n + 1, pos + 1); else prefetch_l2(src + UNIT, UNIT);
                if (!mine) pend |= (1u << s) & 0x700;
            } else if ((fr >> s) & 1) { v_load(M, sb, b, s); q[0] = (sb + S_FV + 8 * s) | (pk ^ 1); }
            else {
                pend |= 1u << s;
                if (s < 3 || s >= VPF) prefetch_l2(src, SLOT);
                else {
                    scrap_copy(sb + S_DUMMY, src, sb + S_DBAR + 8 * (nd & 3));
                    q[0] = (sb + S_DBAR + 8 * (nd & 3)) | ((nd >> 2) & 1);
                    nd++;
                }
            }
        }
    }
#pragma unroll 1
    for (int m = max(nd - 4, 0); m < nd; m++) uwait(sb + S_DBAR + 8 * (m & 3), (m >> 2) & 1);
}

__device__ __forceinline__ float scaled(float s) { return bfr(bfr(s) * 0.07216878364870322f); }
__device__ __forceinline__ void probs(float s, uint32_t ps, uint32_t src, uint32_t ln) {
    const uint32_t q8 = ln >> 2, t4 = ln & 3;
    int key = __float_as_int(s);
    key ^= (key >> 31) & 0x7fffffff;
    key = __reduce_max_sync(~0u, key);
    key ^= (key >> 31) & 0x7fffffff;
    const float ml = __int_as_float(key) * LOG2E;
    sts16(ps + 64 * src + (q8 >> 1) * 16 + t4 * 4 + (q8 & 1) * 2, pack2(ex2(fmaf(s, LOG2E, -ml)), 0.f));
    stsf(ps + PS_MAX + 4 * src, ml);
}
template <int H> __device__ __forceinline__ uint32_t b_pos(uint32_t e) { const uint32_t h = e >= H, k = e - H * h; return h * 192 + (k & 6) * 24 + (k >> 3) * 4 + (k & 1) * 2; }
__device__ __forceinline__ uint32_t a_pos(uint32_t e) { const uint32_t h = e >= 40, k = e - 40 * h; return (k & 6) * 24 + (k >> 3) * 8 + h * 4 + (k & 1) * 2; }
__device__ __forceinline__ uint32_t q_pos(uint32_t d) { const uint32_t s = 3 * ((d >> 4) & 3) + (d >> 6); return s * 32 + (d & 6) * 4 + ((d >> 3) & 1) * 4 + (d & 1) * 2; }
__device__ __forceinline__ uint32_t k_off(uint32_t ln) { return (ln & 8) * 384 + (ln & 7) * 128 + (((ln & 7) ^ (ln >> 4)) << 4); }

#define HSTAMP(k) do {} while (0)
__device__ __forceinline__ void score_warp(const Maps& M, uint32_t sb, uint32_t h, uint32_t ln) {
    uwait(sb + S_QRDY, 0);
    const uint32_t q8 = ln >> 2;
    const uint32_t k0 = k_off(ln);
    const uint64_t pol = pol_normal();
    uint32_t pos = h + 6, bar = sb + S_FK, par = 0, phases = 0;
    uint2 q = lds64(sb + S_QS + 8 * ln), qh = lds64(sb + S_QS + 8 * ln + 256);
#pragma unroll 1
    for (uint32_t n = h; n < 64; n += 2) {
        HSTAMP(0);
        const uint32_t ua = sb + pos * UNIT;
        if (!__all_sync(~0u, mbar_try(bar, par))) uwait(bar, par);
        HSTAMP(1);
        float acc[2][4] = {};
        uint32_t mine = 0;
#pragma unroll
        for (int s = 0; s < 12; s++) {
            uint32_t kf[4];
            ldsm4(kf, (k0 ^ (32 * (s / 3))) + (ua + 1024 * (s % 3)));
            if (s == 11) {
                __syncwarp();
                mine = token(ln == 0 && n >= 16 && (n & 15) < 10, sb + S_TOK + 4 * pos, n + 6);
                stsvol(sb + S_KF + 4 * h, n + 1);
            }
            const bool m = q8 == (s & 7);
            mmaA(acc[s & 1], kf, m ? (s < 8 ? q.x : qh.x) : 0u, m ? (s < 8 ? q.y : qh.y) : 0u);
        }
        const int key8 = unit_key8(n) + 12;
        const uint32_t bar0 = bar;
        const bool last = (n & 14) == 14;
        pos = last ? h + 2 : n >= 16 && pos >= 4 ? h : pos + 2;
        bar = n >= 14 ? sb + S_RING + 8 * pos : bar + 8;
        par = n >= 14 ? (phases >> pos) & 1 : 0;
        phases ^= n >= 14 ? 1u << pos : 0;
        const float w0 = (acc[0][0] + acc[0][1]) + (acc[1][0] + acc[1][1]), w1 = (acc[0][2] + acc[0][3]) + (acc[1][2] + acc[1][3]);
        HSTAMP(2);
        if (__any_sync(~0u, mine == n + 6)) k_load(M, ua, bar0, key8, pol);
        HSTAMP(3);
        float s = ((ln & 1) ? w1 : w0) + __shfl_xor_sync(~0u, (ln & 1) ? w0 : w1, 1);
        s += __shfl_xor_sync(~0u, s, 2);
        sts_hi16(sb + S_SC + (((n & 12) >> 1) + h) * 64 + (n & 2) * 2 + (ln & 29) * 2, scaled(s));
        if (last) {
            __syncwarp();
            arrive_if(ln == 0, sb + S_SCO);
            q = lds64(sb + S_QS + 24 * ((n + 2) & 48) + 8 * ln); qh = lds64(sb + S_QS + 24 * ((n + 2) & 48) + 8 * ln + 256);
        }
    }
}

__device__ __forceinline__ char* xwindow() { return reinterpret_cast<char*>((reinterpret_cast<uintptr_t>(g_x) + (2u << 20) - 1) & ~(uintptr_t)((2u << 20) - 1)); }

struct XPtr {
    uint32_t lo, hi;
    __device__ __forceinline__ explicit XPtr(char* p) : lo((uint32_t)(uintptr_t)p), hi((uint32_t)((uintptr_t)p >> 32)) {}
    __device__ __forceinline__ XPtr(uint32_t l, uint32_t h) : lo(l), hi(h) {}
    __device__ __forceinline__ XPtr operator+(uint32_t o) const { return XPtr(lo + o, hi); }
    __device__ __forceinline__ operator char*() const { uint64_t p; asm("mov.b64 %0, {%1, %2};" : "=l"(p) : "r"(lo), "r"(hi)); return (char*)p; }
};
__device__ __forceinline__ void keep(XPtr& v) { keep(v.lo); }

__device__ __forceinline__ void side_warp(uint32_t sb) {
    const uint32_t bid = blockIdx.x, g = bid >> 3, i = bid & 7, P = pairG(0, 0, i);
    char* p = xwindow() + P * 8192 + (g >> 3) * HALF + (g & 7) * 512 + 448;
    uint32_t best[2] = {~0u, ~0u};
    asm volatile("st.relaxed.gpu.global.b32 [%0], 1;" :: "l"(p) : "memory");
    asm volatile("st.relaxed.gpu.global.b32 [%0], 1;" :: "l"(p + COPY) : "memory");
#pragma unroll 1
    for (int r = 0; r < 64; r++) {
        if (r >= 4 && !(r & 1) && min(best[0], best[1]) < 380 && max(best[0], best[1]) > min(best[0], best[1]) + 80) break;
        uint32_t c0, c1, v;
        asm volatile("mov.u32 %0, %clock;" : "=r"(c0) :: "memory");
        asm volatile("atom.relaxed.gpu.global.exch.b32 %0, [%1], 0;" : "=r"(v) : "l"(p + (r & 1) * COPY) : "memory");
        asm volatile("{\n .reg .pred q;\n setp.eq.u32 q, %1, 0x13579bdf;\n mov.u32 %0, 0;\n @!q mov.u32 %0, %clock;\n}" : "=r"(c1) : "r"(v) : "memory");
        if (r & 1) best[1] = min(best[1], c1 - c0); else best[0] = min(best[0], c1 - c0);
    }
    stsvol(sb + S_SIDE, 1 + ((best[1] < best[0]) ^ (__popc(P & PMASK) & 1)));
}

__device__ __forceinline__ void hop_a(const char* src, uint32_t par, uint32_t dst, bool st, int k) {
    uint2 v[4];
    float e[4], rl;
    int guard = 0;
    bool again;
    do {
#pragma unroll
        for (int s = 0; s < 4; s++) v[s] = ldp64(src + s * 1024);
        again = __any_sync(~0u, (chk4(v, par) & 1) != 0);
        const int M = max(max((int)v[0].x, (int)v[1].x), max((int)v[2].x, (int)v[3].x)) - 254;
#pragma unroll
        for (int s = 0; s < 4; s++) e[s] = __int_as_float(max((int)v[s].x - M, 0) << 22);
        rl = rcp(fmaf(e[0], asf(v[0].y), e[1] * asf(v[1].y)) + fmaf(e[2], asf(v[2].y), e[3] * asf(v[3].y)));
#pragma unroll
        for (int s = 0; s < 4; s++) e[s] = __shfl_sync(~0u, e[s], 24);
        keep(rl);
    } while (again & (++guard < SPIN_LIMIT));
    rl = __shfl_sync(~0u, rl, 24);
    const float o0 = fmaf(e[0], asf(v[0].x), e[1] * asf(v[1].x)) + fmaf(e[2], asf(v[2].x), e[3] * asf(v[3].x));
    const float o1 = fmaf(e[0], asf(v[0].y), e[1] * asf(v[1].y)) + fmaf(e[2], asf(v[2].y), e[3] * asf(v[3].y));
    sts32_if(st, dst, pack2(o0 * rl, o1 * rl));
    SWEEPS(k, guard - 1);
    __syncwarp();
}

__global__ void __launch_bounds__(NTHR, 1)
fused_kernel(const Params P, const __grid_constant__ Maps M) {
    extern __shared__ __align__(1024) unsigned char smem[];
    const uint32_t sb = smem_u32(smem);
    const int tid = threadIdx.x, bid = blockIdx.x;
    const int w = __shfl_sync(~0u, tid >> 5, 0), lane = tid & 31;

    if (w >= 8) {
        asm volatile("setmaxnreg.dec.sync.aligned.u32 " REG_LO ";");
        if (w == 8) {
            stream_warp(P, M, sb, lane);
        } else {
            if (PFMAP && w == 11 && lane < 7) asm volatile("prefetch.tensormap [%0];" :: "l"(&M.k + lane) : "memory");
            if (w == 9) { init_bars<0, 8, 1>(sb); init_bars<16, 22, 1>(sb); }
            else if (w == 10) { init_bars<8, 16, 2>(sb); init_bars<22, 26, 1>(sb); }
            else { init_bars<37, 38, 1>(sb); init_bars<38, 40, 8>(sb); init_bars<40, 41, 1>(sb); init_bars<41, 44, 8>(sb); init_bars<44, 45, 2>(sb); if (lane < 18) stsvol(sb + S_ZERO + 4 * lane, 0); }
            asm volatile("fence.mbarrier_init.release.cluster;" ::: "memory");
            asm volatile("bar.arrive 3, 128;" ::: "memory");
            asm volatile("bar.sync 2, %0;" :: "n"(NTHR) : "memory");
            if (w < 11) score_warp(M, sb, w - 9, lane);
            else {
                if (lane == 0) side_warp(sb);
                __syncwarp();
                uint32_t a = 0, b = 0;
                int k = 0;
                while (ldsvol(sb + S_GATE) == 0 && ++k < SPIN_LIMIT) { warm_mma(a, b); __nanosleep(KWNS); }
                uint4* d = reinterpret_cast<uint4*>(reinterpret_cast<char*>(g_s) + XS + bid * 7680) + lane;
                const uint4 z = make_uint4(0, 0, 0, 0);
#pragma unroll 1
                for (int u = 0; u < 15; u++) d[32 * u] = z;
                d = reinterpret_cast<uint4*>(reinterpret_cast<char*>(g_s) + XS2 + bid * 768) + lane;
                d[0] = z;
                if (lane < 16) d[32] = z;
                const uint32_t side = (ldsvol(sb + S_SIDE) & 1) ^ 1, g = bid >> 3, i = bid & 7;
                const XPtr gx(xwindow());
                auto nearp = [&](uint32_t pr) { return gx.lo + pr * 8192 + ((side ^ __popc(pr & PMASK)) & 1) * COPY; };
                const uint32_t own = (i >> 2) * HALF + (i & 3) * 1024 + (lane & 7) * 128;
                const uint32_t pAC = nearp(pairL(lane >> 4, (lane >> 3) & 1, g)) + own, pE = nearp(pairL(RE, (lane >> 3) & 1, g)) + own;
                const uint32_t pG = nearp(pairG((lane >> 2) & 1, (lane >> 3) & 1, i)) + min(lane & 3, 2) * 128;
                uint32_t tr = 0, tk = 0, ph = 0, src = g + (lane >> 4), seen = 0, n = 16;
                bool go = false, first = true;
                while (n < 64 && ++k < SPIN_LIMIT) {
                    const uint32_t now = __shfl_sync(~0u, gtime32(), 0) * 16;
                    if (!go && utest(sb + S_RELV, ((n >> 4) & 1) ^ 1) && utest(sb + S_FV + 8 * (n >= 48 ? KRE_GATE3 : KRE_GATE), (n >> 4) & 1)) { go = true; tk = now; }
                    if (go && (int)(now - tk) >= 0) {
                        place_load(M, sb, n);
                        tk += n >= 48 ? KRE_TAU3 : (n & 15) < KRE_N1 ? KRE_TAU1 : KRE_TAU;
                        n++;
                        go = (n & 15) != 0;
                        if (!go) LSTAMP(63 + (n >> 3));
                    } else if (first || (int)(now - tr) >= 0) {
                        first = false;
                        tr = now + RFR_TAU;
                        b |= seen & a;
                        warm_mma(a, b);
                        if (RFR_ON) seen = ldp32(XPtr(ph == 0 ? pAC : ph == 1 && lane < 16 ? pE : pG + (src & 8) * (HALF / 8) + (src & 7) * 512, gx.hi));
                        src += ph == 0 ? 0 : ph == 1 ? 2 : 1;
                        ph = ph == 2 ? 0 : ph + 1;
                    } else __nanosleep(KWNS2);
                }
                while (ldsvol(sb + S_GATE) < 6 && ++k < SPIN_LIMIT) { warm_mma(a, b); __nanosleep(KWNS); }
                if (a | b) stsvol(sb + S_GATE, 6);
            }
        }
        return;
    }
    asm volatile("setmaxnreg.inc.sync.aligned.u32 " REG_HI ";");

    const int g = bid >> 3, i = bid & 7;
    const int g8 = lane >> 2, t = lane & 3;
    char* const gs = reinterpret_cast<char*>(g_s);
    const XPtr gx(xwindow());

    auto zero_words = [&] {
        const uint4 z = make_uint4(0, 0, 0, 0);
        const uint32_t c = (tid >> 6) & 1, cp = (tid >> 7) * COPY, k = (tid & 63) * 16;
        *reinterpret_cast<uint4*>((char*)(gx + pairL(RA, c, g) * 8192 + (i >> 2) * HALF + (i & 3) * 1024 + cp + k)) = z;
        *reinterpret_cast<uint4*>((char*)(gx + pairL(RC, c, g) * 8192 + (i >> 2) * HALF + (i & 3) * 1024 + cp + k)) = z;
        *reinterpret_cast<uint4*>((char*)(gx + pairL(RE, c, g) * 8192 + (i >> 2) * HALF + (i & 3) * 1024 + cp + k)) = z;
        if ((tid & 31) < 24) *reinterpret_cast<uint4*>((char*)(gx + pairG((tid >> 5) & 1, c, i) * 8192 + (g >> 3) * HALF + (g & 7) * 512 + cp + (tid & 31) * 16)) = z;
    };
    if (ZPOS == 0) zero_words();
    W80 Wq[6], Wgu[3];
    uint32_t Wo[5][3][4];
    if (w < 4) {
        const uint32_t* xp = reinterpret_cast<const uint32_t*>(P.x + 640 * w);
        float sum = 0.f, sq = 0.f;
#pragma unroll
        for (int u = 0; u < 10; u++) { uint32_t v = xp[lane + 32 * u]; float a = bf_lo(v), b = bf_hi(v); sum += a + b; sq += a * a + b * b; }
#pragma unroll
        for (int o = 16; o > 0; o >>= 1) { sum += __shfl_xor_sync(~0u, sum, o); sq += __shfl_xor_sync(~0u, sq, o); }
        float mean, den; ln_stats(sum, sq, mean, den);
        if (lane < 20) {
            const uint2 v = reinterpret_cast<const uint2*>(P.x + 640 * w + 80 * i)[lane];
            sts64(sb + S_X0 + 160 * w + 8 * lane, v.x, v.y);
            sts32(sb + S_L0 + 384 * w + b_pos<40>(4 * lane), pack2(__fdiv_rn(bfr(bf_lo(v.x) - mean), den), __fdiv_rn(bfr(bf_hi(v.x) - mean), den)));
            sts32(sb + S_L0 + 384 * w + b_pos<40>(4 * lane + 2), pack2(__fdiv_rn(bfr(bf_lo(v.y) - mean), den), __fdiv_rn(bfr(bf_hi(v.y) - mean), den)));
        }
    } else if (w == 4) {
        const uint32_t* xp = reinterpret_cast<const uint32_t*>(P.wr);
        float sum = 0.f;
#pragma unroll
        for (int u = 0; u < 10; u++) { uint32_t v = xp[lane + 32 * u]; sum += bf_lo(v) + bf_hi(v); }
#pragma unroll
        for (int o = 16; o > 0; o >>= 1) sum += __shfl_xor_sync(~0u, sum, o);
        if (lane == 0) stsf(sb + S_SWR, sum);
        if (lane < 20) {
            const uint2 v = reinterpret_cast<const uint2*>(P.wr + 80 * i)[lane];
            sts32(sb + S_XA + 576 + a_pos(4 * lane), v.x); sts32(sb + S_XA + 576 + a_pos(4 * lane + 2), v.y);
            sts32(sb + S_XA + a_pos(4 * lane), ONES); sts32(sb + S_XA + a_pos(4 * lane + 2), ONES);
        }
    }
    asm volatile("bar.sync 2, %0;" :: "n"(NTHR) : "memory");
    auto frag = [](uint32_t (&a)[4], uint32_t p, int pitch) {
        const uint32_t r0 = lds32(p), r1 = lds32(p + pitch), r2 = lds32(p + 2 * pitch), r3 = lds32(p + 3 * pitch);
        a[0] = __byte_perm(r0, r1, 0x5410); a[1] = __byte_perm(r0, r1, 0x7632);
        a[2] = __byte_perm(r2, r3, 0x5410); a[3] = __byte_perm(r2, r3, 0x7632);
    };
    mbar_wait(sb + S_WFULL + 16 * (w >> 2), 0);
    mbar_wait(sb + S_WFULL + 16 * (w >> 2) + 8, 0);
    {
        const uint32_t p = sb + ST_WQ + (w >> 2) * 30720 + (2 * t) * 384 + (48 * (w & 3) + 2 * g8) * 2;
#pragma unroll
        for (int r = 0; r < 10; r++)
#pragma unroll
            for (int m = 0; m < 3; m++) {
                const uint32_t q = p + ((r & 1) * 40 + (r >> 1) * 8) * 384 + 32 * m, r0 = lds32(q), r1 = lds32(q + 384);
                (r < 8 ? Wq[2 * m].a[(r >> 2) & 1][r & 3] : Wq[2 * m].c[r & 1]) = __byte_perm(r0, r1, 0x5410);
                (r < 8 ? Wq[2 * m + 1].a[(r >> 2) & 1][r & 3] : Wq[2 * m + 1].c[r & 1]) = __byte_perm(r0, r1, 0x7632);
            }
    }
    __syncwarp();
    if (lane == 0) mbar_arrive(sb + S_RELW);
    TSTAMP(1);
    {
        char* d = gs + XS + bid * 7680 + (w >> 2) * 3840 + (48 * (w & 3) + 2 * g8) * 4;
        float acc[6][4] = {};
        mul80(acc, Wq, lds128(sb + S_L0 + 48 * lane), lds32(sb + S_L0 + 48 * lane + 16));
#pragma unroll
        for (int m = 0; m < 6; m += 2) stp64(d + t * 768 + 32 * m, acc[m][0] + acc[m][3], acc[m + 1][0] + acc[m + 1][3], 1);
        float sum[6][4] = {};
        mul80(sum, Wq, make_uint4(ONES, ONES, ONES, ONES), ONES);
        if (t == 0)
#pragma unroll
            for (int m = 0; m < 6; m += 2) stp64(d + 4 * 768 + 32 * m, sum[m][0] + sum[m][3], sum[m + 1][0] + sum[m + 1][3], 1);
    }
    mbar_wait(sb + S_WFULL + 32, 0);
    mbar_wait(sb + S_WFULL + 40, 0);
    const uint32_t oct = 3 * (w >> 1) + (w & 1), oct2 = 3 * (w >> 1) + 2;
    {
        const uint32_t p = sb + ST_WG + ((lane & 7) + 40 * ((lane >> 3) & 1) + 8 * (lane >> 4)) * 192;
#pragma unroll
        for (int T = 0; T < 3; T++) {
            const uint32_t q = p + (T < 2 ? T * 15360 + 16 * oct : (w & 1) * 15360 + 16 * oct2);
            ldsm4t(Wgu[T].a[0], q); ldsm4t(Wgu[T].a[1], q + 16 * 192); ldsm2t(Wgu[T].c, q + 32 * 192);
        }
        float sum[3][4] = {};
        mul80(sum, Wgu, make_uint4(ONES, ONES, ONES, ONES), ONES);
        if (t < 3) stp32(gs + XS2 + bid * 768 + (t < 2 ? 64 * oct + 4 * t : 64 * oct2 + 4 * (w & 1)) + 8 * g8,
                         sel4(t, sum[0][0] + sum[0][3], sum[1][0] + sum[1][3], sum[2][0] + sum[2][3], 0.f), 1);
    }
    __syncwarp();
    if (lane == 0) mbar_arrive(sb + S_RELW + 8);
    const char* srcS = gs + XS + g * 8 * 7680 + (i >> 2) * 3840 + min(tid, 191) * 4;
    uint32_t vs[5][8];
#pragma unroll
    for (int b = 0; b < 5; b++)
#pragma unroll
        for (int s = 0; s < 8; s++) vs[b][s] = LOOK1 ? ldp32(srcS + b * 768 + s * 7680) : 0;
    uint32_t cs2[8];
#pragma unroll
    for (int s = 0; s < 8; s++) cs2[s] = LOOK2 ? ldp32(gs + XS2 + (g * 8 + s) * 768 + min(tid, 191) * 4) : 0;
    __syncwarp();
    mbar_wait(sb + S_WFULL + 48 + 8 * (w >> 1), 0);
    {
        const uint32_t po = sb + ST_WO + (48 * w + 12 * t) * 160 + 4 * g8;
#pragma unroll
        for (int s = 0; s < 3; s++)
#pragma unroll
            for (int m = 0; m < 5; m++) frag(Wo[m][s], po + 4 * s * 160 + 32 * m, 160);
    }
    __syncwarp();
    if (lane == 0) mbar_arrive(sb + S_RELW + 16);
    if (ZPOS == 1) zero_words();
    if (tid < 192) {
        int guard = 0;
        while (((or3(chk8(vs[0], 1), chk8(vs[1], 1), chk8(vs[2], 1)) | chk8(vs[3], 1) | chk8(vs[4], 1)) & 1) && ++guard < SPIN_LIMIT) {
#pragma unroll
            for (int b = 0; b < 5; b++)
#pragma unroll
                for (int s = 0; s < 8; s++) vs[b][s] = ldp32(srcS + b * 768 + s * 7680);
        }
        const uint32_t qpos = sb + S_QS + q_pos(tid);
#pragma unroll
        for (int b = 0; b < 4; b++) {
            sts_hi16(qpos + 384 * b, bfr(sum8(vs[b])));
        }
        stsf(sb + S_CSQ + 4 * tid, sum8(vs[4]));
    }
    if (tid < 192) stsf(sb + S_CSGU + 4 * tid, (chk8(cs2, 1) & 1) ? gather8<768>(gs + XS2 + g * 8 * 768 + tid * 4, 1) : sum8(cs2));
    __syncwarp();
    bar_main();
    arrive_if(tid == 0, sb + S_QRDY);
    if (ZPOS == 2) zero_words();
    TSTAMP(2);

    uint32_t side;
    { int k = 0; while ((side = ldsvol(sb + S_SIDE)) == 0 && ++k < SPIN_LIMIT) {} }
    const uint32_t td = __shfl_sync(~0u, tid, lane);
    const uint32_t wp = __shfl_sync(~0u, tid >> 5, 0);
    const uint32_t cc = wp >= 3;
    auto uni = [](uint32_t v) { return __shfl_sync(~0u, v, 0); };
    auto pin = [&](uint32_t v) { return __shfl_sync(~0u, v, td); };
    auto nearp = [&](uint32_t P) { return gx.lo + P * 8192 + ((side ^ 1 ^ __popc(P & PMASK)) & 1) * COPY; };
    constexpr uint32_t COL = 32 * 8192;
    const uint32_t ownL = gx.lo + (i >> 2) * HALF + (i & 3) * 1024, ownG = gx.lo + (g >> 3) * HALF + (g & 7) * 512;
    const uint32_t uPubA = uni(ownL + pairL(RA, 0, g) * 8192 + (wp >> 1) * 256 + (wp & 1) * 96), uPolA = uni(nearp(pairL(RA, 0, g)) + (wp >> 2) * HALF + (wp & 3) * 256);
    const uint32_t uPubB = uni(ownG + pairG(0, cc, i) * 8192), uPolB = uni(nearp(pairG(0, cc, i)));
    const uint32_t uPubC = uni(ownL + pairL(RC, 0, g) * 8192), uPolC = uni(nearp(pairL(RC, wp < 6 ? cc : wp - 6, g)));
    const uint32_t uPubD = uni(ownG + pairG(1, 0, i) * 8192 + (wp < 7 ? 32 * wp : 256)), uPolD = uni(nearp(pairG(1, cc, i)));
    const uint32_t uPubE = uni(ownL + pairL(RE, 0, g) * 8192), uPolE = uni(nearp(pairL(RE, i >> 2, g)));
    const uint32_t uOS = uni(sb + S_OS + 192 * wp), uCol = uni(sb + 64 * cc);
    auto xp = [&](uint32_t lo) { return (char*)XPtr(lo, gx.hi); };
#define IDS() uint32_t z_ = td; opaque(z_); const uint32_t ln = z_ & 31, q8 = ln >> 2, t4 = z_ & 3, n96 = z_ - 96 * cc, n80 = min(n96, 79u); (void)q8; (void)t4; (void)n80; (void)ln

    auto vaddr = [&](uint32_t (&voff)[3]) {
        IDS();
        const uint32_t key3 = 3 * ((ln & 7) + 2 * (ln & 8) + ((ln >> 1) & 8));
#pragma unroll
        for (int T = 0; T < 3; T++) {
            const uint32_t u = 3 * wp + T, r = key3 + (u >> 3);
            voff[T] = r * 128 + (((u ^ r) & 7) << 4);
        }
    };
    auto values = [&](uint32_t (&vf)[8][3][4], auto step, uint32_t ps, uint32_t col, uint32_t par) {
        IDS();
        const uint4 p = lds128(ps + 16 * ln);
        float acc[3][4] = {}, f0 = 0.f, f1 = 0.f, r3 = 0.f;
        int M = 0;
#pragma unroll
        for (int s = 0; s < 8; s++) {
            step(s);
            const bool m = (q8 >> 1) == (s >> 1);
            const uint32_t b0 = m ? ((s & 1) ? p.z : p.x) : 0u, b1 = m ? ((s & 1) ? p.w : p.y) : 0u;
#pragma unroll
            for (int T = 0; T < 3; T++) mmaA(acc[T], vf[s][T], b0, b1);
            if (s == FSTEP) {
                const uint2 mp = lds64(ps + PS_MAX + 8 * t4);
                M = __reduce_max_sync(~0u, __float2int_ru(fmaxf(asf(mp.x), asf(mp.y))));
                f0 = ex2(asf(mp.x) - (float)M); f1 = ex2(asf(mp.y) - (float)M);
                float l[4] = {};
                mma16816(l, ONES, ONES, ONES, ONES, p.x, p.y); mma16816(l, ONES, ONES, ONES, ONES, p.z, p.w);
                r3 = fmaf(f0, l[0], f1 * l[1]);
            }
        }
        CSTAMP(25);
        char* pubA = xp(uPubA + col * COL + 32 * t4 + 4 * q8);
        const float r0 = fmaf(f0, acc[0][0], f1 * acc[0][3]), r1 = fmaf(f0, acc[1][0], f1 * acc[1][3]), r2 = fmaf(f0, acc[2][0], f1 * acc[2][3]);
        const bool hi = t4 & 2, od = t4 & 1;
        const float u0 = (hi ? r2 : r0) + __shfl_xor_sync(~0u, hi ? r0 : r2, 2), u1 = (hi ? r3 : r1) + __shfl_xor_sync(~0u, hi ? r1 : r3, 2);
        const float o = (od ? u1 : u0) + __shfl_xor_sync(~0u, od ? u0 : u1, 1);
        stp32_if(t4 < 3 || ((wp & 1) && q8 < 2), pubA, ln == 3 ? __int_as_float(2 * M) : o, par);
    };

#pragma unroll 1
    for (int ch = 0; ch < 5; ch++) {
        const uint32_t par0 = (ch + 1) & 1, par1 = ch & 1;
        uint32_t voff[3], vf[8][3][4];
        CSTAMP(0);
        if (ch < 4) {
            vaddr(voff);
            mbar_wait(sb + S_SCO, par1);
            if (ch == 0) mbar_wait(sb + S_WFULL + 80, 0);
            TST(0);
            auto ldw = [&](int s) {
                mbar_wait(sb + S_FV + 8 * s, par1);
#pragma unroll
                for (int T = 0; T < 3; T++) ldsm4t(vf[s][T], voff[T] + (sb + v_place(ch, s) * SLOT));
            };
            probs(bf_lo(lds16(sb + S_SC + 2 * td)), sb + S_PS, wp, td & 31);
            ldw(0); ldw(1); ldw(2);
            bar_main();
            arrive_if(td == 0, sb + S_RELR);
            values(vf, [&](int s) {
                if (s == HOPA1 && ch > 0) {
                    IDS();
                    hop_a(xp(uPolA + COL + 8 * min(ln, 24u)), par1, uOS + 4 * ln + 96, ln < 24, 25);
                }
                if (s >= 3) ldw(s);
            }, sb + S_PS, 0, par0);
            TST(1);
            CSTAMP(5);
        } else {
#pragma unroll
            for (int s = 0; s < 36; s++) { vf[s / 12][(s / 4) % 3][s & 3] = 0; opaque(vf[s / 12][(s / 4) % 3][s & 3]); }
        }
        const bool has0 = ch < 4, has1 = ch > 0;
        const bool actc = wp < 6 && (cc ? has1 : has0);
        const uint32_t parc = cc ? par1 : par0;
        const uint32_t pub0 = has0 ? par0 : 0;
        uint32_t n4;
        {
            IDS();
            const uint32_t c = ch == 4;
            const uint32_t osa = pin(uOS + 96 * c + 4 * ln), oa = pin(uOS + 96 * (q8 & 1) + 24 * t4), ra = pin(sb + S_RED + 640 * wp + 320 * (t4 & 1) + 8 * q8);
            n4 = pin(4 * n80);
            hop_a(xp(uPolA + c * COL + 8 * min(ln, 24u) + lag<DELAY_L>(sb)), pub0, osa, ln < 24, 5 * ch);
            TST(2);
            CSTAMP(6);
            float acc[5][4] = {};
            const uint2 b0 = lds64(oa), b1 = lds64(oa + 8), b2 = lds64(oa + 16);
#pragma unroll
            for (int m = 0; m < 5; m++) mmaA(acc[m], Wo[m][0], b0.x, b0.y);
#pragma unroll
            for (int m = 0; m < 5; m++) mmaA(acc[m], Wo[m][1], b1.x, b1.y);
#pragma unroll
            for (int m = 0; m < 5; m++) mmaA(acc[m], Wo[m][2], b2.x, b2.y);
#pragma unroll
            for (int m = 0; m < 5; m++) sts64_if(!(td & 2), ra + 64 * m, (td & 1) ? acc[m][1] : acc[m][0], (td & 1) ? acc[m][3] : acc[m][2]);
        }
        CSTAMP(7);
        float x1 = 0.f;
        uint32_t xr, fl, pubC, pubC2;
        uint32_t xab = 0;
        auto prepC = [&] {
            IDS();
            xr = pin(sb + S_XB + 48 * (ln & 15));
            pubC = pin(uPubC + (t4 & 1) * COL + 192 * (wp >> 1) + 64 * (wp & 1) + 8 * q8);
            pubC2 = pin(uPubC + (t4 & 1) * COL + ((t4 & 2) ? 192 * (wp >> 1) + 128 + 4 * (wp & 1) + 8 * q8 : 768 + 2 * ((q8 + 1) & 6)));
            fl = pin(((t4 & 1) ? par1 : pub0) | (t4 >= 2 || (wp == 7 && q8 < 4 && q8 != 2 - t4) ? 2 : 0));
        };
        if (actc) {
            bar_main();
            CSTAMP(8);
            uint32_t r[8];
#pragma unroll
            for (int s = 0; s < 8; s++) r[s] = lds32(n4 + (5 * uCol - 4 * sb + S_RED + 640 * s));
            stp32_if(true, xp(uPubB + n4), sum8(r), parc);
            CSTAMP(9);
            prepC();
            xab = pin(a_pos(n4 / 4) | (b_pos<40>(n4 / 4) << 16));
            const uint32_t xas = pin(3 * uCol - 2 * sb + S_XA + 192 + (xab & 0xffff)), xbs = pin(6 * uCol - 5 * sb + S_XB + (xab >> 16));
            const float x0 = cc ? ldsf(sb + S_XCAR + n4) : bf_lo(lds16(sb + S_X0 + 160 * (ch & 3) + n4 / 2));
            gather16(xp(uPolB + n4 + lag<DELAY_G>(sb)), parc, 5 * ch + 1, [&](float y, uint32_t) {
                const uint32_t x = pack2(x0 + bfr(y), 0.f);
                sts16(xbs, x);
                sts16(xas, x);
                x1 = bf_lo(x);
                return 0u;
            });
            CSTAMP(10);
        } else {
            bar_main();
            prepC();
        }
        auto stats = [&](uint32_t xa, const uint4& b, uint32_t b4) {
            float a[4] = {};
            const uint4 p0 = lds128(xa), p1 = lds128(xa + 16);
            const uint2 p2 = lds64(xa + 32);
            mmaV(a, p0, b.x, b.y); mmaV(a, p1, b.z, b.w); mma8(a, p2.x, p2.y, b4);
            return a[0] + a[3];
        };
        {
            auto gate_up = [&](auto with_stats) {
                bar_main();
                TST(3);
                CSTAMP(11);
                const uint4 b = lds128(xr);
                const uint32_t b4 = lds32(xr + 16);
                float acc[3][4] = {}, st = 0.f;
                if (with_stats.value) st = stats(xr + (S_XA - S_XB), b, b4);
                mul80(acc, Wgu, b, b4);
                stp64_if(!(td & 2), xp(pubC), tagw(acc[0][0] + acc[0][3], fl & 1), tagw(acc[1][0] + acc[1][3], fl & 1));
                stp32_if(fl > 1, xp(pubC2), !with_stats.value || (td & 2) ? acc[2][0] + acc[2][3] : st, fl & 1);
            };
            if (wp == 7) gate_up(std::true_type()); else gate_up(std::false_type());
        }
        CSTAMP(12);
        float mean = 0.f, den = 1.f;
        {
            IDS();
            const uint32_t wa = pin(sb + S_WD + ((ln & 7) + 48 * ((ln >> 3) & 1) + 8 * (ln >> 4)) * 160 + (wp < 7 ? 16 * wp : 128));
            const uint32_t pubD = pin(uPubD + (t4 & 1) * COL + 16 * (t4 & 2) + 4 * q8 + (fl & 1)), ha = xr + (S_HS - S_XB);
            auto down = [&](const uint32_t (&W)[3][4], const uint4& h0, const uint2& h1) {
                float a0[4] = {}, a1[4] = {}, a2[4] = {};
                mmaA(a0, W[0], h0.x, h0.y); mmaA(a1, W[1], h0.z, h0.w); mmaA(a2, W[2], h1.x, h1.y);
                return ((a0[0] + a0[3]) + (a1[0] + a1[3])) + (a2[0] + a2[3]);
            };
            if (wp < 6) {
                uint32_t Wd[3][4];
                auto ldd = [&] {
#pragma unroll
                    for (int s = 0; s < 3; s++) ldsm4t(Wd[s], wa + s * 2560);
                };
                if (actc) {
                    const uint32_t hsa = pin(6 * uCol - 5 * sb + S_HS + b_pos<48>(n96));
                    const uint32_t src0 = uPolC + lag<DELAY_C>(sb);
                    const char* srcv = xp(src0 + 8 * n96);
                    const char* src = xp(src0 + (ln & 1) * HALF);
                    float gt, up;
                    int guard = 0;
                    bool again;
                    do {
                        uint2 v[8], st[4];
#pragma unroll
                        for (int s = 0; s < 4; s++) st[s] = ldp64(src + 768 + s * 1024);
#pragma unroll
                        for (int s = 0; s < 8; s++) v[s] = ldp64(srcv + (s >> 2) * HALF + (s & 3) * 1024);
                        float sx = (asf(st[0].x) + asf(st[1].x)) + (asf(st[2].x) + asf(st[3].x)), sq = (asf(st[0].y) + asf(st[1].y)) + (asf(st[2].y) + asf(st[3].y));
                        sx += __shfl_xor_sync(~0u, sx, 1); sq += __shfl_xor_sync(~0u, sq, 1);
                        const uint2 cs = lds64(sb + S_CSGU - 768 * cc + 8 * td + ((st[0].x ^ parc) & 1) * 8);
                        again = __any_sync(~0u, (or3(chk4(st, parc), chk8(v, parc), chk8y(v, parc)) & 1) != 0);
                        ln_stats(sx, sq, mean, den);
                        const float rd = rcp(den);
                        gt = fmaf(-mean, asf(cs.x), sum8x(v)); up = fmaf(-mean, asf(cs.y), sum8y(v));
                        ldd();
                        gt *= rd; up *= rd;
                        keep(gt); keep(up);
                    } while (again & (++guard < SPIN_LIMIT));
                    CSTAMP(13);
                    SWEEPS(5 * ch + 2, guard - 1);
                    gt = bfr(gt);
                    const uint32_t h = pack2(bfr(gt * sigmoidf_(gt)) * bfr(up), 0.f);
                    sts16(hsa, h);
                    CSTAMP(14);
                } else ldd();
                bar_main();
                TST(4);
                CSTAMP(15);
                const uint4 h0 = lds128(ha);
                const uint2 h1 = lds64(ha + 16);
                stp32_if(!(td & 2), xp(pubD & ~1u), down(Wd, h0, h1), pubD & 1);
            } else {
                stsvol(sb + S_GATE, ch + 1);
                uint32_t Wd[2][3][4];
#pragma unroll
                for (int s = 0; s < 6; s++) ldsm4t(Wd[s / 3][s % 3], wa + (s / 3) * 16 + (s % 3) * 2560);
                uint32_t v = 0;
                if (wp == 6 ? has0 : has1) {
                    const uint32_t par = wp == 6 ? par0 : par1;
                    const char* src = xp(uPolC + 768 + (ln & 4) * (HALF / 4) + (ln & 3) * 1024 + 4 * min(ln >> 3, 2u) + lag<DELAY_C>(sb));
                    int guard = 0;
                    do v = ldp32(src); while (__any_sync(~0u, (v ^ par) & 1) && ++guard < SPIN_LIMIT);
                }
                bar_main();
                const uint4 h0 = lds128(ha);
                const uint2 h1 = lds64(ha + 16);
                const float d0 = down(Wd[0], h0, h1), d1 = down(Wd[1], h0, h1);
                stp32_if(true, xp(pubD & ~1u), (td & 2) ? d1 : d0, pubD & 1);
                if (wp == 6 ? has0 : has1) {
                    float sx = asf(v);
                    sx += __shfl_xor_sync(~0u, sx, 1); sx += __shfl_xor_sync(~0u, sx, 2); sx += __shfl_xor_sync(~0u, sx, 4);
                    const float sq = __shfl_sync(~0u, sx, 8), xw = __shfl_sync(~0u, sx, 16);
                    ln_stats(sx, sq, mean, den);
                    const float r = bfr(fmaf(-mean, ldsf(sb + S_SWR), xw) * rcp(den));
                    sts32_if(ln == 0, sb + S_STAT + 4 * (wp - 6), __float_as_uint(bfr(sigmoidf_(r))) | (ch + 1));
                }
            }
        }
        CSTAMP(16);
        uint32_t pubE;
        {
            IDS();
            pubE = pin(uPubE + (t4 < 3 ? (wp >> 2) * COL + 192 * (wp & 3) + 64 * t4 + 8 * q8 : (q8 >> 2) * COL + 768 + 4 * (q8 & 1)));
            xr = pin(sb + S_XB + 48 * (ln & 7));
            if (actc && (cc == 0 || g == 0)) {
                const uint32_t m4 = 4 * n80;
                const uint32_t xas = pin(3 * uCol - 2 * sb + S_XA + 192 + a_pos(n80)), xbs = pin(6 * uCol - 5 * sb + S_XB + b_pos<40>(n80));
                const float lnx = __uint_as_float(pin(__float_as_uint(bfr(__fdiv_rn(bfr(x1 - mean), den)))));
                uint32_t x2;
                gather16(xp(uPolD + m4 + lag<DELAY_D>(sb)), parc, 5 * ch + 3, [&](float y, uint32_t z) {
                    const uint32_t gate = ldsvol(sb + S_STAT + 4 * cc + z);
                    x2 = pack2(x1 + bfr(lnx + bfr(bfr(y) * bf_hi(gate))), 0.f);
                    sts16(xbs, x2);
                    sts16(xas, x2);
                    return (uint32_t)((gate & 7) != ch + 1);
                });
                CSTAMP(17);
                if (cc) reinterpret_cast<unsigned short*>(P.out)[640 * (ch - 1) + 80 * i + n80] = (unsigned short)x2;
                x1 = bf_lo(x2);
            }
        }
        CSTAMP(18);
        if (!has0) break;
        {
            auto qproj = [&](auto with_stats) {
                bar_main();
                TST(5);
                CSTAMP(19);
                const uint32_t t4 = td & 3;
                const uint4 b = lds128(xr);
                const uint32_t b4 = lds32(xr + 16);
                float acc[6][4] = {}, st = 0.f;
                if (with_stats.value) st = stats(xr + (S_XA - S_XB), b, b4);
                mul80(acc, Wq, b, b4);
                const float v0 = sel4(t4, acc[0][0] + acc[0][3], acc[2][0] + acc[2][3], acc[4][0] + acc[4][3], acc[4][0] + acc[4][3]);
                const float v1 = sel4(t4, acc[1][0] + acc[1][3], acc[3][0] + acc[3][3], acc[5][0] + acc[5][3], acc[5][0] + acc[5][3]);
                if (with_stats.value) stp32_if((td & 11) == 3, xp(pubE), st, par0);
                stp64_if(t4 < 3, xp(pubE), tagw(v0, par0), tagw(v1, par0));
            };
            if (wp == 7) qproj(std::true_type()); else qproj(std::false_type());
            sts32_if(td < 80, sb + S_XCAR + 4 * td, __float_as_uint(x1));
        }
        CSTAMP(20);
        auto pass2 = [&](auto d0, auto d1, auto d2) {
            constexpr int D0 = d0.value, D1 = d1.value, D = D0 + D1 + d2.value;
            IDS();
            const uint32_t ua = sb + k_place(ch, wp & 6) * SLOT + (wp & 1) * UNIT, k0 = k_off(ln);
            uint32_t kf[12][2][4];
            auto ldk = [&](int s) { const uint32_t a = (k0 ^ (32 * (s / 3))) + (ua + 1024 * (s % 3)); ldsm4(kf[s][0], a); ldsm4(kf[s][1], a + SLOT); };
            if (!(mbar_try(sb + S_FK + 8 * (wp & 6), par1) & mbar_try(sb + S_FK + 8 * (wp | 1), par1))) { mbar_wait(sb + S_FK + 8 * (wp & 6), par1); mbar_wait(sb + S_FK + 8 * (wp | 1), par1); }
#pragma unroll
            for (int s = 0; s < D0; s++) ldk(s);
            if (wp < 6) {
                const uint32_t qsa = pin(sb + S_QS + 384 * ch + q_pos(td));
                const uint32_t src0 = uPolE + lag<(D1 > 0 ? 0 : DELAY_E)>(sb);
                const char* srcv = xp(src0 + 4 * td);
                const char* src = xp(src0 + (ln & 1) * HALF);
                uint32_t v[8]; uint2 st[4];
                auto look = [&] {
#pragma unroll
                    for (int s = 0; s < 4; s++) st[s] = ldp64(src + 768 + s * 1024);
#pragma unroll
                    for (int s = 0; s < 8; s++) v[s] = ldp32(srcv + (s >> 2) * HALF + (s & 3) * 1024);
                };
                if (D1 > 0) {
                    look();
                    __syncwarp();
#pragma unroll
                    for (int s = D0; s < D0 + D1; s++) ldk(s);
                }
                int guard = 0;
                while (true) {
                    if (D1 == 0) look();
                    float sx = (asf(st[0].x) + asf(st[1].x)) + (asf(st[2].x) + asf(st[3].x)), sq = (asf(st[0].y) + asf(st[1].y)) + (asf(st[2].y) + asf(st[3].y));
                    sx += __shfl_xor_sync(~0u, sx, 1); sq += __shfl_xor_sync(~0u, sq, 1);
                    const float cs = ldsf(sb + S_CSQ + 4 * td + ((st[0].x ^ par0) & 1) * 4);
                    const bool again = __any_sync(~0u, ((chk8(v, par0) | chk4(st, par0)) & 1) != 0);
                    ln_stats(sx, sq, mean, den);
                    const uint32_t q = pack2(fmaf(-mean, cs, sum8(v)) * rcp(den), 0.f);
                    sts16(qsa, q);
                    if (!(again & (++guard < SPIN_LIMIT))) break;
                    if (D1 > 0) look();
                }
                SWEEPS(5 * ch + 4, guard - 1);
                CSTAMP(22);
            } else {
#pragma unroll
                for (int s = D0; s < D0 + D1; s++) ldk(s);
            }
#pragma unroll
            for (int s = D0 + D1; s < D; s++) ldk(s);
            if (D == 12) { __syncwarp(); arrive_if(ln == 0, sb + S_RELK); }
            bar_main();
            TST(6);
            CSTAMP(1);
            uint2 q = lds64(sb + S_QS + 384 * ch + 8 * ln);
            float acc[2][4] = {};
            auto ldv1 = [&](int k) { ldsm4t(vf[k / 3][k % 3], voff[k % 3] + (sb + v_place(ch, k / 3) * SLOT)); };
            auto ldv = [&](int s) { ldv1(3 * s); ldv1(3 * s + 1); ldv1(3 * s + 2); };
            constexpr int V0 = 13 - D, NV = (2 * (D - 1)) / 3 < 5 ? (2 * (D - 1)) / 3 : 5;
#pragma unroll
            for (int s = 0; s < 12; s++) {
                const bool m = q8 == (s & 7);
                const uint32_t b0 = m ? q.x : 0u, b1 = m ? q.y : 0u;
                if (s == 7) q = lds64(sb + S_QS + 384 * ch + 8 * ln + 256);
                mmaA(acc[0], kf[s][0], b0, b1);
                mmaA(acc[1], kf[s][1], b0, b1);
                if (s >= 1 && s + D - 1 < 12) ldk(s + D - 1);
                if (s >= 1 && s + D - 1 == 11) { __syncwarp(); arrive_if(ln == 0, sb + S_RELK); }
                if (s == V0) vaddr(voff);
                if (s >= V0 && 2 * (s - V0) < 3 * NV) ldv1(9 + 2 * (s - V0));
                if (s >= V0 && 2 * (s - V0) + 1 < 3 * NV) ldv1(10 + 2 * (s - V0));
            }
            CSTAMP(24);
            {
                const float v0 = acc[0][0] + acc[0][1], v1 = acc[0][2] + acc[0][3], v2 = acc[1][0] + acc[1][1], v3 = acc[1][2] + acc[1][3];
                const bool hi = t4 & 2, od = t4 & 1;
                const float u0 = (hi ? v2 : v0) + __shfl_xor_sync(~0u, hi ? v0 : v2, 2), u1 = (hi ? v3 : v1) + __shfl_xor_sync(~0u, hi ? v1 : v3, 2);
                const float s = (od ? u1 : u0) + __shfl_xor_sync(~0u, od ? u0 : u1, 1);
                CSTAMP(2);
                probs(scaled(s), sb + S_PS + PS_PASS, wp, ln);
                CSTAMP(3);
            }
            bar_main();
            TST(10);
            CSTAMP(4);
            values(vf, [&](int s) { if (s >= (NV > 1 ? 2 : 1) && s + NV + (NV > 1 ? 1 : 2) < 8) ldv(s + NV + (NV > 1 ? 1 : 2)); }, sb + S_PS + PS_PASS, 1, par0);
            arrive_if(ln == 0, sb + S_RELV);
        };
        if (LAST0 > 0 && ch == 3) {
            pass2(std::integral_constant<int, LAST0>(), std::integral_constant<int, LAST1>(), std::integral_constant<int, LAST2>());
#pragma unroll
            for (int m = 0; m < 60; m++) { uint32_t& r = m % 10 < 8 ? Wq[m / 10].a[(m % 10) / 4][m % 2 + 2 * ((m % 10) / 2 % 2)] : Wq[m / 10].c[m % 2]; r = 0; opaque(r); }
        } else pass2(std::integral_constant<int, KPRE>(), std::integral_constant<int, 0>(), std::integral_constant<int, KPRE2>());
        TST(11);
        CSTAMP(23);
    }
    sts32_if(td == 255, sb + S_GATE, 6);
    TSTAMP(3);
}

typedef CUresult (*EncodeFn)(CUtensorMap*, CUtensorMapDataType, cuuint32_t, void*, const cuuint64_t*, const cuuint64_t*, const cuuint32_t*,
                             const cuuint32_t*, CUtensorMapInterleave, CUtensorMapSwizzle, CUtensorMapL2promotion, CUtensorMapFloatOOBfill);

void make_map(EncodeFn enc, CUtensorMap* m, const void* base, uint64_t cols, uint64_t rows, uint32_t box_cols, uint32_t box_rows, bool swizzle) {
    cuuint64_t dims[2] = {cols, rows};
    cuuint64_t strides[1] = {cols * 2};
    cuuint32_t box[2] = {box_cols, box_rows};
    cuuint32_t es[2] = {1, 1};
    enc(m, CU_TENSOR_MAP_DATA_TYPE_BFLOAT16, 2, const_cast<void*>(base), dims, strides, box, es, CU_TENSOR_MAP_INTERLEAVE_NONE,
        swizzle ? CU_TENSOR_MAP_SWIZZLE_128B : CU_TENSOR_MAP_SWIZZLE_NONE, swizzle ? CU_TENSOR_MAP_L2_PROMOTION_NONE : WPROMO, CU_TENSOR_MAP_FLOAT_OOB_FILL_NONE);
}

}

extern "C" void kernel_launch(void* const* d_in, const int* in_sizes, int n_in, void* d_out, int out_size) {
    (void)in_sizes; (void)n_in; (void)out_size;
    static EncodeFn enc = nullptr;
    if (!enc) {
        void* f = nullptr;
        cudaDriverEntryPointQueryResult q;
        cudaGetDriverEntryPoint("cuTensorMapEncodeTiled", &f, cudaEnableDefault, &q);
        enc = (EncodeFn)f;
        cudaFuncSetAttribute(fused_kernel, cudaFuncAttributeMaxDynamicSharedMemorySize, SMEM_BYTES);
    }
    Params P;
    P.x = (const __nv_bfloat16*)d_in[0]; P.k = (const __nv_bfloat16*)d_in[1]; P.v = (const __nv_bfloat16*)d_in[2];
    P.wr = (const __nv_bfloat16*)d_in[6];
    P.out = (__nv_bfloat16*)d_out;
    Maps M;
    {
        cuuint64_t dims[4] = {64, 8, 3, (cuuint64_t)KV_BATCH_KEYS / 2}, strides[3] = {384, 128, 3072};
        cuuint32_t box[4] = {64, 8, 3, 2}, es[4] = {1, 1, 1, 1};
        enc(&M.k, CU_TENSOR_MAP_DATA_TYPE_BFLOAT16, 4, d_in[1], dims, strides, box, es, CU_TENSOR_MAP_INTERLEAVE_NONE, CU_TENSOR_MAP_SWIZZLE_128B,
            CU_TENSOR_MAP_L2_PROMOTION_NONE, CU_TENSOR_MAP_FLOAT_OOB_FILL_NONE);
    }
    make_map(enc, &M.v, P.v, 64, (uint64_t)12 * KV_BATCH_KEYS, 64, 96, true);
    make_map(enc, &M.wq, d_in[3], 6144, 640, 192, 40, false);
    make_map(enc, &M.wo, d_in[4], 640, 6144, 80, 96, false);
    make_map(enc, &M.wg, d_in[7], 1536, 640, 96, 80, false);
    make_map(enc, &M.wu, d_in[8], 1536, 640, 96, 80, false);
    make_map(enc, &M.wd, d_in[9], 640, 1536, 80, 96, false);
    fused_kernel<<<NCTA, NTHR, SMEM_BYTES, cudaStreamPerThread>>>(P, M);
}
```

```cpp
#include <cuda_runtime.h>
#include <cuda.h>
#include <cuda_bf16.h>
#include <stdint.h>
#include <type_traits>

namespace {

constexpr int NCTA = 128;
constexpr int NTHR = 384;
constexpr int UNIT = 6144;
constexpr int SLOT = 12288;
#define TAU 4100
#define TAUW 3900
#define TAU0 3900
#define PF0 2
#define PFMAP 1
#define ZPOS 1
#define LOOK1 0
#define LOOK2 0
#define SLACK 8000
#define SLACK0 SLACK
#define TSH 0
#define HOP1_NS 200
#define RELR_AT 0
#define PSLEEP 0
#define KRE_HALF 0
#define TMIN 2400
#define T_LEAD 0
#define WIN_W 3
#define WIN_S 4
#define WIN_U 10
#define RFR_ON 1
#define KRE_N1 0
#define KRE_TAU1 2500
#define RFR_TAU 6400
#define VPF 5
#define KRE_GATE 0
#define KRE_GATE3 KRE_GATE
#define JFREE 16
#define TFREE 0
#define KRE_TAU 3000
#define KRE_TAU3 KRE_TAU
#define HDEPTH 3
#define LAST0 0
#define LAST1 4
#define LAST2 3
#define FSTEP 4
#define SPEC 1
#define PV1PIPE 0
#define HOPA0 6
#define HOPA1 6
#define WPROMO CU_TENSOR_MAP_L2_PROMOTION_NONE
#define KPRE 1
#define KPRE2 3
#define DELAY_G 6
#define DELAY_L 5
#define DELAY_C 3
#define DELAY_D 6
#define DELAY_E 3
#define REG_LO "40"
#define REG_HI "232"
#define SPIN_LOG 17
constexpr int SPIN_LIMIT = 1 << SPIN_LOG;

__host__ __device__ constexpr uint32_t pairL(uint32_t region, uint32_t c, uint32_t g) { return (g & 1) | ((g >> 1) << 2) | (c << 5) | (region << 6); }
__host__ __device__ constexpr uint32_t pairG(uint32_t d, uint32_t c, uint32_t i) { return (i & 1) | ((i >> 1) << 2) | (d << 4) | (c << 5) | (3u << 6); }
constexpr uint32_t RA = 0, RC = 1, RE = 2, HALF = 16384, COPY = 4096, PMASK = 0x59;
constexpr uint32_t XS = 0;
constexpr uint32_t XS2 = XS + 128 * 7680;
constexpr uint32_t XSEND = XS2 + 128 * 768;
__device__ uint4 g_s[XSEND / 16];
__device__ uint4 g_x[(4u << 20) / 16];
#define SWEEPS(k, n) do {} while (0)

constexpr uint32_t S_WD = 16 * SLOT;
constexpr uint32_t S_DUMMY = S_WD + 15360;
constexpr uint32_t S_BAR = S_DUMMY + 4096;
constexpr uint32_t S_FV = S_BAR, S_FK = S_FV + 64, S_RING = S_FK + 64, S_DBAR = S_RING + 48, S_WFULL = S_DBAR + 32, S_QRDY = S_WFULL + 88;
constexpr uint32_t S_RELK = S_QRDY + 8, S_RELV = S_RELK + 8, S_RELR = S_RELV + 8, S_RELW = S_RELR + 8, S_SCO = S_RELW + 24;
constexpr uint32_t S_OS1 = S_SCO + 8;
constexpr uint32_t S_ZERO = S_OS1 + 8;
constexpr uint32_t S_KF = S_ZERO + 8;
constexpr uint32_t S_TOK = S_KF + 8;
constexpr uint32_t S_SIDE = S_TOK + 80, S_GATE = S_SIDE + 4;
constexpr uint32_t S_STAT = S_GATE + 12, S_SWR = S_STAT + 16;
constexpr uint32_t S_XCAR = S_STAT + 32;
constexpr uint32_t S_CSQ = S_XCAR + 320;
constexpr uint32_t S_CSGU = S_CSQ + 768;
constexpr uint32_t S_RED = S_CSGU + 768;
constexpr uint32_t S_L0 = S_RED;
constexpr uint32_t S_OS = S_RED + 5120;
constexpr uint32_t S_PS = S_OS + 1536;
constexpr uint32_t PS_MAX = 512, PS_PASS = 544;
constexpr uint32_t S_QS = S_PS + 2 * PS_PASS;
constexpr uint32_t S_XB = S_QS + 1536;
constexpr uint32_t S_XA = S_XB + 768;
constexpr uint32_t S_HS = S_XA + 768;
constexpr uint32_t S_X0 = S_HS + 768;
constexpr uint32_t S_SC = S_X0 + 640;
constexpr uint32_t S_TM = S_SC + 512;
constexpr int SMEM_BYTES = S_TM + 256;
static_assert(SMEM_BYTES <= 232448 && S_STAT % 16 == 0 && S_RED % 16 == 0 && S_XB % 16 == 0 && S_HS % 16 == 0 && S_PS % 16 == 0 && S_QS % 16 == 0, "smem");
static_assert(S_SCO == S_BAR + 44 * 8 && S_RELK == S_BAR + 38 * 8, "barriers");
constexpr uint32_t ST_WQ = 3 * SLOT, ST_WG = 8 * SLOT, ST_WO = 11 * SLOT;

__device__ __forceinline__ uint32_t smem_u32(const void* p) { return (uint32_t)__cvta_generic_to_shared(p); }
__device__ __forceinline__ void mbar_init(uint32_t bar, uint32_t cnt) { asm volatile("mbarrier.init.shared::cta.b64 [%0], %1;" :: "r"(bar), "r"(cnt) : "memory"); }
__device__ __forceinline__ void mbar_expect(uint32_t bar, uint32_t bytes) { asm volatile("mbarrier.arrive.expect_tx.shared::cta.b64 _, [%0], %1;" :: "r"(bar), "r"(bytes) : "memory"); }
__device__ __forceinline__ void mbar_arrive(uint32_t bar) { asm volatile("mbarrier.arrive.shared::cta.b64 _, [%0];" :: "r"(bar) : "memory"); }
__device__ __forceinline__ bool mbar_try(uint32_t bar, uint32_t parity) {
    uint32_t ok;
    asm volatile("{\n .reg .pred p;\n mbarrier.try_wait.parity.shared::cta.b64 p, [%1], %2;\n selp.u32 %0, 1, 0, p;\n}" : "=r"(ok) : "r"(bar), "r"(parity) : "memory");
    return ok != 0;
}
__device__ __forceinline__ bool mbar_test(uint32_t bar, uint32_t parity) {
    uint32_t ok;
    asm volatile("{\n .reg .pred p;\n mbarrier.test_wait.parity.shared::cta.b64 p, [%1], %2;\n selp.u32 %0, 1, 0, p;\n}" : "=r"(ok) : "r"(bar), "r"(parity) : "memory");
    return ok != 0;
}
__device__ __forceinline__ void mbar_wait(uint32_t bar, uint32_t parity) {
    int n = 0;
    while (!mbar_try(bar, parity) && ++n < SPIN_LIMIT) {}
}
__device__ __forceinline__ unsigned long long gtime() { unsigned long long t; asm volatile("mov.u64 %0, %globaltimer;" : "=l"(t)); return t; }
__device__ __forceinline__ uint32_t gtime32() { uint32_t t; asm volatile("mov.u32 %0, %globaltimer_lo;" : "=r"(t)); return t; }
__device__ __forceinline__ void bar_main() { asm volatile("bar.sync 1, 256;" ::: "memory"); }

__device__ __forceinline__ void mma16816(float (&c)[4], uint32_t a0, uint32_t a1, uint32_t a2, uint32_t a3, uint32_t b0, uint32_t b1) {
    asm("mma.sync.aligned.m16n8k16.row.col.f32.bf16.bf16.f32 {%0,%1,%2,%3}, {%4,%5,%6,%7}, {%8,%9}, {%0,%1,%2,%3};"
        : "+f"(c[0]), "+f"(c[1]), "+f"(c[2]), "+f"(c[3]) : "r"(a0), "r"(a1), "r"(a2), "r"(a3), "r"(b0), "r"(b1));
}
__device__ __forceinline__ void mmaA(float (&c)[4], const uint32_t (&a)[4], uint32_t b0, uint32_t b1) { mma16816(c, a[0], a[1], a[2], a[3], b0, b1); }
__device__ __forceinline__ void mmaAv(float (&c)[4], const uint32_t (&a)[4], uint32_t b0, uint32_t b1) {
    asm volatile("mma.sync.aligned.m16n8k16.row.col.f32.bf16.bf16.f32 {%0,%1,%2,%3}, {%4,%5,%6,%7}, {%8,%9}, {%0,%1,%2,%3};"
        : "+f"(c[0]), "+f"(c[1]), "+f"(c[2]), "+f"(c[3]) : "r"(a[0]), "r"(a[1]), "r"(a[2]), "r"(a[3]), "r"(b0), "r"(b1) : "memory");
}
__device__ __forceinline__ void mma8(float (&c)[4], uint32_t a0, uint32_t a1, uint32_t b0) {
    asm("mma.sync.aligned.m16n8k8.row.col.f32.bf16.bf16.f32 {%0,%1,%2,%3}, {%4,%5}, {%6}, {%0,%1,%2,%3};"
        : "+f"(c[0]), "+f"(c[1]), "+f"(c[2]), "+f"(c[3]) : "r"(a0), "r"(a1), "r"(b0));
}
struct W80 { uint32_t a[2][4], c[2]; };
template <int N> __device__ __forceinline__ void mul80(float (&acc)[N][4], const W80 (&W)[N], const uint4& b, uint32_t b4) {
#pragma unroll
    for (int m = 0; m < N; m++) mmaA(acc[m], W[m].a[0], b.x, b.y);
#pragma unroll
    for (int m = 0; m < N; m++) mmaA(acc[m], W[m].a[1], b.z, b.w);
#pragma unroll
    for (int m = 0; m < N; m++) mma8(acc[m], W[m].c[0], W[m].c[1], b4);
}
__device__ __forceinline__ void ldsm2t(uint32_t (&r)[2], uint32_t addr) {
    asm volatile("ldmatrix.sync.aligned.m8n8.x2.trans.shared.b16 {%0,%1}, [%2];" : "=r"(r[0]), "=r"(r[1]) : "r"(addr) : "memory");
}
__device__ __forceinline__ void mmaV(float (&c)[4], const uint4& a, uint32_t b0, uint32_t b1) { mma16816(c, a.x, a.y, a.z, a.w, b0, b1); }
__device__ __forceinline__ void ldsm4(uint32_t (&r)[4], uint32_t addr) {
    asm volatile("ldmatrix.sync.aligned.m8n8.x4.shared.b16 {%0,%1,%2,%3}, [%4];" : "=r"(r[0]), "=r"(r[1]), "=r"(r[2]), "=r"(r[3]) : "r"(addr) : "memory");
}
__device__ __forceinline__ void ldsm4t(uint32_t (&r)[4], uint32_t addr) {
    asm volatile("ldmatrix.sync.aligned.m8n8.x4.trans.shared.b16 {%0,%1,%2,%3}, [%4];" : "=r"(r[0]), "=r"(r[1]), "=r"(r[2]), "=r"(r[3]) : "r"(addr) : "memory");
}
__device__ __forceinline__ uint32_t lds16(uint32_t a) { uint16_t v; asm volatile("ld.shared.u16 %0, [%1];" : "=h"(v) : "r"(a) : "memory"); return v; }
__device__ __forceinline__ uint32_t lds32(uint32_t a) { uint32_t v; asm volatile("ld.shared.u32 %0, [%1];" : "=r"(v) : "r"(a) : "memory"); return v; }
__device__ __forceinline__ float ldsf(uint32_t a) { return __uint_as_float(lds32(a)); }
__device__ __forceinline__ uint2 lds64(uint32_t a) { uint2 v; asm volatile("ld.shared.v2.u32 {%0,%1}, [%2];" : "=r"(v.x), "=r"(v.y) : "r"(a) : "memory"); return v; }
__device__ __forceinline__ uint4 lds128(uint32_t a) { uint4 v; asm volatile("ld.shared.v4.u32 {%0,%1,%2,%3}, [%4];" : "=r"(v.x), "=r"(v.y), "=r"(v.z), "=r"(v.w) : "r"(a) : "memory"); return v; }
__device__ __forceinline__ int ldsvol(uint32_t a) { int v; asm volatile("ld.volatile.shared.u32 %0, [%1];" : "=r"(v) : "r"(a) : "memory"); return v; }
__device__ __forceinline__ void stsvol(uint32_t a, int v) { asm volatile("st.volatile.shared.u32 [%0], %1;" :: "r"(a), "r"(v) : "memory"); }
__device__ __forceinline__ void sts_hi16(uint32_t a, float v) { asm volatile("{\n .reg .b16 lo, hi;\n mov.b32 {lo, hi}, %1;\n st.shared.u16 [%0], hi;\n}" :: "r"(a), "r"(__float_as_uint(v)) : "memory"); }
__device__ __forceinline__ void sts16(uint32_t a, uint32_t v) { asm volatile("st.shared.u16 [%0], %1;" :: "r"(a), "r"(v) : "memory"); }
__device__ __forceinline__ void sts32(uint32_t a, uint32_t v) { asm volatile("st.shared.u32 [%0], %1;" :: "r"(a), "r"(v) : "memory"); }
__device__ __forceinline__ void stsf(uint32_t a, float v) { sts32(a, __float_as_uint(v)); }
__device__ __forceinline__ void sts64(uint32_t a, uint32_t x, uint32_t y) { asm volatile("st.shared.v2.u32 [%0], {%1,%2};" :: "r"(a), "r"(x), "r"(y) : "memory"); }

__device__ __forceinline__ void sts_hi16_if(bool p, uint32_t a, float v) {
    asm volatile("{\n .reg .pred p;\n .reg .b16 lo, hi;\n setp.ne.u32 p, %2, 0;\n mov.b32 {lo, hi}, %1;\n @p st.shared.u16 [%0], hi;\n}" :: "r"(a), "r"(__float_as_uint(v)), "r"((uint32_t)p) : "memory");
}
__device__ __forceinline__ void sts32_if(bool p, uint32_t a, uint32_t v) {
    asm volatile("{\n .reg .pred p;\n setp.ne.u32 p, %2, 0;\n @p st.shared.u32 [%0], %1;\n}" :: "r"(a), "r"(v), "r"((uint32_t)p) : "memory");
}
__device__ __forceinline__ void sts64_if(bool p, uint32_t a, float x, float y) {
    asm volatile("{\n .reg .pred p;\n setp.ne.u32 p, %3, 0;\n @p st.shared.v2.f32 [%0], {%1,%2};\n}" :: "r"(a), "f"(x), "f"(y), "r"((uint32_t)p) : "memory");
}
__device__ __forceinline__ void arrive_if(bool p, uint32_t bar) {
    asm volatile("{\n .reg .pred p;\n setp.ne.u32 p, %1, 0;\n @p mbarrier.arrive.shared::cta.b64 _, [%0];\n}" :: "r"(bar), "r"((uint32_t)p) : "memory");
}
__device__ __forceinline__ void opaque(uint32_t& v) { asm volatile("" : "+r"(v)); }
__device__ __forceinline__ void keep(uint32_t& v) { asm volatile("" : "+r"(v)); }
__device__ __forceinline__ void keep(float& v) { asm volatile("" : "+f"(v)); }
template <class T> __device__ __forceinline__ void keep(T*& v) { asm volatile("" : "+l"(v)); }

__device__ __forceinline__ uint32_t ldp32(const char* p) { uint32_t v; asm volatile("ld.relaxed.gpu.global.u32 %0, [%1];" : "=r"(v) : "l"(p) : "memory"); return v; }
__device__ __forceinline__ uint2 ldp64(const char* p) {
    uint2 v; asm volatile("{\n .reg .b64 d;\n ld.relaxed.gpu.global.b64 d, [%2];\n mov.b64 {%0,%1}, d;\n}" : "=r"(v.x), "=r"(v.y) : "l"(p) : "memory"); return v;
}
__device__ __forceinline__ uint32_t tagw(float f, uint32_t par) { return (__float_as_uint(f) & ~1u) | par; }
__device__ __forceinline__ void stp32(char* p, float a, uint32_t par) { asm volatile("st.relaxed.gpu.global.u32 [%0], %1;" :: "l"(p), "r"(tagw(a, par)) : "memory"); }
__device__ __forceinline__ void stp64(char* p, float a, float b, uint32_t par) {
    asm volatile("{\n .reg .b64 d;\n mov.b64 d, {%1,%2};\n st.relaxed.gpu.global.b64 [%0], d;\n}" :: "l"(p), "r"(tagw(a, par)), "r"(tagw(b, par)) : "memory");
}
__device__ __forceinline__ void stp32_if(bool p, char* d, float a, uint32_t par) {
    asm volatile("{\n .reg .pred p;\n setp.ne.u32 p, %2, 0;\n @p st.relaxed.gpu.global.u32 [%0], %1;\n @p st.relaxed.gpu.global.u32 [%0+4096], %1;\n}" :: "l"(d), "r"(tagw(a, par)), "r"((uint32_t)p) : "memory");
}
__device__ __forceinline__ void stp64_if(bool p, char* d, uint32_t lo, uint32_t hi) {
    asm volatile("{\n .reg .pred p;\n .reg .b64 d;\n setp.ne.u32 p, %3, 0;\n mov.b64 d, {%1,%2};\n @p st.relaxed.gpu.global.b64 [%0], d;\n @p st.relaxed.gpu.global.b64 [%0+4096], d;\n}" :: "l"(d), "r"(lo), "r"(hi), "r"((uint32_t)p) : "memory");
}
__device__ __forceinline__ uint32_t chk2(uint32_t a, uint32_t b, uint32_t par) { uint32_t r; asm("lop3.b32 %0, %1, %2, %3, 0x7E;" : "=r"(r) : "r"(a), "r"(b), "r"(par)); return r; }
__device__ __forceinline__ uint32_t or3(uint32_t a, uint32_t b, uint32_t c) { uint32_t r; asm("lop3.b32 %0, %1, %2, %3, 0xFE;" : "=r"(r) : "r"(a), "r"(b), "r"(c)); return r; }
__device__ __forceinline__ uint32_t chk8(const uint32_t (&v)[8], uint32_t par) { return or3(chk2(v[0], v[1], par), chk2(v[2], v[3], par), or3(chk2(v[4], v[5], par), chk2(v[6], v[7], par), 0)); }
__device__ __forceinline__ uint32_t chk8(const uint2 (&v)[8], uint32_t par) { return or3(chk2(v[0].x, v[1].x, par), chk2(v[2].x, v[3].x, par), or3(chk2(v[4].x, v[5].x, par), chk2(v[6].x, v[7].x, par), 0)); }
__device__ __forceinline__ uint32_t chk8y(const uint2 (&v)[8], uint32_t par) { return or3(chk2(v[0].y, v[1].y, par), chk2(v[2].y, v[3].y, par), or3(chk2(v[4].y, v[5].y, par), chk2(v[6].y, v[7].y, par), 0)); }
__device__ __forceinline__ uint32_t chk4(const uint2 (&v)[4], uint32_t par) { return or3(chk2(v[0].x, v[0].y, par), chk2(v[1].x, v[1].y, par), or3(chk2(v[2].x, v[2].y, par), chk2(v[3].x, v[3].y, par), 0)); }
__device__ __forceinline__ float asf(uint32_t v) { return __uint_as_float(v); }
__device__ __forceinline__ float sum8(const uint32_t (&v)[8]) { return ((asf(v[0]) + asf(v[1])) + (asf(v[2]) + asf(v[3]))) + ((asf(v[4]) + asf(v[5])) + (asf(v[6]) + asf(v[7]))); }
__device__ __forceinline__ float sum8x(const uint2 (&v)[8]) { return ((asf(v[0].x) + asf(v[1].x)) + (asf(v[2].x) + asf(v[3].x))) + ((asf(v[4].x) + asf(v[5].x)) + (asf(v[6].x) + asf(v[7].x))); }
__device__ __forceinline__ float sum8y(const uint2 (&v)[8]) { return ((asf(v[0].y) + asf(v[1].y)) + (asf(v[2].y) + asf(v[3].y))) + ((asf(v[4].y) + asf(v[5].y)) + (asf(v[6].y) + asf(v[7].y))); }

__device__ __forceinline__ uint32_t pack2(float lo, float hi) { uint32_t r; asm("cvt.rn.bf16x2.f32 %0, %1, %2;" : "=r"(r) : "f"(hi), "f"(lo)); return r; }
__device__ __forceinline__ float bfr(float x) { return __uint_as_float(pack2(0.0f, x)); }
__device__ __forceinline__ float ex2(float x) { float r; asm("ex2.approx.ftz.f32 %0, %1;" : "=f"(r) : "f"(x)); return r; }
__device__ __forceinline__ float rcp(float x) { float r; asm("rcp.approx.ftz.f32 %0, %1;" : "=f"(r) : "f"(x)); return r; }
__device__ __forceinline__ float sqrt_(float x) { float r; asm("sqrt.approx.ftz.f32 %0, %1;" : "=f"(r) : "f"(x)); return r; }
__device__ __forceinline__ float bf_lo(uint32_t v) { return __uint_as_float(v << 16); }
__device__ __forceinline__ float bf_hi(uint32_t v) { return __uint_as_float(v & 0xffff0000u); }
__device__ __forceinline__ float sel4(int k, float a, float b, float c, float d) { return (k & 2) ? ((k & 1) ? d : c) : ((k & 1) ? b : a); }
constexpr float LOG2E = 1.4426950408889634f;
constexpr uint32_t ONES = 0x3f803f80u;

__device__ __forceinline__ void ln_stats(float sum, float sq, float& mean, float& den) {
    const float m = sum * (1.0f / 640.0f);
    const float var = fmaxf(fmaf(sq, 1.0f / 640.0f, -m * m), 0.0f);
    mean = bfr(m);
    den = bfr(sqrt_(bfr(bfr(var) + 1e-5f)));
}
__device__ __forceinline__ float sigmoidf_(float x) { return rcp(1.0f + ex2(-x * LOG2E)); }

#define TSTAMP(k) do {} while (0)
#define TST(k) do {} while (0)

#define CSTAMP(k) do {} while (0)
template <int N> __device__ __forceinline__ uint32_t lag(uint32_t sb) {
    uint32_t z = 0;
#pragma unroll
    for (int k = 0; k < N; k++) z = ldsvol(sb + S_ZERO + z);
    return z;
}
__device__ __forceinline__ void warm_mma(uint32_t& a, uint32_t& b) {
    asm volatile("mma.sync.aligned.m16n8k8.row.col.f16.f16.f16.f16 {%0,%1}, {%0,%1}, {%0}, {%0,%1};" : "+r"(a), "+r"(b) :: "memory");
}
#define KWNS2 20
#define KWNS 200
template <int STRIDE>
__device__ __forceinline__ float gather8(const char* p, uint32_t par) {
    uint32_t v[8];
    int guard = 0;
    do {
#pragma unroll
        for (int s = 0; s < 8; s++) v[s] = ldp32(p + s * STRIDE);
    } while ((chk8(v, par) & 1) && ++guard < SPIN_LIMIT);
    return sum8(v);
}
template <class F>
__device__ __forceinline__ void gather16(const char* p, uint32_t par, int k, F use) {
    uint32_t v[8], u[8];
    int guard = 0;
    bool again;
    do {
#pragma unroll
        for (int s = 0; s < 8; s++) v[s] = ldp32(p + s * 512);
#pragma unroll
        for (int s = 0; s < 8; s++) u[s] = ldp32(p + HALF + s * 512);
        const uint32_t stale = use(sum8(v) + sum8(u), ((v[0] ^ par) & 1) * 8);
        again = __any_sync(~0u, (or3(chk8(v, par), chk8(u, par), stale) & 1) != 0);
    } while (again & (++guard < SPIN_LIMIT));
    SWEEPS(k, guard - 1);
}

struct Params {
    const __nv_bfloat16 *x, *k, *v, *wr;
    __nv_bfloat16* out;
};
struct Maps { CUtensorMap k, kh, v, vu, wq, wo, wg, wu, wd; };

constexpr int KV_BATCH_KEYS = 32 * 4096;

__device__ __forceinline__ void tma2d(uint32_t dst, const CUtensorMap* m, int c0, int c1, uint32_t bar, uint32_t bytes, uint64_t pol) {
    asm volatile("{\n .reg .pred p;\n elect.sync _|p, 0xffffffff;\n"
                 " @p mbarrier.arrive.expect_tx.shared::cta.b64 _, [%2], %6;\n"
                 " @p cp.async.bulk.tensor.2d.shared::cluster.global.mbarrier::complete_tx::bytes.L2::cache_hint [%0], [%1, {%3, %4}], [%2], %5;\n}"
                 :: "r"(dst), "l"(m), "r"(bar), "r"(c0), "r"(c1), "l"(pol), "r"(bytes) : "memory");
}
__device__ __forceinline__ void scrap_copy(uint32_t dst, const char* src, uint32_t bar) {
    asm volatile("{\n .reg .pred p;\n elect.sync _|p, 0xffffffff;\n"
                 " @p mbarrier.arrive.expect_tx.shared::cta.b64 _, [%2], 12288;\n"
                 " @p cp.async.bulk.shared::cluster.global.mbarrier::complete_tx::bytes [%0], [%1], 4096, [%2];\n"
                 " @p cp.async.bulk.shared::cluster.global.mbarrier::complete_tx::bytes [%0], [%1+4096], 4096, [%2];\n"
                 " @p cp.async.bulk.shared::cluster.global.mbarrier::complete_tx::bytes [%0], [%1+8192], 4096, [%2];\n}"
                 :: "r"(dst), "l"(src), "r"(bar) : "memory");
}
__device__ __forceinline__ void prefetch_l2(const void* p, uint32_t bytes) {
    asm volatile("{\n .reg .pred p;\n elect.sync _|p, 0xffffffff;\n @p cp.async.bulk.prefetch.L2.global [%0], %1;\n}" :: "l"(p), "r"(bytes) : "memory");
}
__device__ __forceinline__ uint64_t pol_first() { uint64_t p; asm("createpolicy.fractional.L2::evict_first.b64 %0, 1.0;" : "=l"(p)); return p; }
__device__ __forceinline__ uint64_t pol_normal() { uint64_t p; asm("createpolicy.fractional.L2::evict_normal.b64 %0, 1.0;" : "=l"(p)); return p; }
__device__ __forceinline__ bool utest(uint32_t bar, uint32_t parity) { return __all_sync(~0u, mbar_test(bar, parity)); }
__device__ __forceinline__ void uwait(uint32_t bar, uint32_t parity) {
    int n = 0;
    while (!__all_sync(~0u, mbar_try(bar, parity)) && ++n < SPIN_LIMIT) {}
}
template <int A, int B, int CNT> __device__ __forceinline__ void init_bars(uint32_t sb) {
#pragma unroll 1
    for (int k = A; k < B; k++)
        asm volatile("{\n .reg .pred p;\n elect.sync _|p, 0xffffffff;\n @p mbarrier.init.shared::cta.b64 [%0], %1;\n}" :: "r"(sb + S_BAR + 8 * k), "n"(CNT) : "memory");
}
__device__ __forceinline__ int first_key() { return (blockIdx.x >> 2) * 4096 + 3072 + (blockIdx.x & 3) * 256; }
__device__ __forceinline__ void load_tile(const CUtensorMap* m, uint32_t dst, uint32_t bar, uint32_t bytes, int key, uint64_t pol) { tma2d(dst, m, 0, 3 * key, bar, bytes, pol); }
__device__ __forceinline__ const char* unit_ptr(const Params& P, int n) {
    return (const char*)((n & 16) ? P.v : P.k) + (size_t)(first_key() + (n >> 5) * KV_BATCH_KEYS + (n & 15) * 16) * 384;
}
#define LSTAMP(k) do {} while (0)

__device__ __forceinline__ uint32_t k_place(uint32_t b, uint32_t s) { return s + 3 + 5 * (b & 1); }
__device__ __forceinline__ uint32_t v_place(uint32_t b, uint32_t s) { return s < 3 ? s : s + 8 - 8 * (b & 1); }
__device__ __forceinline__ void k_load(const Maps& M, uint32_t dst, uint32_t bar, int key8, uint64_t pol) {
    asm volatile("{\n .reg .pred p;\n elect.sync _|p, 0xffffffff;\n"
                 " @p mbarrier.arrive.expect_tx.shared::cta.b64 _, [%2], 6144;\n"
                 " @p cp.async.bulk.tensor.4d.shared::cluster.global.mbarrier::complete_tx::bytes.L2::cache_hint [%0], [%1, {0, 0, 0, %3}], [%2], %4;\n}"
                 :: "r"(dst), "l"(&M.k), "r"(bar), "r"(key8), "l"(pol) : "memory");
}
__device__ __forceinline__ int unit_key8(uint32_t n) { return first_key() / 8 + (n >> 4) * (KV_BATCH_KEYS / 8) + 2 * (n & 15); }
__device__ __forceinline__ void ring_load(const Maps& M, uint32_t sb, uint32_t b, uint32_t u, uint32_t pos) {
    if (u < 16) k_load(M, sb + pos * UNIT, sb + S_RING + 8 * pos, unit_key8(16 * b + u), pol_normal());
    else load_tile(&M.vu, sb + pos * UNIT, sb + S_FV + 4 * (pos & 6), UNIT, first_key() + b * KV_BATCH_KEYS + 16 * pos, pol_first());
}
__device__ __forceinline__ uint32_t token(bool p, uint32_t a, uint32_t n) {
    uint32_t v;
    asm volatile("{\n .reg .pred p;\n setp.ne.u32 p, %2, 0;\n mov.u32 %0, 0;\n @p atom.shared.exch.b32 %0, [%1], %3;\n}" : "=r"(v) : "r"(a), "r"((uint32_t)p), "r"(n) : "memory");
    return v;
}
__device__ __forceinline__ void place_load(const Maps& M, uint32_t sb, uint32_t n) {
    k_load(M, sb + k_place(n >> 4, 0) * SLOT + (n & 15) * UNIT, sb + S_FK + 4 * (n & 14), unit_key8(n), pol_first());
}
__device__ __forceinline__ void half_load(const Maps& M, uint32_t sb, uint32_t m) {
    const uint32_t bar = sb + S_FK + 2 * (m & 28);
    if (!(m & 1)) asm volatile("{\n .reg .pred p;\n elect.sync _|p, 0xffffffff;\n @p mbarrier.arrive.expect_tx.shared::cta.b64 _, [%0], 6144;\n}" :: "r"(bar) : "memory");
    asm volatile("{\n .reg .pred p;\n elect.sync _|p, 0xffffffff;\n"
                 " @p cp.async.bulk.tensor.4d.shared::cluster.global.mbarrier::complete_tx::bytes.L2::cache_hint [%0], [%1, {0, 0, 0, %3}], [%2], %4;\n}"
                 :: "r"(sb + k_place(m >> 5, 0) * SLOT + (m & 31) * 3072), "l"(&M.kh), "r"(bar), "r"(first_key() / 8 + (m >> 5) * (KV_BATCH_KEYS / 8) + (m & 31)), "l"(pol_first()) : "memory");
}
__device__ __forceinline__ void v_load(const Maps& M, uint32_t sb, uint32_t b, uint32_t s) {
    load_tile(&M.v, sb + v_place(b, s) * SLOT, sb + S_FV + 8 * s, SLOT, first_key() + b * KV_BATCH_KEYS + 32 * s, pol_first());
}
__device__ __forceinline__ bool due(uint32_t t) { return __all_sync(~0u, (int)(gtime32() * 16 - t) >= 0); }
__device__ __forceinline__ bool reached(uint32_t a, int v) { return __all_sync(~0u, ldsvol(a) >= v); }

__device__ __forceinline__ void stream_warp(const Params& P, const Maps& M, uint32_t sb, uint32_t lane) {
    const uint64_t pol = pol_first();
    const int bid = blockIdx.x, g = bid >> 3, i = bid & 7;
    const uint32_t wf = sb + S_WFULL;
    if (PF0 > 0) prefetch_l2(unit_ptr(P, 0), PF0 * UNIT);
    uint32_t tn = __shfl_sync(~0u, gtime32(), 0) * 16 - T_LEAD;
    auto pace = [&](uint32_t dt) {
        int k = 0;
        uint32_t now;
        do now = __shfl_sync(~0u, gtime32(), 0) * 16; while ((int)(now - tn) < 0 && ++k < SPIN_LIMIT);
        if ((int)(now - tn) > SLACK0) tn = now - SLACK0;
        tn += dt;
    };
#pragma unroll
    for (int k = 0; k < 10; k++) {
        if (k < 2) {
            if (k == 0) init_bars<26, 27, 1>(sb); else init_bars<27, 37, 1>(sb);
            asm volatile("fence.mbarrier_init.release.cluster;" ::: "memory");
            if (k == 1) { asm volatile("bar.arrive 2, %0;" :: "n"(NTHR) : "memory"); asm volatile("bar.sync 3, 128;" ::: "memory"); }
        }
        if (k >= WIN_W) uwait(wf + 8 * (k - WIN_W), 0);
        pace(TAUW * 5 / 2);
        if (k < 4) tma2d(sb + ST_WQ + 15360 * k, &M.wq, 384 * g + 192 * (k >> 1), 80 * i + 40 * (k & 1), wf + 8 * k, 15360, pol);
        else if (k < 6) tma2d(sb + ST_WG + 15360 * (k - 4), k == 4 ? &M.wg : &M.wu, 96 * g, 80 * i, wf + 8 * k, 15360, pol);
        else tma2d(sb + ST_WO + 15360 * (k - 6), &M.wo, 80 * i, 384 * g + 96 * (k - 6), wf + 8 * k, 15360, pol);
    }
#pragma unroll 1
    for (int n = 0; n < 16; n++) {
        if (n == 0 || n == 5 || n == 11) uwait(sb + S_RELW + (n == 0 ? 0 : n == 5 ? 8 : 16), 0);
        uwait(n < WIN_S ? wf + 8 * (10 - WIN_S + n) : sb + S_FV + 8 * ((n - WIN_S) ^ 8), 0);
        pace(max(min(2 * n + 2 - PF0, 2), 0) * TAU0);
        if (n < 8) { place_load(M, sb, 2 * n); place_load(M, sb, 2 * n + 1); }
        else if (n < 11) { ring_load(M, sb, 0, 2 * n, 2 * n - 16); ring_load(M, sb, 0, 2 * n + 1, 2 * n - 15); }
        else v_load(M, sb, 0, n - 8);
        if (n == 7) { pace(TAUW * 5 / 2); tma2d(sb + S_WD, &M.wd, 80 * i, 96 * g, wf + 80, 15360, pol); }
    }
    int nd = 0;
    uint32_t q[4];
#pragma unroll
    for (int r = 0; r < 4; r++) q[r] = sb + S_FV + 8 * (7 - r);
    tn -= TSH;
    uint32_t td = tn;
    uint32_t pos = 2;
#pragma unroll 1
    for (int m = 16; m < 64; m++) {
        const int b = m >> 4, j = m & 15;
        const char* src = unit_ptr(P, 2 * m);
        const uint32_t tok = sb + S_TOK + (j < 3 ? 4 * pos : j < 11 ? 24 + 4 * pos : 16 + 4 * j) + 4 * lane;
        static_assert(WIN_U <= 12, "a ring position has at most one token of the timetable");
        int k = 0;
        while (true) {
            const uint2 c = lds64(sb + S_KF);
            if (__all_sync(~0u, mbar_test(q[WIN_S - 1] & ~1u, q[WIN_S - 1] & 1) & (min((int)c.x + 1, (int)c.y) >= 16 * b + min(2 * j + 2 - WIN_U, 16))) || ++k >= SPIN_LIMIT) break;
        }
        uint32_t now;
        while (true) {
            now = __shfl_sync(~0u, gtime32(), 0) * 16;
            if ((int)(now - td) >= 0 || ++k >= SPIN_LIMIT) break;
            if (PSLEEP > 0 && (int)(td - now) > 16 * PSLEEP * 2) __nanosleep(PSLEEP);
        }
        const uint32_t mine = __ballot_sync(~0u, token(lane < (j < 11 ? 2 : 1), tok, 2 * m + lane) == 2 * m + lane);
        q[3] = q[2]; q[2] = q[1]; q[1] = q[0]; q[0] = sb + S_QRDY;
        if (j < 11) {
            if (mine & 1) ring_load(M, sb, b, 2 * j, pos); else prefetch_l2(src, UNIT);
            if (mine & 2) ring_load(M, sb, b, 2 * j + 1, pos + 1); else prefetch_l2(src + UNIT, UNIT);
            if (j >= 8) q[0] = (sb + S_FV + 8 * (j - 8)) | (b & 1);
        } else if (mine) { v_load(M, sb, b, j - 8); q[0] = (sb + S_FV + 8 * (j - 8)) | (b & 1); }
        else if (j - 8 >= VPF) prefetch_l2(src, SLOT);
        else {
            scrap_copy(sb + S_DUMMY, src, sb + S_DBAR + 8 * (nd & 3));
            q[0] = (sb + S_DBAR + 8 * (nd & 3)) | ((nd >> 2) & 1);
            nd++;
        }
        pos = j == 15 ? 2 : pos == 4 ? 0 : pos + 2;
        if ((int)(now - tn) > SLACK) tn = now - SLACK;
        tn += 2 * TAU;
        td = (int)(tn - now) > 2 * TMIN ? tn : now + 2 * TMIN;
        if (m >= 48 + JFREE) td = now + TFREE;
    }
#pragma unroll 1
    for (int m = max(nd - 4, 0); m < nd; m++) uwait(sb + S_DBAR + 8 * (m & 3), (m >> 2) & 1);
}

__device__ __forceinline__ float scaled(float s) { return bfr(bfr(s) * 0.07216878364870322f); }
__device__ __forceinline__ void probs(float s, uint32_t ps, uint32_t src, uint32_t ln) {
    const uint32_t q8 = ln >> 2, t4 = ln & 3;
    int key = __float_as_int(s);
    key ^= (key >> 31) & 0x7fffffff;
    key = __reduce_max_sync(~0u, key);
    key ^= (key >> 31) & 0x7fffffff;
    const float ml = __int_as_float(key) * LOG2E;
    sts16(ps + 64 * src + (q8 >> 1) * 16 + t4 * 4 + (q8 & 1) * 2, pack2(ex2(fmaf(s, LOG2E, -ml)), 0.f));
    stsf(ps + PS_MAX + 4 * src, ml);
}
template <int H> __device__ __forceinline__ uint32_t b_pos(uint32_t e) { const uint32_t h = e >= H, k = e - H * h; return h * 192 + (k & 6) * 24 + (k >> 3) * 4 + (k & 1) * 2; }
__device__ __forceinline__ uint32_t a_pos(uint32_t e) { const uint32_t h = e >= 40, k = e - 40 * h; return (k & 6) * 24 + (k >> 3) * 8 + h * 4 + (k & 1) * 2; }
__device__ __forceinline__ uint32_t q_pos(uint32_t d) { const uint32_t s = 3 * ((d >> 4) & 3) + (d >> 6); return s * 32 + (d & 6) * 4 + ((d >> 3) & 1) * 4 + (d & 1) * 2; }
__device__ __forceinline__ uint32_t k_off(uint32_t ln) { return (ln & 8) * 384 + (ln & 7) * 128 + (((ln & 7) ^ (ln >> 4)) << 4); }

#define HSTAMP(k) do {} while (0)
__device__ __forceinline__ char* xwindow() { return reinterpret_cast<char*>((reinterpret_cast<uintptr_t>(g_x) + (2u << 20) - 1) & ~(uintptr_t)((2u << 20) - 1)); }

struct XPtr {
    uint32_t lo, hi;
    __device__ __forceinline__ explicit XPtr(char* p) : lo((uint32_t)(uintptr_t)p), hi((uint32_t)((uintptr_t)p >> 32)) {}
    __device__ __forceinline__ XPtr(uint32_t l, uint32_t h) : lo(l), hi(h) {}
    __device__ __forceinline__ XPtr operator+(uint32_t o) const { return XPtr(lo + o, hi); }
    __device__ __forceinline__ operator char*() const { uint64_t p; asm("mov.b64 %0, {%1, %2};" : "=l"(p) : "r"(lo), "r"(hi)); return (char*)p; }
};
__device__ __forceinline__ void keep(XPtr& v) { keep(v.lo); }

__device__ __forceinline__ void side_warp(uint32_t sb) {
    const uint32_t bid = blockIdx.x, g = bid >> 3, i = bid & 7, P = pairG(0, 0, i);
    char* p = xwindow() + P * 8192 + (g >> 3) * HALF + (g & 7) * 512 + 448;
    uint32_t best[2] = {~0u, ~0u};
    asm volatile("st.relaxed.gpu.global.b32 [%0], 1;" :: "l"(p) : "memory");
    asm volatile("st.relaxed.gpu.global.b32 [%0], 1;" :: "l"(p + COPY) : "memory");
#pragma unroll 1
    for (int r = 0; r < 64; r++) {
        if (r >= 4 && !(r & 1) && min(best[0], best[1]) < 380 && max(best[0], best[1]) > min(best[0], best[1]) + 80) break;
        uint32_t c0, c1, v;
        asm volatile("mov.u32 %0, %clock;" : "=r"(c0) :: "memory");
        asm volatile("atom.relaxed.gpu.global.exch.b32 %0, [%1], 0;" : "=r"(v) : "l"(p + (r & 1) * COPY) : "memory");
        asm volatile("{\n .reg .pred q;\n setp.eq.u32 q, %1, 0x13579bdf;\n mov.u32 %0, 0;\n @!q mov.u32 %0, %clock;\n}" : "=r"(c1) : "r"(v) : "memory");
        if (r & 1) best[1] = min(best[1], c1 - c0); else best[0] = min(best[0], c1 - c0);
    }
    stsvol(sb + S_SIDE, 1 + ((best[1] < best[0]) ^ (__popc(P & PMASK) & 1)));
}

__device__ __forceinline__ void hop_a(const char* src, uint32_t par, uint32_t dst, bool st, int k) {
    uint2 v[4];
    float e[4], rl;
    int guard = 0;
    bool again;
    do {
#pragma unroll
        for (int s = 0; s < 4; s++) v[s] = ldp64(src + s * 1024);
        again = __any_sync(~0u, (chk4(v, par) & 1) != 0);
        const int M = max(max((int)v[0].x, (int)v[1].x), max((int)v[2].x, (int)v[3].x)) - 254;
#pragma unroll
        for (int s = 0; s < 4; s++) e[s] = __int_as_float(max((int)v[s].x - M, 0) << 22);
        rl = rcp(fmaf(e[0], asf(v[0].y), e[1] * asf(v[1].y)) + fmaf(e[2], asf(v[2].y), e[3] * asf(v[3].y)));
#pragma unroll
        for (int s = 0; s < 4; s++) e[s] = __shfl_sync(~0u, e[s], 24);
        keep(rl);
    } while (again & (++guard < SPIN_LIMIT));
    rl = __shfl_sync(~0u, rl, 24);
    const float o0 = fmaf(e[0], asf(v[0].x), e[1] * asf(v[1].x)) + fmaf(e[2], asf(v[2].x), e[3] * asf(v[3].x));
    const float o1 = fmaf(e[0], asf(v[0].y), e[1] * asf(v[1].y)) + fmaf(e[2], asf(v[2].y), e[3] * asf(v[3].y));
    sts32_if(st, dst, pack2(o0 * rl, o1 * rl));
    SWEEPS(k, guard - 1);
    __syncwarp();
}

__device__ __forceinline__ void score_warp(const Maps& M, uint32_t sb, uint32_t h, uint32_t ln) {
    const uint32_t lane0 = ln;
    uwait(sb + S_QRDY, 0);
    const uint32_t q8 = ln >> 2;
    const uint32_t k0 = k_off(ln);
    uint32_t pos = h + 6, bar = sb + S_FK, par = 0, phases = 0;
    uint2 q = lds64(sb + S_QS + 8 * ln), qh = lds64(sb + S_QS + 8 * ln + 256);
    auto first_round = [&](uint32_t b, uint32_t ln) {
        uwait(sb + S_RELR, b & 1);
        const uint32_t u = h + 2 * ln, p = u < 4 ? u + 2 : u - 4;
        uint32_t todo = __ballot_sync(~0u, token(ln < 3, sb + S_TOK + 4 * p, 32 * b + 32 + u) == 32 * b + 32 + u);
#pragma unroll 1
        for (uint32_t r = h; todo; todo >>= 1, r += 2) if (todo & 1) ring_load(M, sb, b + 1, r, r < 4 ? r + 2 : r - 4);
    };
#pragma unroll 1
    for (uint32_t n = h; n < 64; n += 2) {
        HSTAMP(0);
        const uint32_t ua = sb + pos * UNIT;
        if (!__all_sync(~0u, mbar_try(bar, par))) uwait(bar, par);
        HSTAMP(1);
        float acc[2][4] = {};
        uint32_t mine = 0;
        const uint32_t id = n + (n & 48) + 6;
#pragma unroll
        for (int s = 0; s < 12; s++) {
            uint32_t kf[4];
            ldsm4(kf, (k0 ^ (32 * (s / 3))) + (ua + 1024 * (s % 3)));
            if (s == 11) {
                __syncwarp();
                mine = token(ln == 0 && n >= 16, sb + S_TOK + 24 + 4 * pos, id);
                stsvol(sb + S_KF + 4 * h, n + 1);
            }
            const bool m = q8 == (s & 7);
            mmaA(acc[s & 1], kf, m ? (s < 8 ? q.x : qh.x) : 0u, m ? (s < 8 ? q.y : qh.y) : 0u);
        }
        const uint32_t pos0 = pos;
        const bool last = (n & 14) == 14;
        pos = last ? h + 2 : n >= 16 && pos >= 4 ? h : pos + 2;
        bar = n >= 14 ? sb + S_RING + 8 * pos : bar + 8;
        par = n >= 14 ? (phases >> pos) & 1 : 0;
        phases ^= n >= 14 ? 1u << pos : 0;
        const float w0 = (acc[0][0] + acc[0][1]) + (acc[1][0] + acc[1][1]), w1 = (acc[0][2] + acc[0][3]) + (acc[1][2] + acc[1][3]);
        HSTAMP(2);
        if (__any_sync(~0u, mine == id)) ring_load(M, sb, n >> 4, (n & 15) + 6, pos0);
        HSTAMP(3);
        float s = ((ln & 1) ? w1 : w0) + __shfl_xor_sync(~0u, (ln & 1) ? w0 : w1, 1);
        s += __shfl_xor_sync(~0u, s, 2);
        sts_hi16(sb + S_SC + (((n & 12) >> 1) + h) * 64 + (n & 2) * 2 + (ln & 29) * 2, scaled(s));
        if (last) {
            __syncwarp();
            arrive_if(ln == 0, sb + S_SCO);
            const uint32_t b = n >> 4, ln = lane0 + lag<1>(sb);
            if (b > 0) {
                uwait(sb + S_RELK, (b - 1) & 1);
                if (h == 0) LSTAMP(64 + 2 * b);
                const uint32_t sl = 3 + h + 2 * ln, idv = 32 * b + 16 + 2 * sl;
                uint32_t todo = __ballot_sync(~0u, token(sl < 8, sb + S_TOK + 48 + 4 * sl, idv) == idv);
#pragma unroll 1
                for (uint32_t r = 3 + h; todo; todo >>= 1, r += 2) if (todo & 1) v_load(M, sb, b, r);
                const uint32_t g = blockIdx.x >> 3, pr = pairL(RA, 1, g), side = ldsvol(sb + S_SIDE);
                const char* src = xwindow() + pr * 8192 + ((side ^ 1 ^ __popc(pr & PMASK)) & 1) * COPY + h * HALF + 8 * min(ln, 24u);
                uwait(sb + S_RELV, (b - 1) & 1);
                __nanosleep(HOP1_NS);
#pragma unroll 1
                for (uint32_t r = 0; r < 4; r++) {
                    hop_a(src + 256 * r, b & 1, sb + S_OS + 192 * (4 * h + r) + 96 + 4 * ln, ln < 24, 25);
                    if (r == RELR_AT && b < 3) first_round(b, ln);
                }
                arrive_if(ln == 0, sb + S_OS1);
            } else first_round(0, ln);
            q = lds64(sb + S_QS + 24 * ((n + 2) & 48) + 8 * ln); qh = lds64(sb + S_QS + 24 * ((n + 2) & 48) + 8 * ln + 256);
        }
    }
}

__global__ void __launch_bounds__(NTHR, 1)
fused_kernel(const Params P, const __grid_constant__ Maps M) {
    extern __shared__ __align__(1024) unsigned char smem[];
    const uint32_t sb = smem_u32(smem);
    const int tid = threadIdx.x, bid = blockIdx.x;
    const int w = __shfl_sync(~0u, tid >> 5, 0), lane = tid & 31;

    if (w >= 8) {
        asm volatile("setmaxnreg.dec.sync.aligned.u32 " REG_LO ";");
        if (w == 8) {
            stream_warp(P, M, sb, lane);
        } else {
            if (PFMAP && w == 11 && lane < 9) asm volatile("prefetch.tensormap [%0];" :: "l"(&M.k + lane) : "memory");
            if (w == 9) { init_bars<0, 3, 2>(sb); init_bars<3, 8, 1>(sb); init_bars<16, 22, 1>(sb); }
            else if (w == 10) { init_bars<8, 16, 2>(sb); init_bars<22, 26, 1>(sb); }
            else { init_bars<37, 38, 1>(sb); init_bars<38, 40, 8>(sb); init_bars<40, 41, 1>(sb); init_bars<41, 44, 8>(sb); init_bars<44, 46, 2>(sb); stsvol(sb + S_ZERO + 4 * lane, 0); }
            asm volatile("fence.mbarrier_init.release.cluster;" ::: "memory");
            asm volatile("bar.arrive 3, 128;" ::: "memory");
            asm volatile("bar.sync 2, %0;" :: "n"(NTHR) : "memory");
            if (w < 11) score_warp(M, sb, w - 9, lane);
            else {
                if (lane == 0) side_warp(sb);
                __syncwarp();
                uint32_t a = 0, b = 0;
                int k = 0;
                while (ldsvol(sb + S_GATE) == 0 && ++k < SPIN_LIMIT) { warm_mma(a, b); __nanosleep(KWNS); }
                uint4* d = reinterpret_cast<uint4*>(reinterpret_cast<char*>(g_s) + XS + bid * 7680) + lane;
                const uint4 z = make_uint4(0, 0, 0, 0);
#pragma unroll 1
                for (int u = 0; u < 15; u++) d[32 * u] = z;
                d = reinterpret_cast<uint4*>(reinterpret_cast<char*>(g_s) + XS2 + bid * 768) + lane;
                d[0] = z;
                if (lane < 16) d[32] = z;
                const uint32_t side = (ldsvol(sb + S_SIDE) & 1) ^ 1, g = bid >> 3, i = bid & 7;
                const XPtr gx(xwindow());
                auto nearp = [&](uint32_t pr) { return gx.lo + pr * 8192 + ((side ^ __popc(pr & PMASK)) & 1) * COPY; };
                const uint32_t own = (i >> 2) * HALF + (i & 3) * 1024 + (lane & 7) * 128;
                const uint32_t pAC = nearp(pairL(lane >> 4, (lane >> 3) & 1, g)) + own, pE = nearp(pairL(RE, (lane >> 3) & 1, g)) + own;
                const uint32_t pG = nearp(pairG((lane >> 2) & 1, (lane >> 3) & 1, i)) + min(lane & 3, 2) * 128;
                uint32_t tr = 0, tk = 0, ph = 0, src = g + (lane >> 4), seen = 0, n = 16, hf = 0;
                bool go = false, first = true;
                while (n < 64 && ++k < SPIN_LIMIT) {
                    const uint32_t now = __shfl_sync(~0u, gtime32(), 0) * 16;
                    if (!go && utest(sb + S_RELV, ((n >> 4) & 1) ^ 1) && utest(sb + S_FV + 8 * (n >= 48 ? KRE_GATE3 : KRE_GATE), (n >> 4) & 1)) { go = true; tk = now; }
                    if (go && (int)(now - tk) >= 0) {
                        if (KRE_HALF) half_load(M, sb, 2 * n + hf); else place_load(M, sb, n);
                        tk += (n >= 48 ? KRE_TAU3 : (n & 15) < KRE_N1 ? KRE_TAU1 : KRE_TAU) / (KRE_HALF ? 2 : 1);
                        if (KRE_HALF && (hf ^= 1)) continue;
                        n++;
                        go = (n & 15) != 0;
                        if (!go) LSTAMP(63 + (n >> 3));
                    } else if (first || (int)(now - tr) >= 0) {
                        first = false;
                        tr = now + RFR_TAU;
                        b |= seen & a;
                        warm_mma(a, b);
                        if (RFR_ON) seen = ldp32(XPtr(ph == 0 ? pAC : ph == 1 && lane < 16 ? pE : pG + (src & 8) * (HALF / 8) + (src & 7) * 512, gx.hi));
                        src += ph == 0 ? 0 : ph == 1 ? 2 : 1;
                        ph = ph == 2 ? 0 : ph + 1;
                    } else __nanosleep(KWNS2);
                }
                while (ldsvol(sb + S_GATE) < 6 && ++k < SPIN_LIMIT) { warm_mma(a, b); __nanosleep(KWNS); }
                if (a | b) stsvol(sb + S_GATE, 6);
            }
        }
        return;
    }
    asm volatile("setmaxnreg.inc.sync.aligned.u32 " REG_HI ";");

    const int g = bid >> 3, i = bid & 7;
    const int g8 = lane >> 2, t = lane & 3;
    char* const gs = reinterpret_cast<char*>(g_s);
    const XPtr gx(xwindow());

    auto zero_words = [&] {
        const uint4 z = make_uint4(0, 0, 0, 0);
        const uint32_t c = (tid >> 6) & 1, cp = (tid >> 7) * COPY, k = (tid & 63) * 16;
        *reinterpret_cast<uint4*>((char*)(gx + pairL(RA, c, g) * 8192 + (i >> 2) * HALF + (i & 3) * 1024 + cp + k)) = z;
        *reinterpret_cast<uint4*>((char*)(gx + pairL(RC, c, g) * 8192 + (i >> 2) * HALF + (i & 3) * 1024 + cp + k)) = z;
        *reinterpret_cast<uint4*>((char*)(gx + pairL(RE, c, g) * 8192 + (i >> 2) * HALF + (i & 3) * 1024 + cp + k)) = z;
        if ((tid & 31) < 24) *reinterpret_cast<uint4*>((char*)(gx + pairG((tid >> 5) & 1, c, i) * 8192 + (g >> 3) * HALF + (g & 7) * 512 + cp + (tid & 31) * 16)) = z;
    };
    if (ZPOS == 0) zero_words();
    W80 Wq[6], Wgu[3];
    uint32_t Wo[5][3][4];
    if (w < 4) {
        const uint32_t* xp = reinterpret_cast<const uint32_t*>(P.x + 640 * w);
        float sum = 0.f, sq = 0.f;
#pragma unroll
        for (int u = 0; u < 10; u++) { uint32_t v = xp[lane + 32 * u]; float a = bf_lo(v), b = bf_hi(v); sum += a + b; sq += a * a + b * b; }
#pragma unroll
        for (int o = 16; o > 0; o >>= 1) { sum += __shfl_xor_sync(~0u, sum, o); sq += __shfl_xor_sync(~0u, sq, o); }
        float mean, den; ln_stats(sum, sq, mean, den);
        if (lane < 20) {
            const uint2 v = reinterpret_cast<const uint2*>(P.x + 640 * w + 80 * i)[lane];
            sts64(sb + S_X0 + 160 * w + 8 * lane, v.x, v.y);
            sts32(sb + S_L0 + 384 * w + b_pos<40>(4 * lane), pack2(__fdiv_rn(bfr(bf_lo(v.x) - mean), den), __fdiv_rn(bfr(bf_hi(v.x) - mean), den)));
            sts32(sb + S_L0 + 384 * w + b_pos<40>(4 * lane + 2), pack2(__fdiv_rn(bfr(bf_lo(v.y) - mean), den), __fdiv_rn(bfr(bf_hi(v.y) - mean), den)));
        }
    } else if (w == 4) {
        const uint32_t* xp = reinterpret_cast<const uint32_t*>(P.wr);
        float sum = 0.f;
#pragma unroll
        for (int u = 0; u < 10; u++) { uint32_t v = xp[lane + 32 * u]; sum += bf_lo(v) + bf_hi(v); }
#pragma unroll
        for (int o = 16; o > 0; o >>= 1) sum += __shfl_xor_sync(~0u, sum, o);
        if (lane == 0) stsf(sb + S_SWR, sum);
        if (lane < 20) {
            const uint2 v = reinterpret_cast<const uint2*>(P.wr + 80 * i)[lane];
            sts32(sb + S_XA + 576 + a_pos(4 * lane), v.x); sts32(sb + S_XA + 576 + a_pos(4 * lane + 2), v.y);
            sts32(sb + S_XA + a_pos(4 * lane), ONES); sts32(sb + S_XA + a_pos(4 * lane + 2), ONES);
        }
    }
    asm volatile("bar.sync 2, %0;" :: "n"(NTHR) : "memory");
    auto frag = [](uint32_t (&a)[4], uint32_t p, int pitch) {
        const uint32_t r0 = lds32(p), r1 = lds32(p + pitch), r2 = lds32(p + 2 * pitch), r3 = lds32(p + 3 * pitch);
        a[0] = __byte_perm(r0, r1, 0x5410); a[1] = __byte_perm(r0, r1, 0x7632);
        a[2] = __byte_perm(r2, r3, 0x5410); a[3] = __byte_perm(r2, r3, 0x7632);
    };
    mbar_wait(sb + S_WFULL + 16 * (w >> 2), 0);
    mbar_wait(sb + S_WFULL + 16 * (w >> 2) + 8, 0);
    {
        const uint32_t p = sb + ST_WQ + (w >> 2) * 30720 + (2 * t) * 384 + (48 * (w & 3) + 2 * g8) * 2;
#pragma unroll
        for (int r = 0; r < 10; r++)
#pragma unroll
            for (int m = 0; m < 3; m++) {
                const uint32_t q = p + ((r & 1) * 40 + (r >> 1) * 8) * 384 + 32 * m, r0 = lds32(q), r1 = lds32(q + 384);
                (r < 8 ? Wq[2 * m].a[(r >> 2) & 1][r & 3] : Wq[2 * m].c[r & 1]) = __byte_perm(r0, r1, 0x5410);
                (r < 8 ? Wq[2 * m + 1].a[(r >> 2) & 1][r & 3] : Wq[2 * m + 1].c[r & 1]) = __byte_perm(r0, r1, 0x7632);
            }
    }
    __syncwarp();
    if (lane == 0) mbar_arrive(sb + S_RELW);
    TSTAMP(1);
    {
        char* d = gs + XS + bid * 7680 + (w >> 2) * 3840 + (48 * (w & 3) + 2 * g8) * 4;
        float acc[6][4] = {};
        mul80(acc, Wq, lds128(sb + S_L0 + 48 * lane), lds32(sb + S_L0 + 48 * lane + 16));
#pragma unroll
        for (int m = 0; m < 6; m += 2) stp64(d + t * 768 + 32 * m, acc[m][0] + acc[m][3], acc[m + 1][0] + acc[m + 1][3], 1);
        float sum[6][4] = {};
        mul80(sum, Wq, make_uint4(ONES, ONES, ONES, ONES), ONES);
        if (t == 0)
#pragma unroll
            for (int m = 0; m < 6; m += 2) stp64(d + 4 * 768 + 32 * m, sum[m][0] + sum[m][3], sum[m + 1][0] + sum[m + 1][3], 1);
    }
    mbar_wait(sb + S_WFULL + 32, 0);
    mbar_wait(sb + S_WFULL + 40, 0);
    const uint32_t oct = 3 * (w >> 1) + (w & 1), oct2 = 3 * (w >> 1) + 2;
    {
        const uint32_t p = sb + ST_WG + ((lane & 7) + 40 * ((lane >> 3) & 1) + 8 * (lane >> 4)) * 192;
#pragma unroll
        for (int T = 0; T < 3; T++) {
            const uint32_t q = p + (T < 2 ? T * 15360 + 16 * oct : (w & 1) * 15360 + 16 * oct2);
            ldsm4t(Wgu[T].a[0], q); ldsm4t(Wgu[T].a[1], q + 16 * 192); ldsm2t(Wgu[T].c, q + 32 * 192);
        }
        float sum[3][4] = {};
        mul80(sum, Wgu, make_uint4(ONES, ONES, ONES, ONES), ONES);
        if (t < 3) stp32(gs + XS2 + bid * 768 + (t < 2 ? 64 * oct + 4 * t : 64 * oct2 + 4 * (w & 1)) + 8 * g8,
                         sel4(t, sum[0][0] + sum[0][3], sum[1][0] + sum[1][3], sum[2][0] + sum[2][3], 0.f), 1);
    }
    __syncwarp();
    if (lane == 0) mbar_arrive(sb + S_RELW + 8);
    const char* srcS = gs + XS + g * 8 * 7680 + (i >> 2) * 3840 + min(tid, 191) * 4;
    uint32_t vs[5][8];
#pragma unroll
    for (int b = 0; b < 5; b++)
#pragma unroll
        for (int s = 0; s < 8; s++) vs[b][s] = LOOK1 ? ldp32(srcS + b * 768 + s * 7680) : 0;
    uint32_t cs2[8];
#pragma unroll
    for (int s = 0; s < 8; s++) cs2[s] = LOOK2 ? ldp32(gs + XS2 + (g * 8 + s) * 768 + min(tid, 191) * 4) : 0;
    __syncwarp();
    mbar_wait(sb + S_WFULL + 48 + 8 * (w >> 1), 0);
    {
        const uint32_t po = sb + ST_WO + (48 * w + 12 * t) * 160 + 4 * g8;
#pragma unroll
        for (int s = 0; s < 3; s++)
#pragma unroll
            for (int m = 0; m < 5; m++) frag(Wo[m][s], po + 4 * s * 160 + 32 * m, 160);
    }
    __syncwarp();
    if (lane == 0) mbar_arrive(sb + S_RELW + 16);
    if (ZPOS == 1) zero_words();
    if (tid < 192) {
        int guard = 0;
        while (((or3(chk8(vs[0], 1), chk8(vs[1], 1), chk8(vs[2], 1)) | chk8(vs[3], 1) | chk8(vs[4], 1)) & 1) && ++guard < SPIN_LIMIT) {
#pragma unroll
            for (int b = 0; b < 5; b++)
#pragma unroll
                for (int s = 0; s < 8; s++) vs[b][s] = ldp32(srcS + b * 768 + s * 7680);
        }
        const uint32_t qpos = sb + S_QS + q_pos(tid);
#pragma unroll
        for (int b = 0; b < 4; b++) {
            sts_hi16(qpos + 384 * b, bfr(sum8(vs[b])));
        }
        stsf(sb + S_CSQ + 4 * tid, sum8(vs[4]));
    }
    if (tid < 192) stsf(sb + S_CSGU + 4 * tid, (chk8(cs2, 1) & 1) ? gather8<768>(gs + XS2 + g * 8 * 768 + tid * 4, 1) : sum8(cs2));
    __syncwarp();
    bar_main();
    arrive_if(tid == 0, sb + S_QRDY);
    if (ZPOS == 2) zero_words();
    TSTAMP(2);

    uint32_t side;
    { int k = 0; while ((side = ldsvol(sb + S_SIDE)) == 0 && ++k < SPIN_LIMIT) {} }
    const uint32_t td = __shfl_sync(~0u, tid, lane);
    const uint32_t wp = __shfl_sync(~0u, tid >> 5, 0);
    const uint32_t cc = wp >= 3;
    auto uni = [](uint32_t v) { return __shfl_sync(~0u, v, 0); };
    auto pin = [&](uint32_t v) { return __shfl_sync(~0u, v, td); };
    auto nearp = [&](uint32_t P) { return gx.lo + P * 8192 + ((side ^ 1 ^ __popc(P & PMASK)) & 1) * COPY; };
    constexpr uint32_t COL = 32 * 8192;
    const uint32_t ownL = gx.lo + (i >> 2) * HALF + (i & 3) * 1024, ownG = gx.lo + (g >> 3) * HALF + (g & 7) * 512;
    const uint32_t uPubA = uni(ownL + pairL(RA, 0, g) * 8192 + (wp >> 1) * 256 + (wp & 1) * 96), uPolA = uni(nearp(pairL(RA, 0, g)) + (wp >> 2) * HALF + (wp & 3) * 256);
    const uint32_t uPubB = uni(ownG + pairG(0, cc, i) * 8192), uPolB = uni(nearp(pairG(0, cc, i)));
    const uint32_t uPubC = uni(ownL + pairL(RC, 0, g) * 8192), uPolC = uni(nearp(pairL(RC, wp < 6 ? cc : wp - 6, g)));
    const uint32_t uPubD = uni(ownG + pairG(1, 0, i) * 8192 + (wp < 7 ? 32 * wp : 256)), uPolD = uni(nearp(pairG(1, cc, i)));
    const uint32_t uPubE = uni(ownL + pairL(RE, 0, g) * 8192), uPolE = uni(nearp(pairL(RE, i >> 2, g)));
    const uint32_t uOS = uni(sb + S_OS + 192 * wp), uCol = uni(sb + 64 * cc);
    auto xp = [&](uint32_t lo) { return (char*)XPtr(lo, gx.hi); };
#define IDS() uint32_t z_ = td; opaque(z_); const uint32_t ln = z_ & 31, q8 = ln >> 2, t4 = z_ & 3, n96 = z_ - 96 * cc, n80 = min(n96, 79u); (void)q8; (void)t4; (void)n80; (void)ln

    auto vaddr = [&](uint32_t (&voff)[3]) {
        IDS();
        const uint32_t key3 = 3 * ((ln & 7) + 2 * (ln & 8) + ((ln >> 1) & 8));
#pragma unroll
        for (int T = 0; T < 3; T++) {
            const uint32_t u = 3 * wp + T, r = key3 + (u >> 3);
            voff[T] = r * 128 + (((u ^ r) & 7) << 4);
        }
    };
    auto values = [&](uint32_t (&vf)[8][3][4], auto step, uint32_t ps, uint32_t col, uint32_t par) {
        IDS();
        const uint4 p = lds128(ps + 16 * ln);
        float acc[3][4] = {}, f0 = 0.f, f1 = 0.f, r3 = 0.f;
        int M = 0;
#pragma unroll
        for (int s = 0; s < 8; s++) {
            step(s);
            const bool m = (q8 >> 1) == (s >> 1);
            const uint32_t b0 = m ? ((s & 1) ? p.z : p.x) : 0u, b1 = m ? ((s & 1) ? p.w : p.y) : 0u;
#pragma unroll
            for (int T = 0; T < 3; T++) mmaA(acc[T], vf[s][T], b0, b1);
            if (s == FSTEP) {
                const uint2 mp = lds64(ps + PS_MAX + 8 * t4);
                M = __reduce_max_sync(~0u, __float2int_ru(fmaxf(asf(mp.x), asf(mp.y))));
                f0 = ex2(asf(mp.x) - (float)M); f1 = ex2(asf(mp.y) - (float)M);
                float l[4] = {};
                mma16816(l, ONES, ONES, ONES, ONES, p.x, p.y); mma16816(l, ONES, ONES, ONES, ONES, p.z, p.w);
                r3 = fmaf(f0, l[0], f1 * l[1]);
            }
        }
        CSTAMP(25);
        char* pubA = xp(uPubA + col * COL + 32 * t4 + 4 * q8);
        const float r0 = fmaf(f0, acc[0][0], f1 * acc[0][3]), r1 = fmaf(f0, acc[1][0], f1 * acc[1][3]), r2 = fmaf(f0, acc[2][0], f1 * acc[2][3]);
        const bool hi = t4 & 2, od = t4 & 1;
        const float u0 = (hi ? r2 : r0) + __shfl_xor_sync(~0u, hi ? r0 : r2, 2), u1 = (hi ? r3 : r1) + __shfl_xor_sync(~0u, hi ? r1 : r3, 2);
        const float o = (od ? u1 : u0) + __shfl_xor_sync(~0u, od ? u0 : u1, 1);
        stp32_if(t4 < 3 || ((wp & 1) && q8 < 2), pubA, ln == 3 ? __int_as_float(2 * M) : o, par);
    };

#pragma unroll 1
    for (int ch = 0; ch < 5; ch++) {
        const uint32_t par0 = (ch + 1) & 1, par1 = ch & 1;
        uint32_t voff[3], vf[8][3][4];
        CSTAMP(0);
        if (ch < 4) {
            vaddr(voff);
            mbar_wait(sb + S_SCO, par1);
            if (ch == 0) mbar_wait(sb + S_WFULL + 80, 0);
            TST(0);
            auto ldw = [&](int s) {
                mbar_wait(sb + S_FV + 8 * s, par1);
#pragma unroll
                for (int T = 0; T < 3; T++) ldsm4t(vf[s][T], voff[T] + (sb + v_place(ch, s) * SLOT));
            };
            probs(bf_lo(lds16(sb + S_SC + 2 * td)), sb + S_PS, wp, td & 31);
            ldw(0); ldw(1); ldw(2);
            bar_main();
            arrive_if(td == 0, sb + S_RELR);
            values(vf, [&](int s) {
                if (s >= 3) ldw(s);
            }, sb + S_PS, 0, par0);
            TST(1);
            CSTAMP(5);
            if (ch > 0) mbar_wait(sb + S_OS1, par0);
        } else {
#pragma unroll
            for (int s = 0; s < 36; s++) { vf[s / 12][(s / 4) % 3][s & 3] = 0; opaque(vf[s / 12][(s / 4) % 3][s & 3]); }
        }
        const bool has0 = ch < 4, has1 = ch > 0;
        const bool actc = wp < 6 && (cc ? has1 : has0);
        const uint32_t parc = cc ? par1 : par0;
        const uint32_t pub0 = has0 ? par0 : 0;
        uint32_t n4;
        {
            IDS();
            const uint32_t c = ch == 4;
            const uint32_t osa = pin(uOS + 96 * c + 4 * ln), oa = pin(uOS + 96 * (q8 & 1) + 24 * t4), ra = pin(sb + S_RED + 640 * wp + 320 * (t4 & 1) + 8 * q8);
            n4 = pin(4 * n80);
            hop_a(xp(uPolA + c * COL + 8 * min(ln, 24u) + lag<DELAY_L>(sb)), pub0, osa, ln < 24, 5 * ch);
            TST(2);
            CSTAMP(6);
            float acc[5][4] = {};
            const uint2 b0 = lds64(oa), b1 = lds64(oa + 8), b2 = lds64(oa + 16);
#pragma unroll
            for (int m = 0; m < 5; m++) mmaA(acc[m], Wo[m][0], b0.x, b0.y);
#pragma unroll
            for (int m = 0; m < 5; m++) mmaA(acc[m], Wo[m][1], b1.x, b1.y);
#pragma unroll
            for (int m = 0; m < 5; m++) mmaA(acc[m], Wo[m][2], b2.x, b2.y);
#pragma unroll
            for (int m = 0; m < 5; m++) sts64_if(!(td & 2), ra + 64 * m, (td & 1) ? acc[m][1] : acc[m][0], (td & 1) ? acc[m][3] : acc[m][2]);
        }
        CSTAMP(7);
        float x1 = 0.f;
        uint32_t xr, fl, pubC, pubC2;
        uint32_t xab = 0;
        auto prepC = [&] {
            IDS();
            xr = pin(sb + S_XB + 48 * (ln & 15));
            pubC = pin(uPubC + (t4 & 1) * COL + 192 * (wp >> 1) + 64 * (wp & 1) + 8 * q8);
            pubC2 = pin(uPubC + (t4 & 1) * COL + ((t4 & 2) ? 192 * (wp >> 1) + 128 + 4 * (wp & 1) + 8 * q8 : 768 + 2 * ((q8 + 1) & 6)));
            fl = pin(((t4 & 1) ? par1 : pub0) | (t4 >= 2 || (wp == 7 && q8 < 4 && q8 != 2 - t4) ? 2 : 0));
        };
        if (actc) {
            bar_main();
            CSTAMP(8);
            uint32_t r[8];
#pragma unroll
            for (int s = 0; s < 8; s++) r[s] = lds32(n4 + (5 * uCol - 4 * sb + S_RED + 640 * s));
            stp32_if(true, xp(uPubB + n4), sum8(r), parc);
            CSTAMP(9);
            prepC();
            xab = pin(a_pos(n4 / 4) | (b_pos<40>(n4 / 4) << 16));
            const uint32_t xas = pin(3 * uCol - 2 * sb + S_XA + 192 + (xab & 0xffff)), xbs = pin(6 * uCol - 5 * sb + S_XB + (xab >> 16));
            const float x0 = cc ? ldsf(sb + S_XCAR + n4) : bf_lo(lds16(sb + S_X0 + 160 * (ch & 3) + n4 / 2));
            gather16(xp(uPolB + n4 + lag<DELAY_G>(sb)), parc, 5 * ch + 1, [&](float y, uint32_t) {
                const uint32_t x = pack2(x0 + bfr(y), 0.f);
                sts16(xbs, x);
                sts16(xas, x);
                x1 = bf_lo(x);
                return 0u;
            });
            CSTAMP(10);
        } else {
            bar_main();
            prepC();
        }
        auto stats = [&](uint32_t xa, const uint4& b, uint32_t b4) {
            float a[4] = {};
            const uint4 p0 = lds128(xa), p1 = lds128(xa + 16);
            const uint2 p2 = lds64(xa + 32);
            mmaV(a, p0, b.x, b.y); mmaV(a, p1, b.z, b.w); mma8(a, p2.x, p2.y, b4);
            return a[0] + a[3];
        };
        {
            auto gate_up = [&](auto with_stats) {
                bar_main();
                TST(3);
                CSTAMP(11);
                const uint4 b = lds128(xr);
                const uint32_t b4 = lds32(xr + 16);
                float acc[3][4] = {}, st = 0.f;
                if (with_stats.value) st = stats(xr + (S_XA - S_XB), b, b4);
                mul80(acc, Wgu, b, b4);
                stp64_if(!(td & 2), xp(pubC), tagw(acc[0][0] + acc[0][3], fl & 1), tagw(acc[1][0] + acc[1][3], fl & 1));
                stp32_if(fl > 1, xp(pubC2), !with_stats.value || (td & 2) ? acc[2][0] + acc[2][3] : st, fl & 1);
            };
            if (wp == 7) gate_up(std::true_type()); else gate_up(std::false_type());
        }
        CSTAMP(12);
        float mean = 0.f, den = 1.f;
        {
            IDS();
            const uint32_t wa = pin(sb + S_WD + ((ln & 7) + 48 * ((ln >> 3) & 1) + 8 * (ln >> 4)) * 160 + (wp < 7 ? 16 * wp : 128));
            const uint32_t pubD = pin(uPubD + (t4 & 1) * COL + 16 * (t4 & 2) + 4 * q8 + (fl & 1)), ha = xr + (S_HS - S_XB);
            auto down = [&](const uint32_t (&W)[3][4], const uint4& h0, const uint2& h1) {
                float a0[4] = {}, a1[4] = {}, a2[4] = {};
                mmaA(a0, W[0], h0.x, h0.y); mmaA(a1, W[1], h0.z, h0.w); mmaA(a2, W[2], h1.x, h1.y);
                return ((a0[0] + a0[3]) + (a1[0] + a1[3])) + (a2[0] + a2[3]);
            };
            if (wp < 6) {
                uint32_t Wd[3][4];
                auto ldd = [&] {
#pragma unroll
                    for (int s = 0; s < 3; s++) ldsm4t(Wd[s], wa + s * 2560);
                };
                if (actc) {
                    const uint32_t hsa = pin(6 * uCol - 5 * sb + S_HS + b_pos<48>(n96));
                    const uint32_t src0 = uPolC + lag<DELAY_C>(sb);
                    const char* srcv = xp(src0 + 8 * n96);
                    const char* src = xp(src0 + (ln & 1) * HALF);
                    float gt, up;
                    int guard = 0;
                    bool again;
                    do {
                        uint2 v[8], st[4];
#pragma unroll
                        for (int s = 0; s < 4; s++) st[s] = ldp64(src + 768 + s * 1024);
#pragma unroll
                        for (int s = 0; s < 8; s++) v[s] = ldp64(srcv + (s >> 2) * HALF + (s & 3) * 1024);
                        float sx = (asf(st[0].x) + asf(st[1].x)) + (asf(st[2].x) + asf(st[3].x)), sq = (asf(st[0].y) + asf(st[1].y)) + (asf(st[2].y) + asf(st[3].y));
                        sx += __shfl_xor_sync(~0u, sx, 1); sq += __shfl_xor_sync(~0u, sq, 1);
                        const uint2 cs = lds64(sb + S_CSGU - 768 * cc + 8 * td + ((st[0].x ^ parc) & 1) * 8);
                        again = __any_sync(~0u, (or3(chk4(st, parc), chk8(v, parc), chk8y(v, parc)) & 1) != 0);
                        ln_stats(sx, sq, mean, den);
                        const float rd = rcp(den);
                        gt = fmaf(-mean, asf(cs.x), sum8x(v)); up = fmaf(-mean, asf(cs.y), sum8y(v));
                        ldd();
                        gt *= rd; up *= rd;
                        keep(gt); keep(up);
                    } while (again & (++guard < SPIN_LIMIT));
                    CSTAMP(13);
                    SWEEPS(5 * ch + 2, guard - 1);
                    gt = bfr(gt);
                    const uint32_t h = pack2(bfr(gt * sigmoidf_(gt)) * bfr(up), 0.f);
                    sts16(hsa, h);
                    CSTAMP(14);
                } else ldd();
                bar_main();
                TST(4);
                CSTAMP(15);
                const uint4 h0 = lds128(ha);
                const uint2 h1 = lds64(ha + 16);
                stp32_if(!(td & 2), xp(pubD & ~1u), down(Wd, h0, h1), pubD & 1);
            } else {
                stsvol(sb + S_GATE, ch + 1);
                uint32_t Wd[2][3][4];
#pragma unroll
                for (int s = 0; s < 6; s++) ldsm4t(Wd[s / 3][s % 3], wa + (s / 3) * 16 + (s % 3) * 2560);
                uint32_t v = 0;
                if (wp == 6 ? has0 : has1) {
                    const uint32_t par = wp == 6 ? par0 : par1;
                    const char* src = xp(uPolC + 768 + (ln & 4) * (HALF / 4) + (ln & 3) * 1024 + 4 * min(ln >> 3, 2u) + lag<DELAY_C>(sb));
                    int guard = 0;
                    do v = ldp32(src); while (__any_sync(~0u, (v ^ par) & 1) && ++guard < SPIN_LIMIT);
                }
                bar_main();
                const uint4 h0 = lds128(ha);
                const uint2 h1 = lds64(ha + 16);
                const float d0 = down(Wd[0], h0, h1), d1 = down(Wd[1], h0, h1);
                stp32_if(true, xp(pubD & ~1u), (td & 2) ? d1 : d0, pubD & 1);
                if (wp == 6 ? has0 : has1) {
                    float sx = asf(v);
                    sx += __shfl_xor_sync(~0u, sx, 1); sx += __shfl_xor_sync(~0u, sx, 2); sx += __shfl_xor_sync(~0u, sx, 4);
                    const float sq = __shfl_sync(~0u, sx, 8), xw = __shfl_sync(~0u, sx, 16);
                    ln_stats(sx, sq, mean, den);
                    const float r = bfr(fmaf(-mean, ldsf(sb + S_SWR), xw) * rcp(den));
                    sts32_if(ln == 0, sb + S_STAT + 4 * (wp - 6), __float_as_uint(bfr(sigmoidf_(r))) | (ch + 1));
                }
            }
        }
        CSTAMP(16);
        uint32_t pubE;
        {
            IDS();
            pubE = pin(uPubE + (t4 < 3 ? (wp >> 2) * COL + 192 * (wp & 3) + 64 * t4 + 8 * q8 : (q8 >> 2) * COL + 768 + 4 * (q8 & 1)));
            xr = pin(sb + S_XB + 48 * (ln & 7));
            if (actc && (cc == 0 || g == 0)) {
                const uint32_t m4 = 4 * n80;
                const uint32_t xas = pin(3 * uCol - 2 * sb + S_XA + 192 + a_pos(n80)), xbs = pin(6 * uCol - 5 * sb + S_XB + b_pos<40>(n80));
                const float lnx = __uint_as_float(pin(__float_as_uint(bfr(__fdiv_rn(bfr(x1 - mean), den)))));
                uint32_t x2;
                gather16(xp(uPolD + m4 + lag<DELAY_D>(sb)), parc, 5 * ch + 3, [&](float y, uint32_t z) {
                    const uint32_t gate = ldsvol(sb + S_STAT + 4 * cc + z);
                    x2 = pack2(x1 + bfr(lnx + bfr(bfr(y) * bf_hi(gate))), 0.f);
                    sts16(xbs, x2);
                    sts16(xas, x2);
                    return (uint32_t)((gate & 7) != ch + 1);
                });
                CSTAMP(17);
                if (cc) reinterpret_cast<unsigned short*>(P.out)[640 * (ch - 1) + 80 * i + n80] = (unsigned short)x2;
                x1 = bf_lo(x2);
            }
        }
        CSTAMP(18);
        if (!has0) break;
        {
            auto qproj = [&](auto with_stats) {
                bar_main();
                TST(5);
                CSTAMP(19);
                const uint32_t t4 = td & 3;
                const uint4 b = lds128(xr);
                const uint32_t b4 = lds32(xr + 16);
                float acc[6][4] = {}, st = 0.f;
                if (with_stats.value) st = stats(xr + (S_XA - S_XB), b, b4);
                mul80(acc, Wq, b, b4);
                const float v0 = sel4(t4, acc[0][0] + acc[0][3], acc[2][0] + acc[2][3], acc[4][0] + acc[4][3], acc[4][0] + acc[4][3]);
                const float v1 = sel4(t4, acc[1][0] + acc[1][3], acc[3][0] + acc[3][3], acc[5][0] + acc[5][3], acc[5][0] + acc[5][3]);
                if (with_stats.value) stp32_if((td & 11) == 3, xp(pubE), st, par0);
                stp64_if(t4 < 3, xp(pubE), tagw(v0, par0), tagw(v1, par0));
            };
            if (wp == 7) qproj(std::true_type()); else qproj(std::false_type());
            sts32_if(td < 80, sb + S_XCAR + 4 * td, __float_as_uint(x1));
        }
        CSTAMP(20);
        auto pass2 = [&](auto d0, auto d1, auto d2) {
            constexpr int D0 = d0.value, D1 = d1.value, D = D0 + D1 + d2.value;
            IDS();
            const uint32_t ua = sb + k_place(ch, wp & 6) * SLOT + (wp & 1) * UNIT, k0 = k_off(ln);
            uint32_t kf[12][2][4];
            auto ldk = [&](int s) { const uint32_t a = (k0 ^ (32 * (s / 3))) + (ua + 1024 * (s % 3)); ldsm4(kf[s][0], a); ldsm4(kf[s][1], a + SLOT); };
            if (!(mbar_try(sb + S_FK + 8 * (wp & 6), par1) & mbar_try(sb + S_FK + 8 * (wp | 1), par1))) { mbar_wait(sb + S_FK + 8 * (wp & 6), par1); mbar_wait(sb + S_FK + 8 * (wp | 1), par1); }
#pragma unroll
            for (int s = 0; s < D0; s++) ldk(s);
            if (wp < 6) {
                const uint32_t qsa = pin(sb + S_QS + 384 * ch + q_pos(td));
                const uint32_t src0 = uPolE + lag<(D1 > 0 ? 0 : DELAY_E)>(sb);
                const char* srcv = xp(src0 + 4 * td);
                const char* src = xp(src0 + (ln & 1) * HALF);
                uint32_t v[8]; uint2 st[4];
                auto look = [&] {
#pragma unroll
                    for (int s = 0; s < 4; s++) st[s] = ldp64(src + 768 + s * 1024);
#pragma unroll
                    for (int s = 0; s < 8; s++) v[s] = ldp32(srcv + (s >> 2) * HALF + (s & 3) * 1024);
                };
                if (D1 > 0) {
                    look();
                    __syncwarp();
#pragma unroll
                    for (int s = D0; s < D0 + D1; s++) ldk(s);
                }
                int guard = 0;
                while (true) {
                    if (D1 == 0) look();
                    float sx = (asf(st[0].x) + asf(st[1].x)) + (asf(st[2].x) + asf(st[3].x)), sq = (asf(st[0].y) + asf(st[1].y)) + (asf(st[2].y) + asf(st[3].y));
                    sx += __shfl_xor_sync(~0u, sx, 1); sq += __shfl_xor_sync(~0u, sq, 1);
                    const float cs = ldsf(sb + S_CSQ + 4 * td + ((st[0].x ^ par0) & 1) * 4);
                    const bool again = __any_sync(~0u, ((chk8(v, par0) | chk4(st, par0)) & 1) != 0);
                    ln_stats(sx, sq, mean, den);
                    const uint32_t q = pack2(fmaf(-mean, cs, sum8(v)) * rcp(den), 0.f);
                    sts16(qsa, q);
                    if (!(again & (++guard < SPIN_LIMIT))) break;
                    if (D1 > 0) look();
                }
                SWEEPS(5 * ch + 4, guard - 1);
                CSTAMP(22);
            } else {
#pragma unroll
                for (int s = D0; s < D0 + D1; s++) ldk(s);
            }
#pragma unroll
            for (int s = D0 + D1; s < D; s++) ldk(s);
            if (D == 12) { __syncwarp(); arrive_if(ln == 0, sb + S_RELK); }
            bar_main();
            TST(6);
            CSTAMP(1);
            uint2 q = lds64(sb + S_QS + 384 * ch + 8 * ln);
            float acc[2][4] = {};
            auto ldv1 = [&](int k) { ldsm4t(vf[k / 3][k % 3], voff[k % 3] + (sb + v_place(ch, k / 3) * SLOT)); };
            auto ldv = [&](int s) { ldv1(3 * s); ldv1(3 * s + 1); ldv1(3 * s + 2); };
            constexpr int V0 = 13 - D, NV = (2 * (D - 1)) / 3 < 5 ? (2 * (D - 1)) / 3 : 5;
#pragma unroll
            for (int s = 0; s < 12; s++) {
                const bool m = q8 == (s & 7);
                const uint32_t b0 = m ? q.x : 0u, b1 = m ? q.y : 0u;
                if (s == 7) q = lds64(sb + S_QS + 384 * ch + 8 * ln + 256);
                mmaA(acc[0], kf[s][0], b0, b1);
                mmaA(acc[1], kf[s][1], b0, b1);
                if (s >= 1 && s + D - 1 < 12) ldk(s + D - 1);
                if (s >= 1 && s + D - 1 == 11) { __syncwarp(); arrive_if(ln == 0, sb + S_RELK); }
                if (s == V0) vaddr(voff);
                if (s >= V0 && 2 * (s - V0) < 3 * NV) ldv1(9 + 2 * (s - V0));
                if (s >= V0 && 2 * (s - V0) + 1 < 3 * NV) ldv1(10 + 2 * (s - V0));
            }
            CSTAMP(24);
            {
                const float v0 = acc[0][0] + acc[0][1], v1 = acc[0][2] + acc[0][3], v2 = acc[1][0] + acc[1][1], v3 = acc[1][2] + acc[1][3];
                const bool hi = t4 & 2, od = t4 & 1;
                const float u0 = (hi ? v2 : v0) + __shfl_xor_sync(~0u, hi ? v0 : v2, 2), u1 = (hi ? v3 : v1) + __shfl_xor_sync(~0u, hi ? v1 : v3, 2);
                const float s = (od ? u1 : u0) + __shfl_xor_sync(~0u, od ? u0 : u1, 1);
                CSTAMP(2);
                probs(scaled(s), sb + S_PS + PS_PASS, wp, ln);
                CSTAMP(3);
            }
            bar_main();
            TST(10);
            CSTAMP(4);
            values(vf, [&](int s) { if (s >= (NV > 1 ? 2 : 1) && s + NV + (NV > 1 ? 1 : 2) < 8) ldv(s + NV + (NV > 1 ? 1 : 2)); }, sb + S_PS + PS_PASS, 1, par0);
            arrive_if(ln == 0, sb + S_RELV);
        };
        if (LAST0 > 0 && ch == 3) {
            pass2(std::integral_constant<int, LAST0>(), std::integral_constant<int, LAST1>(), std::integral_constant<int, LAST2>());
#pragma unroll
            for (int m = 0; m < 60; m++) { uint32_t& r = m % 10 < 8 ? Wq[m / 10].a[(m % 10) / 4][m % 2 + 2 * ((m % 10) / 2 % 2)] : Wq[m / 10].c[m % 2]; r = 0; opaque(r); }
        } else pass2(std::integral_constant<int, KPRE>(), std::integral_constant<int, 0>(), std::integral_constant<int, KPRE2>());
        TST(11);
        CSTAMP(23);
    }
    sts32_if(td == 255, sb + S_GATE, 6);
    TSTAMP(3);
}

typedef CUresult (*EncodeFn)(CUtensorMap*, CUtensorMapDataType, cuuint32_t, void*, const cuuint64_t*, const cuuint64_t*, const cuuint32_t*,
                             const cuuint32_t*, CUtensorMapInterleave, CUtensorMapSwizzle, CUtensorMapL2promotion, CUtensorMapFloatOOBfill);

void make_map(EncodeFn enc, CUtensorMap* m, const void* base, uint64_t cols, uint64_t rows, uint32_t box_cols, uint32_t box_rows, bool swizzle) {
    cuuint64_t dims[2] = {cols, rows};
    cuuint64_t strides[1] = {cols * 2};
    cuuint32_t box[2] = {box_cols, box_rows};
    cuuint32_t es[2] = {1, 1};
    enc(m, CU_TENSOR_MAP_DATA_TYPE_BFLOAT16, 2, const_cast<void*>(base), dims, strides, box, es, CU_TENSOR_MAP_INTERLEAVE_NONE,
        swizzle ? CU_TENSOR_MAP_SWIZZLE_128B : CU_TENSOR_MAP_SWIZZLE_NONE, swizzle ? CU_TENSOR_MAP_L2_PROMOTION_NONE : WPROMO, CU_TENSOR_MAP_FLOAT_OOB_FILL_NONE);
}

}

extern "C" void kernel_launch(void* const* d_in, const int* in_sizes, int n_in, void* d_out, int out_size) {
    (void)in_sizes; (void)n_in; (void)out_size;
    static EncodeFn enc = nullptr;
    if (!enc) {
        void* f = nullptr;
        cudaDriverEntryPointQueryResult q;
        cudaGetDriverEntryPoint("cuTensorMapEncodeTiled", &f, cudaEnableDefault, &q);
        enc = (EncodeFn)f;
        cudaFuncSetAttribute(fused_kernel, cudaFuncAttributeMaxDynamicSharedMemorySize, SMEM_BYTES);
    }
    Params P;
    P.x = (const __nv_bfloat16*)d_in[0]; P.k = (const __nv_bfloat16*)d_in[1]; P.v = (const __nv_bfloat16*)d_in[2];
    P.wr = (const __nv_bfloat16*)d_in[6];
    P.out = (__nv_bfloat16*)d_out;
    Maps M;
    {
        cuuint64_t dims[4] = {64, 8, 3, (cuuint64_t)KV_BATCH_KEYS / 2}, strides[3] = {384, 128, 3072};
        cuuint32_t box[4] = {64, 8, 3, 2}, es[4] = {1, 1, 1, 1};
        enc(&M.k, CU_TENSOR_MAP_DATA_TYPE_BFLOAT16, 4, d_in[1], dims, strides, box, es, CU_TENSOR_MAP_INTERLEAVE_NONE, CU_TENSOR_MAP_SWIZZLE_128B,
            CU_TENSOR_MAP_L2_PROMOTION_NONE, CU_TENSOR_MAP_FLOAT_OOB_FILL_NONE);
        box[3] = 1;
        enc(&M.kh, CU_TENSOR_MAP_DATA_TYPE_BFLOAT16, 4, d_in[1], dims, strides, box, es, CU_TENSOR_MAP_INTERLEAVE_NONE, CU_TENSOR_MAP_SWIZZLE_128B,
            CU_TENSOR_MAP_L2_PROMOTION_NONE, CU_TENSOR_MAP_FLOAT_OOB_FILL_NONE);
    }
    make_map(enc, &M.v, P.v, 64, (uint64_t)12 * KV_BATCH_KEYS, 64, 96, true);
    make_map(enc, &M.vu, P.v, 64, (uint64_t)12 * KV_BATCH_KEYS, 64, 48, true);
    make_map(enc, &M.wq, d_in[3], 6144, 640, 192, 40, false);
    make_map(enc, &M.wo, d_in[4], 640, 6144, 80, 96, false);
    make_map(enc, &M.wg, d_in[7], 1536, 640, 96, 80, false);
    make_map(enc, &M.wu, d_in[8], 1536, 640, 96, 80, false);
    make_map(enc, &M.wd, d_in[9], 640, 1536, 80, 96, false);
    fused_kernel<<<NCTA, NTHR, SMEM_BYTES, cudaStreamPerThread>>>(P, M);
}
```

```cpp
#include <cuda_runtime.h>
#include <cuda.h>
#include <cuda_bf16.h>
#include <stdint.h>
#include <type_traits>

namespace {

constexpr int NCTA = 128;
constexpr int NTHR = 384;
constexpr int UNIT = 6144;
constexpr int SLOT = 12288;
#define TAU 4100
#define TAUW 3900
#define TAU0 3900
#define PF0 2
#define PFMAP 1
#define ZPOS 1
#define LOOK1 0
#define LOOK2 0
#define SLACK 8000
#define SLACK0 SLACK
#define TSH 0
#define HOP1_NS 200
#define RELR_AT 0
#define PSLEEP 0
#define KRE_HALF 0
#define TMIN 2400
#define T_LEAD 0
#define WIN_W 3
#define WIN_S 4
#define WIN_U 10
#define RFR_ON 1
#define KRE_N1 0
#define KRE_TAU1 2500
#define RFR_TAU 6400
#define VPF 5
#define KRE_GATE 0
#define KRE_GATE3 KRE_GATE
#define JFREE 16
#define TFREE 0
#define KRE_TAU 3000
#define KRE_TAU3 KRE_TAU
#define HDEPTH 3
#define LAST0 3
#define ORDER_L 0x76543210
#define ORDER_R 0x76543210
#define LAST_LATE 0xaa8
#define LAST1 4
#define LAST2 3
#define FSTEP 4
#define SPEC 1
#define PV1PIPE 0
#define HOPA0 6
#define HOPA1 6
#define WPROMO CU_TENSOR_MAP_L2_PROMOTION_NONE
#define KPRE 1
#define KPRE2 3
#define DELAY_G 6
#define DELAY_L 5
#define DELAY_C 3
#define DELAY_D 6
#define DELAY_E 3
#define REG_LO "40"
#define REG_HI "232"
#define SPIN_LOG 17
constexpr int SPIN_LIMIT = 1 << SPIN_LOG;

__host__ __device__ constexpr uint32_t pairL(uint32_t region, uint32_t c, uint32_t g) { return (g & 1) | ((g >> 1) << 2) | (c << 5) | (region << 6); }
__host__ __device__ constexpr uint32_t pairG(uint32_t d, uint32_t c, uint32_t i) { return (i & 1) | ((i >> 1) << 2) | (d << 4) | (c << 5) | (3u << 6); }
constexpr uint32_t RA = 0, RC = 1, RE = 2, HALF = 16384, COPY = 4096, PMASK = 0x59;
constexpr uint32_t XS = 0;
constexpr uint32_t XS2 = XS + 128 * 7680;
constexpr uint32_t XSEND = XS2 + 128 * 768;
__device__ uint4 g_s[XSEND / 16];
__device__ uint4 g_x[(4u << 20) / 16];
#define SWEEPS(k, n) do {} while (0)

constexpr uint32_t S_WD = 16 * SLOT;
constexpr uint32_t S_DUMMY = S_WD + 15360;
constexpr uint32_t S_BAR = S_DUMMY + 4096;
constexpr uint32_t S_FV = S_BAR, S_FK = S_FV + 64, S_RING = S_FK + 64, S_DBAR = S_RING + 48, S_WFULL = S_DBAR + 32, S_QRDY = S_WFULL + 88;
constexpr uint32_t S_RELK = S_QRDY + 8, S_RELV = S_RELK + 8, S_RELR = S_RELV + 8, S_RELW = S_RELR + 8, S_SCO = S_RELW + 24;
constexpr uint32_t S_OS1 = S_SCO + 8;
constexpr uint32_t S_ZERO = S_OS1 + 8;
constexpr uint32_t S_KF = S_ZERO + 8;
constexpr uint32_t S_TOK = S_KF + 8;
constexpr uint32_t S_SIDE = S_TOK + 80, S_GATE = S_SIDE + 4;
constexpr uint32_t S_STAT = S_GATE + 12, S_SWR = S_STAT + 16;
constexpr uint32_t S_XCAR = S_STAT + 32;
constexpr uint32_t S_CSQ = S_XCAR + 320;
constexpr uint32_t S_CSGU = S_CSQ + 768;
constexpr uint32_t S_RED = S_CSGU + 768;
constexpr uint32_t S_L0 = S_RED;
constexpr uint32_t S_OS = S_RED + 5120;
constexpr uint32_t S_PS = S_OS + 1536;
constexpr uint32_t PS_MAX = 512, PS_PASS = 544;
constexpr uint32_t S_QS = S_PS + 2 * PS_PASS;
constexpr uint32_t S_XB = S_QS + 1536;
constexpr uint32_t S_XA = S_XB + 768;
constexpr uint32_t S_HS = S_XA + 768;
constexpr uint32_t S_X0 = S_HS + 768;
constexpr uint32_t S_SC = S_X0 + 640;
constexpr uint32_t S_TM = S_SC + 512;
constexpr int SMEM_BYTES = S_TM + 256;
static_assert(SMEM_BYTES <= 232448 && S_STAT % 16 == 0 && S_RED % 16 == 0 && S_XB % 16 == 0 && S_HS % 16 == 0 && S_PS % 16 == 0 && S_QS % 16 == 0, "smem");
static_assert(S_SCO == S_BAR + 44 * 8 && S_RELK == S_BAR + 38 * 8, "barriers");
constexpr uint32_t ST_WQ = 3 * SLOT, ST_WG = 8 * SLOT, ST_WO = 11 * SLOT;

__device__ __forceinline__ uint32_t smem_u32(const void* p) { return (uint32_t)__cvta_generic_to_shared(p); }
__device__ __forceinline__ void mbar_init(uint32_t bar, uint32_t cnt) { asm volatile("mbarrier.init.shared::cta.b64 [%0], %1;" :: "r"(bar), "r"(cnt) : "memory"); }
__device__ __forceinline__ void mbar_expect(uint32_t bar, uint32_t bytes) { asm volatile("mbarrier.arrive.expect_tx.shared::cta.b64 _, [%0], %1;" :: "r"(bar), "r"(bytes) : "memory"); }
__device__ __forceinline__ void mbar_arrive(uint32_t bar) { asm volatile("mbarrier.arrive.shared::cta.b64 _, [%0];" :: "r"(bar) : "memory"); }
__device__ __forceinline__ bool mbar_try(uint32_t bar, uint32_t parity) {
    uint32_t ok;
    asm volatile("{\n .reg .pred p;\n mbarrier.try_wait.parity.shared::cta.b64 p, [%1], %2;\n selp.u32 %0, 1, 0, p;\n}" : "=r"(ok) : "r"(bar), "r"(parity) : "memory");
    return ok != 0;
}
__device__ __forceinline__ bool mbar_test(uint32_t bar, uint32_t parity) {
    uint32_t ok;
    asm volatile("{\n .reg .pred p;\n mbarrier.test_wait.parity.shared::cta.b64 p, [%1], %2;\n selp.u32 %0, 1, 0, p;\n}" : "=r"(ok) : "r"(bar), "r"(parity) : "memory");
    return ok != 0;
}
__device__ __forceinline__ void mbar_wait(uint32_t bar, uint32_t parity) {
    int n = 0;
    while (!mbar_try(bar, parity) && ++n < SPIN_LIMIT) {}
}
__device__ __forceinline__ unsigned long long gtime() { unsigned long long t; asm volatile("mov.u64 %0, %globaltimer;" : "=l"(t)); return t; }
__device__ __forceinline__ uint32_t gtime32() { uint32_t t; asm volatile("mov.u32 %0, %globaltimer_lo;" : "=r"(t)); return t; }
__device__ __forceinline__ void bar_main() { asm volatile("bar.sync 1, 256;" ::: "memory"); }

__device__ __forceinline__ void mma16816(float (&c)[4], uint32_t a0, uint32_t a1, uint32_t a2, uint32_t a3, uint32_t b0, uint32_t b1) {
    asm("mma.sync.aligned.m16n8k16.row.col.f32.bf16.bf16.f32 {%0,%1,%2,%3}, {%4,%5,%6,%7}, {%8,%9}, {%0,%1,%2,%3};"
        : "+f"(c[0]), "+f"(c[1]), "+f"(c[2]), "+f"(c[3]) : "r"(a0), "r"(a1), "r"(a2), "r"(a3), "r"(b0), "r"(b1));
}
__device__ __forceinline__ void mmaA(float (&c)[4], const uint32_t (&a)[4], uint32_t b0, uint32_t b1) { mma16816(c, a[0], a[1], a[2], a[3], b0, b1); }
__device__ __forceinline__ void mmaAv(float (&c)[4], const uint32_t (&a)[4], uint32_t b0, uint32_t b1) {
    asm volatile("mma.sync.aligned.m16n8k16.row.col.f32.bf16.bf16.f32 {%0,%1,%2,%3}, {%4,%5,%6,%7}, {%8,%9}, {%0,%1,%2,%3};"
        : "+f"(c[0]), "+f"(c[1]), "+f"(c[2]), "+f"(c[3]) : "r"(a[0]), "r"(a[1]), "r"(a[2]), "r"(a[3]), "r"(b0), "r"(b1) : "memory");
}
__device__ __forceinline__ void mma8(float (&c)[4], uint32_t a0, uint32_t a1, uint32_t b0) {
    asm("mma.sync.aligned.m16n8k8.row.col.f32.bf16.bf16.f32 {%0,%1,%2,%3}, {%4,%5}, {%6}, {%0,%1,%2,%3};"
        : "+f"(c[0]), "+f"(c[1]), "+f"(c[2]), "+f"(c[3]) : "r"(a0), "r"(a1), "r"(b0));
}
struct W80 { uint32_t a[2][4], c[2]; };
template <int N> __device__ __forceinline__ void mul80(float (&acc)[N][4], const W80 (&W)[N], const uint4& b, uint32_t b4) {
#pragma unroll
    for (int m = 0; m < N; m++) mmaA(acc[m], W[m].a[0], b.x, b.y);
#pragma unroll
    for (int m = 0; m < N; m++) mmaA(acc[m], W[m].a[1], b.z, b.w);
#pragma unroll
    for (int m = 0; m < N; m++) mma8(acc[m], W[m].c[0], W[m].c[1], b4);
}
__device__ __forceinline__ void ldsm2t(uint32_t (&r)[2], uint32_t addr) {
    asm volatile("ldmatrix.sync.aligned.m8n8.x2.trans.shared.b16 {%0,%1}, [%2];" : "=r"(r[0]), "=r"(r[1]) : "r"(addr) : "memory");
}
__device__ __forceinline__ void mmaV(float (&c)[4], const uint4& a, uint32_t b0, uint32_t b1) { mma16816(c, a.x, a.y, a.z, a.w, b0, b1); }
__device__ __forceinline__ void ldsm4(uint32_t (&r)[4], uint32_t addr) {
    asm volatile("ldmatrix.sync.aligned.m8n8.x4.shared.b16 {%0,%1,%2,%3}, [%4];" : "=r"(r[0]), "=r"(r[1]), "=r"(r[2]), "=r"(r[3]) : "r"(addr) : "memory");
}
__device__ __forceinline__ void ldsm4t(uint32_t (&r)[4], uint32_t addr) {
    asm volatile("ldmatrix.sync.aligned.m8n8.x4.trans.shared.b16 {%0,%1,%2,%3}, [%4];" : "=r"(r[0]), "=r"(r[1]), "=r"(r[2]), "=r"(r[3]) : "r"(addr) : "memory");
}
__device__ __forceinline__ uint32_t lds16(uint32_t a) { uint16_t v; asm volatile("ld.shared.u16 %0, [%1];" : "=h"(v) : "r"(a) : "memory"); return v; }
__device__ __forceinline__ uint32_t lds32(uint32_t a) { uint32_t v; asm volatile("ld.shared.u32 %0, [%1];" : "=r"(v) : "r"(a) : "memory"); return v; }
__device__ __forceinline__ float ldsf(uint32_t a) { return __uint_as_float(lds32(a)); }
__device__ __forceinline__ uint2 lds64(uint32_t a) { uint2 v; asm volatile("ld.shared.v2.u32 {%0,%1}, [%2];" : "=r"(v.x), "=r"(v.y) : "r"(a) : "memory"); return v; }
__device__ __forceinline__ uint4 lds128(uint32_t a) { uint4 v; asm volatile("ld.shared.v4.u32 {%0,%1,%2,%3}, [%4];" : "=r"(v.x), "=r"(v.y), "=r"(v.z), "=r"(v.w) : "r"(a) : "memory"); return v; }
__device__ __forceinline__ int ldsvol(uint32_t a) { int v; asm volatile("ld.volatile.shared.u32 %0, [%1];" : "=r"(v) : "r"(a) : "memory"); return v; }
__device__ __forceinline__ void stsvol(uint32_t a, int v) { asm volatile("st.volatile.shared.u32 [%0], %1;" :: "r"(a), "r"(v) : "memory"); }
__device__ __forceinline__ void sts_hi16(uint32_t a, float v) { asm volatile("{\n .reg .b16 lo, hi;\n mov.b32 {lo, hi}, %1;\n st.shared.u16 [%0], hi;\n}" :: "r"(a), "r"(__float_as_uint(v)) : "memory"); }
__device__ __forceinline__ void sts16(uint32_t a, uint32_t v) { asm volatile("st.shared.u16 [%0], %1;" :: "r"(a), "r"(v) : "memory"); }
__device__ __forceinline__ void sts32(uint32_t a, uint32_t v) { asm volatile("st.shared.u32 [%0], %1;" :: "r"(a), "r"(v) : "memory"); }
__device__ __forceinline__ void stsf(uint32_t a, float v) { sts32(a, __float_as_uint(v)); }
__device__ __forceinline__ void sts64(uint32_t a, uint32_t x, uint32_t y) { asm volatile("st.shared.v2.u32 [%0], {%1,%2};" :: "r"(a), "r"(x), "r"(y) : "memory"); }

__device__ __forceinline__ void sts_hi16_if(bool p, uint32_t a, float v) {
    asm volatile("{\n .reg .pred p;\n .reg .b16 lo, hi;\n setp.ne.u32 p, %2, 0;\n mov.b32 {lo, hi}, %1;\n @p st.shared.u16 [%0], hi;\n}" :: "r"(a), "r"(__float_as_uint(v)), "r"((uint32_t)p) : "memory");
}
__device__ __forceinline__ void sts32_if(bool p, uint32_t a, uint32_t v) {
    asm volatile("{\n .reg .pred p;\n setp.ne.u32 p, %2, 0;\n @p st.shared.u32 [%0], %1;\n}" :: "r"(a), "r"(v), "r"((uint32_t)p) : "memory");
}
__device__ __forceinline__ void sts64_if(bool p, uint32_t a, float x, float y) {
    asm volatile("{\n .reg .pred p;\n setp.ne.u32 p, %3, 0;\n @p st.shared.v2.f32 [%0], {%1,%2};\n}" :: "r"(a), "f"(x), "f"(y), "r"((uint32_t)p) : "memory");
}
__device__ __forceinline__ void arrive_if(bool p, uint32_t bar) {
    asm volatile("{\n .reg .pred p;\n setp.ne.u32 p, %1, 0;\n @p mbarrier.arrive.shared::cta.b64 _, [%0];\n}" :: "r"(bar), "r"((uint32_t)p) : "memory");
}
__device__ __forceinline__ void opaque(uint32_t& v) { asm volatile("" : "+r"(v)); }
__device__ __forceinline__ void keep(uint32_t& v) { asm volatile("" : "+r"(v)); }
__device__ __forceinline__ void keep(float& v) { asm volatile("" : "+f"(v)); }
template <class T> __device__ __forceinline__ void keep(T*& v) { asm volatile("" : "+l"(v)); }

__device__ __forceinline__ uint32_t ldp32(const char* p) { uint32_t v; asm volatile("ld.relaxed.gpu.global.u32 %0, [%1];" : "=r"(v) : "l"(p) : "memory"); return v; }
__device__ __forceinline__ uint2 ldp64(const char* p) {
    uint2 v; asm volatile("{\n .reg .b64 d;\n ld.relaxed.gpu.global.b64 d, [%2];\n mov.b64 {%0,%1}, d;\n}" : "=r"(v.x), "=r"(v.y) : "l"(p) : "memory"); return v;
}
__device__ __forceinline__ uint32_t tagw(float f, uint32_t par) { return (__float_as_uint(f) & ~1u) | par; }
__device__ __forceinline__ void stp32(char* p, float a, uint32_t par) { asm volatile("st.relaxed.gpu.global.u32 [%0], %1;" :: "l"(p), "r"(tagw(a, par)) : "memory"); }
__device__ __forceinline__ void stp64(char* p, float a, float b, uint32_t par) {
    asm volatile("{\n .reg .b64 d;\n mov.b64 d, {%1,%2};\n st.relaxed.gpu.global.b64 [%0], d;\n}" :: "l"(p), "r"(tagw(a, par)), "r"(tagw(b, par)) : "memory");
}
__device__ __forceinline__ void stp32_if(bool p, char* d, float a, uint32_t par) {
    asm volatile("{\n .reg .pred p;\n setp.ne.u32 p, %2, 0;\n @p st.relaxed.gpu.global.u32 [%0], %1;\n @p st.relaxed.gpu.global.u32 [%0+4096], %1;\n}" :: "l"(d), "r"(tagw(a, par)), "r"((uint32_t)p) : "memory");
}
__device__ __forceinline__ void stp64_if(bool p, char* d, uint32_t lo, uint32_t hi) {
    asm volatile("{\n .reg .pred p;\n .reg .b64 d;\n setp.ne.u32 p, %3, 0;\n mov.b64 d, {%1,%2};\n @p st.relaxed.gpu.global.b64 [%0], d;\n @p st.relaxed.gpu.global.b64 [%0+4096], d;\n}" :: "l"(d), "r"(lo), "r"(hi), "r"((uint32_t)p) : "memory");
}
__device__ __forceinline__ uint32_t chk2(uint32_t a, uint32_t b, uint32_t par) { uint32_t r; asm("lop3.b32 %0, %1, %2, %3, 0x7E;" : "=r"(r) : "r"(a), "r"(b), "r"(par)); return r; }
__device__ __forceinline__ uint32_t or3(uint32_t a, uint32_t b, uint32_t c) { uint32_t r; asm("lop3.b32 %0, %1, %2, %3, 0xFE;" : "=r"(r) : "r"(a), "r"(b), "r"(c)); return r; }
__device__ __forceinline__ uint32_t chk8(const uint32_t (&v)[8], uint32_t par) { return or3(chk2(v[0], v[1], par), chk2(v[2], v[3], par), or3(chk2(v[4], v[5], par), chk2(v[6], v[7], par), 0)); }
__device__ __forceinline__ uint32_t chk8(const uint2 (&v)[8], uint32_t par) { return or3(chk2(v[0].x, v[1].x, par), chk2(v[2].x, v[3].x, par), or3(chk2(v[4].x, v[5].x, par), chk2(v[6].x, v[7].x, par), 0)); }
__device__ __forceinline__ uint32_t chk8y(const uint2 (&v)[8], uint32_t par) { return or3(chk2(v[0].y, v[1].y, par), chk2(v[2].y, v[3].y, par), or3(chk2(v[4].y, v[5].y, par), chk2(v[6].y, v[7].y, par), 0)); }
__device__ __forceinline__ uint32_t chk4(const uint2 (&v)[4], uint32_t par) { return or3(chk2(v[0].x, v[0].y, par), chk2(v[1].x, v[1].y, par), or3(chk2(v[2].x, v[2].y, par), chk2(v[3].x, v[3].y, par), 0)); }
__device__ __forceinline__ float asf(uint32_t v) { return __uint_as_float(v); }
__device__ __forceinline__ float sum8(const uint32_t (&v)[8]) { return ((asf(v[0]) + asf(v[1])) + (asf(v[2]) + asf(v[3]))) + ((asf(v[4]) + asf(v[5])) + (asf(v[6]) + asf(v[7]))); }
__device__ __forceinline__ float sum8x(const uint2 (&v)[8]) { return ((asf(v[0].x) + asf(v[1].x)) + (asf(v[2].x) + asf(v[3].x))) + ((asf(v[4].x) + asf(v[5].x)) + (asf(v[6].x) + asf(v[7].x))); }
__device__ __forceinline__ float sum8y(const uint2 (&v)[8]) { return ((asf(v[0].y) + asf(v[1].y)) + (asf(v[2].y) + asf(v[3].y))) + ((asf(v[4].y) + asf(v[5].y)) + (asf(v[6].y) + asf(v[7].y))); }

__device__ __forceinline__ uint32_t pack2(float lo, float hi) { uint32_t r; asm("cvt.rn.bf16x2.f32 %0, %1, %2;" : "=r"(r) : "f"(hi), "f"(lo)); return r; }
__device__ __forceinline__ float bfr(float x) { return __uint_as_float(pack2(0.0f, x)); }
__device__ __forceinline__ float ex2(float x) { float r; asm("ex2.approx.ftz.f32 %0, %1;" : "=f"(r) : "f"(x)); return r; }
__device__ __forceinline__ float rcp(float x) { float r; asm("rcp.approx.ftz.f32 %0, %1;" : "=f"(r) : "f"(x)); return r; }
__device__ __forceinline__ float sqrt_(float x) { float r; asm("sqrt.approx.ftz.f32 %0, %1;" : "=f"(r) : "f"(x)); return r; }
__device__ __forceinline__ float bf_lo(uint32_t v) { return __uint_as_float(v << 16); }
__device__ __forceinline__ float bf_hi(uint32_t v) { return __uint_as_float(v & 0xffff0000u); }
__device__ __forceinline__ float sel4(int k, float a, float b, float c, float d) { return (k & 2) ? ((k & 1) ? d : c) : ((k & 1) ? b : a); }
constexpr float LOG2E = 1.4426950408889634f;
constexpr uint32_t ONES = 0x3f803f80u;

__device__ __forceinline__ void ln_stats(float sum, float sq, float& mean, float& den) {
    const float m = sum * (1.0f / 640.0f);
    const float var = fmaxf(fmaf(sq, 1.0f / 640.0f, -m * m), 0.0f);
    mean = bfr(m);
    den = bfr(sqrt_(bfr(bfr(var) + 1e-5f)));
}
__device__ __forceinline__ float sigmoidf_(float x) { return rcp(1.0f + ex2(-x * LOG2E)); }

#define TSTAMP(k) do {} while (0)
#define TST(k) do {} while (0)

#define CSTAMP(k) do {} while (0)
template <int N> __device__ __forceinline__ uint32_t lag(uint32_t sb) {
    uint32_t z = 0;
#pragma unroll
    for (int k = 0; k < N; k++) z = ldsvol(sb + S_ZERO + z);
    return z;
}
__device__ __forceinline__ void warm_mma(uint32_t& a, uint32_t& b) {
    asm volatile("mma.sync.aligned.m16n8k8.row.col.f16.f16.f16.f16 {%0,%1}, {%0,%1}, {%0}, {%0,%1};" : "+r"(a), "+r"(b) :: "memory");
}
#define KWNS2 20
#define KWNS 200
template <int STRIDE>
__device__ __forceinline__ float gather8(const char* p, uint32_t par) {
    uint32_t v[8];
    int guard = 0;
    do {
#pragma unroll
        for (int s = 0; s < 8; s++) v[s] = ldp32(p + s * STRIDE);
    } while ((chk8(v, par) & 1) && ++guard < SPIN_LIMIT);
    return sum8(v);
}
template <class F>
__device__ __forceinline__ void gather16(const char* p, uint32_t par, int k, F use) {
    uint32_t v[8], u[8];
    int guard = 0;
    bool again;
    do {
#pragma unroll
        for (int s = 0; s < 8; s++) v[s] = ldp32(p + s * 512);
#pragma unroll
        for (int s = 0; s < 8; s++) u[s] = ldp32(p + HALF + s * 512);
        const uint32_t stale = use(sum8(v) + sum8(u), ((v[0] ^ par) & 1) * 8);
        again = __any_sync(~0u, (or3(chk8(v, par), chk8(u, par), stale) & 1) != 0);
    } while (again & (++guard < SPIN_LIMIT));
    SWEEPS(k, guard - 1);
}

struct Params {
    const __nv_bfloat16 *x, *k, *v, *wr;
    __nv_bfloat16* out;
};
struct Maps { CUtensorMap k, kh, v, vu, wq, wo, wg, wu, wd; };

constexpr int KV_BATCH_KEYS = 32 * 4096;

__device__ __forceinline__ void tma2d(uint32_t dst, const CUtensorMap* m, int c0, int c1, uint32_t bar, uint32_t bytes, uint64_t pol) {
    asm volatile("{\n .reg .pred p;\n elect.sync _|p, 0xffffffff;\n"
                 " @p mbarrier.arrive.expect_tx.shared::cta.b64 _, [%2], %6;\n"
                 " @p cp.async.bulk.tensor.2d.shared::cluster.global.mbarrier::complete_tx::bytes.L2::cache_hint [%0], [%1, {%3, %4}], [%2], %5;\n}"
                 :: "r"(dst), "l"(m), "r"(bar), "r"(c0), "r"(c1), "l"(pol), "r"(bytes) : "memory");
}
__device__ __forceinline__ void scrap_copy(uint32_t dst, const char* src, uint32_t bar) {
    asm volatile("{\n .reg .pred p;\n elect.sync _|p, 0xffffffff;\n"
                 " @p mbarrier.arrive.expect_tx.shared::cta.b64 _, [%2], 12288;\n"
                 " @p cp.async.bulk.shared::cluster.global.mbarrier::complete_tx::bytes [%0], [%1], 4096, [%2];\n"
                 " @p cp.async.bulk.shared::cluster.global.mbarrier::complete_tx::bytes [%0], [%1+4096], 4096, [%2];\n"
                 " @p cp.async.bulk.shared::cluster.global.mbarrier::complete_tx::bytes [%0], [%1+8192], 4096, [%2];\n}"
                 :: "r"(dst), "l"(src), "r"(bar) : "memory");
}
__device__ __forceinline__ void prefetch_l2(const void* p, uint32_t bytes) {
    asm volatile("{\n .reg .pred p;\n elect.sync _|p, 0xffffffff;\n @p cp.async.bulk.prefetch.L2.global [%0], %1;\n}" :: "l"(p), "r"(bytes) : "memory");
}
__device__ __forceinline__ uint64_t pol_first() { uint64_t p; asm("createpolicy.fractional.L2::evict_first.b64 %0, 1.0;" : "=l"(p)); return p; }
__device__ __forceinline__ uint64_t pol_normal() { uint64_t p; asm("createpolicy.fractional.L2::evict_normal.b64 %0, 1.0;" : "=l"(p)); return p; }
__device__ __forceinline__ bool utest(uint32_t bar, uint32_t parity) { return __all_sync(~0u, mbar_test(bar, parity)); }
__device__ __forceinline__ void uwait(uint32_t bar, uint32_t parity) {
    int n = 0;
    while (!__all_sync(~0u, mbar_try(bar, parity)) && ++n < SPIN_LIMIT) {}
}
template <int A, int B, int CNT> __device__ __forceinline__ void init_bars(uint32_t sb) {
#pragma unroll 1
    for (int k = A; k < B; k++)
        asm volatile("{\n .reg .pred p;\n elect.sync _|p, 0xffffffff;\n @p mbarrier.init.shared::cta.b64 [%0], %1;\n}" :: "r"(sb + S_BAR + 8 * k), "n"(CNT) : "memory");
}
__device__ __forceinline__ int first_key() { return (blockIdx.x >> 2) * 4096 + 3072 + (blockIdx.x & 3) * 256; }
__device__ __forceinline__ void load_tile(const CUtensorMap* m, uint32_t dst, uint32_t bar, uint32_t bytes, int key, uint64_t pol) { tma2d(dst, m, 0, 3 * key, bar, bytes, pol); }
__device__ __forceinline__ const char* unit_ptr(const Params& P, int n) {
    return (const char*)((n & 16) ? P.v : P.k) + (size_t)(first_key() + (n >> 5) * KV_BATCH_KEYS + (n & 15) * 16) * 384;
}
#define LSTAMP(k) do {} while (0)

__device__ __forceinline__ uint32_t k_place(uint32_t b, uint32_t s) { return s + 3 + 5 * (b & 1); }
__device__ __forceinline__ uint32_t v_place(uint32_t b, uint32_t s) { return s < 3 ? s : s + 8 - 8 * (b & 1); }
__device__ __forceinline__ void k_load(const Maps& M, uint32_t dst, uint32_t bar, int key8, uint64_t pol) {
    asm volatile("{\n .reg .pred p;\n elect.sync _|p, 0xffffffff;\n"
                 " @p mbarrier.arrive.expect_tx.shared::cta.b64 _, [%2], 6144;\n"
                 " @p cp.async.bulk.tensor.4d.shared::cluster.global.mbarrier::complete_tx::bytes.L2::cache_hint [%0], [%1, {0, 0, 0, %3}], [%2], %4;\n}"
                 :: "r"(dst), "l"(&M.k), "r"(bar), "r"(key8), "l"(pol) : "memory");
}
__device__ __forceinline__ int unit_key8(uint32_t n) { return first_key() / 8 + (n >> 4) * (KV_BATCH_KEYS / 8) + 2 * (n & 15); }
__device__ __forceinline__ void ring_load(const Maps& M, uint32_t sb, uint32_t b, uint32_t u, uint32_t pos) {
    if (u < 16) k_load(M, sb + pos * UNIT, sb + S_RING + 8 * pos, unit_key8(16 * b + u), pol_normal());
    else load_tile(&M.vu, sb + pos * UNIT, sb + S_FV + 4 * (pos & 6), UNIT, first_key() + b * KV_BATCH_KEYS + 16 * pos, pol_first());
}
__device__ __forceinline__ uint32_t token(bool p, uint32_t a, uint32_t n) {
    uint32_t v;
    asm volatile("{\n .reg .pred p;\n setp.ne.u32 p, %2, 0;\n mov.u32 %0, 0;\n @p atom.shared.exch.b32 %0, [%1], %3;\n}" : "=r"(v) : "r"(a), "r"((uint32_t)p), "r"(n) : "memory");
    return v;
}
__device__ __forceinline__ void place_load(const Maps& M, uint32_t sb, uint32_t n) {
    k_load(M, sb + k_place(n >> 4, 0) * SLOT + (n & 15) * UNIT, sb + S_FK + 4 * (n & 14), unit_key8(n), pol_first());
}
__device__ __forceinline__ void half_load(const Maps& M, uint32_t sb, uint32_t m) {
    const uint32_t bar = sb + S_FK + 2 * (m & 28);
    if (!(m & 1)) asm volatile("{\n .reg .pred p;\n elect.sync _|p, 0xffffffff;\n @p mbarrier.arrive.expect_tx.shared::cta.b64 _, [%0], 6144;\n}" :: "r"(bar) : "memory");
    asm volatile("{\n .reg .pred p;\n elect.sync _|p, 0xffffffff;\n"
                 " @p cp.async.bulk.tensor.4d.shared::cluster.global.mbarrier::complete_tx::bytes.L2::cache_hint [%0], [%1, {0, 0, 0, %3}], [%2], %4;\n}"
                 :: "r"(sb + k_place(m >> 5, 0) * SLOT + (m & 31) * 3072), "l"(&M.kh), "r"(bar), "r"(first_key() / 8 + (m >> 5) * (KV_BATCH_KEYS / 8) + (m & 31)), "l"(pol_first()) : "memory");
}
__device__ __forceinline__ void v_load(const Maps& M, uint32_t sb, uint32_t b, uint32_t s) {
    load_tile(&M.v, sb + v_place(b, s) * SLOT, sb + S_FV + 8 * s, SLOT, first_key() + b * KV_BATCH_KEYS + 32 * s, pol_first());
}
__device__ __forceinline__ bool due(uint32_t t) { return __all_sync(~0u, (int)(gtime32() * 16 - t) >= 0); }
__device__ __forceinline__ bool reached(uint32_t a, int v) { return __all_sync(~0u, ldsvol(a) >= v); }

__device__ __forceinline__ void stream_warp(const Params& P, const Maps& M, uint32_t sb, uint32_t lane) {
    const uint64_t pol = pol_first();
    const int bid = blockIdx.x, g = bid >> 3, i = bid & 7;
    const uint32_t wf = sb + S_WFULL;
    if (PF0 > 0) prefetch_l2(unit_ptr(P, 0), PF0 * UNIT);
    uint32_t tn = __shfl_sync(~0u, gtime32(), 0) * 16 - T_LEAD;
    auto pace = [&](uint32_t dt) {
        int k = 0;
        uint32_t now;
        do now = __shfl_sync(~0u, gtime32(), 0) * 16; while ((int)(now - tn) < 0 && ++k < SPIN_LIMIT);
        if ((int)(now - tn) > SLACK0) tn = now - SLACK0;
        tn += dt;
    };
#pragma unroll
    for (int k = 0; k < 10; k++) {
        if (k < 2) {
            if (k == 0) init_bars<26, 27, 1>(sb); else init_bars<27, 37, 1>(sb);
            asm volatile("fence.mbarrier_init.release.cluster;" ::: "memory");
            if (k == 1) { asm volatile("bar.arrive 2, %0;" :: "n"(NTHR) : "memory"); asm volatile("bar.sync 3, 128;" ::: "memory"); }
        }
        if (k >= WIN_W) uwait(wf + 8 * (k - WIN_W), 0);
        pace(TAUW * 5 / 2);
        if (k < 4) tma2d(sb + ST_WQ + 15360 * k, &M.wq, 384 * g + 192 * (k >> 1), 80 * i + 40 * (k & 1), wf + 8 * k, 15360, pol);
        else if (k < 6) tma2d(sb + ST_WG + 15360 * (k - 4), k == 4 ? &M.wg : &M.wu, 96 * g, 80 * i, wf + 8 * k, 15360, pol);
        else tma2d(sb + ST_WO + 15360 * (k - 6), &M.wo, 80 * i, 384 * g + 96 * (k - 6), wf + 8 * k, 15360, pol);
    }
#pragma unroll 1
    for (int n = 0; n < 16; n++) {
        if (n == 0 || n == 5 || n == 11) uwait(sb + S_RELW + (n == 0 ? 0 : n == 5 ? 8 : 16), 0);
        uwait(n < WIN_S ? wf + 8 * (10 - WIN_S + n) : sb + S_FV + 8 * ((n - WIN_S) ^ 8), 0);
        pace(max(min(2 * n + 2 - PF0, 2), 0) * TAU0);
        if (n < 8) { place_load(M, sb, 2 * n); place_load(M, sb, 2 * n + 1); }
        else if (n < 11) { ring_load(M, sb, 0, 2 * n, 2 * n - 16); ring_load(M, sb, 0, 2 * n + 1, 2 * n - 15); }
        else v_load(M, sb, 0, n - 8);
        if (n == 7) { pace(TAUW * 5 / 2); tma2d(sb + S_WD, &M.wd, 80 * i, 96 * g, wf + 80, 15360, pol); }
    }
    int nd = 0;
    uint32_t q[4];
#pragma unroll
    for (int r = 0; r < 4; r++) q[r] = sb + S_FV + 8 * (7 - r);
    tn -= TSH;
    uint32_t td = tn;
    uint32_t pos = 2;
#pragma unroll 1
    for (int m = 16; m < 64; m++) {
        const int b = m >> 4, j = m & 15;
        const char* src = unit_ptr(P, 2 * m);
        const uint32_t tok = sb + S_TOK + (j < 3 ? 4 * pos : j < 11 ? 24 + 4 * pos : 16 + 4 * j) + 4 * lane;
        static_assert(WIN_U <= 12, "a ring position has at most one token of the timetable");
        int k = 0;
        while (true) {
            const uint2 c = lds64(sb + S_KF);
            if (__all_sync(~0u, mbar_test(q[WIN_S - 1] & ~1u, q[WIN_S - 1] & 1) & (min((int)c.x + 1, (int)c.y) >= 16 * b + min(2 * j + 2 - WIN_U, 16))) || ++k >= SPIN_LIMIT) break;
        }
        uint32_t now;
        while (true) {
            now = __shfl_sync(~0u, gtime32(), 0) * 16;
            if ((int)(now - td) >= 0 || ++k >= SPIN_LIMIT) break;
            if (PSLEEP > 0 && (int)(td - now) > 16 * PSLEEP * 2) __nanosleep(PSLEEP);
        }
        const uint32_t mine = __ballot_sync(~0u, token(lane < (j < 11 ? 2 : 1), tok, 2 * m + lane) == 2 * m + lane);
        q[3] = q[2]; q[2] = q[1]; q[1] = q[0]; q[0] = sb + S_QRDY;
        if (j < 11) {
            if (mine & 1) ring_load(M, sb, b, 2 * j, pos); else prefetch_l2(src, UNIT);
            if (mine & 2) ring_load(M, sb, b, 2 * j + 1, pos + 1); else prefetch_l2(src + UNIT, UNIT);
            if (j >= 8) q[0] = (sb + S_FV + 8 * (j - 8)) | (b & 1);
        } else if (mine) { v_load(M, sb, b, j - 8); q[0] = (sb + S_FV + 8 * (j - 8)) | (b & 1); }
        else if (j - 8 >= VPF) prefetch_l2(src, SLOT);
        else {
            scrap_copy(sb + S_DUMMY, src, sb + S_DBAR + 8 * (nd & 3));
            q[0] = (sb + S_DBAR + 8 * (nd & 3)) | ((nd >> 2) & 1);
            nd++;
        }
        pos = j == 15 ? 2 : pos == 4 ? 0 : pos + 2;
        if ((int)(now - tn) > SLACK) tn = now - SLACK;
        tn += 2 * TAU;
        td = (int)(tn - now) > 2 * TMIN ? tn : now + 2 * TMIN;
        if (m >= 48 + JFREE) td = now + TFREE;
    }
#pragma unroll 1
    for (int m = max(nd - 4, 0); m < nd; m++) uwait(sb + S_DBAR + 8 * (m & 3), (m >> 2) & 1);
}

__host__ __device__ constexpr uint64_t bit_list(uint32_t m) { uint64_t r = 0; int n = 0; for (int k = 0; k < 12; k++) if ((m >> k) & 1) r |= (uint64_t)k << (4 * n++); return r; }
__device__ __forceinline__ float scaled(float s) { return bfr(bfr(s) * 0.07216878364870322f); }
__device__ __forceinline__ void probs(float s, uint32_t ps, uint32_t src, uint32_t ln) {
    const uint32_t q8 = ln >> 2, t4 = ln & 3;
    int key = __float_as_int(s);
    key ^= (key >> 31) & 0x7fffffff;
    key = __reduce_max_sync(~0u, key);
    key ^= (key >> 31) & 0x7fffffff;
    const float ml = __int_as_float(key) * LOG2E;
    sts16(ps + 64 * src + (q8 >> 1) * 16 + t4 * 4 + (q8 & 1) * 2, pack2(ex2(fmaf(s, LOG2E, -ml)), 0.f));
    stsf(ps + PS_MAX + 4 * src, ml);
}
template <int H> __device__ __forceinline__ uint32_t b_pos(uint32_t e) { const uint32_t h = e >= H, k = e - H * h; return h * 192 + (k & 6) * 24 + (k >> 3) * 4 + (k & 1) * 2; }
__device__ __forceinline__ uint32_t a_pos(uint32_t e) { const uint32_t h = e >= 40, k = e - 40 * h; return (k & 6) * 24 + (k >> 3) * 8 + h * 4 + (k & 1) * 2; }
__device__ __forceinline__ uint32_t q_pos(uint32_t d) { const uint32_t s = 3 * ((d >> 4) & 3) + (d >> 6); return s * 32 + (d & 6) * 4 + ((d >> 3) & 1) * 4 + (d & 1) * 2; }
__device__ __forceinline__ uint32_t k_off(uint32_t ln) { return (ln & 8) * 384 + (ln & 7) * 128 + (((ln & 7) ^ (ln >> 4)) << 4); }

#define HSTAMP(k) do {} while (0)
__device__ __forceinline__ char* xwindow() { return reinterpret_cast<char*>((reinterpret_cast<uintptr_t>(g_x) + (2u << 20) - 1) & ~(uintptr_t)((2u << 20) - 1)); }

struct XPtr {
    uint32_t lo, hi;
    __device__ __forceinline__ explicit XPtr(char* p) : lo((uint32_t)(uintptr_t)p), hi((uint32_t)((uintptr_t)p >> 32)) {}
    __device__ __forceinline__ XPtr(uint32_t l, uint32_t h) : lo(l), hi(h) {}
    __device__ __forceinline__ XPtr operator+(uint32_t o) const { return XPtr(lo + o, hi); }
    __device__ __forceinline__ operator char*() const { uint64_t p; asm("mov.b64 %0, {%1, %2};" : "=l"(p) : "r"(lo), "r"(hi)); return (char*)p; }
};
__device__ __forceinline__ void keep(XPtr& v) { keep(v.lo); }

__device__ __forceinline__ void side_warp(uint32_t sb) {
    const uint32_t bid = blockIdx.x, g = bid >> 3, i = bid & 7, P = pairG(0, 0, i);
    char* p = xwindow() + P * 8192 + (g >> 3) * HALF + (g & 7) * 512 + 448;
    uint32_t best[2] = {~0u, ~0u};
    asm volatile("st.relaxed.gpu.global.b32 [%0], 1;" :: "l"(p) : "memory");
    asm volatile("st.relaxed.gpu.global.b32 [%0], 1;" :: "l"(p + COPY) : "memory");
#pragma unroll 1
    for (int r = 0; r < 64; r++) {
        if (r >= 4 && !(r & 1) && min(best[0], best[1]) < 380 && max(best[0], best[1]) > min(best[0], best[1]) + 80) break;
        uint32_t c0, c1, v;
        asm volatile("mov.u32 %0, %clock;" : "=r"(c0) :: "memory");
        asm volatile("atom.relaxed.gpu.global.exch.b32 %0, [%1], 0;" : "=r"(v) : "l"(p + (r & 1) * COPY) : "memory");
        asm volatile("{\n .reg .pred q;\n setp.eq.u32 q, %1, 0x13579bdf;\n mov.u32 %0, 0;\n @!q mov.u32 %0, %clock;\n}" : "=r"(c1) : "r"(v) : "memory");
        if (r & 1) best[1] = min(best[1], c1 - c0); else best[0] = min(best[0], c1 - c0);
    }
    stsvol(sb + S_SIDE, 1 + ((best[1] < best[0]) ^ (__popc(P & PMASK) & 1)));
}

__device__ __forceinline__ void hop_a(const char* src, uint32_t par, uint32_t dst, bool st, int k) {
    uint2 v[4];
    float e[4], rl;
    int guard = 0;
    bool again;
    do {
#pragma unroll
        for (int s = 0; s < 4; s++) v[s] = ldp64(src + s * 1024);
        again = __any_sync(~0u, (chk4(v, par) & 1) != 0);
        const int M = max(max((int)v[0].x, (int)v[1].x), max((int)v[2].x, (int)v[3].x)) - 254;
#pragma unroll
        for (int s = 0; s < 4; s++) e[s] = __int_as_float(max((int)v[s].x - M, 0) << 22);
        rl = rcp(fmaf(e[0], asf(v[0].y), e[1] * asf(v[1].y)) + fmaf(e[2], asf(v[2].y), e[3] * asf(v[3].y)));
#pragma unroll
        for (int s = 0; s < 4; s++) e[s] = __shfl_sync(~0u, e[s], 24);
        keep(rl);
    } while (again & (++guard < SPIN_LIMIT));
    rl = __shfl_sync(~0u, rl, 24);
    const float o0 = fmaf(e[0], asf(v[0].x), e[1] * asf(v[1].x)) + fmaf(e[2], asf(v[2].x), e[3] * asf(v[3].x));
    const float o1 = fmaf(e[0], asf(v[0].y), e[1] * asf(v[1].y)) + fmaf(e[2], asf(v[2].y), e[3] * asf(v[3].y));
    sts32_if(st, dst, pack2(o0 * rl, o1 * rl));
    SWEEPS(k, guard - 1);
    __syncwarp();
}

__device__ __forceinline__ void score_warp(const Maps& M, uint32_t sb, uint32_t h, uint32_t ln) {
    const uint32_t lane0 = ln;
    uwait(sb + S_QRDY, 0);
    const uint32_t q8 = ln >> 2;
    const uint32_t k0 = k_off(ln);
    uint32_t pos = h + 6, bar = sb + S_FK, par = 0, phases = 0;
    uint2 q = lds64(sb + S_QS + 8 * ln), qh = lds64(sb + S_QS + 8 * ln + 256);
    auto first_round = [&](uint32_t b, uint32_t ln) {
        uwait(sb + S_RELR, b & 1);
        const uint32_t u = h + 2 * ln, p = u < 4 ? u + 2 : u - 4;
        uint32_t todo = __ballot_sync(~0u, token(ln < 3, sb + S_TOK + 4 * p, 32 * b + 32 + u) == 32 * b + 32 + u);
#pragma unroll 1
        for (uint32_t r = h; todo; todo >>= 1, r += 2) if (todo & 1) ring_load(M, sb, b + 1, r, r < 4 ? r + 2 : r - 4);
    };
#pragma unroll 1
    for (uint32_t n = h; n < 64; n += 2) {
        HSTAMP(0);
        const uint32_t ua = sb + pos * UNIT;
        if (!__all_sync(~0u, mbar_try(bar, par))) uwait(bar, par);
        HSTAMP(1);
        float acc[2][4] = {};
        uint32_t mine = 0;
        const uint32_t id = n + (n & 48) + 6;
#pragma unroll
        for (int s = 0; s < 12; s++) {
            uint32_t kf[4];
            ldsm4(kf, (k0 ^ (32 * (s / 3))) + (ua + 1024 * (s % 3)));
            if (s == 11) {
                __syncwarp();
                mine = token(ln == 0 && n >= 16, sb + S_TOK + 24 + 4 * pos, id);
                stsvol(sb + S_KF + 4 * h, n + 1);
            }
            const bool m = q8 == (s & 7);
            mmaA(acc[s & 1], kf, m ? (s < 8 ? q.x : qh.x) : 0u, m ? (s < 8 ? q.y : qh.y) : 0u);
        }
        const uint32_t pos0 = pos;
        const bool last = (n & 14) == 14;
        pos = last ? h + 2 : n >= 16 && pos >= 4 ? h : pos + 2;
        bar = n >= 14 ? sb + S_RING + 8 * pos : bar + 8;
        par = n >= 14 ? (phases >> pos) & 1 : 0;
        phases ^= n >= 14 ? 1u << pos : 0;
        const float w0 = (acc[0][0] + acc[0][1]) + (acc[1][0] + acc[1][1]), w1 = (acc[0][2] + acc[0][3]) + (acc[1][2] + acc[1][3]);
        HSTAMP(2);
        if (__any_sync(~0u, mine == id)) ring_load(M, sb, n >> 4, (n & 15) + 6, pos0);
        HSTAMP(3);
        float s = ((ln & 1) ? w1 : w0) + __shfl_xor_sync(~0u, (ln & 1) ? w0 : w1, 1);
        s += __shfl_xor_sync(~0u, s, 2);
        sts_hi16(sb + S_SC + (((n & 12) >> 1) + h) * 64 + (n & 2) * 2 + (ln & 29) * 2, scaled(s));
        if (last) {
            __syncwarp();
            arrive_if(ln == 0, sb + S_SCO);
            const uint32_t b = n >> 4, ln = lane0 + lag<1>(sb);
            if (b > 0) {
                uwait(sb + S_RELK, (b - 1) & 1);
                if (h == 0) LSTAMP(64 + 2 * b);
                const uint32_t sl = 3 + h + 2 * ln, idv = 32 * b + 16 + 2 * sl;
                uint32_t todo = __ballot_sync(~0u, token(sl < 8, sb + S_TOK + 48 + 4 * sl, idv) == idv);
#pragma unroll 1
                for (uint32_t r = 3 + h; todo; todo >>= 1, r += 2) if (todo & 1) v_load(M, sb, b, r);
                const uint32_t g = blockIdx.x >> 3, pr = pairL(RA, 1, g), side = ldsvol(sb + S_SIDE);
                const char* src = xwindow() + pr * 8192 + ((side ^ 1 ^ __popc(pr & PMASK)) & 1) * COPY + h * HALF + 8 * min(ln, 24u);
                uwait(sb + S_RELV, (b - 1) & 1);
                __nanosleep(HOP1_NS);
#pragma unroll 1
                for (uint32_t r = 0; r < 4; r++) {
                    hop_a(src + 256 * r, b & 1, sb + S_OS + 192 * (4 * h + r) + 96 + 4 * ln, ln < 24, 25);
                    if (r == RELR_AT && b < 3) first_round(b, ln);
                }
                arrive_if(ln == 0, sb + S_OS1);
            } else first_round(0, ln);
            q = lds64(sb + S_QS + 24 * ((n + 2) & 48) + 8 * ln); qh = lds64(sb + S_QS + 24 * ((n + 2) & 48) + 8 * ln + 256);
        }
    }
}

__global__ void __launch_bounds__(NTHR, 1)
fused_kernel(const Params P, const __grid_constant__ Maps M) {
    extern __shared__ __align__(1024) unsigned char smem[];
    const uint32_t sb = smem_u32(smem);
    const int tid = threadIdx.x, bid = blockIdx.x;
    const int w = __shfl_sync(~0u, tid >> 5, 0), lane = tid & 31;

    if (w >= 8) {
        asm volatile("setmaxnreg.dec.sync.aligned.u32 " REG_LO ";");
        if (w == 8) {
            stream_warp(P, M, sb, lane);
        } else {
            if (PFMAP && w == 11 && lane < 9) asm volatile("prefetch.tensormap [%0];" :: "l"(&M.k + lane) : "memory");
            if (w == 9) { init_bars<0, 3, 2>(sb); init_bars<3, 8, 1>(sb); init_bars<16, 22, 1>(sb); }
            else if (w == 10) { init_bars<8, 16, 2>(sb); init_bars<22, 26, 1>(sb); }
            else { init_bars<37, 38, 1>(sb); init_bars<38, 40, 8>(sb); init_bars<40, 41, 1>(sb); init_bars<41, 44, 8>(sb); init_bars<44, 46, 2>(sb); stsvol(sb + S_ZERO + 4 * lane, 0); }
            asm volatile("fence.mbarrier_init.release.cluster;" ::: "memory");
            asm volatile("bar.arrive 3, 128;" ::: "memory");
            asm volatile("bar.sync 2, %0;" :: "n"(NTHR) : "memory");
            if (w < 11) score_warp(M, sb, w - 9, lane);
            else {
                if (lane == 0) side_warp(sb);
                __syncwarp();
                uint32_t a = 0, b = 0;
                int k = 0;
                while (ldsvol(sb + S_GATE) == 0 && ++k < SPIN_LIMIT) { warm_mma(a, b); __nanosleep(KWNS); }
                uint4* d = reinterpret_cast<uint4*>(reinterpret_cast<char*>(g_s) + XS + bid * 7680) + lane;
                const uint4 z = make_uint4(0, 0, 0, 0);
#pragma unroll 1
                for (int u = 0; u < 15; u++) d[32 * u] = z;
                d = reinterpret_cast<uint4*>(reinterpret_cast<char*>(g_s) + XS2 + bid * 768) + lane;
                d[0] = z;
                if (lane < 16) d[32] = z;
                const uint32_t side = (ldsvol(sb + S_SIDE) & 1) ^ 1, g = bid >> 3, i = bid & 7;
                const XPtr gx(xwindow());
                auto nearp = [&](uint32_t pr) { return gx.lo + pr * 8192 + ((side ^ __popc(pr & PMASK)) & 1) * COPY; };
                const uint32_t own = (i >> 2) * HALF + (i & 3) * 1024 + (lane & 7) * 128;
                const uint32_t pAC = nearp(pairL(lane >> 4, (lane >> 3) & 1, g)) + own, pE = nearp(pairL(RE, (lane >> 3) & 1, g)) + own;
                const uint32_t pG = nearp(pairG((lane >> 2) & 1, (lane >> 3) & 1, i)) + min(lane & 3, 2) * 128;
                uint32_t tr = 0, tk = 0, ph = 0, src = g + (lane >> 4), seen = 0, n = 16, hf = 0;
                bool go = false, first = true;
                while (n < 64 && ++k < SPIN_LIMIT) {
                    const uint32_t now = __shfl_sync(~0u, gtime32(), 0) * 16;
                    if (!go && utest(sb + S_RELV, ((n >> 4) & 1) ^ 1) && utest(sb + S_FV + 8 * (n >= 48 ? KRE_GATE3 : KRE_GATE), (n >> 4) & 1)) { go = true; tk = now; }
                    if (go && (int)(now - tk) >= 0) {
                        if (KRE_HALF) half_load(M, sb, 2 * n + hf); else place_load(M, sb, n);
                        tk += (n >= 48 ? KRE_TAU3 : (n & 15) < KRE_N1 ? KRE_TAU1 : KRE_TAU) / (KRE_HALF ? 2 : 1);
                        if (KRE_HALF && (hf ^= 1)) continue;
                        n++;
                        go = (n & 15) != 0;
                        if (!go) LSTAMP(63 + (n >> 3));
                    } else if (first || (int)(now - tr) >= 0) {
                        first = false;
                        tr = now + RFR_TAU;
                        b |= seen & a;
                        warm_mma(a, b);
                        if (RFR_ON) seen = ldp32(XPtr(ph == 0 ? pAC : ph == 1 && lane < 16 ? pE : pG + (src & 8) * (HALF / 8) + (src & 7) * 512, gx.hi));
                        src += ph == 0 ? 0 : ph == 1 ? 2 : 1;
                        ph = ph == 2 ? 0 : ph + 1;
                    } else __nanosleep(KWNS2);
                }
                while (ldsvol(sb + S_GATE) < 6 && ++k < SPIN_LIMIT) { warm_mma(a, b); __nanosleep(KWNS); }
                if (a | b) stsvol(sb + S_GATE, 6);
            }
        }
        return;
    }
    asm volatile("setmaxnreg.inc.sync.aligned.u32 " REG_HI ";");

    const int g = bid >> 3, i = bid & 7;
    const int g8 = lane >> 2, t = lane & 3;
    char* const gs = reinterpret_cast<char*>(g_s);
    const XPtr gx(xwindow());

    auto zero_words = [&] {
        const uint4 z = make_uint4(0, 0, 0, 0);
        const uint32_t c = (tid >> 6) & 1, cp = (tid >> 7) * COPY, k = (tid & 63) * 16;
        *reinterpret_cast<uint4*>((char*)(gx + pairL(RA, c, g) * 8192 + (i >> 2) * HALF + (i & 3) * 1024 + cp + k)) = z;
        *reinterpret_cast<uint4*>((char*)(gx + pairL(RC, c, g) * 8192 + (i >> 2) * HALF + (i & 3) * 1024 + cp + k)) = z;
        *reinterpret_cast<uint4*>((char*)(gx + pairL(RE, c, g) * 8192 + (i >> 2) * HALF + (i & 3) * 1024 + cp + k)) = z;
        if ((tid & 31) < 24) *reinterpret_cast<uint4*>((char*)(gx + pairG((tid >> 5) & 1, c, i) * 8192 + (g >> 3) * HALF + (g & 7) * 512 + cp + (tid & 31) * 16)) = z;
    };
    if (ZPOS == 0) zero_words();
    W80 Wq[6], Wgu[3];
    uint32_t Wo[5][3][4];
    if (w < 4) {
        const uint32_t* xp = reinterpret_cast<const uint32_t*>(P.x + 640 * w);
        float sum = 0.f, sq = 0.f;
#pragma unroll
        for (int u = 0; u < 10; u++) { uint32_t v = xp[lane + 32 * u]; float a = bf_lo(v), b = bf_hi(v); sum += a + b; sq += a * a + b * b; }
#pragma unroll
        for (int o = 16; o > 0; o >>= 1) { sum += __shfl_xor_sync(~0u, sum, o); sq += __shfl_xor_sync(~0u, sq, o); }
        float mean, den; ln_stats(sum, sq, mean, den);
        if (lane < 20) {
            const uint2 v = reinterpret_cast<const uint2*>(P.x + 640 * w + 80 * i)[lane];
            sts64(sb + S_X0 + 160 * w + 8 * lane, v.x, v.y);
            sts32(sb + S_L0 + 384 * w + b_pos<40>(4 * lane), pack2(__fdiv_rn(bfr(bf_lo(v.x) - mean), den), __fdiv_rn(bfr(bf_hi(v.x) - mean), den)));
            sts32(sb + S_L0 + 384 * w + b_pos<40>(4 * lane + 2), pack2(__fdiv_rn(bfr(bf_lo(v.y) - mean), den), __fdiv_rn(bfr(bf_hi(v.y) - mean), den)));
        }
    } else if (w == 4) {
        const uint32_t* xp = reinterpret_cast<const uint32_t*>(P.wr);
        float sum = 0.f;
#pragma unroll
        for (int u = 0; u < 10; u++) { uint32_t v = xp[lane + 32 * u]; sum += bf_lo(v) + bf_hi(v); }
#pragma unroll
        for (int o = 16; o > 0; o >>= 1) sum += __shfl_xor_sync(~0u, sum, o);
        if (lane == 0) stsf(sb + S_SWR, sum);
        if (lane < 20) {
            const uint2 v = reinterpret_cast<const uint2*>(P.wr + 80 * i)[lane];
            sts32(sb + S_XA + 576 + a_pos(4 * lane), v.x); sts32(sb + S_XA + 576 + a_pos(4 * lane + 2), v.y);
            sts32(sb + S_XA + a_pos(4 * lane), ONES); sts32(sb + S_XA + a_pos(4 * lane + 2), ONES);
        }
    }
    asm volatile("bar.sync 2, %0;" :: "n"(NTHR) : "memory");
    auto frag = [](uint32_t (&a)[4], uint32_t p, int pitch) {
        const uint32_t r0 = lds32(p), r1 = lds32(p + pitch), r2 = lds32(p + 2 * pitch), r3 = lds32(p + 3 * pitch);
        a[0] = __byte_perm(r0, r1, 0x5410); a[1] = __byte_perm(r0, r1, 0x7632);
        a[2] = __byte_perm(r2, r3, 0x5410); a[3] = __byte_perm(r2, r3, 0x7632);
    };
    mbar_wait(sb + S_WFULL + 16 * (w >> 2), 0);
    mbar_wait(sb + S_WFULL + 16 * (w >> 2) + 8, 0);
    {
        const uint32_t p = sb + ST_WQ + (w >> 2) * 30720 + (2 * t) * 384 + (48 * (w & 3) + 2 * g8) * 2;
#pragma unroll
        for (int r = 0; r < 10; r++)
#pragma unroll
            for (int m = 0; m < 3; m++) {
                const uint32_t q = p + ((r & 1) * 40 + (r >> 1) * 8) * 384 + 32 * m, r0 = lds32(q), r1 = lds32(q + 384);
                (r < 8 ? Wq[2 * m].a[(r >> 2) & 1][r & 3] : Wq[2 * m].c[r & 1]) = __byte_perm(r0, r1, 0x5410);
                (r < 8 ? Wq[2 * m + 1].a[(r >> 2) & 1][r & 3] : Wq[2 * m + 1].c[r & 1]) = __byte_perm(r0, r1, 0x7632);
            }
    }
    __syncwarp();
    if (lane == 0) mbar_arrive(sb + S_RELW);
    TSTAMP(1);
    {
        char* d = gs + XS + bid * 7680 + (w >> 2) * 3840 + (48 * (w & 3) + 2 * g8) * 4;
        float acc[6][4] = {};
        mul80(acc, Wq, lds128(sb + S_L0 + 48 * lane), lds32(sb + S_L0 + 48 * lane + 16));
#pragma unroll
        for (int m = 0; m < 6; m += 2) stp64(d + t * 768 + 32 * m, acc[m][0] + acc[m][3], acc[m + 1][0] + acc[m + 1][3], 1);
        float sum[6][4] = {};
        mul80(sum, Wq, make_uint4(ONES, ONES, ONES, ONES), ONES);
        if (t == 0)
#pragma unroll
            for (int m = 0; m < 6; m += 2) stp64(d + 4 * 768 + 32 * m, sum[m][0] + sum[m][3], sum[m + 1][0] + sum[m + 1][3], 1);
    }
    mbar_wait(sb + S_WFULL + 32, 0);
    mbar_wait(sb + S_WFULL + 40, 0);
    const uint32_t oct = 3 * (w >> 1) + (w & 1), oct2 = 3 * (w >> 1) + 2;
    {
        const uint32_t p = sb + ST_WG + ((lane & 7) + 40 * ((lane >> 3) & 1) + 8 * (lane >> 4)) * 192;
#pragma unroll
        for (int T = 0; T < 3; T++) {
            const uint32_t q = p + (T < 2 ? T * 15360 + 16 * oct : (w & 1) * 15360 + 16 * oct2);
            ldsm4t(Wgu[T].a[0], q); ldsm4t(Wgu[T].a[1], q + 16 * 192); ldsm2t(Wgu[T].c, q + 32 * 192);
        }
        float sum[3][4] = {};
        mul80(sum, Wgu, make_uint4(ONES, ONES, ONES, ONES), ONES);
        if (t < 3) stp32(gs + XS2 + bid * 768 + (t < 2 ? 64 * oct + 4 * t : 64 * oct2 + 4 * (w & 1)) + 8 * g8,
                         sel4(t, sum[0][0] + sum[0][3], sum[1][0] + sum[1][3], sum[2][0] + sum[2][3], 0.f), 1);
    }
    __syncwarp();
    if (lane == 0) mbar_arrive(sb + S_RELW + 8);
    const char* srcS = gs + XS + g * 8 * 7680 + (i >> 2) * 3840 + min(tid, 191) * 4;
    uint32_t vs[5][8];
#pragma unroll
    for (int b = 0; b < 5; b++)
#pragma unroll
        for (int s = 0; s < 8; s++) vs[b][s] = LOOK1 ? ldp32(srcS + b * 768 + s * 7680) : 0;
    uint32_t cs2[8];
#pragma unroll
    for (int s = 0; s < 8; s++) cs2[s] = LOOK2 ? ldp32(gs + XS2 + (g * 8 + s) * 768 + min(tid, 191) * 4) : 0;
    __syncwarp();
    mbar_wait(sb + S_WFULL + 48 + 8 * (w >> 1), 0);
    {
        const uint32_t po = sb + ST_WO + (48 * w + 12 * t) * 160 + 4 * g8;
#pragma unroll
        for (int s = 0; s < 3; s++)
#pragma unroll
            for (int m = 0; m < 5; m++) frag(Wo[m][s], po + 4 * s * 160 + 32 * m, 160);
    }
    __syncwarp();
    if (lane == 0) mbar_arrive(sb + S_RELW + 16);
    if (ZPOS == 1) zero_words();
    if (tid < 192) {
        int guard = 0;
        while (((or3(chk8(vs[0], 1), chk8(vs[1], 1), chk8(vs[2], 1)) | chk8(vs[3], 1) | chk8(vs[4], 1)) & 1) && ++guard < SPIN_LIMIT) {
#pragma unroll
            for (int b = 0; b < 5; b++)
#pragma unroll
                for (int s = 0; s < 8; s++) vs[b][s] = ldp32(srcS + b * 768 + s * 7680);
        }
        const uint32_t qpos = sb + S_QS + q_pos(tid);
#pragma unroll
        for (int b = 0; b < 4; b++) {
            sts_hi16(qpos + 384 * b, bfr(sum8(vs[b])));
        }
        stsf(sb + S_CSQ + 4 * tid, sum8(vs[4]));
    }
    if (tid < 192) stsf(sb + S_CSGU + 4 * tid, (chk8(cs2, 1) & 1) ? gather8<768>(gs + XS2 + g * 8 * 768 + tid * 4, 1) : sum8(cs2));
    __syncwarp();
    bar_main();
    arrive_if(tid == 0, sb + S_QRDY);
    if (ZPOS == 2) zero_words();
    TSTAMP(2);

    uint32_t side;
    { int k = 0; while ((side = ldsvol(sb + S_SIDE)) == 0 && ++k < SPIN_LIMIT) {} }
    const uint32_t td = __shfl_sync(~0u, tid, lane);
    const uint32_t wp = __shfl_sync(~0u, tid >> 5, 0);
    const uint32_t cc = wp >= 3;
    auto uni = [](uint32_t v) { return __shfl_sync(~0u, v, 0); };
    auto pin = [&](uint32_t v) { return __shfl_sync(~0u, v, td); };
    auto nearp = [&](uint32_t P) { return gx.lo + P * 8192 + ((side ^ 1 ^ __popc(P & PMASK)) & 1) * COPY; };
    constexpr uint32_t COL = 32 * 8192;
    const uint32_t ownL = gx.lo + (i >> 2) * HALF + (i & 3) * 1024, ownG = gx.lo + (g >> 3) * HALF + (g & 7) * 512;
    const uint32_t uPubA = uni(ownL + pairL(RA, 0, g) * 8192 + (wp >> 1) * 256 + (wp & 1) * 96), uPolA = uni(nearp(pairL(RA, 0, g)) + (wp >> 2) * HALF + (wp & 3) * 256);
    const uint32_t uPubB = uni(ownG + pairG(0, cc, i) * 8192), uPolB = uni(nearp(pairG(0, cc, i)));
    const uint32_t uPubC = uni(ownL + pairL(RC, 0, g) * 8192), uPolC = uni(nearp(pairL(RC, wp < 6 ? cc : wp - 6, g)));
    const uint32_t uPubD = uni(ownG + pairG(1, 0, i) * 8192 + (wp < 7 ? 32 * wp : 256)), uPolD = uni(nearp(pairG(1, cc, i)));
    const uint32_t uPubE = uni(ownL + pairL(RE, 0, g) * 8192), uPolE = uni(nearp(pairL(RE, i >> 2, g)));
    const uint32_t uOS = uni(sb + S_OS + 192 * wp), uCol = uni(sb + 64 * cc);
    auto xp = [&](uint32_t lo) { return (char*)XPtr(lo, gx.hi); };
#define IDS() const uint32_t z_ = pin(td); const uint32_t ln = z_ & 31, q8 = ln >> 2, t4 = z_ & 3, n96 = z_ - 96 * cc, n80 = min(n96, 79u); (void)q8; (void)t4; (void)n80; (void)ln

    auto vaddr = [&](uint32_t (&voff)[3]) {
        const uint32_t ln = td & 31;
        const uint32_t key3 = 3 * ((ln & 7) + 2 * (ln & 8) + ((ln >> 1) & 8));
#pragma unroll
        for (int T = 0; T < 3; T++) {
            const uint32_t u = 3 * wp + T, r = key3 + (u >> 3);
            voff[T] = r * 128 + (((u ^ r) & 7) << 4);
        }
    };
    auto values = [&](uint32_t (&vf)[8][3][4], auto order, auto step, uint32_t ps, uint32_t col, uint32_t par) {
        const uint32_t ln = td & 31, q8 = ln >> 2, t4 = td & 3;
        const uint4 p = lds128(ps + 16 * ln);
        float acc[3][4] = {}, f0 = 0.f, f1 = 0.f, r3 = 0.f;
        int M = 0;
#pragma unroll
        for (int k = 0; k < 8; k++) {
            step(k);
            const int s = (order.value >> (4 * k)) & 7;
            const bool m = (q8 >> 1) == (s >> 1);
            const uint32_t b0 = m ? ((s & 1) ? p.z : p.x) : 0u, b1 = m ? ((s & 1) ? p.w : p.y) : 0u;
#pragma unroll
            for (int T = 0; T < 3; T++) mmaA(acc[T], vf[s][T], b0, b1);
            if (k == FSTEP) {
                const uint2 mp = lds64(ps + PS_MAX + 8 * t4);
                M = __reduce_max_sync(~0u, __float2int_ru(fmaxf(asf(mp.x), asf(mp.y))));
                f0 = ex2(asf(mp.x) - (float)M); f1 = ex2(asf(mp.y) - (float)M);
                float l[4] = {};
                mma16816(l, ONES, ONES, ONES, ONES, p.x, p.y); mma16816(l, ONES, ONES, ONES, ONES, p.z, p.w);
                r3 = fmaf(f0, l[0], f1 * l[1]);
            }
        }
        CSTAMP(25);
        char* pubA = xp(uPubA + col * COL + 32 * t4 + 4 * q8);
        const float r0 = fmaf(f0, acc[0][0], f1 * acc[0][3]), r1 = fmaf(f0, acc[1][0], f1 * acc[1][3]), r2 = fmaf(f0, acc[2][0], f1 * acc[2][3]);
        const bool hi = t4 & 2, od = t4 & 1;
        const float u0 = (hi ? r2 : r0) + __shfl_xor_sync(~0u, hi ? r0 : r2, 2), u1 = (hi ? r3 : r1) + __shfl_xor_sync(~0u, hi ? r1 : r3, 2);
        const float o = (od ? u1 : u0) + __shfl_xor_sync(~0u, od ? u0 : u1, 1);
        stp32_if(t4 < 3 || ((wp & 1) && q8 < 2), pubA, ln == 3 ? __int_as_float(2 * M) : o, par);
    };

#pragma unroll 1
    for (int ch = 0; ch < 5; ch++) {
        const uint32_t par0 = (ch + 1) & 1, par1 = ch & 1;
        uint32_t voff[3], vf[8][3][4];
        CSTAMP(0);
        if (ch < 4) {
            vaddr(voff);
            mbar_wait(sb + S_SCO, par1);
            if (ch == 0) mbar_wait(sb + S_WFULL + 80, 0);
            TST(0);
            auto ldw = [&](int s) {
                mbar_wait(sb + S_FV + 8 * s, par1);
#pragma unroll
                for (int T = 0; T < 3; T++) ldsm4t(vf[s][T], voff[T] + (sb + v_place(ch, s) * SLOT));
            };
            probs(bf_lo(lds16(sb + S_SC + 2 * td)), sb + S_PS, wp, td & 31);
            ldw(0); ldw(1); ldw(2);
            bar_main();
            arrive_if(td == 0, sb + S_RELR);
            values(vf, std::integral_constant<uint32_t, 0x76543210>(), [&](int s) {
                if (s >= 3) ldw(s);
            }, sb + S_PS, 0, par0);
            TST(1);
            CSTAMP(5);
            if (ch > 0) mbar_wait(sb + S_OS1, par0);
        } else {
#pragma unroll
            for (int s = 0; s < 36; s++) { vf[s / 12][(s / 4) % 3][s & 3] = 0; opaque(vf[s / 12][(s / 4) % 3][s & 3]); }
        }
        const bool has0 = ch < 4, has1 = ch > 0;
        const bool actc = wp < 6 && (cc ? has1 : has0);
        const uint32_t parc = cc ? par1 : par0;
        const uint32_t pub0 = has0 ? par0 : 0;
        uint32_t n4;
        {
            IDS();
            const uint32_t c = ch == 4;
            const uint32_t osa = pin(uOS + 96 * c + 4 * ln), oa = pin(uOS + 96 * (q8 & 1) + 24 * t4), ra = pin(sb + S_RED + 640 * wp + 320 * (t4 & 1) + 8 * q8);
            n4 = pin(4 * n80);
            hop_a(xp(uPolA + c * COL + 8 * min(ln, 24u) + lag<DELAY_L>(sb)), pub0, osa, ln < 24, 5 * ch);
            TST(2);
            CSTAMP(6);
            float acc[5][4] = {};
            const uint2 b0 = lds64(oa), b1 = lds64(oa + 8), b2 = lds64(oa + 16);
#pragma unroll
            for (int m = 0; m < 5; m++) mmaA(acc[m], Wo[m][0], b0.x, b0.y);
#pragma unroll
            for (int m = 0; m < 5; m++) mmaA(acc[m], Wo[m][1], b1.x, b1.y);
#pragma unroll
            for (int m = 0; m < 5; m++) mmaA(acc[m], Wo[m][2], b2.x, b2.y);
#pragma unroll
            for (int m = 0; m < 5; m++) sts64_if(!(td & 2), ra + 64 * m, (td & 1) ? acc[m][1] : acc[m][0], (td & 1) ? acc[m][3] : acc[m][2]);
        }
        CSTAMP(7);
        float x1 = 0.f;
        uint32_t xr, fl, pubC, pubC2;
        uint32_t xab = 0;
        auto prepC = [&] {
            IDS();
            xr = pin(sb + S_XB + 48 * (ln & 15));
            pubC = pin(uPubC + (t4 & 1) * COL + 192 * (wp >> 1) + 64 * (wp & 1) + 8 * q8);
            pubC2 = pin(uPubC + (t4 & 1) * COL + ((t4 & 2) ? 192 * (wp >> 1) + 128 + 4 * (wp & 1) + 8 * q8 : 768 + 2 * ((q8 + 1) & 6)));
            fl = pin(((t4 & 1) ? par1 : pub0) | (t4 >= 2 || (wp == 7 && q8 < 4 && q8 != 2 - t4) ? 2 : 0));
        };
        if (actc) {
            bar_main();
            CSTAMP(8);
            uint32_t r[8];
#pragma unroll
            for (int s = 0; s < 8; s++) r[s] = lds32(n4 + (5 * uCol - 4 * sb + S_RED + 640 * s));
            stp32_if(true, xp(uPubB + n4), sum8(r), parc);
            CSTAMP(9);
            prepC();
            xab = pin(a_pos(n4 / 4) | (b_pos<40>(n4 / 4) << 16));
            const uint32_t xas = pin(3 * uCol - 2 * sb + S_XA + 192 + (xab & 0xffff)), xbs = pin(6 * uCol - 5 * sb + S_XB + (xab >> 16));
            const float x0 = cc ? ldsf(sb + S_XCAR + n4) : bf_lo(lds16(sb + S_X0 + 160 * (ch & 3) + n4 / 2));
            gather16(xp(uPolB + n4 + lag<DELAY_G>(sb)), parc, 5 * ch + 1, [&](float y, uint32_t) {
                const uint32_t x = pack2(x0 + bfr(y), 0.f);
                sts16(xbs, x);
                sts16(xas, x);
                x1 = bf_lo(x);
                return 0u;
            });
            CSTAMP(10);
        } else {
            bar_main();
            prepC();
        }
        auto stats = [&](uint32_t xa, const uint4& b, uint32_t b4) {
            float a[4] = {};
            const uint4 p0 = lds128(xa), p1 = lds128(xa + 16);
            const uint2 p2 = lds64(xa + 32);
            mmaV(a, p0, b.x, b.y); mmaV(a, p1, b.z, b.w); mma8(a, p2.x, p2.y, b4);
            return a[0] + a[3];
        };
        {
            auto gate_up = [&](auto with_stats) {
                bar_main();
                TST(3);
                CSTAMP(11);
                const uint4 b = lds128(xr);
                const uint32_t b4 = lds32(xr + 16);
                float acc[3][4] = {}, st = 0.f;
                if (with_stats.value) st = stats(xr + (S_XA - S_XB), b, b4);
                mul80(acc, Wgu, b, b4);
                stp64_if(!(td & 2), xp(pubC), tagw(acc[0][0] + acc[0][3], fl & 1), tagw(acc[1][0] + acc[1][3], fl & 1));
                stp32_if(fl > 1, xp(pubC2), !with_stats.value || (td & 2) ? acc[2][0] + acc[2][3] : st, fl & 1);
            };
            if (wp == 7) gate_up(std::true_type()); else gate_up(std::false_type());
        }
        CSTAMP(12);
        float mean = 0.f, den = 1.f;
        {
            IDS();
            const uint32_t wa = pin(sb + S_WD + ((ln & 7) + 48 * ((ln >> 3) & 1) + 8 * (ln >> 4)) * 160 + (wp < 7 ? 16 * wp : 128));
            const uint32_t pubD = pin(uPubD + (t4 & 1) * COL + 16 * (t4 & 2) + 4 * q8 + (fl & 1)), ha = xr + (S_HS - S_XB);
            auto down = [&](const uint32_t (&W)[3][4], const uint4& h0, const uint2& h1) {
                float a0[4] = {}, a1[4] = {}, a2[4] = {};
                mmaA(a0, W[0], h0.x, h0.y); mmaA(a1, W[1], h0.z, h0.w); mmaA(a2, W[2], h1.x, h1.y);
                return ((a0[0] + a0[3]) + (a1[0] + a1[3])) + (a2[0] + a2[3]);
            };
            if (wp < 6) {
                uint32_t Wd[3][4];
                auto ldd = [&] {
#pragma unroll
                    for (int s = 0; s < 3; s++) ldsm4t(Wd[s], wa + s * 2560);
                };
                if (actc) {
                    const uint32_t hsa = pin(6 * uCol - 5 * sb + S_HS + b_pos<48>(n96));
                    const uint32_t src0 = uPolC + lag<DELAY_C>(sb);
                    const char* srcv = xp(src0 + 8 * n96);
                    const char* src = xp(src0 + (ln & 1) * HALF);
                    float gt, up;
                    int guard = 0;
                    bool again;
                    do {
                        uint2 v[8], st[4];
#pragma unroll
                        for (int s = 0; s < 4; s++) st[s] = ldp64(src + 768 + s * 1024);
#pragma unroll
                        for (int s = 0; s < 8; s++) v[s] = ldp64(srcv + (s >> 2) * HALF + (s & 3) * 1024);
                        float sx = (asf(st[0].x) + asf(st[1].x)) + (asf(st[2].x) + asf(st[3].x)), sq = (asf(st[0].y) + asf(st[1].y)) + (asf(st[2].y) + asf(st[3].y));
                        sx += __shfl_xor_sync(~0u, sx, 1); sq += __shfl_xor_sync(~0u, sq, 1);
                        const uint2 cs = lds64(sb + S_CSGU - 768 * cc + 8 * td + ((st[0].x ^ parc) & 1) * 8);
                        again = __any_sync(~0u, (or3(chk4(st, parc), chk8(v, parc), chk8y(v, parc)) & 1) != 0);
                        ln_stats(sx, sq, mean, den);
                        const float rd = rcp(den);
                        gt = fmaf(-mean, asf(cs.x), sum8x(v)); up = fmaf(-mean, asf(cs.y), sum8y(v));
                        ldd();
                        gt *= rd; up *= rd;
                        keep(gt); keep(up);
                    } while (again & (++guard < SPIN_LIMIT));
                    CSTAMP(13);
                    SWEEPS(5 * ch + 2, guard - 1);
                    gt = bfr(gt);
                    const uint32_t h = pack2(bfr(gt * sigmoidf_(gt)) * bfr(up), 0.f);
                    sts16(hsa, h);
                    CSTAMP(14);
                } else ldd();
                bar_main();
                TST(4);
                CSTAMP(15);
                const uint4 h0 = lds128(ha);
                const uint2 h1 = lds64(ha + 16);
                stp32_if(!(td & 2), xp(pubD & ~1u), down(Wd, h0, h1), pubD & 1);
            } else {
                stsvol(sb + S_GATE, ch + 1);
                uint32_t Wd[2][3][4];
#pragma unroll
                for (int s = 0; s < 6; s++) ldsm4t(Wd[s / 3][s % 3], wa + (s / 3) * 16 + (s % 3) * 2560);
                uint32_t v = 0;
                if (wp == 6 ? has0 : has1) {
                    const uint32_t par = wp == 6 ? par0 : par1;
                    const char* src = xp(uPolC + 768 + (ln & 4) * (HALF / 4) + (ln & 3) * 1024 + 4 * min(ln >> 3, 2u) + lag<DELAY_C>(sb));
                    int guard = 0;
                    do v = ldp32(src); while (__any_sync(~0u, (v ^ par) & 1) && ++guard < SPIN_LIMIT);
                }
                bar_main();
                const uint4 h0 = lds128(ha);
                const uint2 h1 = lds64(ha + 16);
                const float d0 = down(Wd[0], h0, h1), d1 = down(Wd[1], h0, h1);
                stp32_if(true, xp(pubD & ~1u), (td & 2) ? d1 : d0, pubD & 1);
                if (wp == 6 ? has0 : has1) {
                    float sx = asf(v);
                    sx += __shfl_xor_sync(~0u, sx, 1); sx += __shfl_xor_sync(~0u, sx, 2); sx += __shfl_xor_sync(~0u, sx, 4);
                    const float sq = __shfl_sync(~0u, sx, 8), xw = __shfl_sync(~0u, sx, 16);
                    ln_stats(sx, sq, mean, den);
                    const float r = bfr(fmaf(-mean, ldsf(sb + S_SWR), xw) * rcp(den));
                    sts32_if(ln == 0, sb + S_STAT + 4 * (wp - 6), __float_as_uint(bfr(sigmoidf_(r))) | (ch + 1));
                }
            }
        }
        CSTAMP(16);
        uint32_t pubE;
        {
            IDS();
            pubE = pin(uPubE + (t4 < 3 ? (wp >> 2) * COL + 192 * (wp & 3) + 64 * t4 + 8 * q8 : (q8 >> 2) * COL + 768 + 4 * (q8 & 1)));
            xr = pin(sb + S_XB + 48 * (ln & 7));
            if (actc && (cc == 0 || g == 0)) {
                const uint32_t m4 = 4 * n80;
                const uint32_t xas = pin(3 * uCol - 2 * sb + S_XA + 192 + a_pos(n80)), xbs = pin(6 * uCol - 5 * sb + S_XB + b_pos<40>(n80));
                const float lnx = __uint_as_float(pin(__float_as_uint(bfr(__fdiv_rn(bfr(x1 - mean), den)))));
                uint32_t x2;
                gather16(xp(uPolD + m4 + lag<DELAY_D>(sb)), parc, 5 * ch + 3, [&](float y, uint32_t z) {
                    const uint32_t gate = ldsvol(sb + S_STAT + 4 * cc + z);
                    x2 = pack2(x1 + bfr(lnx + bfr(bfr(y) * bf_hi(gate))), 0.f);
                    sts16(xbs, x2);
                    sts16(xas, x2);
                    return (uint32_t)((gate & 7) != ch + 1);
                });
                CSTAMP(17);
                if (cc) reinterpret_cast<unsigned short*>(P.out)[640 * (ch - 1) + 80 * i + n80] = (unsigned short)x2;
                x1 = bf_lo(x2);
            }
        }
        CSTAMP(18);
        if (!has0) break;
        {
            auto qproj = [&](auto with_stats) {
                bar_main();
                TST(5);
                CSTAMP(19);
                const uint32_t t4 = td & 3;
                const uint4 b = lds128(xr);
                const uint32_t b4 = lds32(xr + 16);
                float acc[6][4] = {}, st = 0.f;
                if (with_stats.value) st = stats(xr + (S_XA - S_XB), b, b4);
                mul80(acc, Wq, b, b4);
                const float v0 = sel4(t4, acc[0][0] + acc[0][3], acc[2][0] + acc[2][3], acc[4][0] + acc[4][3], acc[4][0] + acc[4][3]);
                const float v1 = sel4(t4, acc[1][0] + acc[1][3], acc[3][0] + acc[3][3], acc[5][0] + acc[5][3], acc[5][0] + acc[5][3]);
                if (with_stats.value) stp32_if((td & 11) == 3, xp(pubE), st, par0);
                stp64_if(t4 < 3, xp(pubE), tagw(v0, par0), tagw(v1, par0));
            };
            if (wp == 7) qproj(std::true_type()); else qproj(std::false_type());
            sts32_if(td < 80, sb + S_XCAR + 4 * td, __float_as_uint(x1));
        }
        CSTAMP(20);
        auto pass2 = [&](auto d0, auto d1, auto d2) {
            constexpr int D0 = d0.value, D1 = d1.value, D = D0 + D1 + d2.value;
            IDS();
            const uint32_t ua = sb + k_place(ch, wp & 6) * SLOT + (wp & 1) * UNIT, k0 = k_off(ln);
            uint32_t kf[12][2][4];
            auto ldk = [&](int s) { const uint32_t a = (k0 ^ (32 * (s / 3))) + (ua + 1024 * (s % 3)); ldsm4(kf[s][0], a); ldsm4(kf[s][1], a + SLOT); };
            auto ldv1 = [&](int k) { ldsm4t(vf[k / 3][k % 3], voff[k % 3] + (sb + v_place(ch, k / 3) * SLOT)); };
            auto ldv = [&](int s) { ldv1(3 * s); ldv1(3 * s + 1); ldv1(3 * s + 2); };
            constexpr uint32_t LATE = LAST_LATE;
            constexpr uint64_t EARLY_LIST = bit_list(~LATE), LATE_LIST = bit_list(LATE);
            auto early = [&](int k) {
                if (D1 == 0) ldk(k);
                else if (k < 3) { ldv1(9 + 2 * k); ldv1(10 + 2 * k); }
                else ldk((EARLY_LIST >> (4 * (k - 3))) & 15);
            };
            if (D1 > 0) vaddr(voff);
            if (!(mbar_try(sb + S_FK + 8 * (wp & 6), par1) & mbar_try(sb + S_FK + 8 * (wp | 1), par1))) { mbar_wait(sb + S_FK + 8 * (wp & 6), par1); mbar_wait(sb + S_FK + 8 * (wp | 1), par1); }
#pragma unroll
            for (int s = 0; s < D0; s++) early(s);
            if (wp < 6) {
                const uint32_t qsa = pin(sb + S_QS + 384 * ch + q_pos(td));
                const uint32_t src0 = uPolE + lag<(D1 > 0 ? 0 : DELAY_E)>(sb);
                const char* srcv = xp(src0 + 4 * td);
                const char* src = xp(src0 + (ln & 1) * HALF);
                uint32_t v[8]; uint2 st[4];
                auto look = [&] {
#pragma unroll
                    for (int s = 0; s < 4; s++) st[s] = ldp64(src + 768 + s * 1024);
#pragma unroll
                    for (int s = 0; s < 8; s++) v[s] = ldp32(srcv + (s >> 2) * HALF + (s & 3) * 1024);
                };
                if (D1 > 0) {
                    look();
                    __syncwarp();
#pragma unroll
                    for (int s = D0; s < D0 + D1; s++) early(s);
                }
                int guard = 0;
                while (true) {
                    if (D1 == 0) look();
                    float sx = (asf(st[0].x) + asf(st[1].x)) + (asf(st[2].x) + asf(st[3].x)), sq = (asf(st[0].y) + asf(st[1].y)) + (asf(st[2].y) + asf(st[3].y));
                    sx += __shfl_xor_sync(~0u, sx, 1); sq += __shfl_xor_sync(~0u, sq, 1);
                    const float cs = ldsf(sb + S_CSQ + 4 * td + ((st[0].x ^ par0) & 1) * 4);
                    const bool again = __any_sync(~0u, ((chk8(v, par0) | chk4(st, par0)) & 1) != 0);
                    ln_stats(sx, sq, mean, den);
                    const uint32_t q = pack2(fmaf(-mean, cs, sum8(v)) * rcp(den), 0.f);
                    sts16(qsa, q);
                    if (!(again & (++guard < SPIN_LIMIT))) break;
                    if (D1 > 0) look();
                }
                SWEEPS(5 * ch + 4, guard - 1);
                CSTAMP(22);
            } else {
#pragma unroll
                for (int s = D0; s < D0 + D1; s++) early(s);
            }
#pragma unroll
            for (int s = D0 + D1; s < D; s++) early(s);
            bar_main();
            TST(6);
            CSTAMP(1);
            uint2 q = lds64(sb + S_QS + 384 * ch + 8 * ln);
            float acc[2][4] = {};
            constexpr int V0 = 13 - D, NV = D1 > 0 ? 2 : (2 * (D - 1)) / 3;
            static_assert(D1 == 0 || LAST0 == 0 || D - 3 + __builtin_popcount(LATE) == 12, "plan");
#pragma unroll
            for (int s = 0; s < 12; s++) {
                const bool m = q8 == (s & 7);
                const uint32_t b0 = m ? q.x : 0u, b1 = m ? q.y : 0u;
                if (s == 7) q = lds64(sb + S_QS + 384 * ch + 8 * ln + 256);
                mmaA(acc[0], kf[s][0], b0, b1);
                mmaA(acc[1], kf[s][1], b0, b1);
                if (D1 > 0) {
                    if (s >= 1 && s <= __builtin_popcount(LATE)) ldk((LATE_LIST >> (4 * (s - 1))) & 15);
                } else {
                    if (s >= 1 && s + D - 1 < 12) ldk(s + D - 1);
                    if (s >= 1 && s + D - 1 == 11) { __syncwarp(); arrive_if(ln == 0, sb + S_RELK); }
                    if (s == V0) vaddr(voff);
                    if (s >= V0 && 2 * (s - V0) < 3 * NV) ldv1(9 + 2 * (s - V0));
                    if (s >= V0 && 2 * (s - V0) + 1 < 3 * NV) ldv1(10 + 2 * (s - V0));
                }
            }
            CSTAMP(24);
            {
                const float v0 = acc[0][0] + acc[0][1], v1 = acc[0][2] + acc[0][3], v2 = acc[1][0] + acc[1][1], v3 = acc[1][2] + acc[1][3];
                const bool hi = t4 & 2, od = t4 & 1;
                const float u0 = (hi ? v2 : v0) + __shfl_xor_sync(~0u, hi ? v0 : v2, 2), u1 = (hi ? v3 : v1) + __shfl_xor_sync(~0u, hi ? v1 : v3, 2);
                const float s = (od ? u1 : u0) + __shfl_xor_sync(~0u, od ? u0 : u1, 1);
                CSTAMP(2);
                probs(scaled(s), sb + S_PS + PS_PASS, wp, ln);
                CSTAMP(3);
            }
            bar_main();
            TST(10);
            CSTAMP(4);
            if (D1 > 0) values(vf, std::integral_constant<uint32_t, ORDER_L>(), [&](int s) { if (s < 3) ldv(s + 5); }, sb + S_PS + PS_PASS, 1, par0);
            else values(vf, std::integral_constant<uint32_t, (NV > 1 ? ORDER_R : 0x76543210)>(),
                        [&](int s) { if (s >= (NV > 1 ? 2 : 1) && s + NV + (NV > 1 ? 1 : 2) < 8) ldv(s + NV + (NV > 1 ? 1 : 2)); }, sb + S_PS + PS_PASS, 1, par0);
            arrive_if(ln == 0, sb + S_RELV);
        };
        if (LAST0 > 0 && ch == 3) {
            pass2(std::integral_constant<int, LAST0>(), std::integral_constant<int, LAST1>(), std::integral_constant<int, LAST2>());
#pragma unroll
            for (int m = 0; m < 60; m++) { uint32_t& r = m % 10 < 8 ? Wq[m / 10].a[(m % 10) / 4][m % 2 + 2 * ((m % 10) / 2 % 2)] : Wq[m / 10].c[m % 2]; r = 0; opaque(r); }
        } else pass2(std::integral_constant<int, KPRE>(), std::integral_constant<int, 0>(), std::integral_constant<int, KPRE2>());
        TST(11);
        CSTAMP(23);
    }
    sts32_if(td == 255, sb + S_GATE, 6);
    TSTAMP(3);
}

typedef CUresult (*EncodeFn)(CUtensorMap*, CUtensorMapDataType, cuuint32_t, void*, const cuuint64_t*, const cuuint64_t*, const cuuint32_t*,
                             const cuuint32_t*, CUtensorMapInterleave, CUtensorMapSwizzle, CUtensorMapL2promotion, CUtensorMapFloatOOBfill);

void make_map(EncodeFn enc, CUtensorMap* m, const void* base, uint64_t cols, uint64_t rows, uint32_t box_cols, uint32_t box_rows, bool swizzle) {
    cuuint64_t dims[2] = {cols, rows};
    cuuint64_t strides[1] = {cols * 2};
    cuuint32_t box[2] = {box_cols, box_rows};
    cuuint32_t es[2] = {1, 1};
    enc(m, CU_TENSOR_MAP_DATA_TYPE_BFLOAT16, 2, const_cast<void*>(base), dims, strides, box, es, CU_TENSOR_MAP_INTERLEAVE_NONE,
        swizzle ? CU_TENSOR_MAP_SWIZZLE_128B : CU_TENSOR_MAP_SWIZZLE_NONE, swizzle ? CU_TENSOR_MAP_L2_PROMOTION_NONE : WPROMO, CU_TENSOR_MAP_FLOAT_OOB_FILL_NONE);
}

}

extern "C" void kernel_launch(void* const* d_in, const int* in_sizes, int n_in, void* d_out, int out_size) {
    (void)in_sizes; (void)n_in; (void)out_size;
    static EncodeFn enc = nullptr;
    if (!enc) {
        void* f = nullptr;
        cudaDriverEntryPointQueryResult q;
        cudaGetDriverEntryPoint("cuTensorMapEncodeTiled", &f, cudaEnableDefault, &q);
        enc = (EncodeFn)f;
        cudaFuncSetAttribute(fused_kernel, cudaFuncAttributeMaxDynamicSharedMemorySize, SMEM_BYTES);
    }
    Params P;
    P.x = (const __nv_bfloat16*)d_in[0]; P.k = (const __nv_bfloat16*)d_in[1]; P.v = (const __nv_bfloat16*)d_in[2];
    P.wr = (const __nv_bfloat16*)d_in[6];
    P.out = (__nv_bfloat16*)d_out;
    Maps M;
    {
        cuuint64_t dims[4] = {64, 8, 3, (cuuint64_t)KV_BATCH_KEYS / 2}, strides[3] = {384, 128, 3072};
        cuuint32_t box[4] = {64, 8, 3, 2}, es[4] = {1, 1, 1, 1};
        enc(&M.k, CU_TENSOR_MAP_DATA_TYPE_BFLOAT16, 4, d_in[1], dims, strides, box, es, CU_TENSOR_MAP_INTERLEAVE_NONE, CU_TENSOR_MAP_SWIZZLE_128B,
            CU_TENSOR_MAP_L2_PROMOTION_NONE, CU_TENSOR_MAP_FLOAT_OOB_FILL_NONE);
        box[3] = 1;
        enc(&M.kh, CU_TENSOR_MAP_DATA_TYPE_BFLOAT16, 4, d_in[1], dims, strides, box, es, CU_TENSOR_MAP_INTERLEAVE_NONE, CU_TENSOR_MAP_SWIZZLE_128B,
            CU_TENSOR_MAP_L2_PROMOTION_NONE, CU_TENSOR_MAP_FLOAT_OOB_FILL_NONE);
    }
    make_map(enc, &M.v, P.v, 64, (uint64_t)12 * KV_BATCH_KEYS, 64, 96, true);
    make_map(enc, &M.vu, P.v, 64, (uint64_t)12 * KV_BATCH_KEYS, 64, 48, true);
    make_map(enc, &M.wq, d_in[3], 6144, 640, 192, 40, false);
    make_map(enc, &M.wo, d_in[4], 640, 6144, 80, 96, false);
    make_map(enc, &M.wg, d_in[7], 1536, 640, 96, 80, false);
    make_map(enc, &M.wu, d_in[8], 1536, 640, 96, 80, false);
    make_map(enc, &M.wd, d_in[9], 640, 1536, 80, 96, false);
    fused_kernel<<<NCTA, NTHR, SMEM_BYTES, cudaStreamPerThread>>>(P, M);
}
```

```cpp
#include <cuda_runtime.h>
#include <cuda.h>
#include <cuda_bf16.h>
#include <stdint.h>
#include <type_traits>

namespace {

constexpr int NCTA = 128;
constexpr int NTHR = 384;
constexpr int UNIT = 6144;
constexpr int SLOT = 12288;
#define TAU 4050
#define TAUW 3900
#define TAU0 3900
#define PF0 2
#define PFMAP 1
#define ZPOS 1
#define LOOK1 0
#define LOOK2 0
#define SLACK 8000
#define SLACK0 SLACK
#define TSH 0
#define HOP1_NS 200
#define RELR_AT 0
#define PSLEEP 0
#define KRE_EARLY 6
#define TMIN 2400
#define T_LEAD 0
#define WIN_W 3
#define WIN_S 4
#define WIN_U 10
#define RFR_ON 1
#define KRE_N1 0
#define KRE_TAU1 2500
#define RFR_TAU 6400
#define VPF 5
#define KRE_GATE 0
#define KRE_GATE3 KRE_GATE
#define JFREE 16
#define TFREE 0
#define KRE_TAU 3000
#define KRE_TAU3 KRE_TAU
#define HDEPTH 3
#define LAST0 3
#define ORDER_L 0x76543210
#define ORDER_R 0x76543210
#define LAST_LATE 0xaa8
#define LAST1 4
#define LAST2 3
#define FSTEP 4
#define SPEC 1
#define PV1PIPE 0
#define HOPA0 6
#define HOPA1 6
#define WPROMO CU_TENSOR_MAP_L2_PROMOTION_NONE
#define KPRE 1
#define KPRE2 3
#define DELAY_G 3
#define DELAY_L 5
#define DELAY_C 3
#define DELAY_D 1
#define DELAY_E 3
#define REG_LO "40"
#define REG_HI "232"
#define SPIN_LOG 17
constexpr int SPIN_LIMIT = 1 << SPIN_LOG;

__host__ __device__ constexpr uint32_t pairL(uint32_t region, uint32_t c, uint32_t g) { return (g & 1) | ((g >> 1) << 2) | (c << 5) | (region << 6); }
__host__ __device__ constexpr uint32_t pairG(uint32_t d, uint32_t c, uint32_t i) { return (i & 1) | ((i >> 1) << 2) | (d << 4) | (c << 5) | (3u << 6); }
constexpr uint32_t RA = 0, RC = 1, RE = 2, HALF = 16384, COPY = 4096, PMASK = 0x59;
constexpr uint32_t XS = 0;
constexpr uint32_t XS2 = XS + 128 * 7680;
constexpr uint32_t XSEND = XS2 + 128 * 768;
__device__ uint4 g_s[XSEND / 16];
__device__ uint4 g_x[(4u << 20) / 16];
#define SWEEPS(k, n) do {} while (0)

constexpr uint32_t S_WD = 16 * SLOT;
constexpr uint32_t S_DUMMY = S_WD + 15360;
constexpr uint32_t S_BAR = S_DUMMY + 4096;
constexpr uint32_t S_FV = S_BAR, S_FK = S_FV + 64, S_RING = S_FK + 64, S_DBAR = S_RING + 48, S_WFULL = S_DBAR + 32, S_QRDY = S_WFULL + 88;
constexpr uint32_t S_RELK = S_QRDY + 8, S_RELV = S_RELK + 8, S_RELR = S_RELV + 8, S_RELW = S_RELR + 8, S_SCO = S_RELW + 24;
constexpr uint32_t S_OS1 = S_SCO + 8;
constexpr uint32_t S_ZERO = S_OS1 + 8;
constexpr uint32_t S_KF = S_ZERO + 8;
constexpr uint32_t S_TOK = S_KF + 8;
constexpr uint32_t S_SIDE = S_TOK + 80, S_GATE = S_SIDE + 4;
constexpr uint32_t S_STAT = S_GATE + 12, S_SWR = S_STAT + 16;
constexpr uint32_t S_XCAR = S_STAT + 32;
constexpr uint32_t S_CSQ = S_XCAR + 320;
constexpr uint32_t S_CSGU = S_CSQ + 768;
constexpr uint32_t S_RED = S_CSGU + 768;
constexpr uint32_t S_L0 = S_RED;
constexpr uint32_t S_OS = S_RED + 5120;
constexpr uint32_t S_PS = S_OS + 1536;
constexpr uint32_t PS_MAX = 512, PS_PASS = 544;
constexpr uint32_t S_QS = S_PS + 2 * PS_PASS;
constexpr uint32_t S_XB = S_QS + 1536;
constexpr uint32_t S_XA = S_XB + 768;
constexpr uint32_t S_HS = S_XA + 768;
constexpr uint32_t S_X0 = S_HS + 768;
constexpr uint32_t S_SC = S_X0 + 640;
constexpr uint32_t S_TM = S_SC + 512;
constexpr int SMEM_BYTES = S_TM + 256;
static_assert(SMEM_BYTES <= 232448 && S_STAT % 16 == 0 && S_RED % 16 == 0 && S_XB % 16 == 0 && S_HS % 16 == 0 && S_PS % 16 == 0 && S_QS % 16 == 0, "smem");
static_assert(S_SCO == S_BAR + 44 * 8 && S_RELK == S_BAR + 38 * 8, "barriers");
constexpr uint32_t ST_WQ = 3 * SLOT, ST_WG = 8 * SLOT, ST_WO = 11 * SLOT;

__device__ __forceinline__ uint32_t smem_u32(const void* p) { return (uint32_t)__cvta_generic_to_shared(p); }
__device__ __forceinline__ void mbar_init(uint32_t bar, uint32_t cnt) { asm volatile("mbarrier.init.shared::cta.b64 [%0], %1;" :: "r"(bar), "r"(cnt) : "memory"); }
__device__ __forceinline__ void mbar_expect(uint32_t bar, uint32_t bytes) { asm volatile("mbarrier.arrive.expect_tx.shared::cta.b64 _, [%0], %1;" :: "r"(bar), "r"(bytes) : "memory"); }
__device__ __forceinline__ void mbar_arrive(uint32_t bar) { asm volatile("mbarrier.arrive.shared::cta.b64 _, [%0];" :: "r"(bar) : "memory"); }
__device__ __forceinline__ bool mbar_try(uint32_t bar, uint32_t parity) {
    uint32_t ok;
    asm volatile("{\n .reg .pred p;\n mbarrier.try_wait.parity.shared::cta.b64 p, [%1], %2;\n selp.u32 %0, 1, 0, p;\n}" : "=r"(ok) : "r"(bar), "r"(parity) : "memory");
    return ok != 0;
}
__device__ __forceinline__ bool mbar_test(uint32_t bar, uint32_t parity) {
    uint32_t ok;
    asm volatile("{\n .reg .pred p;\n mbarrier.test_wait.parity.shared::cta.b64 p, [%1], %2;\n selp.u32 %0, 1, 0, p;\n}" : "=r"(ok) : "r"(bar), "r"(parity) : "memory");
    return ok != 0;
}
__device__ __forceinline__ void mbar_wait(uint32_t bar, uint32_t parity) {
    int n = 0;
    while (!mbar_try(bar, parity) && ++n < SPIN_LIMIT) {}
}
__device__ __forceinline__ unsigned long long gtime() { unsigned long long t; asm volatile("mov.u64 %0, %globaltimer;" : "=l"(t)); return t; }
__device__ __forceinline__ uint32_t gtime32() { uint32_t t; asm volatile("mov.u32 %0, %globaltimer_lo;" : "=r"(t)); return t; }
__device__ __forceinline__ void bar_main() { asm volatile("bar.sync 1, 256;" ::: "memory"); }

__device__ __forceinline__ void mma16816(float (&c)[4], uint32_t a0, uint32_t a1, uint32_t a2, uint32_t a3, uint32_t b0, uint32_t b1) {
    asm("mma.sync.aligned.m16n8k16.row.col.f32.bf16.bf16.f32 {%0,%1,%2,%3}, {%4,%5,%6,%7}, {%8,%9}, {%0,%1,%2,%3};"
        : "+f"(c[0]), "+f"(c[1]), "+f"(c[2]), "+f"(c[3]) : "r"(a0), "r"(a1), "r"(a2), "r"(a3), "r"(b0), "r"(b1));
}
__device__ __forceinline__ void mmaA(float (&c)[4], const uint32_t (&a)[4], uint32_t b0, uint32_t b1) { mma16816(c, a[0], a[1], a[2], a[3], b0, b1); }
__device__ __forceinline__ void mmaAv(float (&c)[4], const uint32_t (&a)[4], uint32_t b0, uint32_t b1) {
    asm volatile("mma.sync.aligned.m16n8k16.row.col.f32.bf16.bf16.f32 {%0,%1,%2,%3}, {%4,%5,%6,%7}, {%8,%9}, {%0,%1,%2,%3};"
        : "+f"(c[0]), "+f"(c[1]), "+f"(c[2]), "+f"(c[3]) : "r"(a[0]), "r"(a[1]), "r"(a[2]), "r"(a[3]), "r"(b0), "r"(b1) : "memory");
}
__device__ __forceinline__ void mma8(float (&c)[4], uint32_t a0, uint32_t a1, uint32_t b0) {
    asm("mma.sync.aligned.m16n8k8.row.col.f32.bf16.bf16.f32 {%0,%1,%2,%3}, {%4,%5}, {%6}, {%0,%1,%2,%3};"
        : "+f"(c[0]), "+f"(c[1]), "+f"(c[2]), "+f"(c[3]) : "r"(a0), "r"(a1), "r"(b0));
}
struct W80 { uint32_t a[2][4], c[2]; };
template <int N> __device__ __forceinline__ void mul80(float (&acc)[N][4], const W80 (&W)[N], const uint4& b, uint32_t b4) {
#pragma unroll
    for (int m = 0; m < N; m++) mmaA(acc[m], W[m].a[0], b.x, b.y);
#pragma unroll
    for (int m = 0; m < N; m++) mmaA(acc[m], W[m].a[1], b.z, b.w);
#pragma unroll
    for (int m = 0; m < N; m++) mma8(acc[m], W[m].c[0], W[m].c[1], b4);
}
__device__ __forceinline__ void ldsm2t(uint32_t (&r)[2], uint32_t addr) {
    asm volatile("ldmatrix.sync.aligned.m8n8.x2.trans.shared.b16 {%0,%1}, [%2];" : "=r"(r[0]), "=r"(r[1]) : "r"(addr) : "memory");
}
__device__ __forceinline__ void mmaV(float (&c)[4], const uint4& a, uint32_t b0, uint32_t b1) { mma16816(c, a.x, a.y, a.z, a.w, b0, b1); }
__device__ __forceinline__ void ldsm4(uint32_t (&r)[4], uint32_t addr) {
    asm volatile("ldmatrix.sync.aligned.m8n8.x4.shared.b16 {%0,%1,%2,%3}, [%4];" : "=r"(r[0]), "=r"(r[1]), "=r"(r[2]), "=r"(r[3]) : "r"(addr) : "memory");
}
__device__ __forceinline__ void ldsm4t(uint32_t (&r)[4], uint32_t addr) {
    asm volatile("ldmatrix.sync.aligned.m8n8.x4.trans.shared.b16 {%0,%1,%2,%3}, [%4];" : "=r"(r[0]), "=r"(r[1]), "=r"(r[2]), "=r"(r[3]) : "r"(addr) : "memory");
}
__device__ __forceinline__ uint32_t lds16(uint32_t a) { uint16_t v; asm volatile("ld.shared.u16 %0, [%1];" : "=h"(v) : "r"(a) : "memory"); return v; }
__device__ __forceinline__ uint32_t lds32(uint32_t a) { uint32_t v; asm volatile("ld.shared.u32 %0, [%1];" : "=r"(v) : "r"(a) : "memory"); return v; }
__device__ __forceinline__ float ldsf(uint32_t a) { return __uint_as_float(lds32(a)); }
__device__ __forceinline__ uint2 lds64(uint32_t a) { uint2 v; asm volatile("ld.shared.v2.u32 {%0,%1}, [%2];" : "=r"(v.x), "=r"(v.y) : "r"(a) : "memory"); return v; }
__device__ __forceinline__ uint4 lds128(uint32_t a) { uint4 v; asm volatile("ld.shared.v4.u32 {%0,%1,%2,%3}, [%4];" : "=r"(v.x), "=r"(v.y), "=r"(v.z), "=r"(v.w) : "r"(a) : "memory"); return v; }
__device__ __forceinline__ int ldsvol(uint32_t a) { int v; asm volatile("ld.volatile.shared.u32 %0, [%1];" : "=r"(v) : "r"(a) : "memory"); return v; }
__device__ __forceinline__ void stsvol(uint32_t a, int v) { asm volatile("st.volatile.shared.u32 [%0], %1;" :: "r"(a), "r"(v) : "memory"); }
__device__ __forceinline__ void sts_hi16(uint32_t a, float v) { asm volatile("{\n .reg .b16 lo, hi;\n mov.b32 {lo, hi}, %1;\n st.shared.u16 [%0], hi;\n}" :: "r"(a), "r"(__float_as_uint(v)) : "memory"); }
__device__ __forceinline__ void sts16(uint32_t a, uint32_t v) { asm volatile("st.shared.u16 [%0], %1;" :: "r"(a), "r"(v) : "memory"); }
__device__ __forceinline__ void sts32(uint32_t a, uint32_t v) { asm volatile("st.shared.u32 [%0], %1;" :: "r"(a), "r"(v) : "memory"); }
__device__ __forceinline__ void stsf(uint32_t a, float v) { sts32(a, __float_as_uint(v)); }
__device__ __forceinline__ void sts64(uint32_t a, uint32_t x, uint32_t y) { asm volatile("st.shared.v2.u32 [%0], {%1,%2};" :: "r"(a), "r"(x), "r"(y) : "memory"); }

__device__ __forceinline__ void sts_hi16_if(bool p, uint32_t a, float v) {
    asm volatile("{\n .reg .pred p;\n .reg .b16 lo, hi;\n setp.ne.u32 p, %2, 0;\n mov.b32 {lo, hi}, %1;\n @p st.shared.u16 [%0], hi;\n}" :: "r"(a), "r"(__float_as_uint(v)), "r"((uint32_t)p) : "memory");
}
__device__ __forceinline__ void sts32_if(bool p, uint32_t a, uint32_t v) {
    asm volatile("{\n .reg .pred p;\n setp.ne.u32 p, %2, 0;\n @p st.shared.u32 [%0], %1;\n}" :: "r"(a), "r"(v), "r"((uint32_t)p) : "memory");
}
__device__ __forceinline__ void sts64_if(bool p, uint32_t a, float x, float y) {
    asm volatile("{\n .reg .pred p;\n setp.ne.u32 p, %3, 0;\n @p st.shared.v2.f32 [%0], {%1,%2};\n}" :: "r"(a), "f"(x), "f"(y), "r"((uint32_t)p) : "memory");
}
__device__ __forceinline__ void arrive_if(bool p, uint32_t bar) {
    asm volatile("{\n .reg .pred p;\n setp.ne.u32 p, %1, 0;\n @p mbarrier.arrive.shared::cta.b64 _, [%0];\n}" :: "r"(bar), "r"((uint32_t)p) : "memory");
}
__device__ __forceinline__ void opaque(uint32_t& v) { asm volatile("" : "+r"(v)); }
__device__ __forceinline__ void keep(uint32_t& v) { asm volatile("" : "+r"(v)); }
__device__ __forceinline__ void keep(float& v) { asm volatile("" : "+f"(v)); }
template <class T> __device__ __forceinline__ void keep(T*& v) { asm volatile("" : "+l"(v)); }

__device__ __forceinline__ uint32_t ldp32(const char* p) { uint32_t v; asm volatile("ld.relaxed.gpu.global.u32 %0, [%1];" : "=r"(v) : "l"(p) : "memory"); return v; }
__device__ __forceinline__ uint2 ldp64(const char* p) {
    uint2 v; asm volatile("{\n .reg .b64 d;\n ld.relaxed.gpu.global.b64 d, [%2];\n mov.b64 {%0,%1}, d;\n}" : "=r"(v.x), "=r"(v.y) : "l"(p) : "memory"); return v;
}
__device__ __forceinline__ uint32_t tagw(float f, uint32_t par) { return (__float_as_uint(f) & ~1u) | par; }
__device__ __forceinline__ void stp32(char* p, float a, uint32_t par) { asm volatile("st.relaxed.gpu.global.u32 [%0], %1;" :: "l"(p), "r"(tagw(a, par)) : "memory"); }
__device__ __forceinline__ void stp64(char* p, float a, float b, uint32_t par) {
    asm volatile("{\n .reg .b64 d;\n mov.b64 d, {%1,%2};\n st.relaxed.gpu.global.b64 [%0], d;\n}" :: "l"(p), "r"(tagw(a, par)), "r"(tagw(b, par)) : "memory");
}
__device__ __forceinline__ void stp32_if(bool p, char* d, float a, uint32_t par) {
    asm volatile("{\n .reg .pred p;\n setp.ne.u32 p, %2, 0;\n @p st.relaxed.gpu.global.u32 [%0], %1;\n @p st.relaxed.gpu.global.u32 [%0+4096], %1;\n}" :: "l"(d), "r"(tagw(a, par)), "r"((uint32_t)p) : "memory");
}
__device__ __forceinline__ void stp64_if(bool p, char* d, uint32_t lo, uint32_t hi) {
    asm volatile("{\n .reg .pred p;\n .reg .b64 d;\n setp.ne.u32 p, %3, 0;\n mov.b64 d, {%1,%2};\n @p st.relaxed.gpu.global.b64 [%0], d;\n @p st.relaxed.gpu.global.b64 [%0+4096], d;\n}" :: "l"(d), "r"(lo), "r"(hi), "r"((uint32_t)p) : "memory");
}
__device__ __forceinline__ uint32_t chk2(uint32_t a, uint32_t b, uint32_t par) { uint32_t r; asm("lop3.b32 %0, %1, %2, %3, 0x7E;" : "=r"(r) : "r"(a), "r"(b), "r"(par)); return r; }
__device__ __forceinline__ uint32_t or3(uint32_t a, uint32_t b, uint32_t c) { uint32_t r; asm("lop3.b32 %0, %1, %2, %3, 0xFE;" : "=r"(r) : "r"(a), "r"(b), "r"(c)); return r; }
__device__ __forceinline__ uint32_t chk8(const uint32_t (&v)[8], uint32_t par) { return or3(chk2(v[0], v[1], par), chk2(v[2], v[3], par), or3(chk2(v[4], v[5], par), chk2(v[6], v[7], par), 0)); }
__device__ __forceinline__ uint32_t chk8(const uint2 (&v)[8], uint32_t par) { return or3(chk2(v[0].x, v[1].x, par), chk2(v[2].x, v[3].x, par), or3(chk2(v[4].x, v[5].x, par), chk2(v[6].x, v[7].x, par), 0)); }
__device__ __forceinline__ uint32_t chk8y(const uint2 (&v)[8], uint32_t par) { return or3(chk2(v[0].y, v[1].y, par), chk2(v[2].y, v[3].y, par), or3(chk2(v[4].y, v[5].y, par), chk2(v[6].y, v[7].y, par), 0)); }
__device__ __forceinline__ uint32_t chk4(const uint2 (&v)[4], uint32_t par) { return or3(chk2(v[0].x, v[0].y, par), chk2(v[1].x, v[1].y, par), or3(chk2(v[2].x, v[2].y, par), chk2(v[3].x, v[3].y, par), 0)); }
__device__ __forceinline__ float asf(uint32_t v) { return __uint_as_float(v); }
__device__ __forceinline__ float sum8(const uint32_t (&v)[8]) { return ((asf(v[0]) + asf(v[1])) + (asf(v[2]) + asf(v[3]))) + ((asf(v[4]) + asf(v[5])) + (asf(v[6]) + asf(v[7]))); }
__device__ __forceinline__ float sum8x(const uint2 (&v)[8]) { return ((asf(v[0].x) + asf(v[1].x)) + (asf(v[2].x) + asf(v[3].x))) + ((asf(v[4].x) + asf(v[5].x)) + (asf(v[6].x) + asf(v[7].x))); }
__device__ __forceinline__ float sum8y(const uint2 (&v)[8]) { return ((asf(v[0].y) + asf(v[1].y)) + (asf(v[2].y) + asf(v[3].y))) + ((asf(v[4].y) + asf(v[5].y)) + (asf(v[6].y) + asf(v[7].y))); }

__device__ __forceinline__ uint32_t pack2(float lo, float hi) { uint32_t r; asm("cvt.rn.bf16x2.f32 %0, %1, %2;" : "=r"(r) : "f"(hi), "f"(lo)); return r; }
__device__ __forceinline__ float bfr(float x) { return __uint_as_float(pack2(0.0f, x)); }
__device__ __forceinline__ float ex2(float x) { float r; asm("ex2.approx.ftz.f32 %0, %1;" : "=f"(r) : "f"(x)); return r; }
__device__ __forceinline__ float rcp(float x) { float r; asm("rcp.approx.ftz.f32 %0, %1;" : "=f"(r) : "f"(x)); return r; }
__device__ __forceinline__ float sqrt_(float x) { float r; asm("sqrt.approx.ftz.f32 %0, %1;" : "=f"(r) : "f"(x)); return r; }
__device__ __forceinline__ float bf_lo(uint32_t v) { return __uint_as_float(v << 16); }
__device__ __forceinline__ float bf_hi(uint32_t v) { return __uint_as_float(v & 0xffff0000u); }
__device__ __forceinline__ float sel4(int k, float a, float b, float c, float d) { return (k & 2) ? ((k & 1) ? d : c) : ((k & 1) ? b : a); }
constexpr float LOG2E = 1.4426950408889634f;
constexpr uint32_t ONES = 0x3f803f80u;

__device__ __forceinline__ void ln_stats(float sum, float sq, float& mean, float& den) {
    const float m = sum * (1.0f / 640.0f);
    const float var = fmaxf(fmaf(sq, 1.0f / 640.0f, -m * m), 0.0f);
    mean = bfr(m);
    den = bfr(sqrt_(bfr(bfr(var) + 1e-5f)));
}
__device__ __forceinline__ float sigmoidf_(float x) { return rcp(1.0f + ex2(-x * LOG2E)); }

#define TSTAMP(k) do {} while (0)
#define TST(k) do {} while (0)

#define CSTAMP(k) do {} while (0)
template <int N> __device__ __forceinline__ uint32_t lag(uint32_t sb) {
    uint32_t z = 0;
#pragma unroll
    for (int k = 0; k < N; k++) z = ldsvol(sb + S_ZERO + z);
    return z;
}
__device__ __forceinline__ void warm_mma(uint32_t& a, uint32_t& b) {
    asm volatile("mma.sync.aligned.m16n8k8.row.col.f16.f16.f16.f16 {%0,%1}, {%0,%1}, {%0}, {%0,%1};" : "+r"(a), "+r"(b) :: "memory");
}
#define KWNS2 20
#define KWNS 200
template <int STRIDE>
__device__ __forceinline__ float gather8(const char* p, uint32_t par) {
    uint32_t v[8];
    int guard = 0;
    do {
#pragma unroll
        for (int s = 0; s < 8; s++) v[s] = ldp32(p + s * STRIDE);
    } while ((chk8(v, par) & 1) && ++guard < SPIN_LIMIT);
    return sum8(v);
}
template <class F>
__device__ __forceinline__ void gather16(const char* p, uint32_t par, int k, F use) {
    uint32_t v[8], u[8];
    int guard = 0;
    bool again;
    do {
#pragma unroll
        for (int s = 0; s < 8; s++) v[s] = ldp32(p + s * 512);
#pragma unroll
        for (int s = 0; s < 8; s++) u[s] = ldp32(p + HALF + s * 512);
        const uint32_t stale = use(sum8(v) + sum8(u), ((v[0] ^ par) & 1) * 8);
        again = __any_sync(~0u, (or3(chk8(v, par), chk8(u, par), stale) & 1) != 0);
    } while (again & (++guard < SPIN_LIMIT));
    SWEEPS(k, guard - 1);
}

struct Params {
    const __nv_bfloat16 *x, *k, *v, *wr;
    __nv_bfloat16* out;
};
struct Maps { CUtensorMap k, v, vu, wq, wo, wg, wu, wd; };

constexpr int KV_BATCH_KEYS = 32 * 4096;

__device__ __forceinline__ void tma2d(uint32_t dst, const CUtensorMap* m, int c0, int c1, uint32_t bar, uint32_t bytes, uint64_t pol) {
    asm volatile("{\n .reg .pred p;\n elect.sync _|p, 0xffffffff;\n"
                 " @p mbarrier.arrive.expect_tx.shared::cta.b64 _, [%2], %6;\n"
                 " @p cp.async.bulk.tensor.2d.shared::cluster.global.mbarrier::complete_tx::bytes.L2::cache_hint [%0], [%1, {%3, %4}], [%2], %5;\n}"
                 :: "r"(dst), "l"(m), "r"(bar), "r"(c0), "r"(c1), "l"(pol), "r"(bytes) : "memory");
}
__device__ __forceinline__ void scrap_copy(uint32_t dst, const char* src, uint32_t bar) {
    asm volatile("{\n .reg .pred p;\n elect.sync _|p, 0xffffffff;\n"
                 " @p mbarrier.arrive.expect_tx.shared::cta.b64 _, [%2], 12288;\n"
                 " @p cp.async.bulk.shared::cluster.global.mbarrier::complete_tx::bytes [%0], [%1], 4096, [%2];\n"
                 " @p cp.async.bulk.shared::cluster.global.mbarrier::complete_tx::bytes [%0], [%1+4096], 4096, [%2];\n"
                 " @p cp.async.bulk.shared::cluster.global.mbarrier::complete_tx::bytes [%0], [%1+8192], 4096, [%2];\n}"
                 :: "r"(dst), "l"(src), "r"(bar) : "memory");
}
__device__ __forceinline__ void prefetch_l2(const void* p, uint32_t bytes) {
    asm volatile("{\n .reg .pred p;\n elect.sync _|p, 0xffffffff;\n @p cp.async.bulk.prefetch.L2.global [%0], %1;\n}" :: "l"(p), "r"(bytes) : "memory");
}
__device__ __forceinline__ uint64_t pol_first() { uint64_t p; asm("createpolicy.fractional.L2::evict_first.b64 %0, 1.0;" : "=l"(p)); return p; }
__device__ __forceinline__ uint64_t pol_normal() { uint64_t p; asm("createpolicy.fractional.L2::evict_normal.b64 %0, 1.0;" : "=l"(p)); return p; }
__device__ __forceinline__ bool utest(uint32_t bar, uint32_t parity) { return __all_sync(~0u, mbar_test(bar, parity)); }
__device__ __forceinline__ void uwait(uint32_t bar, uint32_t parity) {
    int n = 0;
    while (!__all_sync(~0u, mbar_try(bar, parity)) && ++n < SPIN_LIMIT) {}
}
template <int A, int B, int CNT> __device__ __forceinline__ void init_bars(uint32_t sb) {
#pragma unroll 1
    for (int k = A; k < B; k++)
        asm volatile("{\n .reg .pred p;\n elect.sync _|p, 0xffffffff;\n @p mbarrier.init.shared::cta.b64 [%0], %1;\n}" :: "r"(sb + S_BAR + 8 * k), "n"(CNT) : "memory");
}
__device__ __forceinline__ int first_key() { return (blockIdx.x >> 2) * 4096 + 3072 + (blockIdx.x & 3) * 256; }
__device__ __forceinline__ void load_tile(const CUtensorMap* m, uint32_t dst, uint32_t bar, uint32_t bytes, int key, uint64_t pol) { tma2d(dst, m, 0, 3 * key, bar, bytes, pol); }
__device__ __forceinline__ const char* unit_ptr(const Params& P, int n) {
    return (const char*)((n & 16) ? P.v : P.k) + (size_t)(first_key() + (n >> 5) * KV_BATCH_KEYS + (n & 15) * 16) * 384;
}
#define LSTAMP(k) do {} while (0)

__device__ __forceinline__ uint32_t k_place(uint32_t b, uint32_t s) { return s + 3 + 5 * (b & 1); }
__device__ __forceinline__ uint32_t v_place(uint32_t b, uint32_t s) { return s < 3 ? s : s + 8 - 8 * (b & 1); }
__device__ __forceinline__ void k_load(const Maps& M, uint32_t dst, uint32_t bar, int key8, uint64_t pol) {
    asm volatile("{\n .reg .pred p;\n elect.sync _|p, 0xffffffff;\n"
                 " @p mbarrier.arrive.expect_tx.shared::cta.b64 _, [%2], 6144;\n"
                 " @p cp.async.bulk.tensor.4d.shared::cluster.global.mbarrier::complete_tx::bytes.L2::cache_hint [%0], [%1, {0, 0, 0, %3}], [%2], %4;\n}"
                 :: "r"(dst), "l"(&M.k), "r"(bar), "r"(key8), "l"(pol) : "memory");
}
__device__ __forceinline__ int unit_key8(uint32_t n) { return first_key() / 8 + (n >> 4) * (KV_BATCH_KEYS / 8) + 2 * (n & 15); }
__device__ __forceinline__ void ring_load(const Maps& M, uint32_t sb, uint32_t b, uint32_t u, uint32_t pos) {
    if (u < 16) k_load(M, sb + pos * UNIT, sb + S_RING + 8 * pos, unit_key8(16 * b + u), pol_normal());
    else load_tile(&M.vu, sb + pos * UNIT, sb + S_FV + 4 * (pos & 6), UNIT, first_key() + b * KV_BATCH_KEYS + 16 * pos, pol_first());
}
__device__ __forceinline__ uint32_t token(bool p, uint32_t a, uint32_t n) {
    uint32_t v;
    asm volatile("{\n .reg .pred p;\n setp.ne.u32 p, %2, 0;\n mov.u32 %0, 0;\n @p atom.shared.exch.b32 %0, [%1], %3;\n}" : "=r"(v) : "r"(a), "r"((uint32_t)p), "r"(n) : "memory");
    return v;
}
__device__ __forceinline__ void place_load(const Maps& M, uint32_t sb, uint32_t n) {
    k_load(M, sb + k_place(n >> 4, 0) * SLOT + (n & 15) * UNIT, sb + S_FK + 4 * (n & 14), unit_key8(n), pol_first());
}
__device__ __forceinline__ void v_load(const Maps& M, uint32_t sb, uint32_t b, uint32_t s) {
    load_tile(&M.v, sb + v_place(b, s) * SLOT, sb + S_FV + 8 * s, SLOT, first_key() + b * KV_BATCH_KEYS + 32 * s, pol_first());
}
__device__ __forceinline__ bool due(uint32_t t) { return __all_sync(~0u, (int)(gtime32() * 16 - t) >= 0); }
__device__ __forceinline__ bool reached(uint32_t a, int v) { return __all_sync(~0u, ldsvol(a) >= v); }

__device__ __forceinline__ void stream_warp(const Params& P, const Maps& M, uint32_t sb, uint32_t lane) {
    const uint64_t pol = pol_first();
    const int bid = blockIdx.x, g = bid >> 3, i = bid & 7;
    const uint32_t wf = sb + S_WFULL;
    if (PF0 > 0) prefetch_l2(unit_ptr(P, 0), PF0 * UNIT);
    uint32_t tn = __shfl_sync(~0u, gtime32(), 0) * 16 - T_LEAD;
    auto pace = [&](uint32_t dt) {
        int k = 0;
        uint32_t now;
        do now = __shfl_sync(~0u, gtime32(), 0) * 16; while ((int)(now - tn) < 0 && ++k < SPIN_LIMIT);
        if ((int)(now - tn) > SLACK0) tn = now - SLACK0;
        tn += dt;
    };
#pragma unroll
    for (int k = 0; k < 10; k++) {
        if (k < 2) {
            if (k == 0) init_bars<26, 27, 1>(sb); else init_bars<27, 37, 1>(sb);
            asm volatile("fence.mbarrier_init.release.cluster;" ::: "memory");
            if (k == 1) { asm volatile("bar.arrive 2, %0;" :: "n"(NTHR) : "memory"); asm volatile("bar.sync 3, 128;" ::: "memory"); }
        }
        if (k >= WIN_W) uwait(wf + 8 * (k - WIN_W), 0);
        pace(TAUW * 5 / 2);
        if (k < 4) tma2d(sb + ST_WQ + 15360 * k, &M.wq, 384 * g + 192 * (k >> 1), 80 * i + 40 * (k & 1), wf + 8 * k, 15360, pol);
        else if (k < 6) tma2d(sb + ST_WG + 15360 * (k - 4), k == 4 ? &M.wg : &M.wu, 96 * g, 80 * i, wf + 8 * k, 15360, pol);
        else tma2d(sb + ST_WO + 15360 * (k - 6), &M.wo, 80 * i, 384 * g + 96 * (k - 6), wf + 8 * k, 15360, pol);
    }
#pragma unroll 1
    for (int n = 0; n < 16; n++) {
        if (n == 0 || n == 5 || n == 11) uwait(sb + S_RELW + (n == 0 ? 0 : n == 5 ? 8 : 16), 0);
        uwait(n < WIN_S ? wf + 8 * (10 - WIN_S + n) : sb + S_FV + 8 * ((n - WIN_S) ^ 8), 0);
        pace(max(min(2 * n + 2 - PF0, 2), 0) * TAU0);
        if (n < 8) { place_load(M, sb, 2 * n); place_load(M, sb, 2 * n + 1); }
        else if (n < 11) { ring_load(M, sb, 0, 2 * n, 2 * n - 16); ring_load(M, sb, 0, 2 * n + 1, 2 * n - 15); }
        else v_load(M, sb, 0, n - 8);
        if (n == 7) { pace(TAUW * 5 / 2); tma2d(sb + S_WD, &M.wd, 80 * i, 96 * g, wf + 80, 15360, pol); }
    }
    int nd = 0;
    uint32_t q[4];
#pragma unroll
    for (int r = 0; r < 4; r++) q[r] = sb + S_FV + 8 * (7 - r);
    tn -= TSH;
    uint32_t td = tn;
    uint32_t pos = 2;
#pragma unroll 1
    for (int m = 16; m < 64; m++) {
        const int b = m >> 4, j = m & 15;
        const char* src = unit_ptr(P, 2 * m);
        const uint32_t tok = sb + S_TOK + (j < 3 ? 4 * pos : j < 11 ? 24 + 4 * pos : 16 + 4 * j) + 4 * lane;
        static_assert(WIN_U <= 12, "a ring position has at most one token of the timetable");
        int k = 0;
        while (true) {
            const uint2 c = lds64(sb + S_KF);
            if (__all_sync(~0u, mbar_test(q[WIN_S - 1] & ~1u, q[WIN_S - 1] & 1) & (min((int)c.x + 1, (int)c.y) >= 16 * b + min(2 * j + 2 - WIN_U, 16))) || ++k >= SPIN_LIMIT) break;
        }
        uint32_t now;
        while (true) {
            now = __shfl_sync(~0u, gtime32(), 0) * 16;
            if ((int)(now - td) >= 0 || ++k >= SPIN_LIMIT) break;
            if (PSLEEP > 0 && (int)(td - now) > 16 * PSLEEP * 2) __nanosleep(PSLEEP);
        }
        const uint32_t mine = __ballot_sync(~0u, token(lane < (j < 11 ? 2 : 1), tok, 2 * m + lane) == 2 * m + lane);
        q[3] = q[2]; q[2] = q[1]; q[1] = q[0]; q[0] = sb + S_QRDY;
        if (j < 11) {
            if (mine & 1) ring_load(M, sb, b, 2 * j, pos); else prefetch_l2(src, UNIT);
            if (mine & 2) ring_load(M, sb, b, 2 * j + 1, pos + 1); else prefetch_l2(src + UNIT, UNIT);
            if (j >= 8) q[0] = (sb + S_FV + 8 * (j - 8)) | (b & 1);
        } else if (mine) { v_load(M, sb, b, j - 8); q[0] = (sb + S_FV + 8 * (j - 8)) | (b & 1); }
        else if (j - 8 >= VPF) prefetch_l2(src, SLOT);
        else {
            scrap_copy(sb + S_DUMMY, src, sb + S_DBAR + 8 * (nd & 3));
            q[0] = (sb + S_DBAR + 8 * (nd & 3)) | ((nd >> 2) & 1);
            nd++;
        }
        pos = j == 15 ? 2 : pos == 4 ? 0 : pos + 2;
        if ((int)(now - tn) > SLACK) tn = now - SLACK;
        tn += 2 * TAU;
        td = (int)(tn - now) > 2 * TMIN ? tn : now + 2 * TMIN;
        if (m >= 48 + JFREE) td = now + TFREE;
    }
#pragma unroll 1
    for (int m = max(nd - 4, 0); m < nd; m++) uwait(sb + S_DBAR + 8 * (m & 3), (m >> 2) & 1);
}

__host__ __device__ constexpr uint64_t bit_list(uint32_t m) { uint64_t r = 0; int n = 0; for (int k = 0; k < 12; k++) if ((m >> k) & 1) r |= (uint64_t)k << (4 * n++); return r; }
__device__ __forceinline__ float scaled(float s) { return bfr(bfr(s) * 0.07216878364870322f); }
__device__ __forceinline__ void probs(float s, uint32_t ps, uint32_t src, uint32_t ln) {
    const uint32_t q8 = ln >> 2, t4 = ln & 3;
    int key = __float_as_int(s);
    key ^= (key >> 31) & 0x7fffffff;
    key = __reduce_max_sync(~0u, key);
    key ^= (key >> 31) & 0x7fffffff;
    const float ml = __int_as_float(key) * LOG2E;
    sts16(ps + 64 * src + (q8 >> 1) * 16 + t4 * 4 + (q8 & 1) * 2, pack2(ex2(fmaf(s, LOG2E, -ml)), 0.f));
    stsf(ps + PS_MAX + 4 * src, ml);
}
template <int H> __device__ __forceinline__ uint32_t b_pos(uint32_t e) { const uint32_t h = e >= H, k = e - H * h; return h * 192 + (k & 6) * 24 + (k >> 3) * 4 + (k & 1) * 2; }
__device__ __forceinline__ uint32_t a_pos(uint32_t e) { const uint32_t h = e >= 40, k = e - 40 * h; return (k & 6) * 24 + (k >> 3) * 8 + h * 4 + (k & 1) * 2; }
__device__ __forceinline__ uint32_t q_pos(uint32_t d) { const uint32_t s = 3 * ((d >> 4) & 3) + (d >> 6); return s * 32 + (d & 6) * 4 + ((d >> 3) & 1) * 4 + (d & 1) * 2; }
__device__ __forceinline__ uint32_t k_off(uint32_t ln) { return (ln & 8) * 384 + (ln & 7) * 128 + (((ln & 7) ^ (ln >> 4)) << 4); }

#define HSTAMP(k) do {} while (0)
__device__ __forceinline__ char* xwindow() { return reinterpret_cast<char*>((reinterpret_cast<uintptr_t>(g_x) + (2u << 20) - 1) & ~(uintptr_t)((2u << 20) - 1)); }

struct XPtr {
    uint32_t lo, hi;
    __device__ __forceinline__ explicit XPtr(char* p) : lo((uint32_t)(uintptr_t)p), hi((uint32_t)((uintptr_t)p >> 32)) {}
    __device__ __forceinline__ XPtr(uint32_t l, uint32_t h) : lo(l), hi(h) {}
    __device__ __forceinline__ XPtr operator+(uint32_t o) const { return XPtr(lo + o, hi); }
    __device__ __forceinline__ operator char*() const { uint64_t p; asm("mov.b64 %0, {%1, %2};" : "=l"(p) : "r"(lo), "r"(hi)); return (char*)p; }
};
__device__ __forceinline__ void keep(XPtr& v) { keep(v.lo); }

__device__ __forceinline__ void side_warp(uint32_t sb) {
    const uint32_t bid = blockIdx.x, g = bid >> 3, i = bid & 7, P = pairG(0, 0, i);
    char* p = xwindow() + P * 8192 + (g >> 3) * HALF + (g & 7) * 512 + 448;
    uint32_t best[2] = {~0u, ~0u};
    asm volatile("st.relaxed.gpu.global.b32 [%0], 1;" :: "l"(p) : "memory");
    asm volatile("st.relaxed.gpu.global.b32 [%0], 1;" :: "l"(p + COPY) : "memory");
#pragma unroll 1
    for (int r = 0; r < 64; r++) {
        if (r >= 4 && !(r & 1) && min(best[0], best[1]) < 380 && max(best[0], best[1]) > min(best[0], best[1]) + 80) break;
        uint32_t c0, c1, v;
        asm volatile("mov.u32 %0, %clock;" : "=r"(c0) :: "memory");
        asm volatile("atom.relaxed.gpu.global.exch.b32 %0, [%1], 0;" : "=r"(v) : "l"(p + (r & 1) * COPY) : "memory");
        asm volatile("{\n .reg .pred q;\n setp.eq.u32 q, %1, 0x13579bdf;\n mov.u32 %0, 0;\n @!q mov.u32 %0, %clock;\n}" : "=r"(c1) : "r"(v) : "memory");
        if (r & 1) best[1] = min(best[1], c1 - c0); else best[0] = min(best[0], c1 - c0);
    }
    stsvol(sb + S_SIDE, 1 + ((best[1] < best[0]) ^ (__popc(P & PMASK) & 1)));
}

__device__ __forceinline__ void hop_a(const char* src, uint32_t par, uint32_t dst, bool st, int k) {
    uint2 v[4];
    float e[4], rl;
    int guard = 0;
    bool again;
    do {
#pragma unroll
        for (int s = 0; s < 4; s++) v[s] = ldp64(src + s * 1024);
        again = __any_sync(~0u, (chk4(v, par) & 1) != 0);
        const int M = max(max((int)v[0].x, (int)v[1].x), max((int)v[2].x, (int)v[3].x)) - 254;
#pragma unroll
        for (int s = 0; s < 4; s++) e[s] = __int_as_float(max((int)v[s].x - M, 0) << 22);
        rl = rcp(fmaf(e[0], asf(v[0].y), e[1] * asf(v[1].y)) + fmaf(e[2], asf(v[2].y), e[3] * asf(v[3].y)));
#pragma unroll
        for (int s = 0; s < 4; s++) e[s] = __shfl_sync(~0u, e[s], 24);
        keep(rl);
    } while (again & (++guard < SPIN_LIMIT));
    rl = __shfl_sync(~0u, rl, 24);
    const float o0 = fmaf(e[0], asf(v[0].x), e[1] * asf(v[1].x)) + fmaf(e[2], asf(v[2].x), e[3] * asf(v[3].x));
    const float o1 = fmaf(e[0], asf(v[0].y), e[1] * asf(v[1].y)) + fmaf(e[2], asf(v[2].y), e[3] * asf(v[3].y));
    sts32_if(st, dst, pack2(o0 * rl, o1 * rl));
    SWEEPS(k, guard - 1);
    __syncwarp();
}

__device__ __forceinline__ void score_warp(const Maps& M, uint32_t sb, uint32_t h, uint32_t ln) {
    const uint32_t lane0 = ln;
    uwait(sb + S_QRDY, 0);
    const uint32_t q8 = ln >> 2;
    const uint32_t k0 = k_off(ln);
    uint32_t pos = h + 6, bar = sb + S_FK, par = 0, phases = 0;
    uint2 q = lds64(sb + S_QS + 8 * ln), qh = lds64(sb + S_QS + 8 * ln + 256);
    auto first_round = [&](uint32_t b, uint32_t ln) {
        uwait(sb + S_RELR, b & 1);
        const uint32_t u = h + 2 * ln, p = u < 4 ? u + 2 : u - 4;
        uint32_t todo = __ballot_sync(~0u, token(ln < 3, sb + S_TOK + 4 * p, 32 * b + 32 + u) == 32 * b + 32 + u);
#pragma unroll 1
        for (uint32_t r = h; todo; todo >>= 1, r += 2) if (todo & 1) ring_load(M, sb, b + 1, r, r < 4 ? r + 2 : r - 4);
    };
#pragma unroll 1
    for (uint32_t n = h; n < 64; n += 2) {
        HSTAMP(0);
        const uint32_t ua = sb + pos * UNIT;
        if (!__all_sync(~0u, mbar_try(bar, par))) uwait(bar, par);
        HSTAMP(1);
        float acc[2][4] = {};
        uint32_t mine = 0;
        const uint32_t id = n + (n & 48) + 6;
#pragma unroll
        for (int s = 0; s < 12; s++) {
            uint32_t kf[4];
            ldsm4(kf, (k0 ^ (32 * (s / 3))) + (ua + 1024 * (s % 3)));
            if (s == 11) {
                __syncwarp();
                mine = token(ln == 0 && n >= 16, sb + S_TOK + 24 + 4 * pos, id);
                stsvol(sb + S_KF + 4 * h, n + 1);
            }
            const bool m = q8 == (s & 7);
            mmaA(acc[s & 1], kf, m ? (s < 8 ? q.x : qh.x) : 0u, m ? (s < 8 ? q.y : qh.y) : 0u);
        }
        const uint32_t pos0 = pos;
        const bool last = (n & 14) == 14;
        pos = last ? h + 2 : n >= 16 && pos >= 4 ? h : pos + 2;
        bar = n >= 14 ? sb + S_RING + 8 * pos : bar + 8;
        par = n >= 14 ? (phases >> pos) & 1 : 0;
        phases ^= n >= 14 ? 1u << pos : 0;
        const float w0 = (acc[0][0] + acc[0][1]) + (acc[1][0] + acc[1][1]), w1 = (acc[0][2] + acc[0][3]) + (acc[1][2] + acc[1][3]);
        HSTAMP(2);
        if (__any_sync(~0u, mine == id)) ring_load(M, sb, n >> 4, (n & 15) + 6, pos0);
        HSTAMP(3);
        float s = ((ln & 1) ? w1 : w0) + __shfl_xor_sync(~0u, (ln & 1) ? w0 : w1, 1);
        s += __shfl_xor_sync(~0u, s, 2);
        sts_hi16(sb + S_SC + (((n & 12) >> 1) + h) * 64 + (n & 2) * 2 + (ln & 29) * 2, scaled(s));
        if (last) {
            __syncwarp();
            arrive_if(ln == 0, sb + S_SCO);
            const uint32_t b = n >> 4, ln = lane0 + lag<1>(sb);
            if (b > 0) {
                uwait(sb + S_RELK, (b - 1) & 1);
                if (h == 0) LSTAMP(64 + 2 * b);
                const uint32_t sl = 3 + h + 2 * ln, idv = 32 * b + 16 + 2 * sl;
                uint32_t todo = __ballot_sync(~0u, token(sl < 8, sb + S_TOK + 48 + 4 * sl, idv) == idv);
#pragma unroll 1
                for (uint32_t r = 3 + h; todo; todo >>= 1, r += 2) if (todo & 1) v_load(M, sb, b, r);
                const uint32_t g = blockIdx.x >> 3, pr = pairL(RA, 1, g), side = ldsvol(sb + S_SIDE);
                const char* src = xwindow() + pr * 8192 + ((side ^ 1 ^ __popc(pr & PMASK)) & 1) * COPY + h * HALF + 8 * min(ln, 24u);
                uwait(sb + S_RELV, (b - 1) & 1);
                __nanosleep(HOP1_NS);
#pragma unroll 1
                for (uint32_t r = 0; r < 4; r++) {
                    hop_a(src + 256 * r, b & 1, sb + S_OS + 192 * (4 * h + r) + 96 + 4 * ln, ln < 24, 25);
                    if (r == RELR_AT && b < 3) first_round(b, ln);
                }
                arrive_if(ln == 0, sb + S_OS1);
            } else first_round(0, ln);
            q = lds64(sb + S_QS + 24 * ((n + 2) & 48) + 8 * ln); qh = lds64(sb + S_QS + 24 * ((n + 2) & 48) + 8 * ln + 256);
        }
    }
}

__global__ void __launch_bounds__(NTHR, 1)
fused_kernel(const Params P, const __grid_constant__ Maps M) {
    extern __shared__ __align__(1024) unsigned char smem[];
    const uint32_t sb = smem_u32(smem);
    const int tid = threadIdx.x, bid = blockIdx.x;
    const int w = __shfl_sync(~0u, tid >> 5, 0), lane = tid & 31;

    if (w >= 8) {
        asm volatile("setmaxnreg.dec.sync.aligned.u32 " REG_LO ";");
        if (w == 8) {
            stream_warp(P, M, sb, lane);
        } else {
            if (PFMAP && w == 11 && lane < 8) asm volatile("prefetch.tensormap [%0];" :: "l"(&M.k + lane) : "memory");
            if (w == 9) { init_bars<0, 3, 2>(sb); init_bars<3, 8, 1>(sb); init_bars<16, 22, 1>(sb); }
            else if (w == 10) { init_bars<8, 16, 2>(sb); init_bars<22, 26, 1>(sb); }
            else { init_bars<37, 38, 1>(sb); init_bars<38, 40, 8>(sb); init_bars<40, 41, 1>(sb); init_bars<41, 44, 8>(sb); init_bars<44, 46, 2>(sb); stsvol(sb + S_ZERO + 4 * lane, 0); }
            asm volatile("fence.mbarrier_init.release.cluster;" ::: "memory");
            asm volatile("bar.arrive 3, 128;" ::: "memory");
            asm volatile("bar.sync 2, %0;" :: "n"(NTHR) : "memory");
            if (w < 11) score_warp(M, sb, w - 9, lane);
            else {
                if (lane == 0) side_warp(sb);
                __syncwarp();
                uint32_t a = 0, b = 0;
                int k = 0;
                while (ldsvol(sb + S_GATE) == 0 && ++k < SPIN_LIMIT) { warm_mma(a, b); __nanosleep(KWNS); }
                uint4* d = reinterpret_cast<uint4*>(reinterpret_cast<char*>(g_s) + XS + bid * 7680) + lane;
                const uint4 z = make_uint4(0, 0, 0, 0);
#pragma unroll 1
                for (int u = 0; u < 15; u++) d[32 * u] = z;
                d = reinterpret_cast<uint4*>(reinterpret_cast<char*>(g_s) + XS2 + bid * 768) + lane;
                d[0] = z;
                if (lane < 16) d[32] = z;
                const uint32_t side = (ldsvol(sb + S_SIDE) & 1) ^ 1, g = bid >> 3, i = bid & 7;
                const XPtr gx(xwindow());
                auto nearp = [&](uint32_t pr) { return gx.lo + pr * 8192 + ((side ^ __popc(pr & PMASK)) & 1) * COPY; };
                const uint32_t own = (i >> 2) * HALF + (i & 3) * 1024 + (lane & 7) * 128;
                const uint32_t pAC = nearp(pairL(lane >> 4, (lane >> 3) & 1, g)) + own, pE = nearp(pairL(RE, (lane >> 3) & 1, g)) + own;
                const uint32_t pG = nearp(pairG((lane >> 2) & 1, (lane >> 3) & 1, i)) + min(lane & 3, 2) * 128;
                uint32_t tr = 0, tk = 0, ph = 0, src = g + (lane >> 4), seen = 0, n = 16;
                bool go = false, first = true;
                while (n < 64 && ++k < SPIN_LIMIT) {
                    const uint32_t now = __shfl_sync(~0u, gtime32(), 0) * 16;
                    if (!go && utest((n & 15) < KRE_EARLY ? sb + S_RELK : sb + S_RELV, ((n >> 4) & 1) ^ 1)) { go = true; if ((int)(now - tk) > 0 || !(n & 15)) tk = now; }
                    if (go && (int)(now - tk) >= 0) {
                        place_load(M, sb, (n & 16) ? n : (n & 48) | ((n + 10) & 15));
                        tk += n >= 48 ? KRE_TAU3 : (n & 15) < KRE_N1 ? KRE_TAU1 : KRE_TAU;
                        n++;
                        go = (n & 15) != 0 && (n & 15) != KRE_EARLY;
                        if (!(n & 15)) LSTAMP(63 + (n >> 3));
                    } else if (first || (int)(now - tr) >= 0) {
                        first = false;
                        tr = now + RFR_TAU;
                        b |= seen & a;
                        warm_mma(a, b);
                        if (RFR_ON) seen = ldp32(XPtr(ph == 0 ? pAC : ph == 1 && lane < 16 ? pE : pG + (src & 8) * (HALF / 8) + (src & 7) * 512, gx.hi));
                        src += ph == 0 ? 0 : ph == 1 ? 2 : 1;
                        ph = ph == 2 ? 0 : ph + 1;
                    } else __nanosleep(KWNS2);
                }
                while (ldsvol(sb + S_GATE) < 6 && ++k < SPIN_LIMIT) { warm_mma(a, b); __nanosleep(KWNS); }
                if (a | b) stsvol(sb + S_GATE, 6);
            }
        }
        return;
    }
    asm volatile("setmaxnreg.inc.sync.aligned.u32 " REG_HI ";");

    const int g = bid >> 3, i = bid & 7;
    const int g8 = lane >> 2, t = lane & 3;
    char* const gs = reinterpret_cast<char*>(g_s);
    const XPtr gx(xwindow());

    auto zero_words = [&] {
        const uint4 z = make_uint4(0, 0, 0, 0);
        const uint32_t c = (tid >> 6) & 1, cp = (tid >> 7) * COPY, k = (tid & 63) * 16;
        *reinterpret_cast<uint4*>((char*)(gx + pairL(RA, c, g) * 8192 + (i >> 2) * HALF + (i & 3) * 1024 + cp + k)) = z;
        *reinterpret_cast<uint4*>((char*)(gx + pairL(RC, c, g) * 8192 + (i >> 2) * HALF + (i & 3) * 1024 + cp + k)) = z;
        *reinterpret_cast<uint4*>((char*)(gx + pairL(RE, c, g) * 8192 + (i >> 2) * HALF + (i & 3) * 1024 + cp + k)) = z;
        if ((tid & 31) < 24) *reinterpret_cast<uint4*>((char*)(gx + pairG((tid >> 5) & 1, c, i) * 8192 + (g >> 3) * HALF + (g & 7) * 512 + cp + (tid & 31) * 16)) = z;
    };
    if (ZPOS == 0) zero_words();
    W80 Wq[6], Wgu[3];
    uint32_t Wo[5][3][4];
    if (w < 4) {
        const uint32_t* xp = reinterpret_cast<const uint32_t*>(P.x + 640 * w);
        float sum = 0.f, sq = 0.f;
#pragma unroll
        for (int u = 0; u < 10; u++) { uint32_t v = xp[lane + 32 * u]; float a = bf_lo(v), b = bf_hi(v); sum += a + b; sq += a * a + b * b; }
#pragma unroll
        for (int o = 16; o > 0; o >>= 1) { sum += __shfl_xor_sync(~0u, sum, o); sq += __shfl_xor_sync(~0u, sq, o); }
        float mean, den; ln_stats(sum, sq, mean, den);
        if (lane < 20) {
            const uint2 v = reinterpret_cast<const uint2*>(P.x + 640 * w + 80 * i)[lane];
            sts64(sb + S_X0 + 160 * w + 8 * lane, v.x, v.y);
            sts32(sb + S_L0 + 384 * w + b_pos<40>(4 * lane), pack2(__fdiv_rn(bfr(bf_lo(v.x) - mean), den), __fdiv_rn(bfr(bf_hi(v.x) - mean), den)));
            sts32(sb + S_L0 + 384 * w + b_pos<40>(4 * lane + 2), pack2(__fdiv_rn(bfr(bf_lo(v.y) - mean), den), __fdiv_rn(bfr(bf_hi(v.y) - mean), den)));
        }
    } else if (w == 4) {
        const uint32_t* xp = reinterpret_cast<const uint32_t*>(P.wr);
        float sum = 0.f;
#pragma unroll
        for (int u = 0; u < 10; u++) { uint32_t v = xp[lane + 32 * u]; sum += bf_lo(v) + bf_hi(v); }
#pragma unroll
        for (int o = 16; o > 0; o >>= 1) sum += __shfl_xor_sync(~0u, sum, o);
        if (lane == 0) stsf(sb + S_SWR, sum);
        if (lane < 20) {
            const uint2 v = reinterpret_cast<const uint2*>(P.wr + 80 * i)[lane];
            sts32(sb + S_XA + 576 + a_pos(4 * lane), v.x); sts32(sb + S_XA + 576 + a_pos(4 * lane + 2), v.y);
            sts32(sb + S_XA + a_pos(4 * lane), ONES); sts32(sb + S_XA + a_pos(4 * lane + 2), ONES);
        }
    }
    asm volatile("bar.sync 2, %0;" :: "n"(NTHR) : "memory");
    auto frag = [](uint32_t (&a)[4], uint32_t p, int pitch) {
        const uint32_t r0 = lds32(p), r1 = lds32(p + pitch), r2 = lds32(p + 2 * pitch), r3 = lds32(p + 3 * pitch);
        a[0] = __byte_perm(r0, r1, 0x5410); a[1] = __byte_perm(r0, r1, 0x7632);
        a[2] = __byte_perm(r2, r3, 0x5410); a[3] = __byte_perm(r2, r3, 0x7632);
    };
    mbar_wait(sb + S_WFULL + 16 * (w >> 2), 0);
    mbar_wait(sb + S_WFULL + 16 * (w >> 2) + 8, 0);
    {
        const uint32_t p = sb + ST_WQ + (w >> 2) * 30720 + (2 * t) * 384 + (48 * (w & 3) + 2 * g8) * 2;
#pragma unroll
        for (int r = 0; r < 10; r++)
#pragma unroll
            for (int m = 0; m < 3; m++) {
                const uint32_t q = p + ((r & 1) * 40 + (r >> 1) * 8) * 384 + 32 * m, r0 = lds32(q), r1 = lds32(q + 384);
                (r < 8 ? Wq[2 * m].a[(r >> 2) & 1][r & 3] : Wq[2 * m].c[r & 1]) = __byte_perm(r0, r1, 0x5410);
                (r < 8 ? Wq[2 * m + 1].a[(r >> 2) & 1][r & 3] : Wq[2 * m + 1].c[r & 1]) = __byte_perm(r0, r1, 0x7632);
            }
    }
    __syncwarp();
    if (lane == 0) mbar_arrive(sb + S_RELW);
    TSTAMP(1);
    {
        char* d = gs + XS + bid * 7680 + (w >> 2) * 3840 + (48 * (w & 3) + 2 * g8) * 4;
        float acc[6][4] = {};
        mul80(acc, Wq, lds128(sb + S_L0 + 48 * lane), lds32(sb + S_L0 + 48 * lane + 16));
#pragma unroll
        for (int m = 0; m < 6; m += 2) stp64(d + t * 768 + 32 * m, acc[m][0] + acc[m][3], acc[m + 1][0] + acc[m + 1][3], 1);
        float sum[6][4] = {};
        mul80(sum, Wq, make_uint4(ONES, ONES, ONES, ONES), ONES);
        if (t == 0)
#pragma unroll
            for (int m = 0; m < 6; m += 2) stp64(d + 4 * 768 + 32 * m, sum[m][0] + sum[m][3], sum[m + 1][0] + sum[m + 1][3], 1);
    }
    mbar_wait(sb + S_WFULL + 32, 0);
    mbar_wait(sb + S_WFULL + 40, 0);
    const uint32_t oct = 3 * (w >> 1) + (w & 1), oct2 = 3 * (w >> 1) + 2;
    {
        const uint32_t p = sb + ST_WG + ((lane & 7) + 40 * ((lane >> 3) & 1) + 8 * (lane >> 4)) * 192;
#pragma unroll
        for (int T = 0; T < 3; T++) {
            const uint32_t q = p + (T < 2 ? T * 15360 + 16 * oct : (w & 1) * 15360 + 16 * oct2);
            ldsm4t(Wgu[T].a[0], q); ldsm4t(Wgu[T].a[1], q + 16 * 192); ldsm2t(Wgu[T].c, q + 32 * 192);
        }
        float sum[3][4] = {};
        mul80(sum, Wgu, make_uint4(ONES, ONES, ONES, ONES), ONES);
        if (t < 3) stp32(gs + XS2 + bid * 768 + (t < 2 ? 64 * oct + 4 * t : 64 * oct2 + 4 * (w & 1)) + 8 * g8,
                         sel4(t, sum[0][0] + sum[0][3], sum[1][0] + sum[1][3], sum[2][0] + sum[2][3], 0.f), 1);
    }
    __syncwarp();
    if (lane == 0) mbar_arrive(sb + S_RELW + 8);
    const char* srcS = gs + XS + g * 8 * 7680 + (i >> 2) * 3840 + min(tid, 191) * 4;
    uint32_t vs[5][8];
#pragma unroll
    for (int b = 0; b < 5; b++)
#pragma unroll
        for (int s = 0; s < 8; s++) vs[b][s] = LOOK1 ? ldp32(srcS + b * 768 + s * 7680) : 0;
    uint32_t cs2[8];
#pragma unroll
    for (int s = 0; s < 8; s++) cs2[s] = LOOK2 ? ldp32(gs + XS2 + (g * 8 + s) * 768 + min(tid, 191) * 4) : 0;
    __syncwarp();
    mbar_wait(sb + S_WFULL + 48 + 8 * (w >> 1), 0);
    {
        const uint32_t po = sb + ST_WO + (48 * w + 12 * t) * 160 + 4 * g8;
#pragma unroll
        for (int s = 0; s < 3; s++)
#pragma unroll
            for (int m = 0; m < 5; m++) frag(Wo[m][s], po + 4 * s * 160 + 32 * m, 160);
    }
    __syncwarp();
    if (lane == 0) mbar_arrive(sb + S_RELW + 16);
    if (ZPOS == 1) zero_words();
    if (tid < 192) {
        int guard = 0;
        while (((or3(chk8(vs[0], 1), chk8(vs[1], 1), chk8(vs[2], 1)) | chk8(vs[3], 1) | chk8(vs[4], 1)) & 1) && ++guard < SPIN_LIMIT) {
#pragma unroll
            for (int b = 0; b < 5; b++)
#pragma unroll
                for (int s = 0; s < 8; s++) vs[b][s] = ldp32(srcS + b * 768 + s * 7680);
        }
        const uint32_t qpos = sb + S_QS + q_pos(tid);
#pragma unroll
        for (int b = 0; b < 4; b++) {
            sts_hi16(qpos + 384 * b, bfr(sum8(vs[b])));
        }
        stsf(sb + S_CSQ + 4 * tid, sum8(vs[4]));
    }
    if (tid < 192) stsf(sb + S_CSGU + 4 * tid, (chk8(cs2, 1) & 1) ? gather8<768>(gs + XS2 + g * 8 * 768 + tid * 4, 1) : sum8(cs2));
    __syncwarp();
    bar_main();
    arrive_if(tid == 0, sb + S_QRDY);
    if (ZPOS == 2) zero_words();
    TSTAMP(2);

    uint32_t side;
    { int k = 0; while ((side = ldsvol(sb + S_SIDE)) == 0 && ++k < SPIN_LIMIT) {} }
    const uint32_t td = __shfl_sync(~0u, tid, lane);
    const uint32_t wp = __shfl_sync(~0u, tid >> 5, 0);
    const uint32_t cc = wp >= 3;
    auto uni = [](uint32_t v) { return __shfl_sync(~0u, v, 0); };
    auto pin = [&](uint32_t v) { return __shfl_sync(~0u, v, td); };
    auto nearp = [&](uint32_t P) { return gx.lo + P * 8192 + ((side ^ 1 ^ __popc(P & PMASK)) & 1) * COPY; };
    constexpr uint32_t COL = 32 * 8192;
    const uint32_t ownL = gx.lo + (i >> 2) * HALF + (i & 3) * 1024, ownG = gx.lo + (g >> 3) * HALF + (g & 7) * 512;
    const uint32_t uPubA = uni(ownL + pairL(RA, 0, g) * 8192 + (wp >> 1) * 256 + (wp & 1) * 96), uPolA = uni(nearp(pairL(RA, 0, g)) + (wp >> 2) * HALF + (wp & 3) * 256);
    const uint32_t uPubB = uni(ownG + pairG(0, cc, i) * 8192), uPolB = uni(nearp(pairG(0, cc, i)));
    const uint32_t uPubC = uni(ownL + pairL(RC, 0, g) * 8192), uPolC = uni(nearp(pairL(RC, wp < 6 ? cc : wp - 6, g)));
    const uint32_t uPubD = uni(ownG + pairG(1, 0, i) * 8192 + (wp < 7 ? 32 * wp : 256)), uPolD = uni(nearp(pairG(1, cc, i)));
    const uint32_t uPubE = uni(ownL + pairL(RE, 0, g) * 8192), uPolE = uni(nearp(pairL(RE, i >> 2, g)));
    const uint32_t uOS = uni(sb + S_OS + 192 * wp), uCol = uni(sb + 64 * cc);
    auto xp = [&](uint32_t lo) { return (char*)XPtr(lo, gx.hi); };
#define IDS() const uint32_t z_ = pin(td); const uint32_t ln = z_ & 31, q8 = ln >> 2, t4 = z_ & 3, n96 = z_ - 96 * cc, n80 = min(n96, 79u); (void)q8; (void)t4; (void)n80; (void)ln

    auto vaddr = [&](uint32_t (&voff)[3]) {
        const uint32_t ln = td & 31;
        const uint32_t key3 = 3 * ((ln & 7) + 2 * (ln & 8) + ((ln >> 1) & 8));
#pragma unroll
        for (int T = 0; T < 3; T++) {
            const uint32_t u = 3 * wp + T, r = key3 + (u >> 3);
            voff[T] = r * 128 + (((u ^ r) & 7) << 4);
        }
    };
    auto values = [&](uint32_t (&vf)[8][3][4], auto order, auto step, uint32_t ps, uint32_t col, uint32_t par) {
        const uint32_t ln = td & 31, q8 = ln >> 2, t4 = td & 3;
        const uint4 p = lds128(ps + 16 * ln);
        float acc[3][4] = {}, f0 = 0.f, f1 = 0.f, r3 = 0.f;
        int M = 0;
#pragma unroll
        for (int k = 0; k < 8; k++) {
            step(k);
            const int s = (order.value >> (4 * k)) & 7;
            const bool m = (q8 >> 1) == (s >> 1);
            const uint32_t b0 = m ? ((s & 1) ? p.z : p.x) : 0u, b1 = m ? ((s & 1) ? p.w : p.y) : 0u;
#pragma unroll
            for (int T = 0; T < 3; T++) mmaA(acc[T], vf[s][T], b0, b1);
            if (k == FSTEP) {
                const uint2 mp = lds64(ps + PS_MAX + 8 * t4);
                M = __reduce_max_sync(~0u, __float2int_ru(fmaxf(asf(mp.x), asf(mp.y))));
                f0 = ex2(asf(mp.x) - (float)M); f1 = ex2(asf(mp.y) - (float)M);
                float l[4] = {};
                mma16816(l, ONES, ONES, ONES, ONES, p.x, p.y); mma16816(l, ONES, ONES, ONES, ONES, p.z, p.w);
                r3 = fmaf(f0, l[0], f1 * l[1]);
            }
        }
        CSTAMP(25);
        char* pubA = xp(uPubA + col * COL + 32 * t4 + 4 * q8);
        const float r0 = fmaf(f0, acc[0][0], f1 * acc[0][3]), r1 = fmaf(f0, acc[1][0], f1 * acc[1][3]), r2 = fmaf(f0, acc[2][0], f1 * acc[2][3]);
        const bool hi = t4 & 2, od = t4 & 1;
        const float u0 = (hi ? r2 : r0) + __shfl_xor_sync(~0u, hi ? r0 : r2, 2), u1 = (hi ? r3 : r1) + __shfl_xor_sync(~0u, hi ? r1 : r3, 2);
        const float o = (od ? u1 : u0) + __shfl_xor_sync(~0u, od ? u0 : u1, 1);
        stp32_if(t4 < 3 || ((wp & 1) && q8 < 2), pubA, ln == 3 ? __int_as_float(2 * M) : o, par);
    };

#pragma unroll 1
    for (int ch = 0; ch < 5; ch++) {
        const uint32_t par0 = (ch + 1) & 1, par1 = ch & 1;
        uint32_t voff[3], vf[8][3][4];
        CSTAMP(0);
        if (ch < 4) {
            vaddr(voff);
            mbar_wait(sb + S_SCO, par1);
            if (ch == 0) mbar_wait(sb + S_WFULL + 80, 0);
            TST(0);
            auto ldw = [&](int s) {
                mbar_wait(sb + S_FV + 8 * s, par1);
#pragma unroll
                for (int T = 0; T < 3; T++) ldsm4t(vf[s][T], voff[T] + (sb + v_place(ch, s) * SLOT));
            };
            probs(bf_lo(lds16(sb + S_SC + 2 * td)), sb + S_PS, wp, td & 31);
            ldw(0); ldw(1); ldw(2);
            bar_main();
            arrive_if(td == 0, sb + S_RELR);
            values(vf, std::integral_constant<uint32_t, 0x76543210>(), [&](int s) {
                if (s >= 3) ldw(s);
            }, sb + S_PS, 0, par0);
            TST(1);
            CSTAMP(5);
            if (ch > 0) mbar_wait(sb + S_OS1, par0);
        } else {
#pragma unroll
            for (int s = 0; s < 36; s++) { vf[s / 12][(s / 4) % 3][s & 3] = 0; opaque(vf[s / 12][(s / 4) % 3][s & 3]); }
        }
        const bool has0 = ch < 4, has1 = ch > 0;
        const bool actc = wp < 6 && (cc ? has1 : has0);
        const uint32_t parc = cc ? par1 : par0;
        const uint32_t pub0 = has0 ? par0 : 0;
        uint32_t n4;
        {
            IDS();
            const uint32_t c = ch == 4;
            const uint32_t osa = pin(uOS + 96 * c + 4 * ln), oa = pin(uOS + 96 * (q8 & 1) + 24 * t4), ra = pin(sb + S_RED + 640 * wp + 320 * (t4 & 1) + 8 * q8);
            n4 = pin(4 * n80);
            hop_a(xp(uPolA + c * COL + 8 * min(ln, 24u) + lag<DELAY_L>(sb)), pub0, osa, ln < 24, 5 * ch);
            TST(2);
            CSTAMP(6);
            float acc[5][4] = {};
            const uint2 b0 = lds64(oa), b1 = lds64(oa + 8), b2 = lds64(oa + 16);
#pragma unroll
            for (int m = 0; m < 5; m++) mmaA(acc[m], Wo[m][0], b0.x, b0.y);
#pragma unroll
            for (int m = 0; m < 5; m++) mmaA(acc[m], Wo[m][1], b1.x, b1.y);
#pragma unroll
            for (int m = 0; m < 5; m++) mmaA(acc[m], Wo[m][2], b2.x, b2.y);
#pragma unroll
            for (int m = 0; m < 5; m++) sts64_if(!(td & 2), ra + 64 * m, (td & 1) ? acc[m][1] : acc[m][0], (td & 1) ? acc[m][3] : acc[m][2]);
        }
        CSTAMP(7);
        uint32_t xr, fl, pubC, pubC2;
        auto prepC = [&] {
            IDS();
            xr = pin(sb + S_XB + 48 * (ln & 15));
            pubC = pin(uPubC + (t4 & 1) * COL + 192 * (wp >> 1) + 64 * (wp & 1) + 8 * q8);
            pubC2 = pin(uPubC + (t4 & 1) * COL + ((t4 & 2) ? 192 * (wp >> 1) + 128 + 4 * (wp & 1) + 8 * q8 : 768 + 2 * ((q8 + 1) & 6)));
            fl = pin(((t4 & 1) ? par1 : pub0) | (t4 >= 2 || (wp == 7 && q8 < 4 && q8 != 2 - t4) ? 2 : 0));
        };
        if (actc) {
            bar_main();
            CSTAMP(8);
            uint32_t r[8];
#pragma unroll
            for (int s = 0; s < 8; s++) r[s] = lds32(n4 + (5 * uCol - 4 * sb + S_RED + 640 * s));
            stp32_if(true, xp(uPubB + n4), sum8(r), parc);
            CSTAMP(9);
            prepC();
            const uint32_t xas = pin(3 * uCol - 2 * sb + S_XA + 192 + a_pos(n4 / 4)), xbs = pin(6 * uCol - 5 * sb + S_XB + b_pos<40>(n4 / 4));
            const float x0 = cc ? ldsf(sb + S_XCAR + n4) : bf_lo(lds16(sb + S_X0 + 160 * (ch & 3) + n4 / 2));
            gather16(xp(uPolB + n4 + lag<DELAY_G>(sb)), parc, 5 * ch + 1, [&](float y, uint32_t) {
                const uint32_t x = pack2(x0 + bfr(y), 0.f);
                sts16(xbs, x);
                sts16(xas, x);
                return 0u;
            });
            CSTAMP(10);
        } else {
            bar_main();
            prepC();
        }
        auto stats = [&](uint32_t xa, const uint4& b, uint32_t b4) {
            float a[4] = {};
            const uint4 p0 = lds128(xa), p1 = lds128(xa + 16);
            const uint2 p2 = lds64(xa + 32);
            mmaV(a, p0, b.x, b.y); mmaV(a, p1, b.z, b.w); mma8(a, p2.x, p2.y, b4);
            return a[0] + a[3];
        };
        {
            auto gate_up = [&](auto with_stats) {
                bar_main();
                TST(3);
                CSTAMP(11);
                const uint4 b = lds128(xr);
                const uint32_t b4 = lds32(xr + 16);
                float acc[3][4] = {}, st = 0.f;
                if (with_stats.value) st = stats(xr + (S_XA - S_XB), b, b4);
                mul80(acc, Wgu, b, b4);
                stp64_if(!(td & 2), xp(pubC), tagw(acc[0][0] + acc[0][3], fl & 1), tagw(acc[1][0] + acc[1][3], fl & 1));
                stp32_if(fl > 1, xp(pubC2), !with_stats.value || (td & 2) ? acc[2][0] + acc[2][3] : st, fl & 1);
            };
            if (wp == 7) gate_up(std::true_type()); else gate_up(std::false_type());
        }
        CSTAMP(12);
        float mean = 0.f, den = 1.f;
        {
            IDS();
            const uint32_t wh = pin((((ln & 7) + 48 * ((ln >> 3) & 1) + 8 * (ln >> 4)) * 160 + (wp < 7 ? 16 * wp : 128)) | ((384 * cc + b_pos<48>(n96)) << 16));
            const uint32_t pubD = pin(uPubD + (t4 & 1) * COL + 16 * (t4 & 2) + 4 * q8 + (fl & 1)), ha = xr + (S_HS - S_XB);
            auto down = [&](const uint32_t (&W)[3][4], const uint4& h0, const uint2& h1) {
                float a0[4] = {}, a1[4] = {}, a2[4] = {};
                mmaA(a0, W[0], h0.x, h0.y); mmaA(a1, W[1], h0.z, h0.w); mmaA(a2, W[2], h1.x, h1.y);
                return ((a0[0] + a0[3]) + (a1[0] + a1[3])) + (a2[0] + a2[3]);
            };
            if (wp < 6) {
                uint32_t Wd[3][4];
                auto ldd = [&](uint32_t z) {
#pragma unroll
                    for (int s = 0; s < 3; s++) ldsm4t(Wd[s], ((wh ^ z) & 0xffff) + (sb + S_WD + s * 2560));
                };
                if (actc) {
                    const uint32_t src0 = uPolC + lag<DELAY_C>(sb);
                    const char* srcv = xp(src0 + 8 * n96);
                    const char* src = xp(src0 + (ln & 1) * HALF);
                    float gt, up;
                    int guard = 0;
                    bool again;
                    do {
                        uint2 v[8], st[4];
#pragma unroll
                        for (int s = 0; s < 4; s++) st[s] = ldp64(src + 768 + s * 1024);
#pragma unroll
                        for (int s = 0; s < 8; s++) v[s] = ldp64(srcv + (s >> 2) * HALF + (s & 3) * 1024);
                        float sx = (asf(st[0].x) + asf(st[1].x)) + (asf(st[2].x) + asf(st[3].x)), sq = (asf(st[0].y) + asf(st[1].y)) + (asf(st[2].y) + asf(st[3].y));
                        sx += __shfl_xor_sync(~0u, sx, 1); sq += __shfl_xor_sync(~0u, sq, 1);
                        const uint32_t z = ((st[0].x ^ parc) & 1) * 16;
                        const uint2 cs = lds64(sb + S_CSGU - 768 * cc + 8 * td + z);
                        again = __any_sync(~0u, (or3(chk4(st, parc), chk8(v, parc), chk8y(v, parc)) & 1) != 0);
                        ln_stats(sx, sq, mean, den);
                        const float rd = rcp(den);
                        gt = fmaf(-mean, asf(cs.x), sum8x(v)); up = fmaf(-mean, asf(cs.y), sum8y(v));
                        ldd(z);
                        gt *= rd; up *= rd;
                        keep(gt); keep(up);
                    } while (again & (++guard < SPIN_LIMIT));
                    CSTAMP(13);
                    SWEEPS(5 * ch + 2, guard - 1);
                    gt = bfr(gt);
                    const uint32_t h = pack2(bfr(gt * sigmoidf_(gt)) * bfr(up), 0.f);
                    sts16((wh >> 16) + (sb + S_HS), h);
                    CSTAMP(14);
                } else ldd(0);
                bar_main();
                TST(4);
                CSTAMP(15);
                const uint4 h0 = lds128(ha);
                const uint2 h1 = lds64(ha + 16);
                stp32_if(!(td & 2), xp(pubD & ~1u), down(Wd, h0, h1), pubD & 1);
            } else {
                stsvol(sb + S_GATE, ch + 1);
                uint32_t Wd[2][3][4];
#pragma unroll
                for (int s = 0; s < 6; s++) ldsm4t(Wd[s / 3][s % 3], (wh & 0xffff) + (sb + S_WD + (s / 3) * 16 + (s % 3) * 2560));
                uint32_t v = 0;
                if (wp == 6 ? has0 : has1) {
                    const uint32_t par = wp == 6 ? par0 : par1;
                    const char* src = xp(uPolC + 768 + (ln & 4) * (HALF / 4) + (ln & 3) * 1024 + 4 * min(ln >> 3, 2u) + lag<DELAY_C>(sb));
                    int guard = 0;
                    do v = ldp32(src); while (__any_sync(~0u, (v ^ par) & 1) && ++guard < SPIN_LIMIT);
                }
                bar_main();
                const uint4 h0 = lds128(ha);
                const uint2 h1 = lds64(ha + 16);
                const float d0 = down(Wd[0], h0, h1), d1 = down(Wd[1], h0, h1);
                stp32_if(true, xp(pubD & ~1u), (td & 2) ? d1 : d0, pubD & 1);
                if (wp == 6 ? has0 : has1) {
                    float sx = asf(v);
                    sx += __shfl_xor_sync(~0u, sx, 1); sx += __shfl_xor_sync(~0u, sx, 2); sx += __shfl_xor_sync(~0u, sx, 4);
                    const float sq = __shfl_sync(~0u, sx, 8), xw = __shfl_sync(~0u, sx, 16);
                    ln_stats(sx, sq, mean, den);
                    const float r = bfr(fmaf(-mean, ldsf(sb + S_SWR), xw) * rcp(den));
                    sts32_if(ln == 0, sb + S_STAT + 4 * (wp - 6), __float_as_uint(bfr(sigmoidf_(r))) | (ch + 1));
                }
            }
        }
        CSTAMP(16);
        uint32_t pubE;
        float x1 = 0.f;
        {
            IDS();
            pubE = pin(uPubE + (t4 < 3 ? (wp >> 2) * COL + 192 * (wp & 3) + 64 * t4 + 8 * q8 : (q8 >> 2) * COL + 768 + 4 * (q8 & 1)));
            xr = pin(sb + S_XB + 48 * (ln & 7));
            if (actc && (cc == 0 || g == 0)) {
                const uint32_t m4 = 4 * n80;
                const uint32_t xas = pin(3 * uCol - 2 * sb + S_XA + 192 + a_pos(n80)), xbs = pin(6 * uCol - 5 * sb + S_XB + b_pos<40>(n80));
                x1 = bf_lo(lds16(xbs));
                const float lnx = __uint_as_float(pin(__float_as_uint(bfr(__fdiv_rn(bfr(x1 - mean), den)))));
                uint32_t x2;
                gather16(xp(uPolD + m4 + lag<DELAY_D>(sb)), parc, 5 * ch + 3, [&](float y, uint32_t z) {
                    const uint32_t gate = ldsvol(sb + S_STAT + 4 * cc + z);
                    x2 = pack2(x1 + bfr(lnx + bfr(bfr(y) * bf_hi(gate))), 0.f);
                    sts16(xbs, x2);
                    sts16(xas, x2);
                    return (uint32_t)((gate & 7) != ch + 1);
                });
                CSTAMP(17);
                if (cc) reinterpret_cast<unsigned short*>(P.out)[640 * (ch - 1) + 80 * i + n80] = (unsigned short)x2;
                x1 = bf_lo(x2);
            }
        }
        CSTAMP(18);
        if (!has0) break;
        {
            auto qproj = [&](auto with_stats) {
                bar_main();
                TST(5);
                CSTAMP(19);
                const uint32_t t4 = td & 3;
                const uint4 b = lds128(xr);
                const uint32_t b4 = lds32(xr + 16);
                float acc[6][4] = {}, st = 0.f;
                if (with_stats.value) st = stats(xr + (S_XA - S_XB), b, b4);
                mul80(acc, Wq, b, b4);
                const float v0 = sel4(t4, acc[0][0] + acc[0][3], acc[2][0] + acc[2][3], acc[4][0] + acc[4][3], acc[4][0] + acc[4][3]);
                const float v1 = sel4(t4, acc[1][0] + acc[1][3], acc[3][0] + acc[3][3], acc[5][0] + acc[5][3], acc[5][0] + acc[5][3]);
                if (with_stats.value) stp32_if((td & 11) == 3, xp(pubE), st, par0);
                stp64_if(t4 < 3, xp(pubE), tagw(v0, par0), tagw(v1, par0));
            };
            if (wp == 7) qproj(std::true_type()); else qproj(std::false_type());
            sts32_if(td < 80, sb + S_XCAR + 4 * td, __float_as_uint(x1));
        }
        CSTAMP(20);
        auto pass2 = [&](auto d0, auto d1, auto d2) {
            constexpr int D0 = d0.value, D1 = d1.value, D = D0 + D1 + d2.value;
            IDS();
            const uint32_t ua = sb + k_place(ch, wp & 6) * SLOT + (wp & 1) * UNIT, k0 = k_off(ln);
            uint32_t kf[12][2][4];
            auto ldk = [&](int s) { const uint32_t a = (k0 ^ (32 * (s / 3))) + (ua + 1024 * (s % 3)); ldsm4(kf[s][0], a); ldsm4(kf[s][1], a + SLOT); };
            auto ldv1 = [&](int k) { ldsm4t(vf[k / 3][k % 3], voff[k % 3] + (sb + v_place(ch, k / 3) * SLOT)); };
            auto ldv = [&](int s) { ldv1(3 * s); ldv1(3 * s + 1); ldv1(3 * s + 2); };
            constexpr uint32_t LATE = LAST_LATE;
            constexpr uint64_t EARLY_LIST = bit_list(~LATE), LATE_LIST = bit_list(LATE);
            auto early = [&](int k) {
                if (D1 == 0) ldk(k);
                else if (k < 3) { ldv1(9 + 2 * k); ldv1(10 + 2 * k); }
                else ldk((EARLY_LIST >> (4 * (k - 3))) & 15);
            };
            if (D1 > 0) vaddr(voff);
            if (!(mbar_try(sb + S_FK + 8 * (wp & 6), par1) & mbar_try(sb + S_FK + 8 * (wp | 1), par1))) { mbar_wait(sb + S_FK + 8 * (wp & 6), par1); mbar_wait(sb + S_FK + 8 * (wp | 1), par1); }
#pragma unroll
            for (int s = 0; s < D0; s++) early(s);
            if (wp < 6) {
                const uint32_t qsa = pin(sb + S_QS + 384 * ch + q_pos(td));
                const uint32_t src0 = uPolE + lag<(D1 > 0 ? 0 : DELAY_E)>(sb);
                const char* srcv = xp(src0 + 4 * td);
                const char* src = xp(src0 + (ln & 1) * HALF);
                uint32_t v[8]; uint2 st[4];
                auto look = [&] {
#pragma unroll
                    for (int s = 0; s < 4; s++) st[s] = ldp64(src + 768 + s * 1024);
#pragma unroll
                    for (int s = 0; s < 8; s++) v[s] = ldp32(srcv + (s >> 2) * HALF + (s & 3) * 1024);
                };
                if (D1 > 0) {
                    look();
                    __syncwarp();
#pragma unroll
                    for (int s = D0; s < D0 + D1; s++) early(s);
                }
                int guard = 0;
                while (true) {
                    if (D1 == 0) look();
                    float sx = (asf(st[0].x) + asf(st[1].x)) + (asf(st[2].x) + asf(st[3].x)), sq = (asf(st[0].y) + asf(st[1].y)) + (asf(st[2].y) + asf(st[3].y));
                    sx += __shfl_xor_sync(~0u, sx, 1); sq += __shfl_xor_sync(~0u, sq, 1);
                    const float cs = ldsf(sb + S_CSQ + 4 * td + ((st[0].x ^ par0) & 1) * 4);
                    const bool again = __any_sync(~0u, ((chk8(v, par0) | chk4(st, par0)) & 1) != 0);
                    ln_stats(sx, sq, mean, den);
                    const uint32_t q = pack2(fmaf(-mean, cs, sum8(v)) * rcp(den), 0.f);
                    sts16(qsa, q);
                    if (!(again & (++guard < SPIN_LIMIT))) break;
                    if (D1 > 0) look();
                }
                SWEEPS(5 * ch + 4, guard - 1);
                CSTAMP(22);
            } else {
#pragma unroll
                for (int s = D0; s < D0 + D1; s++) early(s);
            }
#pragma unroll
            for (int s = D0 + D1; s < D; s++) early(s);
            bar_main();
            TST(6);
            CSTAMP(1);
            uint2 q = lds64(sb + S_QS + 384 * ch + 8 * ln);
            float acc[2][4] = {};
            constexpr int V0 = 13 - D, NV = D1 > 0 ? 2 : (2 * (D - 1)) / 3;
            static_assert(D1 == 0 || LAST0 == 0 || D - 3 + __builtin_popcount(LATE) == 12, "plan");
#pragma unroll
            for (int s = 0; s < 12; s++) {
                const bool m = q8 == (s & 7);
                const uint32_t b0 = m ? q.x : 0u, b1 = m ? q.y : 0u;
                if (s == 7) q = lds64(sb + S_QS + 384 * ch + 8 * ln + 256);
                mmaA(acc[0], kf[s][0], b0, b1);
                mmaA(acc[1], kf[s][1], b0, b1);
                if (D1 > 0) {
                    if (s >= 1 && s <= __builtin_popcount(LATE)) ldk((LATE_LIST >> (4 * (s - 1))) & 15);
                } else {
                    if (s >= 1 && s + D - 1 < 12) ldk(s + D - 1);
                    if (s >= 1 && s + D - 1 == 11) { __syncwarp(); arrive_if(ln == 0, sb + S_RELK); }
                    if (s == V0) vaddr(voff);
                    if (s >= V0 && 2 * (s - V0) < 3 * NV) ldv1(9 + 2 * (s - V0));
                    if (s >= V0 && 2 * (s - V0) + 1 < 3 * NV) ldv1(10 + 2 * (s - V0));
                }
            }
            CSTAMP(24);
            {
                const float v0 = acc[0][0] + acc[0][1], v1 = acc[0][2] + acc[0][3], v2 = acc[1][0] + acc[1][1], v3 = acc[1][2] + acc[1][3];
                const bool hi = t4 & 2, od = t4 & 1;
                const float u0 = (hi ? v2 : v0) + __shfl_xor_sync(~0u, hi ? v0 : v2, 2), u1 = (hi ? v3 : v1) + __shfl_xor_sync(~0u, hi ? v1 : v3, 2);
                const float s = (od ? u1 : u0) + __shfl_xor_sync(~0u, od ? u0 : u1, 1);
                CSTAMP(2);
                probs(scaled(s), sb + S_PS + PS_PASS, wp, ln);
                CSTAMP(3);
            }
            bar_main();
            TST(10);
            CSTAMP(4);
            if (D1 > 0) values(vf, std::integral_constant<uint32_t, ORDER_L>(), [&](int s) { if (s < 3) ldv(s + 5); }, sb + S_PS + PS_PASS, 1, par0);
            else values(vf, std::integral_constant<uint32_t, (NV > 1 ? ORDER_R : 0x76543210)>(),
                        [&](int s) { if (s >= (NV > 1 ? 2 : 1) && s + NV + (NV > 1 ? 1 : 2) < 8) ldv(s + NV + (NV > 1 ? 1 : 2)); }, sb + S_PS + PS_PASS, 1, par0);
            arrive_if(ln == 0, sb + S_RELV);
        };
        if (LAST0 > 0 && ch == 3) {
            pass2(std::integral_constant<int, LAST0>(), std::integral_constant<int, LAST1>(), std::integral_constant<int, LAST2>());
#pragma unroll
            for (int m = 0; m < 60; m++) { uint32_t& r = m % 10 < 8 ? Wq[m / 10].a[(m % 10) / 4][m % 2 + 2 * ((m % 10) / 2 % 2)] : Wq[m / 10].c[m % 2]; r = 0; opaque(r); }
        } else pass2(std::integral_constant<int, KPRE>(), std::integral_constant<int, 0>(), std::integral_constant<int, KPRE2>());
        TST(11);
        CSTAMP(23);
    }
    sts32_if(td == 255, sb + S_GATE, 6);
    TSTAMP(3);
}

typedef CUresult (*EncodeFn)(CUtensorMap*, CUtensorMapDataType, cuuint32_t, void*, const cuuint64_t*, const cuuint64_t*, const cuuint32_t*,
                             const cuuint32_t*, CUtensorMapInterleave, CUtensorMapSwizzle, CUtensorMapL2promotion, CUtensorMapFloatOOBfill);

void make_map(EncodeFn enc, CUtensorMap* m, const void* base, uint64_t cols, uint64_t rows, uint32_t box_cols, uint32_t box_rows, bool swizzle) {
    cuuint64_t dims[2] = {cols, rows};
    cuuint64_t strides[1] = {cols * 2};
    cuuint32_t box[2] = {box_cols, box_rows};
    cuuint32_t es[2] = {1, 1};
    enc(m, CU_TENSOR_MAP_DATA_TYPE_BFLOAT16, 2, const_cast<void*>(base), dims, strides, box, es, CU_TENSOR_MAP_INTERLEAVE_NONE,
        swizzle ? CU_TENSOR_MAP_SWIZZLE_128B : CU_TENSOR_MAP_SWIZZLE_NONE, swizzle ? CU_TENSOR_MAP_L2_PROMOTION_NONE : WPROMO, CU_TENSOR_MAP_FLOAT_OOB_FILL_NONE);
}

}

extern "C" void kernel_launch(void* const* d_in, const int* in_sizes, int n_in, void* d_out, int out_size) {
    (void)in_sizes; (void)n_in; (void)out_size;
    static EncodeFn enc = nullptr;
    if (!enc) {
        void* f = nullptr;
        cudaDriverEntryPointQueryResult q;
        cudaGetDriverEntryPoint("cuTensorMapEncodeTiled", &f, cudaEnableDefault, &q);
        enc = (EncodeFn)f;
        cudaFuncSetAttribute(fused_kernel, cudaFuncAttributeMaxDynamicSharedMemorySize, SMEM_BYTES);
    }
    Params P;
    P.x = (const __nv_bfloat16*)d_in[0]; P.k = (const __nv_bfloat16*)d_in[1]; P.v = (const __nv_bfloat16*)d_in[2];
    P.wr = (const __nv_bfloat16*)d_in[6];
    P.out = (__nv_bfloat16*)d_out;
    Maps M;
    {
        cuuint64_t dims[4] = {64, 8, 3, (cuuint64_t)KV_BATCH_KEYS / 2}, strides[3] = {384, 128, 3072};
        cuuint32_t box[4] = {64, 8, 3, 2}, es[4] = {1, 1, 1, 1};
        enc(&M.k, CU_TENSOR_MAP_DATA_TYPE_BFLOAT16, 4, d_in[1], dims, strides, box, es, CU_TENSOR_MAP_INTERLEAVE_NONE, CU_TENSOR_MAP_SWIZZLE_128B,
            CU_TENSOR_MAP_L2_PROMOTION_NONE, CU_TENSOR_MAP_FLOAT_OOB_FILL_NONE);
    }
    make_map(enc, &M.v, P.v, 64, (uint64_t)12 * KV_BATCH_KEYS, 64, 96, true);
    make_map(enc, &M.vu, P.v, 64, (uint64_t)12 * KV_BATCH_KEYS, 64, 48, true);
    make_map(enc, &M.wq, d_in[3], 6144, 640, 192, 40, false);
    make_map(enc, &M.wo, d_in[4], 640, 6144, 80, 96, false);
    make_map(enc, &M.wg, d_in[7], 1536, 640, 96, 80, false);
    make_map(enc, &M.wu, d_in[8], 1536, 640, 96, 80, false);
    make_map(enc, &M.wd, d_in[9], 640, 1536, 80, 96, false);
    fused_kernel<<<NCTA, NTHR, SMEM_BYTES, cudaStreamPerThread>>>(P, M);
}
```

```cpp
#include <cuda_runtime.h>
#include <cuda.h>
#include <cuda_bf16.h>
#include <stdint.h>
#include <type_traits>

namespace {

constexpr int NCTA = 128;
constexpr int NTHR = 384;
constexpr int UNIT = 6144;
constexpr int SLOT = 12288;
#define TAU 4000
#define TAUW 3900
#define TAU0 3900
#define PF0 2
#define PFMAP 1
#define ZPOS 1
#define LOOK1 0
#define LOOK2 0
#define SLACK 4000
#define SLACK0 SLACK
#define TSH 0
#define HOP1_NS 200
#define RELR_AT 0
#define PSLEEP 0
#define KRE_EARLY 6
#define PFTOP 2
#define RFR_XS 8
#define TMIN 2400
#define T_LEAD 0
#define WIN_W 3
#define WIN_S 4
#define WIN_U 10
#define RFR_ON 1
#define KRE_N1 0
#define KRE_TAU1 2500
#define RFR_TAU 6400
#define VPF 5
#define KRE_GATE 0
#define KRE_GATE3 KRE_GATE
#define JFREE 16
#define TFREE 0
#define KRE_TAU 3000
#define KRE_TAU3 KRE_TAU
#define HDEPTH 3
#define LAST0 3
#define ORDER_L 0x76543210
#define ORDER_R 0x76543210
#define LAST_LATE 0xaa8
#define LAST1 4
#define LAST2 3
#define FSTEP 4
#define SPEC 1
#define PV1PIPE 0
#define HOPA0 6
#define HOPA1 6
#define WPROMO CU_TENSOR_MAP_L2_PROMOTION_NONE
#define KPRE 1
#define KPRE2 3
#define DELAY_G 3
#define DELAY_L 5
#define DELAY_C 3
#define DELAY_D 1
#define DELAY_E 3
#define REG_LO "40"
#define REG_HI "232"
#define SPIN_LOG 17
constexpr int SPIN_LIMIT = 1 << SPIN_LOG;

__host__ __device__ constexpr uint32_t pairL(uint32_t region, uint32_t c, uint32_t g) { return (g & 1) | ((g >> 1) << 2) | (c << 5) | (region << 6); }
__host__ __device__ constexpr uint32_t pairG(uint32_t d, uint32_t c, uint32_t i) { return (i & 1) | ((i >> 1) << 2) | (d << 4) | (c << 5) | (3u << 6); }
constexpr uint32_t RA = 0, RC = 1, RE = 2, HALF = 16384, COPY = 4096, PMASK = 0x59;
constexpr uint32_t XS = 0;
constexpr uint32_t XS2 = XS + 128 * 7680;
constexpr uint32_t XSEND = XS2 + 128 * 768;
__device__ uint4 g_s[XSEND / 16];
__device__ uint4 g_x[(4u << 20) / 16];
#define SWEEPS(k, n) do {} while (0)

constexpr uint32_t S_WD = 16 * SLOT;
constexpr uint32_t S_DUMMY = S_WD + 15360;
constexpr uint32_t S_BAR = S_DUMMY + 4096;
constexpr uint32_t S_FV = S_BAR, S_FK = S_FV + 64, S_RING = S_FK + 64, S_DBAR = S_RING + 48, S_WFULL = S_DBAR + 32, S_QRDY = S_WFULL + 88;
constexpr uint32_t S_RELK = S_QRDY + 8, S_RELV = S_RELK + 8, S_RELR = S_RELV + 8, S_RELW = S_RELR + 8, S_SCO = S_RELW + 24;
constexpr uint32_t S_OS1 = S_SCO + 8;
constexpr uint32_t S_ZERO = S_OS1 + 8;
constexpr uint32_t S_KF = S_ZERO + 8;
constexpr uint32_t S_TOK = S_KF + 8;
constexpr uint32_t S_SIDE = S_TOK + 80, S_GATE = S_SIDE + 4;
constexpr uint32_t S_STAT = S_GATE + 12, S_SWR = S_STAT + 16;
constexpr uint32_t S_XCAR = S_STAT + 32;
constexpr uint32_t S_CSQ = S_XCAR + 320;
constexpr uint32_t S_CSGU = S_CSQ + 768;
constexpr uint32_t S_RED = S_CSGU + 768;
constexpr uint32_t S_L0 = S_RED;
constexpr uint32_t S_OS = S_RED + 5120;
constexpr uint32_t S_PS = S_OS + 1536;
constexpr uint32_t PS_MAX = 512, PS_PASS = 544;
constexpr uint32_t S_QS = S_PS + 2 * PS_PASS;
constexpr uint32_t S_XB = S_QS + 1536;
constexpr uint32_t S_XA = S_XB + 768;
constexpr uint32_t S_HS = S_XA + 768;
constexpr uint32_t S_X0 = S_HS + 768;
constexpr uint32_t S_SC = S_X0 + 640;
constexpr uint32_t S_TM = S_SC + 512;
constexpr int SMEM_BYTES = S_TM + 256;
static_assert(SMEM_BYTES <= 232448 && S_STAT % 16 == 0 && S_RED % 16 == 0 && S_XB % 16 == 0 && S_HS % 16 == 0 && S_PS % 16 == 0 && S_QS % 16 == 0, "smem");
static_assert(S_SCO == S_BAR + 44 * 8 && S_RELK == S_BAR + 38 * 8, "barriers");
constexpr uint32_t ST_WQ = 3 * SLOT, ST_WG = 8 * SLOT, ST_WO = 11 * SLOT;

__device__ __forceinline__ uint32_t smem_u32(const void* p) { return (uint32_t)__cvta_generic_to_shared(p); }
__device__ __forceinline__ void mbar_init(uint32_t bar, uint32_t cnt) { asm volatile("mbarrier.init.shared::cta.b64 [%0], %1;" :: "r"(bar), "r"(cnt) : "memory"); }
__device__ __forceinline__ void mbar_expect(uint32_t bar, uint32_t bytes) { asm volatile("mbarrier.arrive.expect_tx.shared::cta.b64 _, [%0], %1;" :: "r"(bar), "r"(bytes) : "memory"); }
__device__ __forceinline__ void mbar_arrive(uint32_t bar) { asm volatile("mbarrier.arrive.shared::cta.b64 _, [%0];" :: "r"(bar) : "memory"); }
__device__ __forceinline__ bool mbar_try(uint32_t bar, uint32_t parity) {
    uint32_t ok;
    asm volatile("{\n .reg .pred p;\n mbarrier.try_wait.parity.shared::cta.b64 p, [%1], %2;\n selp.u32 %0, 1, 0, p;\n}" : "=r"(ok) : "r"(bar), "r"(parity) : "memory");
    return ok != 0;
}
__device__ __forceinline__ bool mbar_test(uint32_t bar, uint32_t parity) {
    uint32_t ok;
    asm volatile("{\n .reg .pred p;\n mbarrier.test_wait.parity.shared::cta.b64 p, [%1], %2;\n selp.u32 %0, 1, 0, p;\n}" : "=r"(ok) : "r"(bar), "r"(parity) : "memory");
    return ok != 0;
}
__device__ __forceinline__ void mbar_wait(uint32_t bar, uint32_t parity) {
    int n = 0;
    while (!mbar_try(bar, parity) && ++n < SPIN_LIMIT) {}
}
__device__ __forceinline__ unsigned long long gtime() { unsigned long long t; asm volatile("mov.u64 %0, %globaltimer;" : "=l"(t)); return t; }
__device__ __forceinline__ uint32_t gtime32() { uint32_t t; asm volatile("mov.u32 %0, %globaltimer_lo;" : "=r"(t)); return t; }
__device__ __forceinline__ void bar_main() { asm volatile("bar.sync 1, 256;" ::: "memory"); }

__device__ __forceinline__ void mma16816(float (&c)[4], uint32_t a0, uint32_t a1, uint32_t a2, uint32_t a3, uint32_t b0, uint32_t b1) {
    asm("mma.sync.aligned.m16n8k16.row.col.f32.bf16.bf16.f32 {%0,%1,%2,%3}, {%4,%5,%6,%7}, {%8,%9}, {%0,%1,%2,%3};"
        : "+f"(c[0]), "+f"(c[1]), "+f"(c[2]), "+f"(c[3]) : "r"(a0), "r"(a1), "r"(a2), "r"(a3), "r"(b0), "r"(b1));
}
__device__ __forceinline__ void mmaA(float (&c)[4], const uint32_t (&a)[4], uint32_t b0, uint32_t b1) { mma16816(c, a[0], a[1], a[2], a[3], b0, b1); }
__device__ __forceinline__ void mmaAv(float (&c)[4], const uint32_t (&a)[4], uint32_t b0, uint32_t b1) {
    asm volatile("mma.sync.aligned.m16n8k16.row.col.f32.bf16.bf16.f32 {%0,%1,%2,%3}, {%4,%5,%6,%7}, {%8,%9}, {%0,%1,%2,%3};"
        : "+f"(c[0]), "+f"(c[1]), "+f"(c[2]), "+f"(c[3]) : "r"(a[0]), "r"(a[1]), "r"(a[2]), "r"(a[3]), "r"(b0), "r"(b1) : "memory");
}
__device__ __forceinline__ void mma8(float (&c)[4], uint32_t a0, uint32_t a1, uint32_t b0) {
    asm("mma.sync.aligned.m16n8k8.row.col.f32.bf16.bf16.f32 {%0,%1,%2,%3}, {%4,%5}, {%6}, {%0,%1,%2,%3};"
        : "+f"(c[0]), "+f"(c[1]), "+f"(c[2]), "+f"(c[3]) : "r"(a0), "r"(a1), "r"(b0));
}
struct W80 { uint32_t a[2][4], c[2]; };
template <int N> __device__ __forceinline__ void mul80(float (&acc)[N][4], const W80 (&W)[N], const uint4& b, uint32_t b4) {
#pragma unroll
    for (int m = 0; m < N; m++) mmaA(acc[m], W[m].a[0], b.x, b.y);
#pragma unroll
    for (int m = 0; m < N; m++) mmaA(acc[m], W[m].a[1], b.z, b.w);
#pragma unroll
    for (int m = 0; m < N; m++) mma8(acc[m], W[m].c[0], W[m].c[1], b4);
}
__device__ __forceinline__ void ldsm2t(uint32_t (&r)[2], uint32_t addr) {
    asm volatile("ldmatrix.sync.aligned.m8n8.x2.trans.shared.b16 {%0,%1}, [%2];" : "=r"(r[0]), "=r"(r[1]) : "r"(addr) : "memory");
}
__device__ __forceinline__ void mmaV(float (&c)[4], const uint4& a, uint32_t b0, uint32_t b1) { mma16816(c, a.x, a.y, a.z, a.w, b0, b1); }
__device__ __forceinline__ void ldsm4(uint32_t (&r)[4], uint32_t addr) {
    asm volatile("ldmatrix.sync.aligned.m8n8.x4.shared.b16 {%0,%1,%2,%3}, [%4];" : "=r"(r[0]), "=r"(r[1]), "=r"(r[2]), "=r"(r[3]) : "r"(addr) : "memory");
}
__device__ __forceinline__ void ldsm4t(uint32_t (&r)[4], uint32_t addr) {
    asm volatile("ldmatrix.sync.aligned.m8n8.x4.trans.shared.b16 {%0,%1,%2,%3}, [%4];" : "=r"(r[0]), "=r"(r[1]), "=r"(r[2]), "=r"(r[3]) : "r"(addr) : "memory");
}
__device__ __forceinline__ uint32_t lds16(uint32_t a) { uint16_t v; asm volatile("ld.shared.u16 %0, [%1];" : "=h"(v) : "r"(a) : "memory"); return v; }
__device__ __forceinline__ uint32_t lds32(uint32_t a) { uint32_t v; asm volatile("ld.shared.u32 %0, [%1];" : "=r"(v) : "r"(a) : "memory"); return v; }
__device__ __forceinline__ float ldsf(uint32_t a) { return __uint_as_float(lds32(a)); }
__device__ __forceinline__ uint2 lds64(uint32_t a) { uint2 v; asm volatile("ld.shared.v2.u32 {%0,%1}, [%2];" : "=r"(v.x), "=r"(v.y) : "r"(a) : "memory"); return v; }
__device__ __forceinline__ uint4 lds128(uint32_t a) { uint4 v; asm volatile("ld.shared.v4.u32 {%0,%1,%2,%3}, [%4];" : "=r"(v.x), "=r"(v.y), "=r"(v.z), "=r"(v.w) : "r"(a) : "memory"); return v; }
__device__ __forceinline__ int ldsvol(uint32_t a) { int v; asm volatile("ld.volatile.shared.u32 %0, [%1];" : "=r"(v) : "r"(a) : "memory"); return v; }
__device__ __forceinline__ void stsvol(uint32_t a, int v) { asm volatile("st.volatile.shared.u32 [%0], %1;" :: "r"(a), "r"(v) : "memory"); }
__device__ __forceinline__ void sts_hi16(uint32_t a, float v) { asm volatile("{\n .reg .b16 lo, hi;\n mov.b32 {lo, hi}, %1;\n st.shared.u16 [%0], hi;\n}" :: "r"(a), "r"(__float_as_uint(v)) : "memory"); }
__device__ __forceinline__ void sts16(uint32_t a, uint32_t v) { asm volatile("st.shared.u16 [%0], %1;" :: "r"(a), "r"(v) : "memory"); }
__device__ __forceinline__ void sts32(uint32_t a, uint32_t v) { asm volatile("st.shared.u32 [%0], %1;" :: "r"(a), "r"(v) : "memory"); }
__device__ __forceinline__ void stsf(uint32_t a, float v) { sts32(a, __float_as_uint(v)); }
__device__ __forceinline__ void sts64(uint32_t a, uint32_t x, uint32_t y) { asm volatile("st.shared.v2.u32 [%0], {%1,%2};" :: "r"(a), "r"(x), "r"(y) : "memory"); }

__device__ __forceinline__ void sts_hi16_if(bool p, uint32_t a, float v) {
    asm volatile("{\n .reg .pred p;\n .reg .b16 lo, hi;\n setp.ne.u32 p, %2, 0;\n mov.b32 {lo, hi}, %1;\n @p st.shared.u16 [%0], hi;\n}" :: "r"(a), "r"(__float_as_uint(v)), "r"((uint32_t)p) : "memory");
}
__device__ __forceinline__ void sts32_if(bool p, uint32_t a, uint32_t v) {
    asm volatile("{\n .reg .pred p;\n setp.ne.u32 p, %2, 0;\n @p st.shared.u32 [%0], %1;\n}" :: "r"(a), "r"(v), "r"((uint32_t)p) : "memory");
}
__device__ __forceinline__ void sts64_if(bool p, uint32_t a, float x, float y) {
    asm volatile("{\n .reg .pred p;\n setp.ne.u32 p, %3, 0;\n @p st.shared.v2.f32 [%0], {%1,%2};\n}" :: "r"(a), "f"(x), "f"(y), "r"((uint32_t)p) : "memory");
}
__device__ __forceinline__ void arrive_if(bool p, uint32_t bar) {
    asm volatile("{\n .reg .pred p;\n setp.ne.u32 p, %1, 0;\n @p mbarrier.arrive.shared::cta.b64 _, [%0];\n}" :: "r"(bar), "r"((uint32_t)p) : "memory");
}
__device__ __forceinline__ void opaque(uint32_t& v) { asm volatile("" : "+r"(v)); }
__device__ __forceinline__ void keep(uint32_t& v) { asm volatile("" : "+r"(v)); }
__device__ __forceinline__ void keep(float& v) { asm volatile("" : "+f"(v)); }
template <class T> __device__ __forceinline__ void keep(T*& v) { asm volatile("" : "+l"(v)); }

__device__ __forceinline__ uint32_t ldp32(const char* p) { uint32_t v; asm volatile("ld.relaxed.gpu.global.u32 %0, [%1];" : "=r"(v) : "l"(p) : "memory"); return v; }
__device__ __forceinline__ uint2 ldp64(const char* p) {
    uint2 v; asm volatile("{\n .reg .b64 d;\n ld.relaxed.gpu.global.b64 d, [%2];\n mov.b64 {%0,%1}, d;\n}" : "=r"(v.x), "=r"(v.y) : "l"(p) : "memory"); return v;
}
__device__ __forceinline__ uint32_t tagw(float f, uint32_t par) { return (__float_as_uint(f) & ~1u) | par; }
__device__ __forceinline__ void stp32(char* p, float a, uint32_t par) { asm volatile("st.relaxed.gpu.global.u32 [%0], %1;" :: "l"(p), "r"(tagw(a, par)) : "memory"); }
__device__ __forceinline__ void stp64(char* p, float a, float b, uint32_t par) {
    asm volatile("{\n .reg .b64 d;\n mov.b64 d, {%1,%2};\n st.relaxed.gpu.global.b64 [%0], d;\n}" :: "l"(p), "r"(tagw(a, par)), "r"(tagw(b, par)) : "memory");
}
__device__ __forceinline__ void stp32_if(bool p, char* d, float a, uint32_t par) {
    asm volatile("{\n .reg .pred p;\n setp.ne.u32 p, %2, 0;\n @p st.relaxed.gpu.global.u32 [%0], %1;\n @p st.relaxed.gpu.global.u32 [%0+4096], %1;\n}" :: "l"(d), "r"(tagw(a, par)), "r"((uint32_t)p) : "memory");
}
__device__ __forceinline__ void stp64_if(bool p, char* d, uint32_t lo, uint32_t hi) {
    asm volatile("{\n .reg .pred p;\n .reg .b64 d;\n setp.ne.u32 p, %3, 0;\n mov.b64 d, {%1,%2};\n @p st.relaxed.gpu.global.b64 [%0], d;\n @p st.relaxed.gpu.global.b64 [%0+4096], d;\n}" :: "l"(d), "r"(lo), "r"(hi), "r"((uint32_t)p) : "memory");
}
__device__ __forceinline__ uint32_t chk2(uint32_t a, uint32_t b, uint32_t par) { uint32_t r; asm("lop3.b32 %0, %1, %2, %3, 0x7E;" : "=r"(r) : "r"(a), "r"(b), "r"(par)); return r; }
__device__ __forceinline__ uint32_t or3(uint32_t a, uint32_t b, uint32_t c) { uint32_t r; asm("lop3.b32 %0, %1, %2, %3, 0xFE;" : "=r"(r) : "r"(a), "r"(b), "r"(c)); return r; }
__device__ __forceinline__ uint32_t chk8(const uint32_t (&v)[8], uint32_t par) { return or3(chk2(v[0], v[1], par), chk2(v[2], v[3], par), or3(chk2(v[4], v[5], par), chk2(v[6], v[7], par), 0)); }
__device__ __forceinline__ uint32_t chk8(const uint2 (&v)[8], uint32_t par) { return or3(chk2(v[0].x, v[1].x, par), chk2(v[2].x, v[3].x, par), or3(chk2(v[4].x, v[5].x, par), chk2(v[6].x, v[7].x, par), 0)); }
__device__ __forceinline__ uint32_t chk8y(const uint2 (&v)[8], uint32_t par) { return or3(chk2(v[0].y, v[1].y, par), chk2(v[2].y, v[3].y, par), or3(chk2(v[4].y, v[5].y, par), chk2(v[6].y, v[7].y, par), 0)); }
__device__ __forceinline__ uint32_t chk4(const uint2 (&v)[4], uint32_t par) { return or3(chk2(v[0].x, v[0].y, par), chk2(v[1].x, v[1].y, par), or3(chk2(v[2].x, v[2].y, par), chk2(v[3].x, v[3].y, par), 0)); }
__device__ __forceinline__ float asf(uint32_t v) { return __uint_as_float(v); }
__device__ __forceinline__ float sum8(const uint32_t (&v)[8]) { return ((asf(v[0]) + asf(v[1])) + (asf(v[2]) + asf(v[3]))) + ((asf(v[4]) + asf(v[5])) + (asf(v[6]) + asf(v[7]))); }
__device__ __forceinline__ float sum8x(const uint2 (&v)[8]) { return ((asf(v[0].x) + asf(v[1].x)) + (asf(v[2].x) + asf(v[3].x))) + ((asf(v[4].x) + asf(v[5].x)) + (asf(v[6].x) + asf(v[7].x))); }
__device__ __forceinline__ float sum8y(const uint2 (&v)[8]) { return ((asf(v[0].y) + asf(v[1].y)) + (asf(v[2].y) + asf(v[3].y))) + ((asf(v[4].y) + asf(v[5].y)) + (asf(v[6].y) + asf(v[7].y))); }

__device__ __forceinline__ uint32_t pack2(float lo, float hi) { uint32_t r; asm("cvt.rn.bf16x2.f32 %0, %1, %2;" : "=r"(r) : "f"(hi), "f"(lo)); return r; }
__device__ __forceinline__ float bfr(float x) { return __uint_as_float(pack2(0.0f, x)); }
__device__ __forceinline__ float ex2(float x) { float r; asm("ex2.approx.ftz.f32 %0, %1;" : "=f"(r) : "f"(x)); return r; }
__device__ __forceinline__ float rcp(float x) { float r; asm("rcp.approx.ftz.f32 %0, %1;" : "=f"(r) : "f"(x)); return r; }
__device__ __forceinline__ float sqrt_(float x) { float r; asm("sqrt.approx.ftz.f32 %0, %1;" : "=f"(r) : "f"(x)); return r; }
__device__ __forceinline__ float bf_lo(uint32_t v) { return __uint_as_float(v << 16); }
__device__ __forceinline__ float bf_hi(uint32_t v) { return __uint_as_float(v & 0xffff0000u); }
__device__ __forceinline__ float sel4(int k, float a, float b, float c, float d) { return (k & 2) ? ((k & 1) ? d : c) : ((k & 1) ? b : a); }
constexpr float LOG2E = 1.4426950408889634f;
constexpr uint32_t ONES = 0x3f803f80u;

__device__ __forceinline__ void ln_stats(float sum, float sq, float& mean, float& den) {
    const float m = sum * (1.0f / 640.0f);
    const float var = fmaxf(fmaf(sq, 1.0f / 640.0f, -m * m), 0.0f);
    mean = bfr(m);
    den = bfr(sqrt_(bfr(bfr(var) + 1e-5f)));
}
__device__ __forceinline__ float sigmoidf_(float x) { return rcp(1.0f + ex2(-x * LOG2E)); }

#define TSTAMP(k) do {} while (0)
#define TST(k) do {} while (0)

#define CSTAMP(k) do {} while (0)
template <int N> __device__ __forceinline__ uint32_t lag(uint32_t sb) {
    uint32_t z = 0;
#pragma unroll
    for (int k = 0; k < N; k++) z = ldsvol(sb + S_ZERO + z);
    return z;
}
__device__ __forceinline__ void warm_mma(uint32_t& a, uint32_t& b) {
    asm volatile("mma.sync.aligned.m16n8k8.row.col.f16.f16.f16.f16 {%0,%1}, {%0,%1}, {%0}, {%0,%1};" : "+r"(a), "+r"(b) :: "memory");
}
#define KWNS2 20
#define KWNS 200
template <int STRIDE>
__device__ __forceinline__ float gather8(const char* p, uint32_t par) {
    uint32_t v[8];
    int guard = 0;
    do {
#pragma unroll
        for (int s = 0; s < 8; s++) v[s] = ldp32(p + s * STRIDE);
    } while ((chk8(v, par) & 1) && ++guard < SPIN_LIMIT);
    return sum8(v);
}
template <class F>
__device__ __forceinline__ void gather16(const char* p, uint32_t par, int k, F use) {
    uint32_t v[8], u[8];
    int guard = 0;
    bool again;
    do {
#pragma unroll
        for (int s = 0; s < 8; s++) v[s] = ldp32(p + s * 512);
#pragma unroll
        for (int s = 0; s < 8; s++) u[s] = ldp32(p + HALF + s * 512);
        const uint32_t stale = use(sum8(v) + sum8(u), ((v[0] ^ par) & 1) * 8);
        again = __any_sync(~0u, (or3(chk8(v, par), chk8(u, par), stale) & 1) != 0);
    } while (again & (++guard < SPIN_LIMIT));
    SWEEPS(k, guard - 1);
}

struct Params {
    const __nv_bfloat16 *x, *k, *v, *wr;
    __nv_bfloat16* out;
};
struct Maps { CUtensorMap k, v, vu, wq, wo, wg, wu, wd; };

constexpr int KV_BATCH_KEYS = 32 * 4096;

__device__ __forceinline__ void tma2d(uint32_t dst, const CUtensorMap* m, int c0, int c1, uint32_t bar, uint32_t bytes, uint64_t pol) {
    asm volatile("{\n .reg .pred p;\n elect.sync _|p, 0xffffffff;\n"
                 " @p mbarrier.arrive.expect_tx.shared::cta.b64 _, [%2], %6;\n"
                 " @p cp.async.bulk.tensor.2d.shared::cluster.global.mbarrier::complete_tx::bytes.L2::cache_hint [%0], [%1, {%3, %4}], [%2], %5;\n}"
                 :: "r"(dst), "l"(m), "r"(bar), "r"(c0), "r"(c1), "l"(pol), "r"(bytes) : "memory");
}
__device__ __forceinline__ void scrap_copy(uint32_t dst, const char* src, uint32_t bar) {
    asm volatile("{\n .reg .pred p;\n elect.sync _|p, 0xffffffff;\n"
                 " @p mbarrier.arrive.expect_tx.shared::cta.b64 _, [%2], 12288;\n"
                 " @p cp.async.bulk.shared::cluster.global.mbarrier::complete_tx::bytes [%0], [%1], 4096, [%2];\n"
                 " @p cp.async.bulk.shared::cluster.global.mbarrier::complete_tx::bytes [%0], [%1+4096], 4096, [%2];\n"
                 " @p cp.async.bulk.shared::cluster.global.mbarrier::complete_tx::bytes [%0], [%1+8192], 4096, [%2];\n}"
                 :: "r"(dst), "l"(src), "r"(bar) : "memory");
}
__device__ __forceinline__ void prefetch_l2(const void* p, uint32_t bytes) {
    asm volatile("{\n .reg .pred p;\n elect.sync _|p, 0xffffffff;\n @p cp.async.bulk.prefetch.L2.global [%0], %1;\n}" :: "l"(p), "r"(bytes) : "memory");
}
__device__ __forceinline__ uint64_t pol_first() { uint64_t p; asm("createpolicy.fractional.L2::evict_first.b64 %0, 1.0;" : "=l"(p)); return p; }
__device__ __forceinline__ uint64_t pol_normal() { uint64_t p; asm("createpolicy.fractional.L2::evict_normal.b64 %0, 1.0;" : "=l"(p)); return p; }
__device__ __forceinline__ bool utest(uint32_t bar, uint32_t parity) { return __all_sync(~0u, mbar_test(bar, parity)); }
__device__ __forceinline__ void uwait(uint32_t bar, uint32_t parity) {
    int n = 0;
    while (!__all_sync(~0u, mbar_try(bar, parity)) && ++n < SPIN_LIMIT) {}
}
template <int A, int B, int CNT> __device__ __forceinline__ void init_bars(uint32_t sb) {
#pragma unroll 1
    for (int k = A; k < B; k++)
        asm volatile("{\n .reg .pred p;\n elect.sync _|p, 0xffffffff;\n @p mbarrier.init.shared::cta.b64 [%0], %1;\n}" :: "r"(sb + S_BAR + 8 * k), "n"(CNT) : "memory");
}
__device__ __forceinline__ int first_key() { return (blockIdx.x >> 2) * 4096 + 3072 + (blockIdx.x & 3) * 256; }
__device__ __forceinline__ void load_tile(const CUtensorMap* m, uint32_t dst, uint32_t bar, uint32_t bytes, int key, uint64_t pol) { tma2d(dst, m, 0, 3 * key, bar, bytes, pol); }
__device__ __forceinline__ const char* unit_ptr(const Params& P, int n) {
    return (const char*)((n & 16) ? P.v : P.k) + (size_t)(first_key() + (n >> 5) * KV_BATCH_KEYS + (n & 15) * 16) * 384;
}
#define LSTAMP(k) do {} while (0)

__device__ __forceinline__ uint32_t k_place(uint32_t b, uint32_t s) { return s + 3 + 5 * (b & 1); }
__device__ __forceinline__ uint32_t v_place(uint32_t b, uint32_t s) { return s < 3 ? s : s + 8 - 8 * (b & 1); }
__device__ __forceinline__ void k_load(const Maps& M, uint32_t dst, uint32_t bar, int key8, uint64_t pol) {
    asm volatile("{\n .reg .pred p;\n elect.sync _|p, 0xffffffff;\n"
                 " @p mbarrier.arrive.expect_tx.shared::cta.b64 _, [%2], 6144;\n"
                 " @p cp.async.bulk.tensor.4d.shared::cluster.global.mbarrier::complete_tx::bytes.L2::cache_hint [%0], [%1, {0, 0, 0, %3}], [%2], %4;\n}"
                 :: "r"(dst), "l"(&M.k), "r"(bar), "r"(key8), "l"(pol) : "memory");
}
__device__ __forceinline__ int unit_key8(uint32_t n) { return first_key() / 8 + (n >> 4) * (KV_BATCH_KEYS / 8) + 2 * (n & 15); }
__device__ __forceinline__ void ring_load(const Maps& M, uint32_t sb, uint32_t b, uint32_t u, uint32_t pos) {
    if (u < 16) k_load(M, sb + pos * UNIT, sb + S_RING + 8 * pos, unit_key8(16 * b + u), pol_normal());
    else load_tile(&M.vu, sb + pos * UNIT, sb + S_FV + 4 * (pos & 6), UNIT, first_key() + b * KV_BATCH_KEYS + 16 * pos, pol_first());
}
__device__ __forceinline__ uint32_t token(bool p, uint32_t a, uint32_t n) {
    uint32_t v;
    asm volatile("{\n .reg .pred p;\n setp.ne.u32 p, %2, 0;\n mov.u32 %0, 0;\n @p atom.shared.exch.b32 %0, [%1], %3;\n}" : "=r"(v) : "r"(a), "r"((uint32_t)p), "r"(n) : "memory");
    return v;
}
__device__ __forceinline__ void place_load(const Maps& M, uint32_t sb, uint32_t n) {
    k_load(M, sb + k_place(n >> 4, 0) * SLOT + (n & 15) * UNIT, sb + S_FK + 4 * (n & 14), unit_key8(n), pol_first());
}
__device__ __forceinline__ void v_load(const Maps& M, uint32_t sb, uint32_t b, uint32_t s) {
    load_tile(&M.v, sb + v_place(b, s) * SLOT, sb + S_FV + 8 * s, SLOT, first_key() + b * KV_BATCH_KEYS + 32 * s, pol_first());
}
__device__ __forceinline__ bool due(uint32_t t) { return __all_sync(~0u, (int)(gtime32() * 16 - t) >= 0); }
__device__ __forceinline__ bool reached(uint32_t a, int v) { return __all_sync(~0u, ldsvol(a) >= v); }

__device__ __forceinline__ void stream_warp(const Params& P, const Maps& M, uint32_t sb, uint32_t lane) {
    const uint64_t pol = pol_first();
    const int bid = blockIdx.x, g = bid >> 3, i = bid & 7;
    const uint32_t wf = sb + S_WFULL;
    if (PF0 > 0 && !PFTOP) prefetch_l2(unit_ptr(P, 0), PF0 * UNIT);
    uint32_t tn = __shfl_sync(~0u, gtime32(), 0) * 16 - T_LEAD;
    auto pace = [&](uint32_t dt) {
        int k = 0;
        uint32_t now;
        do now = __shfl_sync(~0u, gtime32(), 0) * 16; while ((int)(now - tn) < 0 && ++k < SPIN_LIMIT);
        if ((int)(now - tn) > SLACK0) tn = now - SLACK0;
        tn += dt;
    };
#pragma unroll
    for (int k = 0; k < 10; k++) {
        if (k < 2) {
            if (k == 0) init_bars<26, 27, 1>(sb); else init_bars<27, 37, 1>(sb);
            asm volatile("fence.mbarrier_init.release.cluster;" ::: "memory");
            if (k == 1) { asm volatile("bar.arrive 2, %0;" :: "n"(NTHR) : "memory"); asm volatile("bar.sync 3, 128;" ::: "memory"); }
        }
        if (k >= WIN_W) uwait(wf + 8 * (k - WIN_W), 0);
        pace(TAUW * 5 / 2);
        if (k < 4) tma2d(sb + ST_WQ + 15360 * k, &M.wq, 384 * g + 192 * (k >> 1), 80 * i + 40 * (k & 1), wf + 8 * k, 15360, pol);
        else if (k < 6) tma2d(sb + ST_WG + 15360 * (k - 4), k == 4 ? &M.wg : &M.wu, 96 * g, 80 * i, wf + 8 * k, 15360, pol);
        else tma2d(sb + ST_WO + 15360 * (k - 6), &M.wo, 80 * i, 384 * g + 96 * (k - 6), wf + 8 * k, 15360, pol);
    }
#pragma unroll 1
    for (int n = 0; n < 16; n++) {
        if (n == 0 || n == 5 || n == 11) uwait(sb + S_RELW + (n == 0 ? 0 : n == 5 ? 8 : 16), 0);
        uwait(n < WIN_S ? wf + 8 * (10 - WIN_S + n) : sb + S_FV + 8 * ((n - WIN_S) ^ 8), 0);
        pace(max(min(2 * n + 2 - PF0, 2), 0) * TAU0);
        if (n < 8) { place_load(M, sb, 2 * n); place_load(M, sb, 2 * n + 1); }
        else if (n < 11) { ring_load(M, sb, 0, 2 * n, 2 * n - 16); ring_load(M, sb, 0, 2 * n + 1, 2 * n - 15); }
        else v_load(M, sb, 0, n - 8);
        if (n == 7) { pace(TAUW * 5 / 2); tma2d(sb + S_WD, &M.wd, 80 * i, 96 * g, wf + 80, 15360, pol); }
    }
    int nd = 0;
    uint32_t q[4];
#pragma unroll
    for (int r = 0; r < 4; r++) q[r] = sb + S_FV + 8 * (7 - r);
    tn -= TSH;
    uint32_t td = tn;
    uint32_t pos = 2;
#pragma unroll 1
    for (int m = 16; m < 64; m++) {
        const int b = m >> 4, j = m & 15;
        const char* src = unit_ptr(P, 2 * m);
        const uint32_t tok = sb + S_TOK + (j < 3 ? 4 * pos : j < 11 ? 24 + 4 * pos : 16 + 4 * j) + 4 * lane;
        static_assert(WIN_U <= 12, "a ring position has at most one token of the timetable");
        int k = 0;
        while (true) {
            const uint2 c = lds64(sb + S_KF);
            if (__all_sync(~0u, mbar_test(q[WIN_S - 1] & ~1u, q[WIN_S - 1] & 1) & (min((int)c.x + 1, (int)c.y) >= 16 * b + min(2 * j + 2 - WIN_U, 16))) || ++k >= SPIN_LIMIT) break;
        }
        uint32_t now;
        while (true) {
            now = __shfl_sync(~0u, gtime32(), 0) * 16;
            if ((int)(now - td) >= 0 || ++k >= SPIN_LIMIT) break;
            if (PSLEEP > 0 && (int)(td - now) > 16 * PSLEEP * 2) __nanosleep(PSLEEP);
        }
        const uint32_t mine = __ballot_sync(~0u, token(lane < (j < 11 ? 2 : 1), tok, 2 * m + lane) == 2 * m + lane);
        q[3] = q[2]; q[2] = q[1]; q[1] = q[0]; q[0] = sb + S_QRDY;
        if (j < 11) {
            if (mine & 1) ring_load(M, sb, b, 2 * j, pos); else prefetch_l2(src, UNIT);
            if (mine & 2) ring_load(M, sb, b, 2 * j + 1, pos + 1); else prefetch_l2(src + UNIT, UNIT);
            if (j >= 8) q[0] = (sb + S_FV + 8 * (j - 8)) | (b & 1);
        } else if (mine) { v_load(M, sb, b, j - 8); q[0] = (sb + S_FV + 8 * (j - 8)) | (b & 1); }
        else if (j - 8 >= VPF) prefetch_l2(src, SLOT);
        else {
            scrap_copy(sb + S_DUMMY, src, sb + S_DBAR + 8 * (nd & 3));
            q[0] = (sb + S_DBAR + 8 * (nd & 3)) | ((nd >> 2) & 1);
            nd++;
        }
        pos = j == 15 ? 2 : pos == 4 ? 0 : pos + 2;
        if ((int)(now - tn) > SLACK) tn = now - SLACK;
        tn += 2 * TAU;
        td = (int)(tn - now) > 2 * TMIN ? tn : now + 2 * TMIN;
        if (m >= 48 + JFREE) td = now + TFREE;
    }
#pragma unroll 1
    for (int m = max(nd - 4, 0); m < nd; m++) uwait(sb + S_DBAR + 8 * (m & 3), (m >> 2) & 1);
}

__host__ __device__ constexpr uint64_t bit_list(uint32_t m) { uint64_t r = 0; int n = 0; for (int k = 0; k < 12; k++) if ((m >> k) & 1) r |= (uint64_t)k << (4 * n++); return r; }
__device__ __forceinline__ float scaled(float s) { return bfr(bfr(s) * 0.07216878364870322f); }
__device__ __forceinline__ void probs(float s, uint32_t ps, uint32_t src, uint32_t ln) {
    const uint32_t q8 = ln >> 2, t4 = ln & 3;
    int key = __float_as_int(s);
    key ^= (key >> 31) & 0x7fffffff;
    key = __reduce_max_sync(~0u, key);
    key ^= (key >> 31) & 0x7fffffff;
    const float ml = __int_as_float(key) * LOG2E;
    sts16(ps + 64 * src + (q8 >> 1) * 16 + t4 * 4 + (q8 & 1) * 2, pack2(ex2(fmaf(s, LOG2E, -ml)), 0.f));
    stsf(ps + PS_MAX + 4 * src, ml);
}
template <int H> __device__ __forceinline__ uint32_t b_pos(uint32_t e) { const uint32_t h = e >= H, k = e - H * h; return h * 192 + (k & 6) * 24 + (k >> 3) * 4 + (k & 1) * 2; }
__device__ __forceinline__ uint32_t a_pos(uint32_t e) { const uint32_t h = e >= 40, k = e - 40 * h; return (k & 6) * 24 + (k >> 3) * 8 + h * 4 + (k & 1) * 2; }
__device__ __forceinline__ uint32_t q_pos(uint32_t d) { const uint32_t s = 3 * ((d >> 4) & 3) + (d >> 6); return s * 32 + (d & 6) * 4 + ((d >> 3) & 1) * 4 + (d & 1) * 2; }
__device__ __forceinline__ uint32_t k_off(uint32_t ln) { return (ln & 8) * 384 + (ln & 7) * 128 + (((ln & 7) ^ (ln >> 4)) << 4); }

#define HSTAMP(k) do {} while (0)
__device__ __forceinline__ char* xwindow() { return reinterpret_cast<char*>((reinterpret_cast<uintptr_t>(g_x) + (2u << 20) - 1) & ~(uintptr_t)((2u << 20) - 1)); }

struct XPtr {
    uint32_t lo, hi;
    __device__ __forceinline__ explicit XPtr(char* p) : lo((uint32_t)(uintptr_t)p), hi((uint32_t)((uintptr_t)p >> 32)) {}
    __device__ __forceinline__ XPtr(uint32_t l, uint32_t h) : lo(l), hi(h) {}
    __device__ __forceinline__ XPtr operator+(uint32_t o) const { return XPtr(lo + o, hi); }
    __device__ __forceinline__ operator char*() const { uint64_t p; asm("mov.b64 %0, {%1, %2};" : "=l"(p) : "r"(lo), "r"(hi)); return (char*)p; }
};
__device__ __forceinline__ void keep(XPtr& v) { keep(v.lo); }

__device__ __forceinline__ void side_warp(uint32_t sb) {
    const uint32_t bid = blockIdx.x, g = bid >> 3, i = bid & 7, P = pairG(0, 0, i);
    char* p = xwindow() + P * 8192 + (g >> 3) * HALF + (g & 7) * 512 + 448;
    uint32_t best[2] = {~0u, ~0u};
    asm volatile("st.relaxed.gpu.global.b32 [%0], 1;" :: "l"(p) : "memory");
    asm volatile("st.relaxed.gpu.global.b32 [%0], 1;" :: "l"(p + COPY) : "memory");
#pragma unroll 1
    for (int r = 0; r < 64; r++) {
        if (r >= 4 && !(r & 1) && min(best[0], best[1]) < 380 && max(best[0], best[1]) > min(best[0], best[1]) + 80) break;
        uint32_t c0, c1, v;
        asm volatile("mov.u32 %0, %clock;" : "=r"(c0) :: "memory");
        asm volatile("atom.relaxed.gpu.global.exch.b32 %0, [%1], 0;" : "=r"(v) : "l"(p + (r & 1) * COPY) : "memory");
        asm volatile("{\n .reg .pred q;\n setp.eq.u32 q, %1, 0x13579bdf;\n mov.u32 %0, 0;\n @!q mov.u32 %0, %clock;\n}" : "=r"(c1) : "r"(v) : "memory");
        if (r & 1) best[1] = min(best[1], c1 - c0); else best[0] = min(best[0], c1 - c0);
    }
    stsvol(sb + S_SIDE, 1 + ((best[1] < best[0]) ^ (__popc(P & PMASK) & 1)));
}

template <int N>
__device__ __forceinline__ void hop_a(const char* src, uint32_t par, uint32_t dst, bool st, int k) {
    uint2 v[N][4];
    float e[4], rl;
    int guard = 0;
    bool again;
    do {
#pragma unroll
        for (int s = 0; s < 4 * N; s++) v[s / 4][s % 4] = ldp64(src + (s / 4) * 256 + (s % 4) * 1024);
        again = __any_sync(~0u, ((chk4(v[0], par) | chk4(v[N - 1], par)) & 1) != 0);
        const int M = max(max((int)v[0][0].x, (int)v[0][1].x), max((int)v[0][2].x, (int)v[0][3].x)) - 254;
#pragma unroll
        for (int s = 0; s < 4; s++) e[s] = __int_as_float(max((int)v[0][s].x - M, 0) << 22);
        rl = rcp(fmaf(e[0], asf(v[0][0].y), e[1] * asf(v[0][1].y)) + fmaf(e[2], asf(v[0][2].y), e[3] * asf(v[0][3].y)));
#pragma unroll
        for (int s = 0; s < 4; s++) e[s] = __shfl_sync(~0u, e[s], 24);
        keep(rl);
    } while (again & (++guard < SPIN_LIMIT));
    rl = __shfl_sync(~0u, rl, 24);
#pragma unroll
    for (int n = 0; n < N; n++) {
        const float o0 = fmaf(e[0], asf(v[n][0].x), e[1] * asf(v[n][1].x)) + fmaf(e[2], asf(v[n][2].x), e[3] * asf(v[n][3].x));
        const float o1 = fmaf(e[0], asf(v[n][0].y), e[1] * asf(v[n][1].y)) + fmaf(e[2], asf(v[n][2].y), e[3] * asf(v[n][3].y));
        sts32_if(st, dst + 192 * n, pack2(o0 * rl, o1 * rl));
    }
    SWEEPS(k, guard - 1);
    __syncwarp();
}

__device__ __forceinline__ void score_warp(const Maps& M, uint32_t sb, uint32_t h, uint32_t ln) {
    const uint32_t lane0 = ln;
    uwait(sb + S_QRDY, 0);
    const uint32_t q8 = ln >> 2;
    const uint32_t k0 = k_off(ln);
    uint32_t pos = h + 6, bar = sb + S_FK, par = 0, phases = 0;
    uint2 q = lds64(sb + S_QS + 8 * ln), qh = lds64(sb + S_QS + 8 * ln + 256);
    auto first_round = [&](uint32_t b, uint32_t ln) {
        uwait(sb + S_RELR, b & 1);
        const uint32_t u = h + 2 * ln, p = u < 4 ? u + 2 : u - 4;
        uint32_t todo = __ballot_sync(~0u, token(ln < 3, sb + S_TOK + 4 * p, 32 * b + 32 + u) == 32 * b + 32 + u);
#pragma unroll 1
        for (uint32_t r = h; todo; todo >>= 1, r += 2) if (todo & 1) ring_load(M, sb, b + 1, r, r < 4 ? r + 2 : r - 4);
    };
#pragma unroll 1
    for (uint32_t n = h; n < 64; n += 2) {
        HSTAMP(0);
        const uint32_t ua = sb + pos * UNIT;
        if (!__all_sync(~0u, mbar_try(bar, par))) uwait(bar, par);
        HSTAMP(1);
        float acc[2][4] = {};
        uint32_t mine = 0;
        const uint32_t id = n + (n & 48) + 6;
#pragma unroll
        for (int s = 0; s < 12; s++) {
            uint32_t kf[4];
            ldsm4(kf, (k0 ^ (32 * (s / 3))) + (ua + 1024 * (s % 3)));
            if (s == 11) {
                __syncwarp();
                mine = token(ln == 0 && n >= 16, sb + S_TOK + 24 + 4 * pos, id);
                stsvol(sb + S_KF + 4 * h, n + 1);
            }
            const bool m = q8 == (s & 7);
            mmaA(acc[s & 1], kf, m ? (s < 8 ? q.x : qh.x) : 0u, m ? (s < 8 ? q.y : qh.y) : 0u);
        }
        const uint32_t pos0 = pos;
        const bool last = (n & 14) == 14;
        pos = last ? h + 2 : n >= 16 && pos >= 4 ? h : pos + 2;
        bar = n >= 14 ? sb + S_RING + 8 * pos : bar + 8;
        par = n >= 14 ? (phases >> pos) & 1 : 0;
        phases ^= n >= 14 ? 1u << pos : 0;
        const float w0 = (acc[0][0] + acc[0][1]) + (acc[1][0] + acc[1][1]), w1 = (acc[0][2] + acc[0][3]) + (acc[1][2] + acc[1][3]);
        HSTAMP(2);
        if (__any_sync(~0u, mine == id)) ring_load(M, sb, n >> 4, (n & 15) + 6, pos0);
        HSTAMP(3);
        float s = ((ln & 1) ? w1 : w0) + __shfl_xor_sync(~0u, (ln & 1) ? w0 : w1, 1);
        s += __shfl_xor_sync(~0u, s, 2);
        sts_hi16(sb + S_SC + (((n & 12) >> 1) + h) * 64 + (n & 2) * 2 + (ln & 29) * 2, scaled(s));
        if (last) {
            __syncwarp();
            arrive_if(ln == 0, sb + S_SCO);
            const uint32_t b = n >> 4, ln = lane0 + lag<1>(sb);
            if (b > 0) {
                uwait(sb + S_RELK, (b - 1) & 1);
                if (h == 0) LSTAMP(64 + 2 * b);
                const uint32_t sl = 3 + h + 2 * ln, idv = 32 * b + 16 + 2 * sl;
                uint32_t todo = __ballot_sync(~0u, token(sl < 8, sb + S_TOK + 48 + 4 * sl, idv) == idv);
#pragma unroll 1
                for (uint32_t r = 3 + h; todo; todo >>= 1, r += 2) if (todo & 1) v_load(M, sb, b, r);
                const uint32_t g = blockIdx.x >> 3, pr = pairL(RA, 1, g), side = ldsvol(sb + S_SIDE);
                const char* src = xwindow() + pr * 8192 + ((side ^ 1 ^ __popc(pr & PMASK)) & 1) * COPY + h * HALF + 8 * min(ln, 24u);
                uwait(sb + S_RELV, (b - 1) & 1);
                __nanosleep(HOP1_NS);
#pragma unroll 1
                for (uint32_t r = 0; r < 4; r += 2) {
                    hop_a<2>(src + 256 * r, b & 1, sb + S_OS + 192 * (4 * h + r) + 96 + 4 * ln, ln < 24, 25);
                    if (r == RELR_AT && b < 3) first_round(b, ln);
                }
                arrive_if(ln == 0, sb + S_OS1);
            } else first_round(0, ln);
            q = lds64(sb + S_QS + 24 * ((n + 2) & 48) + 8 * ln); qh = lds64(sb + S_QS + 24 * ((n + 2) & 48) + 8 * ln + 256);
        }
    }
}

__global__ void __launch_bounds__(NTHR, 1)
fused_kernel(const Params P, const __grid_constant__ Maps M) {
    extern __shared__ __align__(1024) unsigned char smem[];
    const uint32_t sb = smem_u32(smem);
    const int tid = threadIdx.x, bid = blockIdx.x;
    if (PFTOP && tid == 0) {
        if (PFTOP == 2) asm volatile("prefetch.tensormap [%0];" :: "l"(&M.wq) : "memory");
        asm volatile("cp.async.bulk.prefetch.L2.global [%0], %1;" :: "l"(unit_ptr(P, 0)), "r"(PF0 * UNIT) : "memory");
    }
    const int w = __shfl_sync(~0u, tid >> 5, 0), lane = tid & 31;

    if (w >= 8) {
        asm volatile("setmaxnreg.dec.sync.aligned.u32 " REG_LO ";");
        if (w == 8) {
            stream_warp(P, M, sb, lane);
        } else {
            if (PFMAP && w == 11 && lane < 8) asm volatile("prefetch.tensormap [%0];" :: "l"(&M.k + lane) : "memory");
            if (w == 9) { init_bars<0, 3, 2>(sb); init_bars<3, 8, 1>(sb); init_bars<16, 22, 1>(sb); }
            else if (w == 10) { init_bars<8, 16, 2>(sb); init_bars<22, 26, 1>(sb); }
            else { init_bars<37, 38, 1>(sb); init_bars<38, 40, 8>(sb); init_bars<40, 41, 1>(sb); init_bars<41, 44, 8>(sb); init_bars<44, 46, 2>(sb); stsvol(sb + S_ZERO + 4 * lane, 0); }
            asm volatile("fence.mbarrier_init.release.cluster;" ::: "memory");
            asm volatile("bar.arrive 3, 128;" ::: "memory");
            asm volatile("bar.sync 2, %0;" :: "n"(NTHR) : "memory");
            if (w < 11) score_warp(M, sb, w - 9, lane);
            else {
                if (lane == 0) side_warp(sb);
                __syncwarp();
                uint32_t a = 0, b = 0;
                int k = 0;
                while (ldsvol(sb + S_GATE) == 0 && ++k < SPIN_LIMIT) { warm_mma(a, b); __nanosleep(KWNS); }
                uint4* d = reinterpret_cast<uint4*>(reinterpret_cast<char*>(g_s) + XS + bid * 7680) + lane;
                const uint4 z = make_uint4(0, 0, 0, 0);
#pragma unroll 1
                for (int u = 0; u < 15; u++) d[32 * u] = z;
                d = reinterpret_cast<uint4*>(reinterpret_cast<char*>(g_s) + XS2 + bid * 768) + lane;
                d[0] = z;
                if (lane < 16) d[32] = z;
                const uint32_t side = (ldsvol(sb + S_SIDE) & 1) ^ 1, g = bid >> 3, i = bid & 7;
                const XPtr gx(xwindow());
                auto nearp = [&](uint32_t pr) { return gx.lo + pr * 8192 + ((side ^ __popc(pr & PMASK)) & 1) * COPY; };
                const uint32_t own = (i >> 2) * HALF + (i & 3) * 1024 + (lane & 7) * 128;
                const uint32_t pAC = nearp(pairL(lane >> 4, (lane >> 3) & 1, g)) + own, pE = nearp(pairL(RE, (lane >> 3) & 1, g)) + own;
                const uint32_t pG = nearp(pairG((lane >> 2) & 1, (lane >> 3) & 1, i)) + min(lane & 3, 2) * 128;
                uint32_t tr = 0, tk = 0, ph = 0, src = g + (lane >> 4), seen = 0, n = 16, cs = 0;
                bool go = false, first = true;
                while (n < 64 && ++k < SPIN_LIMIT) {
                    const uint32_t now = __shfl_sync(~0u, gtime32(), 0) * 16;
                    if (!go && utest((n & 15) < KRE_EARLY ? sb + S_RELK : sb + S_RELV, ((n >> 4) & 1) ^ 1)) { go = true; if ((int)(now - tk) > 0 || !(n & 15)) tk = now; }
                    if (go && (int)(now - tk) >= 0) {
                        place_load(M, sb, (n & 16) ? n : (n & 48) | ((n + 10) & 15));
                        tk += n >= 48 ? KRE_TAU3 : (n & 15) < KRE_N1 ? KRE_TAU1 : KRE_TAU;
                        n++;
                        go = (n & 15) != 0 && (n & 15) != KRE_EARLY;
                        if (!(n & 15)) LSTAMP(63 + (n >> 3));
                    } else if (first || (int)(now - tr) >= 0) {
                        first = false;
                        tr = now + RFR_TAU;
                        b |= seen & a;
                        warm_mma(a, b);
                        if (RFR_ON) seen = ldp32(XPtr(ph == 0 ? pAC : ph == 1 && lane < 16 ? pE : pG + (src & 8) * (HALF / 8) + (src & 7) * 512, gx.hi));
                        if (RFR_XS && (++cs & (RFR_XS - 1)) < 2) {
                            const uint32_t l = lane + 32 * (cs & 1);
                            *reinterpret_cast<volatile uint32_t*>(reinterpret_cast<char*>(g_s) + (l < 60 ? XS + bid * 7680 + 128 * l : XS2 + bid * 768 + 128 * (l - 60))) = 0;
                        }
                        src += ph == 0 ? 0 : ph == 1 ? 2 : 1;
                        ph = ph == 2 ? 0 : ph + 1;
                    } else __nanosleep(KWNS2);
                }
                while (ldsvol(sb + S_GATE) < 6 && ++k < SPIN_LIMIT) { warm_mma(a, b); __nanosleep(KWNS); }
                if (a | b) stsvol(sb + S_GATE, 6);
            }
        }
        return;
    }
    asm volatile("setmaxnreg.inc.sync.aligned.u32 " REG_HI ";");

    const int g = bid >> 3, i = bid & 7;
    const int g8 = lane >> 2, t = lane & 3;
    char* const gs = reinterpret_cast<char*>(g_s);
    const XPtr gx(xwindow());

    auto zero_words = [&] {
        const uint4 z = make_uint4(0, 0, 0, 0);
        const uint32_t c = (tid >> 6) & 1, cp = (tid >> 7) * COPY, k = (tid & 63) * 16;
        *reinterpret_cast<uint4*>((char*)(gx + pairL(RA, c, g) * 8192 + (i >> 2) * HALF + (i & 3) * 1024 + cp + k)) = z;
        *reinterpret_cast<uint4*>((char*)(gx + pairL(RC, c, g) * 8192 + (i >> 2) * HALF + (i & 3) * 1024 + cp + k)) = z;
        *reinterpret_cast<uint4*>((char*)(gx + pairL(RE, c, g) * 8192 + (i >> 2) * HALF + (i & 3) * 1024 + cp + k)) = z;
        if ((tid & 31) < 24) *reinterpret_cast<uint4*>((char*)(gx + pairG((tid >> 5) & 1, c, i) * 8192 + (g >> 3) * HALF + (g & 7) * 512 + cp + (tid & 31) * 16)) = z;
    };
    if (ZPOS == 0) zero_words();
    W80 Wq[6], Wgu[3];
    uint32_t Wo[5][3][4];
    if (w < 4) {
        const uint32_t* xp = reinterpret_cast<const uint32_t*>(P.x + 640 * w);
        float sum = 0.f, sq = 0.f;
#pragma unroll
        for (int u = 0; u < 10; u++) { uint32_t v = xp[lane + 32 * u]; float a = bf_lo(v), b = bf_hi(v); sum += a + b; sq += a * a + b * b; }
#pragma unroll
        for (int o = 16; o > 0; o >>= 1) { sum += __shfl_xor_sync(~0u, sum, o); sq += __shfl_xor_sync(~0u, sq, o); }
        float mean, den; ln_stats(sum, sq, mean, den);
        if (lane < 20) {
            const uint2 v = reinterpret_cast<const uint2*>(P.x + 640 * w + 80 * i)[lane];
            sts64(sb + S_X0 + 160 * w + 8 * lane, v.x, v.y);
            sts32(sb + S_L0 + 384 * w + b_pos<40>(4 * lane), pack2(__fdiv_rn(bfr(bf_lo(v.x) - mean), den), __fdiv_rn(bfr(bf_hi(v.x) - mean), den)));
            sts32(sb + S_L0 + 384 * w + b_pos<40>(4 * lane + 2), pack2(__fdiv_rn(bfr(bf_lo(v.y) - mean), den), __fdiv_rn(bfr(bf_hi(v.y) - mean), den)));
        }
    } else if (w == 4) {
        const uint32_t* xp = reinterpret_cast<const uint32_t*>(P.wr);
        float sum = 0.f;
#pragma unroll
        for (int u = 0; u < 10; u++) { uint32_t v = xp[lane + 32 * u]; sum += bf_lo(v) + bf_hi(v); }
#pragma unroll
        for (int o = 16; o > 0; o >>= 1) sum += __shfl_xor_sync(~0u, sum, o);
        if (lane == 0) stsf(sb + S_SWR, sum);
        if (lane < 20) {
            const uint2 v = reinterpret_cast<const uint2*>(P.wr + 80 * i)[lane];
            sts32(sb + S_XA + 576 + a_pos(4 * lane), v.x); sts32(sb + S_XA + 576 + a_pos(4 * lane + 2), v.y);
            sts32(sb + S_XA + a_pos(4 * lane), ONES); sts32(sb + S_XA + a_pos(4 * lane + 2), ONES);
        }
    }
    asm volatile("bar.sync 2, %0;" :: "n"(NTHR) : "memory");
    auto frag = [](uint32_t (&a)[4], uint32_t p, int pitch) {
        const uint32_t r0 = lds32(p), r1 = lds32(p + pitch), r2 = lds32(p + 2 * pitch), r3 = lds32(p + 3 * pitch);
        a[0] = __byte_perm(r0, r1, 0x5410); a[1] = __byte_perm(r0, r1, 0x7632);
        a[2] = __byte_perm(r2, r3, 0x5410); a[3] = __byte_perm(r2, r3, 0x7632);
    };
    mbar_wait(sb + S_WFULL + 16 * (w >> 2), 0);
    mbar_wait(sb + S_WFULL + 16 * (w >> 2) + 8, 0);
    {
        const uint32_t p = sb + ST_WQ + (w >> 2) * 30720 + (2 * t) * 384 + (48 * (w & 3) + 2 * g8) * 2;
#pragma unroll
        for (int r = 0; r < 10; r++)
#pragma unroll
            for (int m = 0; m < 3; m++) {
                const uint32_t q = p + ((r & 1) * 40 + (r >> 1) * 8) * 384 + 32 * m, r0 = lds32(q), r1 = lds32(q + 384);
                (r < 8 ? Wq[2 * m].a[(r >> 2) & 1][r & 3] : Wq[2 * m].c[r & 1]) = __byte_perm(r0, r1, 0x5410);
                (r < 8 ? Wq[2 * m + 1].a[(r >> 2) & 1][r & 3] : Wq[2 * m + 1].c[r & 1]) = __byte_perm(r0, r1, 0x7632);
            }
    }
    __syncwarp();
    if (lane == 0) mbar_arrive(sb + S_RELW);
    TSTAMP(1);
    {
        char* d = gs + XS + bid * 7680 + (w >> 2) * 3840 + (48 * (w & 3) + 2 * g8) * 4;
        float acc[6][4] = {};
        mul80(acc, Wq, lds128(sb + S_L0 + 48 * lane), lds32(sb + S_L0 + 48 * lane + 16));
#pragma unroll
        for (int m = 0; m < 6; m += 2) stp64(d + t * 768 + 32 * m, acc[m][0] + acc[m][3], acc[m + 1][0] + acc[m + 1][3], 1);
        float sum[6][4] = {};
        mul80(sum, Wq, make_uint4(ONES, ONES, ONES, ONES), ONES);
        if (t == 0)
#pragma unroll
            for (int m = 0; m < 6; m += 2) stp64(d + 4 * 768 + 32 * m, sum[m][0] + sum[m][3], sum[m + 1][0] + sum[m + 1][3], 1);
    }
    mbar_wait(sb + S_WFULL + 32, 0);
    mbar_wait(sb + S_WFULL + 40, 0);
    const uint32_t oct = 3 * (w >> 1) + (w & 1), oct2 = 3 * (w >> 1) + 2;
    {
        const uint32_t p = sb + ST_WG + ((lane & 7) + 40 * ((lane >> 3) & 1) + 8 * (lane >> 4)) * 192;
#pragma unroll
        for (int T = 0; T < 3; T++) {
            const uint32_t q = p + (T < 2 ? T * 15360 + 16 * oct : (w & 1) * 15360 + 16 * oct2);
            ldsm4t(Wgu[T].a[0], q); ldsm4t(Wgu[T].a[1], q + 16 * 192); ldsm2t(Wgu[T].c, q + 32 * 192);
        }
        float sum[3][4] = {};
        mul80(sum, Wgu, make_uint4(ONES, ONES, ONES, ONES), ONES);
        if (t < 3) stp32(gs + XS2 + bid * 768 + (t < 2 ? 64 * oct + 4 * t : 64 * oct2 + 4 * (w & 1)) + 8 * g8,
                         sel4(t, sum[0][0] + sum[0][3], sum[1][0] + sum[1][3], sum[2][0] + sum[2][3], 0.f), 1);
    }
    __syncwarp();
    if (lane == 0) mbar_arrive(sb + S_RELW + 8);
    const char* srcS = gs + XS + g * 8 * 7680 + (i >> 2) * 3840 + min(tid, 191) * 4;
    uint32_t vs[5][8];
#pragma unroll
    for (int b = 0; b < 5; b++)
#pragma unroll
        for (int s = 0; s < 8; s++) vs[b][s] = LOOK1 ? ldp32(srcS + b * 768 + s * 7680) : 0;
    uint32_t cs2[8];
#pragma unroll
    for (int s = 0; s < 8; s++) cs2[s] = LOOK2 ? ldp32(gs + XS2 + (g * 8 + s) * 768 + min(tid, 191) * 4) : 0;
    __syncwarp();
    mbar_wait(sb + S_WFULL + 48 + 8 * (w >> 1), 0);
    {
        const uint32_t po = sb + ST_WO + (48 * w + 12 * t) * 160 + 4 * g8;
#pragma unroll
        for (int s = 0; s < 3; s++)
#pragma unroll
            for (int m = 0; m < 5; m++) frag(Wo[m][s], po + 4 * s * 160 + 32 * m, 160);
    }
    __syncwarp();
    if (lane == 0) mbar_arrive(sb + S_RELW + 16);
    if (ZPOS == 1) zero_words();
    if (tid < 192) {
        int guard = 0;
        while (((or3(chk8(vs[0], 1), chk8(vs[1], 1), chk8(vs[2], 1)) | chk8(vs[3], 1) | chk8(vs[4], 1)) & 1) && ++guard < SPIN_LIMIT) {
#pragma unroll
            for (int b = 0; b < 5; b++)
#pragma unroll
                for (int s = 0; s < 8; s++) vs[b][s] = ldp32(srcS + b * 768 + s * 7680);
        }
        const uint32_t qpos = sb + S_QS + q_pos(tid);
#pragma unroll
        for (int b = 0; b < 4; b++) {
            sts_hi16(qpos + 384 * b, bfr(sum8(vs[b])));
        }
        stsf(sb + S_CSQ + 4 * tid, sum8(vs[4]));
    }
    if (tid < 192) stsf(sb + S_CSGU + 4 * tid, (chk8(cs2, 1) & 1) ? gather8<768>(gs + XS2 + g * 8 * 768 + tid * 4, 1) : sum8(cs2));
    __syncwarp();
    bar_main();
    arrive_if(tid == 0, sb + S_QRDY);
    if (ZPOS == 2) zero_words();
    TSTAMP(2);

    uint32_t side;
    { int k = 0; while ((side = ldsvol(sb + S_SIDE)) == 0 && ++k < SPIN_LIMIT) {} }
    const uint32_t td = __shfl_sync(~0u, tid, lane);
    const uint32_t wp = __shfl_sync(~0u, tid >> 5, 0);
    const uint32_t cc = wp >= 3;
    auto uni = [](uint32_t v) { return __shfl_sync(~0u, v, 0); };
    auto pin = [&](uint32_t v) { return __shfl_sync(~0u, v, td); };
    auto nearp = [&](uint32_t P) { return gx.lo + P * 8192 + ((side ^ 1 ^ __popc(P & PMASK)) & 1) * COPY; };
    constexpr uint32_t COL = 32 * 8192;
    const uint32_t ownL = gx.lo + (i >> 2) * HALF + (i & 3) * 1024, ownG = gx.lo + (g >> 3) * HALF + (g & 7) * 512;
    const uint32_t uPubA = uni(ownL + pairL(RA, 0, g) * 8192 + (wp >> 1) * 256 + (wp & 1) * 96), uPolA = uni(nearp(pairL(RA, 0, g)) + (wp >> 2) * HALF + (wp & 3) * 256);
    const uint32_t uPubB = uni(ownG + pairG(0, cc, i) * 8192), uPolB = uni(nearp(pairG(0, cc, i)));
    const uint32_t uPubC = uni(ownL + pairL(RC, 0, g) * 8192), uPolC = uni(nearp(pairL(RC, wp < 6 ? cc : wp - 6, g)));
    const uint32_t uPubD = uni(ownG + pairG(1, 0, i) * 8192 + (wp < 7 ? 32 * wp : 256)), uPolD = uni(nearp(pairG(1, cc, i)));
    const uint32_t uPubE = uni(ownL + pairL(RE, 0, g) * 8192), uPolE = uni(nearp(pairL(RE, i >> 2, g)));
    const uint32_t uOS = uni(sb + S_OS + 192 * wp), uCol = uni(sb + 64 * cc);
    auto xp = [&](uint32_t lo) { return (char*)XPtr(lo, gx.hi); };
#define IDS() const uint32_t z_ = pin(td); const uint32_t ln = z_ & 31, q8 = ln >> 2, t4 = z_ & 3, n96 = z_ - 96 * cc, n80 = min(n96, 79u); (void)q8; (void)t4; (void)n80; (void)ln

    auto vaddr = [&](uint32_t (&voff)[3]) {
        const uint32_t ln = td & 31;
        const uint32_t key3 = 3 * ((ln & 7) + 2 * (ln & 8) + ((ln >> 1) & 8));
#pragma unroll
        for (int T = 0; T < 3; T++) {
            const uint32_t u = 3 * wp + T, r = key3 + (u >> 3);
            voff[T] = r * 128 + (((u ^ r) & 7) << 4);
        }
    };
    auto values = [&](uint32_t (&vf)[8][3][4], auto order, auto step, uint32_t ps, uint32_t col, uint32_t par) {
        const uint32_t ln = td & 31, q8 = ln >> 2, t4 = td & 3;
        const uint4 p = lds128(ps + 16 * ln);
        float acc[3][4] = {}, f0 = 0.f, f1 = 0.f, r3 = 0.f;
        int M = 0;
#pragma unroll
        for (int k = 0; k < 8; k++) {
            step(k);
            const int s = (order.value >> (4 * k)) & 7;
            const bool m = (q8 >> 1) == (s >> 1);
            const uint32_t b0 = m ? ((s & 1) ? p.z : p.x) : 0u, b1 = m ? ((s & 1) ? p.w : p.y) : 0u;
#pragma unroll
            for (int T = 0; T < 3; T++) mmaA(acc[T], vf[s][T], b0, b1);
            if (k == FSTEP) {
                const uint2 mp = lds64(ps + PS_MAX + 8 * t4);
                M = __reduce_max_sync(~0u, __float2int_ru(fmaxf(asf(mp.x), asf(mp.y))));
                f0 = ex2(asf(mp.x) - (float)M); f1 = ex2(asf(mp.y) - (float)M);
                float l[4] = {};
                mma16816(l, ONES, ONES, ONES, ONES, p.x, p.y); mma16816(l, ONES, ONES, ONES, ONES, p.z, p.w);
                r3 = fmaf(f0, l[0], f1 * l[1]);
            }
        }
        CSTAMP(25);
        char* pubA = xp(uPubA + col * COL + 32 * t4 + 4 * q8);
        const float r0 = fmaf(f0, acc[0][0], f1 * acc[0][3]), r1 = fmaf(f0, acc[1][0], f1 * acc[1][3]), r2 = fmaf(f0, acc[2][0], f1 * acc[2][3]);
        const bool hi = t4 & 2, od = t4 & 1;
        const float u0 = (hi ? r2 : r0) + __shfl_xor_sync(~0u, hi ? r0 : r2, 2), u1 = (hi ? r3 : r1) + __shfl_xor_sync(~0u, hi ? r1 : r3, 2);
        const float o = (od ? u1 : u0) + __shfl_xor_sync(~0u, od ? u0 : u1, 1);
        stp32_if(t4 < 3 || ((wp & 1) && q8 < 2), pubA, ln == 3 ? __int_as_float(2 * M) : o, par);
    };

#pragma unroll 1
    for (int ch = 0; ch < 5; ch++) {
        const uint32_t par0 = (ch + 1) & 1, par1 = ch & 1;
        uint32_t voff[3], vf[8][3][4];
        CSTAMP(0);
        if (ch < 4) {
            vaddr(voff);
            mbar_wait(sb + S_SCO, par1);
            if (ch == 0) mbar_wait(sb + S_WFULL + 80, 0);
            TST(0);
            auto ldw = [&](int s) {
                mbar_wait(sb + S_FV + 8 * s, par1);
#pragma unroll
                for (int T = 0; T < 3; T++) ldsm4t(vf[s][T], voff[T] + (sb + v_place(ch, s) * SLOT));
            };
            probs(bf_lo(lds16(sb + S_SC + 2 * td)), sb + S_PS, wp, td & 31);
            ldw(0); ldw(1); ldw(2);
            bar_main();
            arrive_if(td == 0, sb + S_RELR);
            values(vf, std::integral_constant<uint32_t, 0x76543210>(), [&](int s) {
                if (s >= 3) ldw(s);
            }, sb + S_PS, 0, par0);
            TST(1);
            CSTAMP(5);
            if (ch > 0) mbar_wait(sb + S_OS1, par0);
        } else {
#pragma unroll
            for (int s = 0; s < 36; s++) { vf[s / 12][(s / 4) % 3][s & 3] = 0; opaque(vf[s / 12][(s / 4) % 3][s & 3]); }
        }
        const bool has0 = ch < 4, has1 = ch > 0;
        const bool actc = wp < 6 && (cc ? has1 : has0);
        const uint32_t parc = cc ? par1 : par0;
        const uint32_t pub0 = has0 ? par0 : 0;
        uint32_t n4;
        {
            IDS();
            const uint32_t c = ch == 4;
            const uint32_t osa = pin(uOS + 96 * c + 4 * ln), oa = pin(uOS + 96 * (q8 & 1) + 24 * t4), ra = pin(sb + S_RED + 640 * wp + 320 * (t4 & 1) + 8 * q8);
            n4 = pin(4 * n80);
            hop_a<1>(xp(uPolA + c * COL + 8 * min(ln, 24u) + lag<DELAY_L>(sb)), pub0, osa, ln < 24, 5 * ch);
            TST(2);
            CSTAMP(6);
            float acc[5][4] = {};
            const uint2 b0 = lds64(oa), b1 = lds64(oa + 8), b2 = lds64(oa + 16);
#pragma unroll
            for (int m = 0; m < 5; m++) mmaA(acc[m], Wo[m][0], b0.x, b0.y);
#pragma unroll
            for (int m = 0; m < 5; m++) mmaA(acc[m], Wo[m][1], b1.x, b1.y);
#pragma unroll
            for (int m = 0; m < 5; m++) mmaA(acc[m], Wo[m][2], b2.x, b2.y);
#pragma unroll
            for (int m = 0; m < 5; m++) sts64_if(!(td & 2), ra + 64 * m, (td & 1) ? acc[m][1] : acc[m][0], (td & 1) ? acc[m][3] : acc[m][2]);
        }
        CSTAMP(7);
        uint32_t xr, fl, pubC, pubC2;
        auto prepC = [&] {
            IDS();
            xr = pin(sb + S_XB + 48 * (ln & 15));
            pubC = pin(uPubC + (t4 & 1) * COL + 192 * (wp >> 1) + 64 * (wp & 1) + 8 * q8);
            pubC2 = pin(uPubC + (t4 & 1) * COL + ((t4 & 2) ? 192 * (wp >> 1) + 128 + 4 * (wp & 1) + 8 * q8 : 768 + 2 * ((q8 + 1) & 6)));
            fl = pin(((t4 & 1) ? par1 : pub0) | (t4 >= 2 || (wp == 7 && q8 < 4 && q8 != 2 - t4) ? 2 : 0));
        };
        if (actc) {
            bar_main();
            CSTAMP(8);
            uint32_t r[8];
#pragma unroll
            for (int s = 0; s < 8; s++) r[s] = lds32(n4 + (5 * uCol - 4 * sb + S_RED + 640 * s));
            stp32_if(true, xp(uPubB + n4), sum8(r), parc);
            CSTAMP(9);
            prepC();
            const uint32_t xas = pin(3 * uCol - 2 * sb + S_XA + 192 + a_pos(n4 / 4)), xbs = pin(6 * uCol - 5 * sb + S_XB + b_pos<40>(n4 / 4));
            const float x0 = cc ? ldsf(sb + S_XCAR + n4) : bf_lo(lds16(sb + S_X0 + 160 * (ch & 3) + n4 / 2));
            gather16(xp(uPolB + n4 + lag<DELAY_G>(sb)), parc, 5 * ch + 1, [&](float y, uint32_t) {
                const uint32_t x = pack2(x0 + bfr(y), 0.f);
                sts16(xbs, x);
                sts16(xas, x);
                return 0u;
            });
            CSTAMP(10);
        } else {
            bar_main();
            prepC();
        }
        auto stats = [&](uint32_t xa, const uint4& b, uint32_t b4) {
            float a[4] = {};
            const uint4 p0 = lds128(xa), p1 = lds128(xa + 16);
            const uint2 p2 = lds64(xa + 32);
            mmaV(a, p0, b.x, b.y); mmaV(a, p1, b.z, b.w); mma8(a, p2.x, p2.y, b4);
            return a[0] + a[3];
        };
        {
            auto gate_up = [&](auto with_stats) {
                bar_main();
                TST(3);
                CSTAMP(11);
                const uint4 b = lds128(xr);
                const uint32_t b4 = lds32(xr + 16);
                float acc[3][4] = {}, st = 0.f;
                if (with_stats.value) st = stats(xr + (S_XA - S_XB), b, b4);
                mul80(acc, Wgu, b, b4);
                stp64_if(!(td & 2), xp(pubC), tagw(acc[0][0] + acc[0][3], fl & 1), tagw(acc[1][0] + acc[1][3], fl & 1));
                stp32_if(fl > 1, xp(pubC2), !with_stats.value || (td & 2) ? acc[2][0] + acc[2][3] : st, fl & 1);
            };
            if (wp == 7) gate_up(std::true_type()); else gate_up(std::false_type());
        }
        CSTAMP(12);
        float mean = 0.f, den = 1.f;
        {
            IDS();
            const uint32_t wh = pin((((ln & 7) + 48 * ((ln >> 3) & 1) + 8 * (ln >> 4)) * 160 + (wp < 7 ? 16 * wp : 128)) | ((384 * cc + b_pos<48>(n96)) << 16));
            const uint32_t pubD = pin(uPubD + (t4 & 1) * COL + 16 * (t4 & 2) + 4 * q8 + (fl & 1)), ha = xr + (S_HS - S_XB);
            auto down = [&](const uint32_t (&W)[3][4], const uint4& h0, const uint2& h1) {
                float a0[4] = {}, a1[4] = {}, a2[4] = {};
                mmaA(a0, W[0], h0.x, h0.y); mmaA(a1, W[1], h0.z, h0.w); mmaA(a2, W[2], h1.x, h1.y);
                return ((a0[0] + a0[3]) + (a1[0] + a1[3])) + (a2[0] + a2[3]);
            };
            if (wp < 6) {
                uint32_t Wd[3][4];
                auto ldd = [&](uint32_t z) {
#pragma unroll
                    for (int s = 0; s < 3; s++) ldsm4t(Wd[s], ((wh ^ z) & 0xffff) + (sb + S_WD + s * 2560));
                };
                if (actc) {
                    const uint32_t src0 = uPolC + lag<DELAY_C>(sb);
                    const char* srcv = xp(src0 + 8 * n96);
                    const char* src = xp(src0 + (ln & 1) * HALF);
                    float gt, up;
                    int guard = 0;
                    bool again;
                    do {
                        uint2 v[8], st[4];
#pragma unroll
                        for (int s = 0; s < 4; s++) st[s] = ldp64(src + 768 + s * 1024);
#pragma unroll
                        for (int s = 0; s < 8; s++) v[s] = ldp64(srcv + (s >> 2) * HALF + (s & 3) * 1024);
                        float sx = (asf(st[0].x) + asf(st[1].x)) + (asf(st[2].x) + asf(st[3].x)), sq = (asf(st[0].y) + asf(st[1].y)) + (asf(st[2].y) + asf(st[3].y));
                        sx += __shfl_xor_sync(~0u, sx, 1); sq += __shfl_xor_sync(~0u, sq, 1);
                        const uint32_t z = ((st[0].x ^ parc) & 1) * 16;
                        const uint2 cs = lds64(sb + S_CSGU - 768 * cc + 8 * td + z);
                        again = __any_sync(~0u, (or3(chk4(st, parc), chk8(v, parc), chk8y(v, parc)) & 1) != 0);
                        ln_stats(sx, sq, mean, den);
                        const float rd = rcp(den);
                        gt = fmaf(-mean, asf(cs.x), sum8x(v)); up = fmaf(-mean, asf(cs.y), sum8y(v));
                        ldd(z);
                        gt *= rd; up *= rd;
                        keep(gt); keep(up);
                    } while (again & (++guard < SPIN_LIMIT));
                    CSTAMP(13);
                    SWEEPS(5 * ch + 2, guard - 1);
                    gt = bfr(gt);
                    const uint32_t h = pack2(bfr(gt * sigmoidf_(gt)) * bfr(up), 0.f);
                    sts16((wh >> 16) + (sb + S_HS), h);
                    CSTAMP(14);
                } else ldd(0);
                bar_main();
                TST(4);
                CSTAMP(15);
                const uint4 h0 = lds128(ha);
                const uint2 h1 = lds64(ha + 16);
                stp32_if(!(td & 2), xp(pubD & ~1u), down(Wd, h0, h1), pubD & 1);
            } else {
                stsvol(sb + S_GATE, ch + 1);
                uint32_t Wd[2][3][4];
#pragma unroll
                for (int s = 0; s < 6; s++) ldsm4t(Wd[s / 3][s % 3], (wh & 0xffff) + (sb + S_WD + (s / 3) * 16 + (s % 3) * 2560));
                uint32_t v = 0;
                if (wp == 6 ? has0 : has1) {
                    const uint32_t par = wp == 6 ? par0 : par1;
                    const char* src = xp(uPolC + 768 + (ln & 4) * (HALF / 4) + (ln & 3) * 1024 + 4 * min(ln >> 3, 2u) + lag<DELAY_C>(sb));
                    int guard = 0;
                    do v = ldp32(src); while (__any_sync(~0u, (v ^ par) & 1) && ++guard < SPIN_LIMIT);
                }
                bar_main();
                const uint4 h0 = lds128(ha);
                const uint2 h1 = lds64(ha + 16);
                const float d0 = down(Wd[0], h0, h1), d1 = down(Wd[1], h0, h1);
                stp32_if(true, xp(pubD & ~1u), (td & 2) ? d1 : d0, pubD & 1);
                if (wp == 6 ? has0 : has1) {
                    float sx = asf(v);
                    sx += __shfl_xor_sync(~0u, sx, 1); sx += __shfl_xor_sync(~0u, sx, 2); sx += __shfl_xor_sync(~0u, sx, 4);
                    const float sq = __shfl_sync(~0u, sx, 8), xw = __shfl_sync(~0u, sx, 16);
                    ln_stats(sx, sq, mean, den);
                    const float r = bfr(fmaf(-mean, ldsf(sb + S_SWR), xw) * rcp(den));
                    sts32_if(ln == 0, sb + S_STAT + 4 * (wp - 6), __float_as_uint(bfr(sigmoidf_(r))) | (ch + 1));
                }
            }
        }
        CSTAMP(16);
        uint32_t pubE;
        float x1 = 0.f;
        {
            IDS();
            pubE = pin(uPubE + (t4 < 3 ? (wp >> 2) * COL + 192 * (wp & 3) + 64 * t4 + 8 * q8 : (q8 >> 2) * COL + 768 + 4 * (q8 & 1)));
            xr = pin(sb + S_XB + 48 * (ln & 7));
            if (actc && (cc == 0 || g == 0)) {
                const uint32_t m4 = 4 * n80;
                const uint32_t xas = pin(3 * uCol - 2 * sb + S_XA + 192 + a_pos(n80)), xbs = pin(6 * uCol - 5 * sb + S_XB + b_pos<40>(n80));
                x1 = bf_lo(lds16(xbs));
                const float lnx = __uint_as_float(pin(__float_as_uint(bfr(__fdiv_rn(bfr(x1 - mean), den)))));
                uint32_t x2;
                gather16(xp(uPolD + m4 + lag<DELAY_D>(sb)), parc, 5 * ch + 3, [&](float y, uint32_t z) {
                    const uint32_t gate = ldsvol(sb + S_STAT + 4 * cc + z);
                    x2 = pack2(x1 + bfr(lnx + bfr(bfr(y) * bf_hi(gate))), 0.f);
                    sts16(xbs, x2);
                    sts16(xas, x2);
                    return (uint32_t)((gate & 7) != ch + 1);
                });
                CSTAMP(17);
                if (cc) reinterpret_cast<unsigned short*>(P.out)[640 * (ch - 1) + 80 * i + n80] = (unsigned short)x2;
                x1 = bf_lo(x2);
            }
        }
        CSTAMP(18);
        if (!has0) break;
        {
            auto qproj = [&](auto with_stats) {
                bar_main();
                TST(5);
                CSTAMP(19);
                const uint32_t t4 = td & 3;
                const uint4 b = lds128(xr);
                const uint32_t b4 = lds32(xr + 16);
                float acc[6][4] = {}, st = 0.f;
                if (with_stats.value) st = stats(xr + (S_XA - S_XB), b, b4);
                mul80(acc, Wq, b, b4);
                const float v0 = sel4(t4, acc[0][0] + acc[0][3], acc[2][0] + acc[2][3], acc[4][0] + acc[4][3], acc[4][0] + acc[4][3]);
                const float v1 = sel4(t4, acc[1][0] + acc[1][3], acc[3][0] + acc[3][3], acc[5][0] + acc[5][3], acc[5][0] + acc[5][3]);
                if (with_stats.value) stp32_if((td & 11) == 3, xp(pubE), st, par0);
                stp64_if(t4 < 3, xp(pubE), tagw(v0, par0), tagw(v1, par0));
            };
            if (wp == 7) qproj(std::true_type()); else qproj(std::false_type());
            sts32_if(td < 80, sb + S_XCAR + 4 * td, __float_as_uint(x1));
        }
        CSTAMP(20);
        auto pass2 = [&](auto d0, auto d1, auto d2) {
            constexpr int D0 = d0.value, D1 = d1.value, D = D0 + D1 + d2.value;
            IDS();
            const uint32_t ua = sb + k_place(ch, wp & 6) * SLOT + (wp & 1) * UNIT, k0 = k_off(ln);
            uint32_t kf[12][2][4];
            auto ldk = [&](int s) { const uint32_t a = (k0 ^ (32 * (s / 3))) + (ua + 1024 * (s % 3)); ldsm4(kf[s][0], a); ldsm4(kf[s][1], a + SLOT); };
            auto ldv1 = [&](int k) { ldsm4t(vf[k / 3][k % 3], voff[k % 3] + (sb + v_place(ch, k / 3) * SLOT)); };
            auto ldv = [&](int s) { ldv1(3 * s); ldv1(3 * s + 1); ldv1(3 * s + 2); };
            constexpr uint32_t LATE = LAST_LATE;
            constexpr uint64_t EARLY_LIST = bit_list(~LATE), LATE_LIST = bit_list(LATE);
            auto early = [&](int k) {
                if (D1 == 0) ldk(k);
                else if (k < 3) { ldv1(9 + 2 * k); ldv1(10 + 2 * k); }
                else ldk((EARLY_LIST >> (4 * (k - 3))) & 15);
            };
            if (D1 > 0) vaddr(voff);
            if (!(mbar_try(sb + S_FK + 8 * (wp & 6), par1) & mbar_try(sb + S_FK + 8 * (wp | 1), par1))) { mbar_wait(sb + S_FK + 8 * (wp & 6), par1); mbar_wait(sb + S_FK + 8 * (wp | 1), par1); }
#pragma unroll
            for (int s = 0; s < D0; s++) early(s);
            if (wp < 6) {
                const uint32_t qsa = pin(sb + S_QS + 384 * ch + q_pos(td));
                const uint32_t src0 = uPolE + lag<(D1 > 0 ? 0 : DELAY_E)>(sb);
                const char* srcv = xp(src0 + 4 * td);
                const char* src = xp(src0 + (ln & 1) * HALF);
                uint32_t v[8]; uint2 st[4];
                auto look = [&] {
#pragma unroll
                    for (int s = 0; s < 4; s++) st[s] = ldp64(src + 768 + s * 1024);
#pragma unroll
                    for (int s = 0; s < 8; s++) v[s] = ldp32(srcv + (s >> 2) * HALF + (s & 3) * 1024);
                };
                if (D1 > 0) {
                    look();
                    __syncwarp();
#pragma unroll
                    for (int s = D0; s < D0 + D1; s++) early(s);
                }
                int guard = 0;
                while (true) {
                    if (D1 == 0) look();
                    float sx = (asf(st[0].x) + asf(st[1].x)) + (asf(st[2].x) + asf(st[3].x)), sq = (asf(st[0].y) + asf(st[1].y)) + (asf(st[2].y) + asf(st[3].y));
                    sx += __shfl_xor_sync(~0u, sx, 1); sq += __shfl_xor_sync(~0u, sq, 1);
                    const float cs = ldsf(sb + S_CSQ + 4 * td + ((st[0].x ^ par0) & 1) * 4);
                    const bool again = __any_sync(~0u, ((chk8(v, par0) | chk4(st, par0)) & 1) != 0);
                    ln_stats(sx, sq, mean, den);
                    const uint32_t q = pack2(fmaf(-mean, cs, sum8(v)) * rcp(den), 0.f);
                    sts16(qsa, q);
                    if (!(again & (++guard < SPIN_LIMIT))) break;
                    if (D1 > 0) look();
                }
                SWEEPS(5 * ch + 4, guard - 1);
                CSTAMP(22);
            } else {
#pragma unroll
                for (int s = D0; s < D0 + D1; s++) early(s);
            }
#pragma unroll
            for (int s = D0 + D1; s < D; s++) early(s);
            bar_main();
            TST(6);
            CSTAMP(1);
            uint2 q = lds64(sb + S_QS + 384 * ch + 8 * ln);
            float acc[2][4] = {};
            constexpr int V0 = 13 - D, NV = D1 > 0 ? 2 : (2 * (D - 1)) / 3;
            static_assert(D1 == 0 || LAST0 == 0 || D - 3 + __builtin_popcount(LATE) == 12, "plan");
#pragma unroll
            for (int s = 0; s < 12; s++) {
                const bool m = q8 == (s & 7);
                const uint32_t b0 = m ? q.x : 0u, b1 = m ? q.y : 0u;
                if (s == 7) q = lds64(sb + S_QS + 384 * ch + 8 * ln + 256);
                mmaA(acc[0], kf[s][0], b0, b1);
                mmaA(acc[1], kf[s][1], b0, b1);
                if (D1 > 0) {
                    if (s >= 1 && s <= __builtin_popcount(LATE)) ldk((LATE_LIST >> (4 * (s - 1))) & 15);
                } else {
                    if (s >= 1 && s + D - 1 < 12) ldk(s + D - 1);
                    if (s >= 1 && s + D - 1 == 11) { __syncwarp(); arrive_if(ln == 0, sb + S_RELK); }
                    if (s == V0) vaddr(voff);
                    if (s >= V0 && 2 * (s - V0) < 3 * NV) ldv1(9 + 2 * (s - V0));
                    if (s >= V0 && 2 * (s - V0) + 1 < 3 * NV) ldv1(10 + 2 * (s - V0));
                }
            }
            CSTAMP(24);
            {
                const float v0 = acc[0][0] + acc[0][1], v1 = acc[0][2] + acc[0][3], v2 = acc[1][0] + acc[1][1], v3 = acc[1][2] + acc[1][3];
                const bool hi = t4 & 2, od = t4 & 1;
                const float u0 = (hi ? v2 : v0) + __shfl_xor_sync(~0u, hi ? v0 : v2, 2), u1 = (hi ? v3 : v1) + __shfl_xor_sync(~0u, hi ? v1 : v3, 2);
                const float s = (od ? u1 : u0) + __shfl_xor_sync(~0u, od ? u0 : u1, 1);
                CSTAMP(2);
                probs(scaled(s), sb + S_PS + PS_PASS, wp, ln);
                CSTAMP(3);
            }
            bar_main();
            TST(10);
            CSTAMP(4);
            if (D1 > 0) values(vf, std::integral_constant<uint32_t, ORDER_L>(), [&](int s) { if (s < 3) ldv(s + 5); }, sb + S_PS + PS_PASS, 1, par0);
            else values(vf, std::integral_constant<uint32_t, (NV > 1 ? ORDER_R : 0x76543210)>(),
                        [&](int s) { if (s >= (NV > 1 ? 2 : 1) && s + NV + (NV > 1 ? 1 : 2) < 8) ldv(s + NV + (NV > 1 ? 1 : 2)); }, sb + S_PS + PS_PASS, 1, par0);
            arrive_if(ln == 0, sb + S_RELV);
        };
        if (LAST0 > 0 && ch == 3) {
            pass2(std::integral_constant<int, LAST0>(), std::integral_constant<int, LAST1>(), std::integral_constant<int, LAST2>());
#pragma unroll
            for (int m = 0; m < 60; m++) { uint32_t& r = m % 10 < 8 ? Wq[m / 10].a[(m % 10) / 4][m % 2 + 2 * ((m % 10) / 2 % 2)] : Wq[m / 10].c[m % 2]; r = 0; opaque(r); }
        } else pass2(std::integral_constant<int, KPRE>(), std::integral_constant<int, 0>(), std::integral_constant<int, KPRE2>());
        TST(11);
        CSTAMP(23);
    }
    sts32_if(td == 255, sb + S_GATE, 6);
    TSTAMP(3);
}

typedef CUresult (*EncodeFn)(CUtensorMap*, CUtensorMapDataType, cuuint32_t, void*, const cuuint64_t*, const cuuint64_t*, const cuuint32_t*,
                             const cuuint32_t*, CUtensorMapInterleave, CUtensorMapSwizzle, CUtensorMapL2promotion, CUtensorMapFloatOOBfill);

void make_map(EncodeFn enc, CUtensorMap* m, const void* base, uint64_t cols, uint64_t rows, uint32_t box_cols, uint32_t box_rows, bool swizzle) {
    cuuint64_t dims[2] = {cols, rows};
    cuuint64_t strides[1] = {cols * 2};
    cuuint32_t box[2] = {box_cols, box_rows};
    cuuint32_t es[2] = {1, 1};
    enc(m, CU_TENSOR_MAP_DATA_TYPE_BFLOAT16, 2, const_cast<void*>(base), dims, strides, box, es, CU_TENSOR_MAP_INTERLEAVE_NONE,
        swizzle ? CU_TENSOR_MAP_SWIZZLE_128B : CU_TENSOR_MAP_SWIZZLE_NONE, swizzle ? CU_TENSOR_MAP_L2_PROMOTION_NONE : WPROMO, CU_TENSOR_MAP_FLOAT_OOB_FILL_NONE);
}

}

extern "C" void kernel_launch(void* const* d_in, const int* in_sizes, int n_in, void* d_out, int out_size) {
    (void)in_sizes; (void)n_in; (void)out_size;
    static EncodeFn enc = nullptr;
    if (!enc) {
        void* f = nullptr;
        cudaDriverEntryPointQueryResult q;
        cudaGetDriverEntryPoint("cuTensorMapEncodeTiled", &f, cudaEnableDefault, &q);
        enc = (EncodeFn)f;
        cudaFuncSetAttribute(fused_kernel, cudaFuncAttributeMaxDynamicSharedMemorySize, SMEM_BYTES);
    }
    Params P;
    P.x = (const __nv_bfloat16*)d_in[0]; P.k = (const __nv_bfloat16*)d_in[1]; P.v = (const __nv_bfloat16*)d_in[2];
    P.wr = (const __nv_bfloat16*)d_in[6];
    P.out = (__nv_bfloat16*)d_out;
    Maps M;
    {
        cuuint64_t dims[4] = {64, 8, 3, (cuuint64_t)KV_BATCH_KEYS / 2}, strides[3] = {384, 128, 3072};
        cuuint32_t box[4] = {64, 8, 3, 2}, es[4] = {1, 1, 1, 1};
        enc(&M.k, CU_TENSOR_MAP_DATA_TYPE_BFLOAT16, 4, d_in[1], dims, strides, box, es, CU_TENSOR_MAP_INTERLEAVE_NONE, CU_TENSOR_MAP_SWIZZLE_128B,
            CU_TENSOR_MAP_L2_PROMOTION_NONE, CU_TENSOR_MAP_FLOAT_OOB_FILL_NONE);
    }
    make_map(enc, &M.v, P.v, 64, (uint64_t)12 * KV_BATCH_KEYS, 64, 96, true);
    make_map(enc, &M.vu, P.v, 64, (uint64_t)12 * KV_BATCH_KEYS, 64, 48, true);
    make_map(enc, &M.wq, d_in[3], 6144, 640, 192, 40, false);
    make_map(enc, &M.wo, d_in[4], 640, 6144, 80, 96, false);
    make_map(enc, &M.wg, d_in[7], 1536, 640, 96, 80, false);
    make_map(enc, &M.wu, d_in[8], 1536, 640, 96, 80, false);
    make_map(enc, &M.wd, d_in[9], 640, 1536, 80, 96, false);
    fused_kernel<<<NCTA, NTHR, SMEM_BYTES, cudaStreamPerThread>>>(P, M);
}
```

```cpp
#include <cuda_runtime.h>
#include <cuda.h>
#include <cuda_bf16.h>
#include <stdint.h>
#include <type_traits>

namespace {

constexpr int NCTA = 128;
constexpr int NTHR = 384;
constexpr int UNIT = 6144;
constexpr int SLOT = 12288;
#define TAU 4000
#define TAUW 3850
#define TAU0 3850
#define PF0 2
#define PFMAP 1
#define ZPOS 1
#define LOOK1 0
#define LOOK2 0
#define SLACK 4000
#define SLACK0 2000
#define TSH 0
#define HOP1_NS 200
#define RELR_AT 0
#define PSLEEP 0
#define KRE_EARLY 6
#define PFTOP 2
#define RFR_XS 2
#define TMIN 2400
#define T_LEAD 0
#define WIN_W 3
#define WIN_S 4
#define WIN_U 10
#define RFR_ON 1
#define KRE_N1 0
#define KRE_TAU1 2500
#define RFR_TAU 25600
#define VPF 4
#define KRE_GATE 0
#define KRE_GATE3 KRE_GATE
#define JFREE 16
#define TFREE 0
#define KRE_TAU 3000
#define KRE_TAU3 KRE_TAU
#define HDEPTH 3
#define LAST0 3
#define ORDER_L 0x76543210
#define ORDER_R 0x76543210
#define LAST_LATE 0xaa8
#define LAST1 4
#define LAST2 3
#define FSTEP 4
#define SPEC 1
#define PV1PIPE 0
#define HOPA0 6
#define HOPA1 6
#define WPROMO CU_TENSOR_MAP_L2_PROMOTION_NONE
#define KPRE 1
#define KPRE2 3
#define DELAY_G 3
#define DELAY_L 5
#define DELAY_C 3
#define DELAY_D 1
#define DELAY_E 3
#define REG_LO "40"
#define REG_HI "232"
#define SPIN_LOG 17
constexpr int SPIN_LIMIT = 1 << SPIN_LOG;

__host__ __device__ constexpr uint32_t pairL(uint32_t region, uint32_t c, uint32_t g) { return (g & 1) | ((g >> 1) << 2) | (c << 5) | (region << 6); }
__host__ __device__ constexpr uint32_t pairG(uint32_t d, uint32_t c, uint32_t i) { return (i & 1) | ((i >> 1) << 2) | (d << 4) | (c << 5) | (3u << 6); }
constexpr uint32_t RA = 0, RC = 1, RE = 2, HALF = 16384, COPY = 4096, PMASK = 0x59;
constexpr uint32_t XS = 0;
constexpr uint32_t XS2 = XS + 128 * 7680;
constexpr uint32_t XSEND = XS2 + 128 * 768;
__device__ uint4 g_s[XSEND / 16];
__device__ uint4 g_x[(4u << 20) / 16];
#define SWEEPS(k, n) do {} while (0)

constexpr uint32_t S_WD = 16 * SLOT;
constexpr uint32_t S_DUMMY = S_WD + 15360;
constexpr uint32_t S_BAR = S_DUMMY + 4096;
constexpr uint32_t S_FV = S_BAR, S_FK = S_FV + 64, S_RING = S_FK + 64, S_DBAR = S_RING + 48, S_WFULL = S_DBAR + 32, S_QRDY = S_WFULL + 88;
constexpr uint32_t S_RELK = S_QRDY + 8, S_RELV = S_RELK + 8, S_RELR = S_RELV + 8, S_RELW = S_RELR + 8, S_SCO = S_RELW + 24;
constexpr uint32_t S_OS1 = S_SCO + 8;
constexpr uint32_t S_ZERO = S_OS1 + 8;
constexpr uint32_t S_KF = S_ZERO + 8;
constexpr uint32_t S_TOK = S_KF + 8;
constexpr uint32_t S_SIDE = S_TOK + 80, S_GATE = S_SIDE + 4;
constexpr uint32_t S_STAT = S_GATE + 12, S_SWR = S_STAT + 16;
constexpr uint32_t S_XCAR = S_STAT + 32;
constexpr uint32_t S_CSQ = S_XCAR + 320;
constexpr uint32_t S_CSGU = S_CSQ + 768;
constexpr uint32_t S_RED = S_CSGU + 768;
constexpr uint32_t S_L0 = S_RED;
constexpr uint32_t S_OS = S_RED + 5120;
constexpr uint32_t S_PS = S_OS + 1536;
constexpr uint32_t PS_MAX = 512, PS_PASS = 544;
constexpr uint32_t S_QS = S_PS + 2 * PS_PASS;
constexpr uint32_t S_XB = S_QS + 1536;
constexpr uint32_t S_XA = S_XB + 768;
constexpr uint32_t S_HS = S_XA + 768;
constexpr uint32_t S_X0 = S_HS + 768;
constexpr uint32_t S_SC = S_X0 + 640;
constexpr uint32_t S_TM = S_SC + 512;
constexpr int SMEM_BYTES = S_TM + 256;
static_assert(SMEM_BYTES <= 232448 && S_STAT % 16 == 0 && S_RED % 16 == 0 && S_XB % 16 == 0 && S_HS % 16 == 0 && S_PS % 16 == 0 && S_QS % 16 == 0, "smem");
static_assert(S_SCO == S_BAR + 44 * 8 && S_RELK == S_BAR + 38 * 8, "barriers");
constexpr uint32_t ST_WQ = 3 * SLOT, ST_WG = 8 * SLOT, ST_WO = 11 * SLOT;

__device__ __forceinline__ uint32_t smem_u32(const void* p) { return (uint32_t)__cvta_generic_to_shared(p); }
__device__ __forceinline__ void mbar_init(uint32_t bar, uint32_t cnt) { asm volatile("mbarrier.init.shared::cta.b64 [%0], %1;" :: "r"(bar), "r"(cnt) : "memory"); }
__device__ __forceinline__ void mbar_expect(uint32_t bar, uint32_t bytes) { asm volatile("mbarrier.arrive.expect_tx.shared::cta.b64 _, [%0], %1;" :: "r"(bar), "r"(bytes) : "memory"); }
__device__ __forceinline__ void mbar_arrive(uint32_t bar) { asm volatile("mbarrier.arrive.shared::cta.b64 _, [%0];" :: "r"(bar) : "memory"); }
__device__ __forceinline__ bool mbar_try(uint32_t bar, uint32_t parity) {
    uint32_t ok;
    asm volatile("{\n .reg .pred p;\n mbarrier.try_wait.parity.shared::cta.b64 p, [%1], %2;\n selp.u32 %0, 1, 0, p;\n}" : "=r"(ok) : "r"(bar), "r"(parity) : "memory");
    return ok != 0;
}
__device__ __forceinline__ bool mbar_test(uint32_t bar, uint32_t parity) {
    uint32_t ok;
    asm volatile("{\n .reg .pred p;\n mbarrier.test_wait.parity.shared::cta.b64 p, [%1], %2;\n selp.u32 %0, 1, 0, p;\n}" : "=r"(ok) : "r"(bar), "r"(parity) : "memory");
    return ok != 0;
}
__device__ __forceinline__ void mbar_wait(uint32_t bar, uint32_t parity) {
    int n = 0;
    while (!mbar_try(bar, parity) && ++n < SPIN_LIMIT) {}
}
__device__ __forceinline__ unsigned long long gtime() { unsigned long long t; asm volatile("mov.u64 %0, %globaltimer;" : "=l"(t)); return t; }
__device__ __forceinline__ uint32_t gtime32() { uint32_t t; asm volatile("mov.u32 %0, %globaltimer_lo;" : "=r"(t)); return t; }
__device__ __forceinline__ void bar_main() { asm volatile("bar.sync 1, 256;" ::: "memory"); }

__device__ __forceinline__ void mma16816(float (&c)[4], uint32_t a0, uint32_t a1, uint32_t a2, uint32_t a3, uint32_t b0, uint32_t b1) {
    asm("mma.sync.aligned.m16n8k16.row.col.f32.bf16.bf16.f32 {%0,%1,%2,%3}, {%4,%5,%6,%7}, {%8,%9}, {%0,%1,%2,%3};"
        : "+f"(c[0]), "+f"(c[1]), "+f"(c[2]), "+f"(c[3]) : "r"(a0), "r"(a1), "r"(a2), "r"(a3), "r"(b0), "r"(b1));
}
__device__ __forceinline__ void mmaA(float (&c)[4], const uint32_t (&a)[4], uint32_t b0, uint32_t b1) { mma16816(c, a[0], a[1], a[2], a[3], b0, b1); }
__device__ __forceinline__ void mmaAv(float (&c)[4], const uint32_t (&a)[4], uint32_t b0, uint32_t b1) {
    asm volatile("mma.sync.aligned.m16n8k16.row.col.f32.bf16.bf16.f32 {%0,%1,%2,%3}, {%4,%5,%6,%7}, {%8,%9}, {%0,%1,%2,%3};"
        : "+f"(c[0]), "+f"(c[1]), "+f"(c[2]), "+f"(c[3]) : "r"(a[0]), "r"(a[1]), "r"(a[2]), "r"(a[3]), "r"(b0), "r"(b1) : "memory");
}
__device__ __forceinline__ void mma8(float (&c)[4], uint32_t a0, uint32_t a1, uint32_t b0) {
    asm("mma.sync.aligned.m16n8k8.row.col.f32.bf16.bf16.f32 {%0,%1,%2,%3}, {%4,%5}, {%6}, {%0,%1,%2,%3};"
        : "+f"(c[0]), "+f"(c[1]), "+f"(c[2]), "+f"(c[3]) : "r"(a0), "r"(a1), "r"(b0));
}
struct W80 { uint32_t a[2][4], c[2]; };
template <int N> __device__ __forceinline__ void mul80(float (&acc)[N][4], const W80 (&W)[N], const uint4& b, uint32_t b4) {
#pragma unroll
    for (int m = 0; m < N; m++) mmaA(acc[m], W[m].a[0], b.x, b.y);
#pragma unroll
    for (int m = 0; m < N; m++) mmaA(acc[m], W[m].a[1], b.z, b.w);
#pragma unroll
    for (int m = 0; m < N; m++) mma8(acc[m], W[m].c[0], W[m].c[1], b4);
}
__device__ __forceinline__ void ldsm2t(uint32_t (&r)[2], uint32_t addr) {
    asm volatile("ldmatrix.sync.aligned.m8n8.x2.trans.shared.b16 {%0,%1}, [%2];" : "=r"(r[0]), "=r"(r[1]) : "r"(addr) : "memory");
}
__device__ __forceinline__ void mmaV(float (&c)[4], const uint4& a, uint32_t b0, uint32_t b1) { mma16816(c, a.x, a.y, a.z, a.w, b0, b1); }
__device__ __forceinline__ void ldsm4(uint32_t (&r)[4], uint32_t addr) {
    asm volatile("ldmatrix.sync.aligned.m8n8.x4.shared.b16 {%0,%1,%2,%3}, [%4];" : "=r"(r[0]), "=r"(r[1]), "=r"(r[2]), "=r"(r[3]) : "r"(addr) : "memory");
}
__device__ __forceinline__ void ldsm4t(uint32_t (&r)[4], uint32_t addr) {
    asm volatile("ldmatrix.sync.aligned.m8n8.x4.trans.shared.b16 {%0,%1,%2,%3}, [%4];" : "=r"(r[0]), "=r"(r[1]), "=r"(r[2]), "=r"(r[3]) : "r"(addr) : "memory");
}
__device__ __forceinline__ uint32_t lds16(uint32_t a) { uint16_t v; asm volatile("ld.shared.u16 %0, [%1];" : "=h"(v) : "r"(a) : "memory"); return v; }
__device__ __forceinline__ uint32_t lds32(uint32_t a) { uint32_t v; asm volatile("ld.shared.u32 %0, [%1];" : "=r"(v) : "r"(a) : "memory"); return v; }
__device__ __forceinline__ float ldsf(uint32_t a) { return __uint_as_float(lds32(a)); }
__device__ __forceinline__ uint2 lds64(uint32_t a) { uint2 v; asm volatile("ld.shared.v2.u32 {%0,%1}, [%2];" : "=r"(v.x), "=r"(v.y) : "r"(a) : "memory"); return v; }
__device__ __forceinline__ uint4 lds128(uint32_t a) { uint4 v; asm volatile("ld.shared.v4.u32 {%0,%1,%2,%3}, [%4];" : "=r"(v.x), "=r"(v.y), "=r"(v.z), "=r"(v.w) : "r"(a) : "memory"); return v; }
__device__ __forceinline__ int ldsvol(uint32_t a) { int v; asm volatile("ld.volatile.shared.u32 %0, [%1];" : "=r"(v) : "r"(a) : "memory"); return v; }
__device__ __forceinline__ void stsvol(uint32_t a, int v) { asm volatile("st.volatile.shared.u32 [%0], %1;" :: "r"(a), "r"(v) : "memory"); }
__device__ __forceinline__ void sts_hi16(uint32_t a, float v) { asm volatile("{\n .reg .b16 lo, hi;\n mov.b32 {lo, hi}, %1;\n st.shared.u16 [%0], hi;\n}" :: "r"(a), "r"(__float_as_uint(v)) : "memory"); }
__device__ __forceinline__ void sts16(uint32_t a, uint32_t v) { asm volatile("st.shared.u16 [%0], %1;" :: "r"(a), "r"(v) : "memory"); }
__device__ __forceinline__ void sts32(uint32_t a, uint32_t v) { asm volatile("st.shared.u32 [%0], %1;" :: "r"(a), "r"(v) : "memory"); }
__device__ __forceinline__ void stsf(uint32_t a, float v) { sts32(a, __float_as_uint(v)); }
__device__ __forceinline__ void sts64(uint32_t a, uint32_t x, uint32_t y) { asm volatile("st.shared.v2.u32 [%0], {%1,%2};" :: "r"(a), "r"(x), "r"(y) : "memory"); }

__device__ __forceinline__ void sts_hi16_if(bool p, uint32_t a, float v) {
    asm volatile("{\n .reg .pred p;\n .reg .b16 lo, hi;\n setp.ne.u32 p, %2, 0;\n mov.b32 {lo, hi}, %1;\n @p st.shared.u16 [%0], hi;\n}" :: "r"(a), "r"(__float_as_uint(v)), "r"((uint32_t)p) : "memory");
}
__device__ __forceinline__ void sts32_if(bool p, uint32_t a, uint32_t v) {
    asm volatile("{\n .reg .pred p;\n setp.ne.u32 p, %2, 0;\n @p st.shared.u32 [%0], %1;\n}" :: "r"(a), "r"(v), "r"((uint32_t)p) : "memory");
}
__device__ __forceinline__ void sts64_if(bool p, uint32_t a, float x, float y) {
    asm volatile("{\n .reg .pred p;\n setp.ne.u32 p, %3, 0;\n @p st.shared.v2.f32 [%0], {%1,%2};\n}" :: "r"(a), "f"(x), "f"(y), "r"((uint32_t)p) : "memory");
}
__device__ __forceinline__ void arrive_if(bool p, uint32_t bar) {
    asm volatile("{\n .reg .pred p;\n setp.ne.u32 p, %1, 0;\n @p mbarrier.arrive.shared::cta.b64 _, [%0];\n}" :: "r"(bar), "r"((uint32_t)p) : "memory");
}
__device__ __forceinline__ void opaque(uint32_t& v) { asm volatile("" : "+r"(v)); }
__device__ __forceinline__ void keep(uint32_t& v) { asm volatile("" : "+r"(v)); }
__device__ __forceinline__ void keep(float& v) { asm volatile("" : "+f"(v)); }
template <class T> __device__ __forceinline__ void keep(T*& v) { asm volatile("" : "+l"(v)); }

__device__ __forceinline__ uint32_t ldp32(const char* p) { uint32_t v; asm volatile("ld.relaxed.gpu.global.u32 %0, [%1];" : "=r"(v) : "l"(p) : "memory"); return v; }
__device__ __forceinline__ uint2 ldp64(const char* p) {
    uint2 v; asm volatile("{\n .reg .b64 d;\n ld.relaxed.gpu.global.b64 d, [%2];\n mov.b64 {%0,%1}, d;\n}" : "=r"(v.x), "=r"(v.y) : "l"(p) : "memory"); return v;
}
__device__ __forceinline__ uint32_t tagw(float f, uint32_t par) { return (__float_as_uint(f) & ~1u) | par; }
__device__ __forceinline__ void stp32(char* p, float a, uint32_t par) { asm volatile("st.relaxed.gpu.global.u32 [%0], %1;" :: "l"(p), "r"(tagw(a, par)) : "memory"); }
__device__ __forceinline__ void stp64(char* p, float a, float b, uint32_t par) {
    asm volatile("{\n .reg .b64 d;\n mov.b64 d, {%1,%2};\n st.relaxed.gpu.global.b64 [%0], d;\n}" :: "l"(p), "r"(tagw(a, par)), "r"(tagw(b, par)) : "memory");
}
__device__ __forceinline__ void stp32_if(bool p, char* d, float a, uint32_t par) {
    asm volatile("{\n .reg .pred p;\n setp.ne.u32 p, %2, 0;\n @p st.relaxed.gpu.global.u32 [%0], %1;\n @p st.relaxed.gpu.global.u32 [%0+4096], %1;\n}" :: "l"(d), "r"(tagw(a, par)), "r"((uint32_t)p) : "memory");
}
__device__ __forceinline__ void stp64_if(bool p, char* d, uint32_t lo, uint32_t hi) {
    asm volatile("{\n .reg .pred p;\n .reg .b64 d;\n setp.ne.u32 p, %3, 0;\n mov.b64 d, {%1,%2};\n @p st.relaxed.gpu.global.b64 [%0], d;\n @p st.relaxed.gpu.global.b64 [%0+4096], d;\n}" :: "l"(d), "r"(lo), "r"(hi), "r"((uint32_t)p) : "memory");
}
__device__ __forceinline__ uint32_t chk2(uint32_t a, uint32_t b, uint32_t par) { uint32_t r; asm("lop3.b32 %0, %1, %2, %3, 0x7E;" : "=r"(r) : "r"(a), "r"(b), "r"(par)); return r; }
__device__ __forceinline__ uint32_t or3(uint32_t a, uint32_t b, uint32_t c) { uint32_t r; asm("lop3.b32 %0, %1, %2, %3, 0xFE;" : "=r"(r) : "r"(a), "r"(b), "r"(c)); return r; }
__device__ __forceinline__ uint32_t chk8(const uint32_t (&v)[8], uint32_t par) { return or3(chk2(v[0], v[1], par), chk2(v[2], v[3], par), or3(chk2(v[4], v[5], par), chk2(v[6], v[7], par), 0)); }
__device__ __forceinline__ uint32_t chk8(const uint2 (&v)[8], uint32_t par) { return or3(chk2(v[0].x, v[1].x, par), chk2(v[2].x, v[3].x, par), or3(chk2(v[4].x, v[5].x, par), chk2(v[6].x, v[7].x, par), 0)); }
__device__ __forceinline__ uint32_t chk8y(const uint2 (&v)[8], uint32_t par) { return or3(chk2(v[0].y, v[1].y, par), chk2(v[2].y, v[3].y, par), or3(chk2(v[4].y, v[5].y, par), chk2(v[6].y, v[7].y, par), 0)); }
__device__ __forceinline__ uint32_t chk4(const uint2 (&v)[4], uint32_t par) { return or3(chk2(v[0].x, v[0].y, par), chk2(v[1].x, v[1].y, par), or3(chk2(v[2].x, v[2].y, par), chk2(v[3].x, v[3].y, par), 0)); }
__device__ __forceinline__ float asf(uint32_t v) { return __uint_as_float(v); }
__device__ __forceinline__ float sum8(const uint32_t (&v)[8]) { return ((asf(v[0]) + asf(v[1])) + (asf(v[2]) + asf(v[3]))) + ((asf(v[4]) + asf(v[5])) + (asf(v[6]) + asf(v[7]))); }
__device__ __forceinline__ float sum8x(const uint2 (&v)[8]) { return ((asf(v[0].x) + asf(v[1].x)) + (asf(v[2].x) + asf(v[3].x))) + ((asf(v[4].x) + asf(v[5].x)) + (asf(v[6].x) + asf(v[7].x))); }
__device__ __forceinline__ float sum8y(const uint2 (&v)[8]) { return ((asf(v[0].y) + asf(v[1].y)) + (asf(v[2].y) + asf(v[3].y))) + ((asf(v[4].y) + asf(v[5].y)) + (asf(v[6].y) + asf(v[7].y))); }

__device__ __forceinline__ uint32_t pack2(float lo, float hi) { uint32_t r; asm("cvt.rn.bf16x2.f32 %0, %1, %2;" : "=r"(r) : "f"(hi), "f"(lo)); return r; }
__device__ __forceinline__ float bfr(float x) { return __uint_as_float(pack2(0.0f, x)); }
__device__ __forceinline__ float ex2(float x) { float r; asm("ex2.approx.ftz.f32 %0, %1;" : "=f"(r) : "f"(x)); return r; }
__device__ __forceinline__ float rcp(float x) { float r; asm("rcp.approx.ftz.f32 %0, %1;" : "=f"(r) : "f"(x)); return r; }
__device__ __forceinline__ float sqrt_(float x) { float r; asm("sqrt.approx.ftz.f32 %0, %1;" : "=f"(r) : "f"(x)); return r; }
__device__ __forceinline__ float bf_lo(uint32_t v) { return __uint_as_float(v << 16); }
__device__ __forceinline__ float bf_hi(uint32_t v) { return __uint_as_float(v & 0xffff0000u); }
__device__ __forceinline__ float sel4(int k, float a, float b, float c, float d) { return (k & 2) ? ((k & 1) ? d : c) : ((k & 1) ? b : a); }
constexpr float LOG2E = 1.4426950408889634f;
constexpr uint32_t ONES = 0x3f803f80u;

__device__ __forceinline__ void ln_stats(float sum, float sq, float& mean, float& den) {
    const float m = sum * (1.0f / 640.0f);
    const float var = fmaxf(fmaf(sq, 1.0f / 640.0f, -m * m), 0.0f);
    mean = bfr(m);
    den = bfr(sqrt_(bfr(bfr(var) + 1e-5f)));
}
__device__ __forceinline__ float sigmoidf_(float x) { return rcp(1.0f + ex2(-x * LOG2E)); }

#define TSTAMP(k) do {} while (0)
#define TST(k) do {} while (0)

#define CSTAMP(k) do {} while (0)
template <int N> __device__ __forceinline__ uint32_t lag(uint32_t sb) {
    uint32_t z = 0;
#pragma unroll
    for (int k = 0; k < N; k++) z = ldsvol(sb + S_ZERO + z);
    return z;
}
__device__ __forceinline__ void warm_mma(uint32_t& a, uint32_t& b) {
    asm volatile("mma.sync.aligned.m16n8k8.row.col.f16.f16.f16.f16 {%0,%1}, {%0,%1}, {%0}, {%0,%1};" : "+r"(a), "+r"(b) :: "memory");
}
#define KWNS2 20
#define KWNS 200
template <int STRIDE>
__device__ __forceinline__ float gather8(const char* p, uint32_t par) {
    uint32_t v[8];
    int guard = 0;
    do {
#pragma unroll
        for (int s = 0; s < 8; s++) v[s] = ldp32(p + s * STRIDE);
    } while ((chk8(v, par) & 1) && ++guard < SPIN_LIMIT);
    return sum8(v);
}
template <class F>
__device__ __forceinline__ void gather16(const char* p, uint32_t par, int k, F use) {
    uint32_t v[8], u[8];
    int guard = 0;
    bool again;
    do {
#pragma unroll
        for (int s = 0; s < 8; s++) v[s] = ldp32(p + s * 512);
#pragma unroll
        for (int s = 0; s < 8; s++) u[s] = ldp32(p + HALF + s * 512);
        const uint32_t stale = use(sum8(v) + sum8(u), ((v[0] ^ par) & 1) * 8);
        again = __any_sync(~0u, (or3(chk8(v, par), chk8(u, par), stale) & 1) != 0);
    } while (again & (++guard < SPIN_LIMIT));
    SWEEPS(k, guard - 1);
}

struct Params {
    const __nv_bfloat16 *x, *k, *v, *wr;
    __nv_bfloat16* out;
};
struct Maps { CUtensorMap k, v, vu, wq, wo, wg, wu, wd; };

constexpr int KV_BATCH_KEYS = 32 * 4096;

__device__ __forceinline__ void tma2d(uint32_t dst, const CUtensorMap* m, int c0, int c1, uint32_t bar, uint32_t bytes, uint64_t pol) {
    asm volatile("{\n .reg .pred p;\n elect.sync _|p, 0xffffffff;\n"
                 " @p mbarrier.arrive.expect_tx.shared::cta.b64 _, [%2], %6;\n"
                 " @p cp.async.bulk.tensor.2d.shared::cluster.global.mbarrier::complete_tx::bytes.L2::cache_hint [%0], [%1, {%3, %4}], [%2], %5;\n}"
                 :: "r"(dst), "l"(m), "r"(bar), "r"(c0), "r"(c1), "l"(pol), "r"(bytes) : "memory");
}
__device__ __forceinline__ void scrap_copy(uint32_t dst, const char* src, uint32_t bar) {
    asm volatile("{\n .reg .pred p;\n elect.sync _|p, 0xffffffff;\n"
                 " @p mbarrier.arrive.expect_tx.shared::cta.b64 _, [%2], 12288;\n"
                 " @p cp.async.bulk.shared::cluster.global.mbarrier::complete_tx::bytes [%0], [%1], 4096, [%2];\n"
                 " @p cp.async.bulk.shared::cluster.global.mbarrier::complete_tx::bytes [%0], [%1+4096], 4096, [%2];\n"
                 " @p cp.async.bulk.shared::cluster.global.mbarrier::complete_tx::bytes [%0], [%1+8192], 4096, [%2];\n}"
                 :: "r"(dst), "l"(src), "r"(bar) : "memory");
}
__device__ __forceinline__ void prefetch_l2(const void* p, uint32_t bytes) {
    asm volatile("{\n .reg .pred p;\n elect.sync _|p, 0xffffffff;\n @p cp.async.bulk.prefetch.L2.global [%0], %1;\n}" :: "l"(p), "r"(bytes) : "memory");
}
__device__ __forceinline__ uint64_t pol_first() { uint64_t p; asm("createpolicy.fractional.L2::evict_first.b64 %0, 1.0;" : "=l"(p)); return p; }
__device__ __forceinline__ uint64_t pol_normal() { uint64_t p; asm("createpolicy.fractional.L2::evict_normal.b64 %0, 1.0;" : "=l"(p)); return p; }
__device__ __forceinline__ bool utest(uint32_t bar, uint32_t parity) { return __all_sync(~0u, mbar_test(bar, parity)); }
__device__ __forceinline__ void uwait(uint32_t bar, uint32_t parity) {
    int n = 0;
    while (!__all_sync(~0u, mbar_try(bar, parity)) && ++n < SPIN_LIMIT) {}
}
template <int A, int B, int CNT> __device__ __forceinline__ void init_bars(uint32_t sb) {
#pragma unroll 1
    for (int k = A; k < B; k++)
        asm volatile("{\n .reg .pred p;\n elect.sync _|p, 0xffffffff;\n @p mbarrier.init.shared::cta.b64 [%0], %1;\n}" :: "r"(sb + S_BAR + 8 * k), "n"(CNT) : "memory");
}
__device__ __forceinline__ int first_key() { return (blockIdx.x >> 2) * 4096 + 3072 + (blockIdx.x & 3) * 256; }
__device__ __forceinline__ void load_tile(const CUtensorMap* m, uint32_t dst, uint32_t bar, uint32_t bytes, int key, uint64_t pol) { tma2d(dst, m, 0, 3 * key, bar, bytes, pol); }
__device__ __forceinline__ const char* unit_ptr(const Params& P, int n) {
    return (const char*)((n & 16) ? P.v : P.k) + (size_t)(first_key() + (n >> 5) * KV_BATCH_KEYS + (n & 15) * 16) * 384;
}
#define LSTAMP(k) do {} while (0)

__device__ __forceinline__ uint32_t k_place(uint32_t b, uint32_t s) { return s + 3 + 5 * (b & 1); }
__device__ __forceinline__ uint32_t v_place(uint32_t b, uint32_t s) { return s < 3 ? s : s + 8 - 8 * (b & 1); }
__device__ __forceinline__ void k_load(const Maps& M, uint32_t dst, uint32_t bar, int key8, uint64_t pol) {
    asm volatile("{\n .reg .pred p;\n elect.sync _|p, 0xffffffff;\n"
                 " @p mbarrier.arrive.expect_tx.shared::cta.b64 _, [%2], 6144;\n"
                 " @p cp.async.bulk.tensor.4d.shared::cluster.global.mbarrier::complete_tx::bytes.L2::cache_hint [%0], [%1, {0, 0, 0, %3}], [%2], %4;\n}"
                 :: "r"(dst), "l"(&M.k), "r"(bar), "r"(key8), "l"(pol) : "memory");
}
__device__ __forceinline__ int unit_key8(uint32_t n) { return first_key() / 8 + (n >> 4) * (KV_BATCH_KEYS / 8) + 2 * (n & 15); }
__device__ __forceinline__ void ring_load(const Maps& M, uint32_t sb, uint32_t b, uint32_t u, uint32_t pos) {
    if (u < 16) k_load(M, sb + pos * UNIT, sb + S_RING + 8 * pos, unit_key8(16 * b + u), pol_normal());
    else load_tile(&M.vu, sb + pos * UNIT, sb + S_FV + 4 * (pos & 6), UNIT, first_key() + b * KV_BATCH_KEYS + 16 * pos, pol_first());
}
__device__ __forceinline__ uint32_t token(bool p, uint32_t a, uint32_t n) {
    uint32_t v;
    asm volatile("{\n .reg .pred p;\n setp.ne.u32 p, %2, 0;\n mov.u32 %0, 0;\n @p atom.shared.exch.b32 %0, [%1], %3;\n}" : "=r"(v) : "r"(a), "r"((uint32_t)p), "r"(n) : "memory");
    return v;
}
__device__ __forceinline__ void place_load(const Maps& M, uint32_t sb, uint32_t n) {
    k_load(M, sb + k_place(n >> 4, 0) * SLOT + (n & 15) * UNIT, sb + S_FK + 4 * (n & 14), unit_key8(n), pol_first());
}
__device__ __forceinline__ void v_load(const Maps& M, uint32_t sb, uint32_t b, uint32_t s) {
    load_tile(&M.v, sb + v_place(b, s) * SLOT, sb + S_FV + 8 * s, SLOT, first_key() + b * KV_BATCH_KEYS + 32 * s, pol_first());
}
__device__ __forceinline__ bool due(uint32_t t) { return __all_sync(~0u, (int)(gtime32() * 16 - t) >= 0); }
__device__ __forceinline__ bool reached(uint32_t a, int v) { return __all_sync(~0u, ldsvol(a) >= v); }

__device__ __forceinline__ void stream_warp(const Params& P, const Maps& M, uint32_t sb, uint32_t lane) {
    const uint64_t pol = pol_first();
    const int bid = blockIdx.x, g = bid >> 3, i = bid & 7;
    const uint32_t wf = sb + S_WFULL;
    if (PF0 > 0 && !PFTOP) prefetch_l2(unit_ptr(P, 0), PF0 * UNIT);
    uint32_t tn = __shfl_sync(~0u, gtime32(), 0) * 16 - T_LEAD;
    auto pace = [&](uint32_t dt) {
        int k = 0;
        uint32_t now;
        do now = __shfl_sync(~0u, gtime32(), 0) * 16; while ((int)(now - tn) < 0 && ++k < SPIN_LIMIT);
        if ((int)(now - tn) > SLACK0) tn = now - SLACK0;
        tn += dt;
    };
#pragma unroll
    for (int k = 0; k < 10; k++) {
        if (k < 2) {
            if (k == 0) init_bars<26, 27, 1>(sb); else init_bars<27, 37, 1>(sb);
            asm volatile("fence.mbarrier_init.release.cluster;" ::: "memory");
            if (k == 1) { asm volatile("bar.arrive 2, %0;" :: "n"(NTHR) : "memory"); asm volatile("bar.sync 3, 128;" ::: "memory"); }
        }
        if (k >= WIN_W) uwait(wf + 8 * (k - WIN_W), 0);
        pace(TAUW * 5 / 2);
        if (k < 4) tma2d(sb + ST_WQ + 15360 * k, &M.wq, 384 * g + 192 * (k >> 1), 80 * i + 40 * (k & 1), wf + 8 * k, 15360, pol);
        else if (k < 6) tma2d(sb + ST_WG + 15360 * (k - 4), k == 4 ? &M.wg : &M.wu, 96 * g, 80 * i, wf + 8 * k, 15360, pol);
        else tma2d(sb + ST_WO + 15360 * (k - 6), &M.wo, 80 * i, 384 * g + 96 * (k - 6), wf + 8 * k, 15360, pol);
    }
#pragma unroll 1
    for (int n = 0; n < 16; n++) {
        if (n == 0 || n == 5 || n == 11) uwait(sb + S_RELW + (n == 0 ? 0 : n == 5 ? 8 : 16), 0);
        uwait(n < WIN_S ? wf + 8 * (10 - WIN_S + n) : sb + S_FV + 8 * ((n - WIN_S) ^ 8), 0);
        pace(max(min(2 * n + 2 - PF0, 2), 0) * TAU0);
        if (n < 8) { place_load(M, sb, 2 * n); place_load(M, sb, 2 * n + 1); }
        else if (n < 11) { ring_load(M, sb, 0, 2 * n, 2 * n - 16); ring_load(M, sb, 0, 2 * n + 1, 2 * n - 15); }
        else v_load(M, sb, 0, n - 8);
        if (n == 7) { pace(TAUW * 5 / 2); tma2d(sb + S_WD, &M.wd, 80 * i, 96 * g, wf + 80, 15360, pol); }
    }
    int nd = 0;
    uint32_t q[4];
#pragma unroll
    for (int r = 0; r < 4; r++) q[r] = sb + S_FV + 8 * (7 - r);
    tn -= TSH;
    uint32_t td = tn;
    uint32_t pos = 2;
#pragma unroll 1
    for (int m = 16; m < 64; m++) {
        const int b = m >> 4, j = m & 15;
        const char* src = unit_ptr(P, 2 * m);
        const uint32_t tok = sb + S_TOK + (j < 3 ? 4 * pos : j < 11 ? 24 + 4 * pos : 16 + 4 * j) + 4 * lane;
        static_assert(WIN_U <= 12, "a ring position has at most one token of the timetable");
        int k = 0;
        while (true) {
            const uint2 c = lds64(sb + S_KF);
            if (__all_sync(~0u, mbar_test(q[WIN_S - 1] & ~1u, q[WIN_S - 1] & 1) & (min((int)c.x + 1, (int)c.y) >= 16 * b + min(2 * j + 2 - WIN_U, 16))) || ++k >= SPIN_LIMIT) break;
        }
        uint32_t now;
        while (true) {
            now = __shfl_sync(~0u, gtime32(), 0) * 16;
            if ((int)(now - td) >= 0 || ++k >= SPIN_LIMIT) break;
            if (PSLEEP > 0 && (int)(td - now) > 16 * PSLEEP * 2) __nanosleep(PSLEEP);
        }
        const uint32_t mine = __ballot_sync(~0u, token(lane < (j < 11 ? 2 : 1), tok, 2 * m + lane) == 2 * m + lane);
        q[3] = q[2]; q[2] = q[1]; q[1] = q[0]; q[0] = sb + S_QRDY;
        if (j < 11) {
            if (mine & 1) ring_load(M, sb, b, 2 * j, pos); else prefetch_l2(src, UNIT);
            if (mine & 2) ring_load(M, sb, b, 2 * j + 1, pos + 1); else prefetch_l2(src + UNIT, UNIT);
            if (j >= 8) q[0] = (sb + S_FV + 8 * (j - 8)) | (b & 1);
        } else if (mine) { v_load(M, sb, b, j - 8); q[0] = (sb + S_FV + 8 * (j - 8)) | (b & 1); }
        else if (j - 8 >= VPF) prefetch_l2(src, SLOT);
        else {
            scrap_copy(sb + S_DUMMY, src, sb + S_DBAR + 8 * (nd & 3));
            q[0] = (sb + S_DBAR + 8 * (nd & 3)) | ((nd >> 2) & 1);
            nd++;
        }
        pos = j == 15 ? 2 : pos == 4 ? 0 : pos + 2;
        if ((int)(now - tn) > SLACK) tn = now - SLACK;
        tn += 2 * TAU;
        td = (int)(tn - now) > 2 * TMIN ? tn : now + 2 * TMIN;
        if (m >= 48 + JFREE) td = now + TFREE;
    }
#pragma unroll 1
    for (int m = max(nd - 4, 0); m < nd; m++) uwait(sb + S_DBAR + 8 * (m & 3), (m >> 2) & 1);
}

__host__ __device__ constexpr uint64_t bit_list(uint32_t m) { uint64_t r = 0; int n = 0; for (int k = 0; k < 12; k++) if ((m >> k) & 1) r |= (uint64_t)k << (4 * n++); return r; }
__device__ __forceinline__ float scaled(float s) { return bfr(bfr(s) * 0.07216878364870322f); }
__device__ __forceinline__ void probs(float s, uint32_t ps, uint32_t src, uint32_t ln) {
    const uint32_t q8 = ln >> 2, t4 = ln & 3;
    int key = __float_as_int(s);
    key ^= (key >> 31) & 0x7fffffff;
    key = __reduce_max_sync(~0u, key);
    key ^= (key >> 31) & 0x7fffffff;
    const float ml = __int_as_float(key) * LOG2E;
    sts16(ps + 64 * src + (q8 >> 1) * 16 + t4 * 4 + (q8 & 1) * 2, pack2(ex2(fmaf(s, LOG2E, -ml)), 0.f));
    stsf(ps + PS_MAX + 4 * src, ml);
}
template <int H> __device__ __forceinline__ uint32_t b_pos(uint32_t e) { const uint32_t h = e >= H, k = e - H * h; return h * 192 + (k & 6) * 24 + (k >> 3) * 4 + (k & 1) * 2; }
__device__ __forceinline__ uint32_t a_pos(uint32_t e) { const uint32_t h = e >= 40, k = e - 40 * h; return (k & 6) * 24 + (k >> 3) * 8 + h * 4 + (k & 1) * 2; }
__device__ __forceinline__ uint32_t q_pos(uint32_t d) { const uint32_t s = 3 * ((d >> 4) & 3) + (d >> 6); return s * 32 + (d & 6) * 4 + ((d >> 3) & 1) * 4 + (d & 1) * 2; }
__device__ __forceinline__ uint32_t k_off(uint32_t ln) { return (ln & 8) * 384 + (ln & 7) * 128 + (((ln & 7) ^ (ln >> 4)) << 4); }

#define HSTAMP(k) do {} while (0)
__device__ __forceinline__ char* xwindow() { return reinterpret_cast<char*>((reinterpret_cast<uintptr_t>(g_x) + (2u << 20) - 1) & ~(uintptr_t)((2u << 20) - 1)); }

struct XPtr {
    uint32_t lo, hi;
    __device__ __forceinline__ explicit XPtr(char* p) : lo((uint32_t)(uintptr_t)p), hi((uint32_t)((uintptr_t)p >> 32)) {}
    __device__ __forceinline__ XPtr(uint32_t l, uint32_t h) : lo(l), hi(h) {}
    __device__ __forceinline__ XPtr operator+(uint32_t o) const { return XPtr(lo + o, hi); }
    __device__ __forceinline__ operator char*() const { uint64_t p; asm("mov.b64 %0, {%1, %2};" : "=l"(p) : "r"(lo), "r"(hi)); return (char*)p; }
};
__device__ __forceinline__ void keep(XPtr& v) { keep(v.lo); }

__device__ __forceinline__ void side_warp(uint32_t sb) {
    const uint32_t bid = blockIdx.x, g = bid >> 3, i = bid & 7, P = pairG(0, 0, i);
    char* p = xwindow() + P * 8192 + (g >> 3) * HALF + (g & 7) * 512 + 448;
    uint32_t best[2] = {~0u, ~0u};
    asm volatile("st.relaxed.gpu.global.b32 [%0], 1;" :: "l"(p) : "memory");
    asm volatile("st.relaxed.gpu.global.b32 [%0], 1;" :: "l"(p + COPY) : "memory");
#pragma unroll 1
    for (int r = 0; r < 64; r++) {
        if (r >= 4 && !(r & 1) && min(best[0], best[1]) < 380 && max(best[0], best[1]) > min(best[0], best[1]) + 80) break;
        uint32_t c0, c1, v;
        asm volatile("mov.u32 %0, %clock;" : "=r"(c0) :: "memory");
        asm volatile("atom.relaxed.gpu.global.exch.b32 %0, [%1], 0;" : "=r"(v) : "l"(p + (r & 1) * COPY) : "memory");
        asm volatile("{\n .reg .pred q;\n setp.eq.u32 q, %1, 0x13579bdf;\n mov.u32 %0, 0;\n @!q mov.u32 %0, %clock;\n}" : "=r"(c1) : "r"(v) : "memory");
        if (r & 1) best[1] = min(best[1], c1 - c0); else best[0] = min(best[0], c1 - c0);
    }
    stsvol(sb + S_SIDE, 1 + ((best[1] < best[0]) ^ (__popc(P & PMASK) & 1)));
}

template <int N>
__device__ __forceinline__ void hop_a(const char* src, uint32_t par, uint32_t dst, bool st, int k) {
    uint2 v[N][4];
    float e[4], rl;
    int guard = 0;
    bool again;
    do {
#pragma unroll
        for (int s = 0; s < 4 * N; s++) v[s / 4][s % 4] = ldp64(src + (s / 4) * 256 + (s % 4) * 1024);
        again = __any_sync(~0u, ((chk4(v[0], par) | chk4(v[N - 1], par)) & 1) != 0);
        const int M = max(max((int)v[0][0].x, (int)v[0][1].x), max((int)v[0][2].x, (int)v[0][3].x)) - 254;
#pragma unroll
        for (int s = 0; s < 4; s++) e[s] = __int_as_float(max((int)v[0][s].x - M, 0) << 22);
        rl = rcp(fmaf(e[0], asf(v[0][0].y), e[1] * asf(v[0][1].y)) + fmaf(e[2], asf(v[0][2].y), e[3] * asf(v[0][3].y)));
#pragma unroll
        for (int s = 0; s < 4; s++) e[s] = __shfl_sync(~0u, e[s], 24);
        keep(rl);
    } while (again & (++guard < SPIN_LIMIT));
    rl = __shfl_sync(~0u, rl, 24);
#pragma unroll
    for (int n = 0; n < N; n++) {
        const float o0 = fmaf(e[0], asf(v[n][0].x), e[1] * asf(v[n][1].x)) + fmaf(e[2], asf(v[n][2].x), e[3] * asf(v[n][3].x));
        const float o1 = fmaf(e[0], asf(v[n][0].y), e[1] * asf(v[n][1].y)) + fmaf(e[2], asf(v[n][2].y), e[3] * asf(v[n][3].y));
        sts32_if(st, dst + 192 * n, pack2(o0 * rl, o1 * rl));
    }
    SWEEPS(k, guard - 1);
    __syncwarp();
}

__device__ __forceinline__ void score_warp(const Maps& M, uint32_t sb, uint32_t h, uint32_t ln) {
    const uint32_t lane0 = ln;
    uwait(sb + S_QRDY, 0);
    const uint32_t q8 = ln >> 2;
    const uint32_t k0 = k_off(ln);
    uint32_t pos = h + 6, bar = sb + S_FK, par = 0, phases = 0;
    uint2 q = lds64(sb + S_QS + 8 * ln), qh = lds64(sb + S_QS + 8 * ln + 256);
    auto first_round = [&](uint32_t b, uint32_t ln) {
        uwait(sb + S_RELR, b & 1);
        const uint32_t u = h + 2 * ln, p = u < 4 ? u + 2 : u - 4;
        uint32_t todo = __ballot_sync(~0u, token(ln < 3, sb + S_TOK + 4 * p, 32 * b + 32 + u) == 32 * b + 32 + u);
#pragma unroll 1
        for (uint32_t r = h; todo; todo >>= 1, r += 2) if (todo & 1) ring_load(M, sb, b + 1, r, r < 4 ? r + 2 : r - 4);
    };
#pragma unroll 1
    for (uint32_t n = h; n < 64; n += 2) {
        HSTAMP(0);
        const uint32_t ua = sb + pos * UNIT;
        if (!__all_sync(~0u, mbar_try(bar, par))) uwait(bar, par);
        HSTAMP(1);
        float acc[2][4] = {};
        uint32_t mine = 0;
        const uint32_t id = n + (n & 48) + 6;
#pragma unroll
        for (int s = 0; s < 12; s++) {
            uint32_t kf[4];
            ldsm4(kf, (k0 ^ (32 * (s / 3))) + (ua + 1024 * (s % 3)));
            if (s == 11) {
                __syncwarp();
                mine = token(ln == 0 && n >= 16, sb + S_TOK + 24 + 4 * pos, id);
                stsvol(sb + S_KF + 4 * h, n + 1);
            }
            const bool m = q8 == (s & 7);
            mmaA(acc[s & 1], kf, m ? (s < 8 ? q.x : qh.x) : 0u, m ? (s < 8 ? q.y : qh.y) : 0u);
        }
        const uint32_t pos0 = pos;
        const bool last = (n & 14) == 14;
        pos = last ? h + 2 : n >= 16 && pos >= 4 ? h : pos + 2;
        bar = n >= 14 ? sb + S_RING + 8 * pos : bar + 8;
        par = n >= 14 ? (phases >> pos) & 1 : 0;
        phases ^= n >= 14 ? 1u << pos : 0;
        const float w0 = (acc[0][0] + acc[0][1]) + (acc[1][0] + acc[1][1]), w1 = (acc[0][2] + acc[0][3]) + (acc[1][2] + acc[1][3]);
        HSTAMP(2);
        if (__any_sync(~0u, mine == id)) ring_load(M, sb, n >> 4, (n & 15) + 6, pos0);
        HSTAMP(3);
        float s = ((ln & 1) ? w1 : w0) + __shfl_xor_sync(~0u, (ln & 1) ? w0 : w1, 1);
        s += __shfl_xor_sync(~0u, s, 2);
        sts_hi16(sb + S_SC + (((n & 12) >> 1) + h) * 64 + (n & 2) * 2 + (ln & 29) * 2, scaled(s));
        if (last) {
            __syncwarp();
            arrive_if(ln == 0, sb + S_SCO);
            const uint32_t b = n >> 4, ln = lane0 + lag<1>(sb);
            if (b > 0) {
                uwait(sb + S_RELK, (b - 1) & 1);
                if (h == 0) LSTAMP(64 + 2 * b);
                const uint32_t sl = 3 + h + 2 * ln, idv = 32 * b + 16 + 2 * sl;
                uint32_t todo = __ballot_sync(~0u, token(sl < 8, sb + S_TOK + 48 + 4 * sl, idv) == idv);
#pragma unroll 1
                for (uint32_t r = 3 + h; todo; todo >>= 1, r += 2) if (todo & 1) v_load(M, sb, b, r);
                const uint32_t g = blockIdx.x >> 3, pr = pairL(RA, 1, g), side = ldsvol(sb + S_SIDE);
                const char* src = xwindow() + pr * 8192 + ((side ^ 1 ^ __popc(pr & PMASK)) & 1) * COPY + h * HALF + 8 * min(ln, 24u);
                uwait(sb + S_RELV, (b - 1) & 1);
                __nanosleep(HOP1_NS);
#pragma unroll 1
                for (uint32_t r = 0; r < 4; r += 2) {
                    hop_a<2>(src + 256 * r, b & 1, sb + S_OS + 192 * (4 * h + r) + 96 + 4 * ln, ln < 24, 25);
                    if (r == RELR_AT && b < 3) first_round(b, ln);
                }
                arrive_if(ln == 0, sb + S_OS1);
            } else first_round(0, ln);
            q = lds64(sb + S_QS + 24 * ((n + 2) & 48) + 8 * ln); qh = lds64(sb + S_QS + 24 * ((n + 2) & 48) + 8 * ln + 256);
        }
    }
}

__global__ void __launch_bounds__(NTHR, 1)
fused_kernel(const Params P, const __grid_constant__ Maps M) {
    extern __shared__ __align__(1024) unsigned char smem[];
    const uint32_t sb = smem_u32(smem);
    const int tid = threadIdx.x, bid = blockIdx.x;
    if (PFTOP && tid == 0) {
        if (PFTOP == 2) asm volatile("prefetch.tensormap [%0];" :: "l"(&M.wq) : "memory");
        asm volatile("cp.async.bulk.prefetch.L2.global [%0], %1;" :: "l"(unit_ptr(P, 0)), "r"(PF0 * UNIT) : "memory");
    }
    const int w = __shfl_sync(~0u, tid >> 5, 0), lane = tid & 31;

    if (w >= 8) {
        asm volatile("setmaxnreg.dec.sync.aligned.u32 " REG_LO ";");
        if (w == 8) {
            stream_warp(P, M, sb, lane);
        } else {
            if (PFMAP && w == 11 && lane < 8) asm volatile("prefetch.tensormap [%0];" :: "l"(&M.k + lane) : "memory");
            if (w == 9) { init_bars<0, 3, 2>(sb); init_bars<3, 8, 1>(sb); init_bars<16, 22, 1>(sb); }
            else if (w == 10) { init_bars<8, 16, 2>(sb); init_bars<22, 26, 1>(sb); }
            else { init_bars<37, 38, 1>(sb); init_bars<38, 40, 8>(sb); init_bars<40, 41, 1>(sb); init_bars<41, 44, 8>(sb); init_bars<44, 46, 2>(sb); stsvol(sb + S_ZERO + 4 * lane, 0); }
            asm volatile("fence.mbarrier_init.release.cluster;" ::: "memory");
            asm volatile("bar.arrive 3, 128;" ::: "memory");
            asm volatile("bar.sync 2, %0;" :: "n"(NTHR) : "memory");
            if (w < 11) score_warp(M, sb, w - 9, lane);
            else {
                if (lane == 0) side_warp(sb);
                __syncwarp();
                uint32_t a = 0, b = 0;
                int k = 0;
                while (ldsvol(sb + S_GATE) == 0 && ++k < SPIN_LIMIT) { warm_mma(a, b); __nanosleep(KWNS); }
                uint4* d = reinterpret_cast<uint4*>(reinterpret_cast<char*>(g_s) + XS + bid * 7680) + lane;
                const uint4 z = make_uint4(0, 0, 0, 0);
#pragma unroll 1
                for (int u = 0; u < 15; u++) d[32 * u] = z;
                d = reinterpret_cast<uint4*>(reinterpret_cast<char*>(g_s) + XS2 + bid * 768) + lane;
                d[0] = z;
                if (lane < 16) d[32] = z;
                const uint32_t side = (ldsvol(sb + S_SIDE) & 1) ^ 1, g = bid >> 3, i = bid & 7;
                const XPtr gx(xwindow());
                auto nearp = [&](uint32_t pr) { return gx.lo + pr * 8192 + ((side ^ __popc(pr & PMASK)) & 1) * COPY; };
                const uint32_t own = (i >> 2) * HALF + (i & 3) * 1024 + (lane & 7) * 128;
                const uint32_t pAC = nearp(pairL(lane >> 4, (lane >> 3) & 1, g)) + own, pE = nearp(pairL(RE, (lane >> 3) & 1, g)) + own;
                const uint32_t pG = nearp(pairG((lane >> 2) & 1, (lane >> 3) & 1, i)) + min(lane & 3, 2) * 128;
                uint32_t tr = 0, tk = 0, ph = 0, src = g + (lane >> 4), seen = 0, n = 16, cs = 0;
                bool go = false, first = true;
                while (n < 64 && ++k < SPIN_LIMIT) {
                    const uint32_t now = __shfl_sync(~0u, gtime32(), 0) * 16;
                    if (!go && utest((n & 15) < KRE_EARLY ? sb + S_RELK : sb + S_RELV, ((n >> 4) & 1) ^ 1)) { go = true; if ((int)(now - tk) > 0 || !(n & 15)) tk = now; }
                    if (go && (int)(now - tk) >= 0) {
                        place_load(M, sb, (n & 16) ? n : (n & 48) | ((n + 10) & 15));
                        tk += n >= 48 ? KRE_TAU3 : (n & 15) < KRE_N1 ? KRE_TAU1 : KRE_TAU;
                        n++;
                        go = (n & 15) != 0 && (n & 15) != KRE_EARLY;
                        if (!(n & 15)) LSTAMP(63 + (n >> 3));
                    } else if (first || (int)(now - tr) >= 0) {
                        first = false;
                        tr = now + RFR_TAU;
                        b |= seen & a;
                        warm_mma(a, b);
                        if (RFR_ON) seen = ldp32(XPtr(ph == 0 ? pAC : ph == 1 && lane < 16 ? pE : pG + (src & 8) * (HALF / 8) + (src & 7) * 512, gx.hi));
                        if (RFR_XS && (++cs & (RFR_XS - 1)) < 2) {
                            const uint32_t l = lane + 32 * (cs & 1);
                            *reinterpret_cast<volatile uint32_t*>(reinterpret_cast<char*>(g_s) + (l < 60 ? XS + bid * 7680 + 128 * l : XS2 + bid * 768 + 128 * (l - 60))) = 0;
                        }
                        src += ph == 0 ? 0 : ph == 1 ? 2 : 1;
                        ph = ph == 2 ? 0 : ph + 1;
                    } else __nanosleep(KWNS2);
                }
                while (ldsvol(sb + S_GATE) < 6 && ++k < SPIN_LIMIT) { warm_mma(a, b); __nanosleep(KWNS); }
                if (a | b) stsvol(sb + S_GATE, 6);
            }
        }
        return;
    }
    asm volatile("setmaxnreg.inc.sync.aligned.u32 " REG_HI ";");

    const int g = bid >> 3, i = bid & 7;
    const int g8 = lane >> 2, t = lane & 3;
    char* const gs = reinterpret_cast<char*>(g_s);
    const XPtr gx(xwindow());

    auto zero_words = [&] {
        const uint4 z = make_uint4(0, 0, 0, 0);
        const uint32_t c = (tid >> 6) & 1, cp = (tid >> 7) * COPY, k = (tid & 63) * 16;
        *reinterpret_cast<uint4*>((char*)(gx + pairL(RA, c, g) * 8192 + (i >> 2) * HALF + (i & 3) * 1024 + cp + k)) = z;
        *reinterpret_cast<uint4*>((char*)(gx + pairL(RC, c, g) * 8192 + (i >> 2) * HALF + (i & 3) * 1024 + cp + k)) = z;
        *reinterpret_cast<uint4*>((char*)(gx + pairL(RE, c, g) * 8192 + (i >> 2) * HALF + (i & 3) * 1024 + cp + k)) = z;
        if ((tid & 31) < 24) *reinterpret_cast<uint4*>((char*)(gx + pairG((tid >> 5) & 1, c, i) * 8192 + (g >> 3) * HALF + (g & 7) * 512 + cp + (tid & 31) * 16)) = z;
    };
    if (ZPOS == 0) zero_words();
    W80 Wq[6], Wgu[3];
    uint32_t Wo[5][3][4];
    if (w < 4) {
        const uint32_t* xp = reinterpret_cast<const uint32_t*>(P.x + 640 * w);
        float sum = 0.f, sq = 0.f;
#pragma unroll
        for (int u = 0; u < 10; u++) { uint32_t v = xp[lane + 32 * u]; float a = bf_lo(v), b = bf_hi(v); sum += a + b; sq += a * a + b * b; }
#pragma unroll
        for (int o = 16; o > 0; o >>= 1) { sum += __shfl_xor_sync(~0u, sum, o); sq += __shfl_xor_sync(~0u, sq, o); }
        float mean, den; ln_stats(sum, sq, mean, den);
        if (lane < 20) {
            const uint2 v = reinterpret_cast<const uint2*>(P.x + 640 * w + 80 * i)[lane];
            sts64(sb + S_X0 + 160 * w + 8 * lane, v.x, v.y);
            sts32(sb + S_L0 + 384 * w + b_pos<40>(4 * lane), pack2(__fdiv_rn(bfr(bf_lo(v.x) - mean), den), __fdiv_rn(bfr(bf_hi(v.x) - mean), den)));
            sts32(sb + S_L0 + 384 * w + b_pos<40>(4 * lane + 2), pack2(__fdiv_rn(bfr(bf_lo(v.y) - mean), den), __fdiv_rn(bfr(bf_hi(v.y) - mean), den)));
        }
    } else if (w == 4) {
        const uint32_t* xp = reinterpret_cast<const uint32_t*>(P.wr);
        float sum = 0.f;
#pragma unroll
        for (int u = 0; u < 10; u++) { uint32_t v = xp[lane + 32 * u]; sum += bf_lo(v) + bf_hi(v); }
#pragma unroll
        for (int o = 16; o > 0; o >>= 1) sum += __shfl_xor_sync(~0u, sum, o);
        if (lane == 0) stsf(sb + S_SWR, sum);
        if (lane < 20) {
            const uint2 v = reinterpret_cast<const uint2*>(P.wr + 80 * i)[lane];
            sts32(sb + S_XA + 576 + a_pos(4 * lane), v.x); sts32(sb + S_XA + 576 + a_pos(4 * lane + 2), v.y);
            sts32(sb + S_XA + a_pos(4 * lane), ONES); sts32(sb + S_XA + a_pos(4 * lane + 2), ONES);
        }
    }
    asm volatile("bar.sync 2, %0;" :: "n"(NTHR) : "memory");
    auto frag = [](uint32_t (&a)[4], uint32_t p, int pitch) {
        const uint32_t r0 = lds32(p), r1 = lds32(p + pitch), r2 = lds32(p + 2 * pitch), r3 = lds32(p + 3 * pitch);
        a[0] = __byte_perm(r0, r1, 0x5410); a[1] = __byte_perm(r0, r1, 0x7632);
        a[2] = __byte_perm(r2, r3, 0x5410); a[3] = __byte_perm(r2, r3, 0x7632);
    };
    mbar_wait(sb + S_WFULL + 16 * (w >> 2), 0);
    mbar_wait(sb + S_WFULL + 16 * (w >> 2) + 8, 0);
    {
        const uint32_t p = sb + ST_WQ + (w >> 2) * 30720 + (2 * t) * 384 + (48 * (w & 3) + 2 * g8) * 2;
#pragma unroll
        for (int r = 0; r < 10; r++)
#pragma unroll
            for (int m = 0; m < 3; m++) {
                const uint32_t q = p + ((r & 1) * 40 + (r >> 1) * 8) * 384 + 32 * m, r0 = lds32(q), r1 = lds32(q + 384);
                (r < 8 ? Wq[2 * m].a[(r >> 2) & 1][r & 3] : Wq[2 * m].c[r & 1]) = __byte_perm(r0, r1, 0x5410);
                (r < 8 ? Wq[2 * m + 1].a[(r >> 2) & 1][r & 3] : Wq[2 * m + 1].c[r & 1]) = __byte_perm(r0, r1, 0x7632);
            }
    }
    __syncwarp();
    if (lane == 0) mbar_arrive(sb + S_RELW);
    TSTAMP(1);
    {
        char* d = gs + XS + bid * 7680 + (w >> 2) * 3840 + (48 * (w & 3) + 2 * g8) * 4;
        float acc[6][4] = {};
        mul80(acc, Wq, lds128(sb + S_L0 + 48 * lane), lds32(sb + S_L0 + 48 * lane + 16));
#pragma unroll
        for (int m = 0; m < 6; m += 2) stp64(d + t * 768 + 32 * m, acc[m][0] + acc[m][3], acc[m + 1][0] + acc[m + 1][3], 1);
        float sum[6][4] = {};
        mul80(sum, Wq, make_uint4(ONES, ONES, ONES, ONES), ONES);
        if (t == 0)
#pragma unroll
            for (int m = 0; m < 6; m += 2) stp64(d + 4 * 768 + 32 * m, sum[m][0] + sum[m][3], sum[m + 1][0] + sum[m + 1][3], 1);
    }
    mbar_wait(sb + S_WFULL + 32, 0);
    mbar_wait(sb + S_WFULL + 40, 0);
    const uint32_t oct = 3 * (w >> 1) + (w & 1), oct2 = 3 * (w >> 1) + 2;
    {
        const uint32_t p = sb + ST_WG + ((lane & 7) + 40 * ((lane >> 3) & 1) + 8 * (lane >> 4)) * 192;
#pragma unroll
        for (int T = 0; T < 3; T++) {
            const uint32_t q = p + (T < 2 ? T * 15360 + 16 * oct : (w & 1) * 15360 + 16 * oct2);
            ldsm4t(Wgu[T].a[0], q); ldsm4t(Wgu[T].a[1], q + 16 * 192); ldsm2t(Wgu[T].c, q + 32 * 192);
        }
        float sum[3][4] = {};
        mul80(sum, Wgu, make_uint4(ONES, ONES, ONES, ONES), ONES);
        if (t < 3) stp32(gs + XS2 + bid * 768 + (t < 2 ? 64 * oct + 4 * t : 64 * oct2 + 4 * (w & 1)) + 8 * g8,
                         sel4(t, sum[0][0] + sum[0][3], sum[1][0] + sum[1][3], sum[2][0] + sum[2][3], 0.f), 1);
    }
    __syncwarp();
    if (lane == 0) mbar_arrive(sb + S_RELW + 8);
    const char* srcS = gs + XS + g * 8 * 7680 + (i >> 2) * 3840 + min(tid, 191) * 4;
    uint32_t vs[5][8];
#pragma unroll
    for (int b = 0; b < 5; b++)
#pragma unroll
        for (int s = 0; s < 8; s++) vs[b][s] = LOOK1 ? ldp32(srcS + b * 768 + s * 7680) : 0;
    uint32_t cs2[8];
#pragma unroll
    for (int s = 0; s < 8; s++) cs2[s] = LOOK2 ? ldp32(gs + XS2 + (g * 8 + s) * 768 + min(tid, 191) * 4) : 0;
    __syncwarp();
    mbar_wait(sb + S_WFULL + 48 + 8 * (w >> 1), 0);
    {
        const uint32_t po = sb + ST_WO + (48 * w + 12 * t) * 160 + 4 * g8;
#pragma unroll
        for (int s = 0; s < 3; s++)
#pragma unroll
            for (int m = 0; m < 5; m++) frag(Wo[m][s], po + 4 * s * 160 + 32 * m, 160);
    }
    __syncwarp();
    if (lane == 0) mbar_arrive(sb + S_RELW + 16);
    if (ZPOS == 1) zero_words();
    if (tid < 192) {
        int guard = 0;
        while (((or3(chk8(vs[0], 1), chk8(vs[1], 1), chk8(vs[2], 1)) | chk8(vs[3], 1) | chk8(vs[4], 1)) & 1) && ++guard < SPIN_LIMIT) {
#pragma unroll
            for (int b = 0; b < 5; b++)
#pragma unroll
                for (int s = 0; s < 8; s++) vs[b][s] = ldp32(srcS + b * 768 + s * 7680);
        }
        const uint32_t qpos = sb + S_QS + q_pos(tid);
#pragma unroll
        for (int b = 0; b < 4; b++) {
            sts_hi16(qpos + 384 * b, bfr(sum8(vs[b])));
        }
        stsf(sb + S_CSQ + 4 * tid, sum8(vs[4]));
    }
    if (tid < 192) stsf(sb + S_CSGU + 4 * tid, (chk8(cs2, 1) & 1) ? gather8<768>(gs + XS2 + g * 8 * 768 + tid * 4, 1) : sum8(cs2));
    __syncwarp();
    bar_main();
    arrive_if(tid == 0, sb + S_QRDY);
    if (ZPOS == 2) zero_words();
    TSTAMP(2);

    uint32_t side;
    { int k = 0; while ((side = ldsvol(sb + S_SIDE)) == 0 && ++k < SPIN_LIMIT) {} }
    const uint32_t td = __shfl_sync(~0u, tid, lane);
    const uint32_t wp = __shfl_sync(~0u, tid >> 5, 0);
    const uint32_t cc = wp >= 3;
    auto uni = [](uint32_t v) { return __shfl_sync(~0u, v, 0); };
    auto pin = [&](uint32_t v) { return __shfl_sync(~0u, v, td); };
    auto nearp = [&](uint32_t P) { return gx.lo + P * 8192 + ((side ^ 1 ^ __popc(P & PMASK)) & 1) * COPY; };
    constexpr uint32_t COL = 32 * 8192;
    const uint32_t ownL = gx.lo + (i >> 2) * HALF + (i & 3) * 1024, ownG = gx.lo + (g >> 3) * HALF + (g & 7) * 512;
    const uint32_t uPubA = uni(ownL + pairL(RA, 0, g) * 8192 + (wp >> 1) * 256 + (wp & 1) * 96), uPolA = uni(nearp(pairL(RA, 0, g)) + (wp >> 2) * HALF + (wp & 3) * 256);
    const uint32_t uPubB = uni(ownG + pairG(0, cc, i) * 8192), uPolB = uni(nearp(pairG(0, cc, i)));
    const uint32_t uPubC = uni(ownL + pairL(RC, 0, g) * 8192), uPolC = uni(nearp(pairL(RC, wp < 6 ? cc : wp - 6, g)));
    const uint32_t uPubD = uni(ownG + pairG(1, 0, i) * 8192 + (wp < 7 ? 32 * wp : 256)), uPolD = uni(nearp(pairG(1, cc, i)));
    const uint32_t uPubE = uni(ownL + pairL(RE, 0, g) * 8192), uPolE = uni(nearp(pairL(RE, i >> 2, g)));
    const uint32_t uOS = uni(sb + S_OS + 192 * wp), uCol = uni(sb + 64 * cc);
    auto xp = [&](uint32_t lo) { return (char*)XPtr(lo, gx.hi); };
#define IDS() const uint32_t z_ = pin(td); const uint32_t ln = z_ & 31, q8 = ln >> 2, t4 = z_ & 3, n96 = z_ - 96 * cc, n80 = min(n96, 79u); (void)q8; (void)t4; (void)n80; (void)ln

    auto vaddr = [&](uint32_t (&voff)[3]) {
        const uint32_t ln = td & 31;
        const uint32_t key3 = 3 * ((ln & 7) + 2 * (ln & 8) + ((ln >> 1) & 8));
#pragma unroll
        for (int T = 0; T < 3; T++) {
            const uint32_t u = 3 * wp + T, r = key3 + (u >> 3);
            voff[T] = r * 128 + (((u ^ r) & 7) << 4);
        }
    };
    auto values = [&](uint32_t (&vf)[8][3][4], auto order, auto step, uint32_t ps, uint32_t col, uint32_t par) {
        const uint32_t ln = td & 31, q8 = ln >> 2, t4 = td & 3;
        const uint4 p = lds128(ps + 16 * ln);
        float acc[3][4] = {}, f0 = 0.f, f1 = 0.f, r3 = 0.f;
        int M = 0;
#pragma unroll
        for (int k = 0; k < 8; k++) {
            step(k);
            const int s = (order.value >> (4 * k)) & 7;
            const bool m = (q8 >> 1) == (s >> 1);
            const uint32_t b0 = m ? ((s & 1) ? p.z : p.x) : 0u, b1 = m ? ((s & 1) ? p.w : p.y) : 0u;
#pragma unroll
            for (int T = 0; T < 3; T++) mmaA(acc[T], vf[s][T], b0, b1);
            if (k == FSTEP) {
                const uint2 mp = lds64(ps + PS_MAX + 8 * t4);
                M = __reduce_max_sync(~0u, __float2int_ru(fmaxf(asf(mp.x), asf(mp.y))));
                f0 = ex2(asf(mp.x) - (float)M); f1 = ex2(asf(mp.y) - (float)M);
                float l[4] = {};
                mma16816(l, ONES, ONES, ONES, ONES, p.x, p.y); mma16816(l, ONES, ONES, ONES, ONES, p.z, p.w);
                r3 = fmaf(f0, l[0], f1 * l[1]);
            }
        }
        CSTAMP(25);
        char* pubA = xp(uPubA + col * COL + 32 * t4 + 4 * q8);
        const float r0 = fmaf(f0, acc[0][0], f1 * acc[0][3]), r1 = fmaf(f0, acc[1][0], f1 * acc[1][3]), r2 = fmaf(f0, acc[2][0], f1 * acc[2][3]);
        const bool hi = t4 & 2, od = t4 & 1;
        const float u0 = (hi ? r2 : r0) + __shfl_xor_sync(~0u, hi ? r0 : r2, 2), u1 = (hi ? r3 : r1) + __shfl_xor_sync(~0u, hi ? r1 : r3, 2);
        const float o = (od ? u1 : u0) + __shfl_xor_sync(~0u, od ? u0 : u1, 1);
        stp32_if(t4 < 3 || ((wp & 1) && q8 < 2), pubA, ln == 3 ? __int_as_float(2 * M) : o, par);
    };

#pragma unroll 1
    for (int ch = 0; ch < 5; ch++) {
        const uint32_t par0 = (ch + 1) & 1, par1 = ch & 1;
        uint32_t voff[3], vf[8][3][4];
        CSTAMP(0);
        if (ch < 4) {
            vaddr(voff);
            mbar_wait(sb + S_SCO, par1);
            if (ch == 0) mbar_wait(sb + S_WFULL + 80, 0);
            TST(0);
            auto ldw = [&](int s) {
                mbar_wait(sb + S_FV + 8 * s, par1);
#pragma unroll
                for (int T = 0; T < 3; T++) ldsm4t(vf[s][T], voff[T] + (sb + v_place(ch, s) * SLOT));
            };
            probs(bf_lo(lds16(sb + S_SC + 2 * td)), sb + S_PS, wp, td & 31);
            ldw(0); ldw(1); ldw(2);
            bar_main();
            arrive_if(td == 0, sb + S_RELR);
            values(vf, std::integral_constant<uint32_t, 0x76543210>(), [&](int s) {
                if (s >= 3) ldw(s);
            }, sb + S_PS, 0, par0);
            TST(1);
            CSTAMP(5);
            if (ch > 0) mbar_wait(sb + S_OS1, par0);
        } else {
#pragma unroll
            for (int s = 0; s < 36; s++) { vf[s / 12][(s / 4) % 3][s & 3] = 0; opaque(vf[s / 12][(s / 4) % 3][s & 3]); }
        }
        const bool has0 = ch < 4, has1 = ch > 0;
        const bool actc = wp < 6 && (cc ? has1 : has0);
        const uint32_t parc = cc ? par1 : par0;
        const uint32_t pub0 = has0 ? par0 : 0;
        uint32_t n4;
        {
            IDS();
            const uint32_t c = ch == 4;
            const uint32_t osa = pin(uOS + 96 * c + 4 * ln), oa = pin(uOS + 96 * (q8 & 1) + 24 * t4), ra = pin(sb + S_RED + 640 * wp + 320 * (t4 & 1) + 8 * q8);
            n4 = pin(4 * n80);
            hop_a<1>(xp(uPolA + c * COL + 8 * min(ln, 24u) + lag<DELAY_L>(sb)), pub0, osa, ln < 24, 5 * ch);
            TST(2);
            CSTAMP(6);
            float acc[5][4] = {};
            const uint2 b0 = lds64(oa), b1 = lds64(oa + 8), b2 = lds64(oa + 16);
#pragma unroll
            for (int m = 0; m < 5; m++) mmaA(acc[m], Wo[m][0], b0.x, b0.y);
#pragma unroll
            for (int m = 0; m < 5; m++) mmaA(acc[m], Wo[m][1], b1.x, b1.y);
#pragma unroll
            for (int m = 0; m < 5; m++) mmaA(acc[m], Wo[m][2], b2.x, b2.y);
#pragma unroll
            for (int m = 0; m < 5; m++) sts64_if(!(td & 2), ra + 64 * m, (td & 1) ? acc[m][1] : acc[m][0], (td & 1) ? acc[m][3] : acc[m][2]);
        }
        CSTAMP(7);
        uint32_t xr, fl, pubC, pubC2;
        auto prepC = [&] {
            IDS();
            xr = pin(sb + S_XB + 48 * (ln & 15));
            pubC = pin(uPubC + (t4 & 1) * COL + 192 * (wp >> 1) + 64 * (wp & 1) + 8 * q8);
            pubC2 = pin(uPubC + (t4 & 1) * COL + ((t4 & 2) ? 192 * (wp >> 1) + 128 + 4 * (wp & 1) + 8 * q8 : 768 + 2 * ((q8 + 1) & 6)));
            fl = pin(((t4 & 1) ? par1 : pub0) | (t4 >= 2 || (wp == 7 && q8 < 4 && q8 != 2 - t4) ? 2 : 0));
        };
        if (actc) {
            bar_main();
            CSTAMP(8);
            uint32_t r[8];
#pragma unroll
            for (int s = 0; s < 8; s++) r[s] = lds32(n4 + (5 * uCol - 4 * sb + S_RED + 640 * s));
            stp32_if(true, xp(uPubB + n4), sum8(r), parc);
            CSTAMP(9);
            prepC();
            const uint32_t xas = pin(3 * uCol - 2 * sb + S_XA + 192 + a_pos(n4 / 4)), xbs = pin(6 * uCol - 5 * sb + S_XB + b_pos<40>(n4 / 4));
            const float x0 = cc ? ldsf(sb + S_XCAR + n4) : bf_lo(lds16(sb + S_X0 + 160 * (ch & 3) + n4 / 2));
            gather16(xp(uPolB + n4 + lag<DELAY_G>(sb)), parc, 5 * ch + 1, [&](float y, uint32_t) {
                const uint32_t x = pack2(x0 + bfr(y), 0.f);
                sts16(xbs, x);
                sts16(xas, x);
                return 0u;
            });
            CSTAMP(10);
        } else {
            bar_main();
            prepC();
        }
        auto stats = [&](uint32_t xa, const uint4& b, uint32_t b4) {
            float a[4] = {};
            const uint4 p0 = lds128(xa), p1 = lds128(xa + 16);
            const uint2 p2 = lds64(xa + 32);
            mmaV(a, p0, b.x, b.y); mmaV(a, p1, b.z, b.w); mma8(a, p2.x, p2.y, b4);
            return a[0] + a[3];
        };
        {
            auto gate_up = [&](auto with_stats) {
                bar_main();
                TST(3);
                CSTAMP(11);
                const uint4 b = lds128(xr);
                const uint32_t b4 = lds32(xr + 16);
                float acc[3][4] = {}, st = 0.f;
                if (with_stats.value) st = stats(xr + (S_XA - S_XB), b, b4);
                mul80(acc, Wgu, b, b4);
                stp64_if(!(td & 2), xp(pubC), tagw(acc[0][0] + acc[0][3], fl & 1), tagw(acc[1][0] + acc[1][3], fl & 1));
                stp32_if(fl > 1, xp(pubC2), !with_stats.value || (td & 2) ? acc[2][0] + acc[2][3] : st, fl & 1);
            };
            if (wp == 7) gate_up(std::true_type()); else gate_up(std::false_type());
        }
        CSTAMP(12);
        float mean = 0.f, den = 1.f;
        {
            IDS();
            const uint32_t wh = pin((((ln & 7) + 48 * ((ln >> 3) & 1) + 8 * (ln >> 4)) * 160 + (wp < 7 ? 16 * wp : 128)) | ((384 * cc + b_pos<48>(n96)) << 16));
            const uint32_t pubD = pin(uPubD + (t4 & 1) * COL + 16 * (t4 & 2) + 4 * q8 + (fl & 1)), ha = xr + (S_HS - S_XB);
            auto down = [&](const uint32_t (&W)[3][4], const uint4& h0, const uint2& h1) {
                float a0[4] = {}, a1[4] = {}, a2[4] = {};
                mmaA(a0, W[0], h0.x, h0.y); mmaA(a1, W[1], h0.z, h0.w); mmaA(a2, W[2], h1.x, h1.y);
                return ((a0[0] + a0[3]) + (a1[0] + a1[3])) + (a2[0] + a2[3]);
            };
            if (wp < 6) {
                uint32_t Wd[3][4];
                auto ldd = [&](uint32_t z) {
#pragma unroll
                    for (int s = 0; s < 3; s++) ldsm4t(Wd[s], ((wh ^ z) & 0xffff) + (sb + S_WD + s * 2560));
                };
                if (actc) {
                    const uint32_t src0 = uPolC + lag<DELAY_C>(sb);
                    const char* srcv = xp(src0 + 8 * n96);
                    const char* src = xp(src0 + (ln & 1) * HALF);
                    float gt, up;
                    int guard = 0;
                    bool again;
                    do {
                        uint2 v[8], st[4];
#pragma unroll
                        for (int s = 0; s < 4; s++) st[s] = ldp64(src + 768 + s * 1024);
#pragma unroll
                        for (int s = 0; s < 8; s++) v[s] = ldp64(srcv + (s >> 2) * HALF + (s & 3) * 1024);
                        float sx = (asf(st[0].x) + asf(st[1].x)) + (asf(st[2].x) + asf(st[3].x)), sq = (asf(st[0].y) + asf(st[1].y)) + (asf(st[2].y) + asf(st[3].y));
                        sx += __shfl_xor_sync(~0u, sx, 1); sq += __shfl_xor_sync(~0u, sq, 1);
                        const uint32_t z = ((st[0].x ^ parc) & 1) * 16;
                        const uint2 cs = lds64(sb + S_CSGU - 768 * cc + 8 * td + z);
                        again = __any_sync(~0u, (or3(chk4(st, parc), chk8(v, parc), chk8y(v, parc)) & 1) != 0);
                        ln_stats(sx, sq, mean, den);
                        const float rd = rcp(den);
                        gt = fmaf(-mean, asf(cs.x), sum8x(v)); up = fmaf(-mean, asf(cs.y), sum8y(v));
                        ldd(z);
                        gt *= rd; up *= rd;
                        keep(gt); keep(up);
                    } while (again & (++guard < SPIN_LIMIT));
                    CSTAMP(13);
                    SWEEPS(5 * ch + 2, guard - 1);
                    gt = bfr(gt);
                    const uint32_t h = pack2(bfr(gt * sigmoidf_(gt)) * bfr(up), 0.f);
                    sts16((wh >> 16) + (sb + S_HS), h);
                    CSTAMP(14);
                } else ldd(0);
                bar_main();
                TST(4);
                CSTAMP(15);
                const uint4 h0 = lds128(ha);
                const uint2 h1 = lds64(ha + 16);
                stp32_if(!(td & 2), xp(pubD & ~1u), down(Wd, h0, h1), pubD & 1);
            } else {
                stsvol(sb + S_GATE, ch + 1);
                uint32_t Wd[2][3][4];
#pragma unroll
                for (int s = 0; s < 6; s++) ldsm4t(Wd[s / 3][s % 3], (wh & 0xffff) + (sb + S_WD + (s / 3) * 16 + (s % 3) * 2560));
                uint32_t v = 0;
                if (wp == 6 ? has0 : has1) {
                    const uint32_t par = wp == 6 ? par0 : par1;
                    const char* src = xp(uPolC + 768 + (ln & 4) * (HALF / 4) + (ln & 3) * 1024 + 4 * min(ln >> 3, 2u) + lag<DELAY_C>(sb));
                    int guard = 0;
                    do v = ldp32(src); while (__any_sync(~0u, (v ^ par) & 1) && ++guard < SPIN_LIMIT);
                }
                bar_main();
                const uint4 h0 = lds128(ha);
                const uint2 h1 = lds64(ha + 16);
                const float d0 = down(Wd[0], h0, h1), d1 = down(Wd[1], h0, h1);
                stp32_if(true, xp(pubD & ~1u), (td & 2) ? d1 : d0, pubD & 1);
                if (wp == 6 ? has0 : has1) {
                    float sx = asf(v);
                    sx += __shfl_xor_sync(~0u, sx, 1); sx += __shfl_xor_sync(~0u, sx, 2); sx += __shfl_xor_sync(~0u, sx, 4);
                    const float sq = __shfl_sync(~0u, sx, 8), xw = __shfl_sync(~0u, sx, 16);
                    ln_stats(sx, sq, mean, den);
                    const float r = bfr(fmaf(-mean, ldsf(sb + S_SWR), xw) * rcp(den));
                    sts32_if(ln == 0, sb + S_STAT + 4 * (wp - 6), __float_as_uint(bfr(sigmoidf_(r))) | (ch + 1));
                }
            }
        }
        CSTAMP(16);
        uint32_t pubE;
        float x1 = 0.f;
        {
            IDS();
            pubE = pin(uPubE + (t4 < 3 ? (wp >> 2) * COL + 192 * (wp & 3) + 64 * t4 + 8 * q8 : (q8 >> 2) * COL + 768 + 4 * (q8 & 1)));
            xr = pin(sb + S_XB + 48 * (ln & 7));
            if (actc && (cc == 0 || g == 0)) {
                const uint32_t m4 = 4 * n80;
                const uint32_t xas = pin(3 * uCol - 2 * sb + S_XA + 192 + a_pos(n80)), xbs = pin(6 * uCol - 5 * sb + S_XB + b_pos<40>(n80));
                x1 = bf_lo(lds16(xbs));
                const float lnx = __uint_as_float(pin(__float_as_uint(bfr(__fdiv_rn(bfr(x1 - mean), den)))));
                uint32_t x2;
                gather16(xp(uPolD + m4 + lag<DELAY_D>(sb)), parc, 5 * ch + 3, [&](float y, uint32_t z) {
                    const uint32_t gate = ldsvol(sb + S_STAT + 4 * cc + z);
                    x2 = pack2(x1 + bfr(lnx + bfr(bfr(y) * bf_hi(gate))), 0.f);
                    sts16(xbs, x2);
                    sts16(xas, x2);
                    return (uint32_t)((gate & 7) != ch + 1);
                });
                CSTAMP(17);
                if (cc) reinterpret_cast<unsigned short*>(P.out)[640 * (ch - 1) + 80 * i + n80] = (unsigned short)x2;
                x1 = bf_lo(x2);
            }
        }
        CSTAMP(18);
        if (!has0) break;
        {
            auto qproj = [&](auto with_stats) {
                bar_main();
                TST(5);
                CSTAMP(19);
                const uint32_t t4 = td & 3;
                const uint4 b = lds128(xr);
                const uint32_t b4 = lds32(xr + 16);
                float acc[6][4] = {}, st = 0.f;
                if (with_stats.value) st = stats(xr + (S_XA - S_XB), b, b4);
                mul80(acc, Wq, b, b4);
                const float v0 = sel4(t4, acc[0][0] + acc[0][3], acc[2][0] + acc[2][3], acc[4][0] + acc[4][3], acc[4][0] + acc[4][3]);
                const float v1 = sel4(t4, acc[1][0] + acc[1][3], acc[3][0] + acc[3][3], acc[5][0] + acc[5][3], acc[5][0] + acc[5][3]);
                if (with_stats.value) stp32_if((td & 11) == 3, xp(pubE), st, par0);
                stp64_if(t4 < 3, xp(pubE), tagw(v0, par0), tagw(v1, par0));
            };
            if (wp == 7) qproj(std::true_type()); else qproj(std::false_type());
            sts32_if(td < 80, sb + S_XCAR + 4 * td, __float_as_uint(x1));
        }
        CSTAMP(20);
        auto pass2 = [&](auto d0, auto d1, auto d2) {
            constexpr int D0 = d0.value, D1 = d1.value, D = D0 + D1 + d2.value;
            IDS();
            const uint32_t ua = sb + k_place(ch, wp & 6) * SLOT + (wp & 1) * UNIT, k0 = k_off(ln);
            uint32_t kf[12][2][4];
            auto ldk = [&](int s) { const uint32_t a = (k0 ^ (32 * (s / 3))) + (ua + 1024 * (s % 3)); ldsm4(kf[s][0], a); ldsm4(kf[s][1], a + SLOT); };
            auto ldv1 = [&](int k) { ldsm4t(vf[k / 3][k % 3], voff[k % 3] + (sb + v_place(ch, k / 3) * SLOT)); };
            auto ldv = [&](int s) { ldv1(3 * s); ldv1(3 * s + 1); ldv1(3 * s + 2); };
            constexpr uint32_t LATE = LAST_LATE;
            constexpr uint64_t EARLY_LIST = bit_list(~LATE), LATE_LIST = bit_list(LATE);
            auto early = [&](int k) {
                if (D1 == 0) ldk(k);
                else if (k < 3) { ldv1(9 + 2 * k); ldv1(10 + 2 * k); }
                else ldk((EARLY_LIST >> (4 * (k - 3))) & 15);
            };
            if (D1 > 0) vaddr(voff);
            if (!(mbar_try(sb + S_FK + 8 * (wp & 6), par1) & mbar_try(sb + S_FK + 8 * (wp | 1), par1))) { mbar_wait(sb + S_FK + 8 * (wp & 6), par1); mbar_wait(sb + S_FK + 8 * (wp | 1), par1); }
#pragma unroll
            for (int s = 0; s < D0; s++) early(s);
            if (wp < 6) {
                const uint32_t qsa = pin(sb + S_QS + 384 * ch + q_pos(td));
                const uint32_t src0 = uPolE + lag<(D1 > 0 ? 0 : DELAY_E)>(sb);
                const char* srcv = xp(src0 + 4 * td);
                const char* src = xp(src0 + (ln & 1) * HALF);
                uint32_t v[8]; uint2 st[4];
                auto look = [&] {
#pragma unroll
                    for (int s = 0; s < 4; s++) st[s] = ldp64(src + 768 + s * 1024);
#pragma unroll
                    for (int s = 0; s < 8; s++) v[s] = ldp32(srcv + (s >> 2) * HALF + (s & 3) * 1024);
                };
                if (D1 > 0) {
                    look();
                    __syncwarp();
#pragma unroll
                    for (int s = D0; s < D0 + D1; s++) early(s);
                }
                int guard = 0;
                while (true) {
                    if (D1 == 0) look();
                    float sx = (asf(st[0].x) + asf(st[1].x)) + (asf(st[2].x) + asf(st[3].x)), sq = (asf(st[0].y) + asf(st[1].y)) + (asf(st[2].y) + asf(st[3].y));
                    sx += __shfl_xor_sync(~0u, sx, 1); sq += __shfl_xor_sync(~0u, sq, 1);
                    const float cs = ldsf(sb + S_CSQ + 4 * td + ((st[0].x ^ par0) & 1) * 4);
                    const bool again = __any_sync(~0u, ((chk8(v, par0) | chk4(st, par0)) & 1) != 0);
                    ln_stats(sx, sq, mean, den);
                    const uint32_t q = pack2(fmaf(-mean, cs, sum8(v)) * rcp(den), 0.f);
                    sts16(qsa, q);
                    if (!(again & (++guard < SPIN_LIMIT))) break;
                    if (D1 > 0) look();
                }
                SWEEPS(5 * ch + 4, guard - 1);
                CSTAMP(22);
            } else {
#pragma unroll
                for (int s = D0; s < D0 + D1; s++) early(s);
            }
#pragma unroll
            for (int s = D0 + D1; s < D; s++) early(s);
            bar_main();
            TST(6);
            CSTAMP(1);
            uint2 q = lds64(sb + S_QS + 384 * ch + 8 * ln);
            float acc[2][4] = {};
            constexpr int V0 = 13 - D, NV = D1 > 0 ? 2 : (2 * (D - 1)) / 3;
            static_assert(D1 == 0 || LAST0 == 0 || D - 3 + __builtin_popcount(LATE) == 12, "plan");
#pragma unroll
            for (int s = 0; s < 12; s++) {
                const bool m = q8 == (s & 7);
                const uint32_t b0 = m ? q.x : 0u, b1 = m ? q.y : 0u;
                if (s == 7) q = lds64(sb + S_QS + 384 * ch + 8 * ln + 256);
                mmaA(acc[0], kf[s][0], b0, b1);
                mmaA(acc[1], kf[s][1], b0, b1);
                if (D1 > 0) {
                    if (s >= 1 && s <= __builtin_popcount(LATE)) ldk((LATE_LIST >> (4 * (s - 1))) & 15);
                } else {
                    if (s >= 1 && s + D - 1 < 12) ldk(s + D - 1);
                    if (s >= 1 && s + D - 1 == 11) { __syncwarp(); arrive_if(ln == 0, sb + S_RELK); }
                    if (s == V0) vaddr(voff);
                    if (s >= V0 && 2 * (s - V0) < 3 * NV) ldv1(9 + 2 * (s - V0));
                    if (s >= V0 && 2 * (s - V0) + 1 < 3 * NV) ldv1(10 + 2 * (s - V0));
                }
            }
            CSTAMP(24);
            {
                const float v0 = acc[0][0] + acc[0][1], v1 = acc[0][2] + acc[0][3], v2 = acc[1][0] + acc[1][1], v3 = acc[1][2] + acc[1][3];
                const bool hi = t4 & 2, od = t4 & 1;
                const float u0 = (hi ? v2 : v0) + __shfl_xor_sync(~0u, hi ? v0 : v2, 2), u1 = (hi ? v3 : v1) + __shfl_xor_sync(~0u, hi ? v1 : v3, 2);
                const float s = (od ? u1 : u0) + __shfl_xor_sync(~0u, od ? u0 : u1, 1);
                CSTAMP(2);
                probs(scaled(s), sb + S_PS + PS_PASS, wp, ln);
                CSTAMP(3);
            }
            bar_main();
            TST(10);
            CSTAMP(4);
            if (D1 > 0) values(vf, std::integral_constant<uint32_t, ORDER_L>(), [&](int s) { if (s < 3) ldv(s + 5); }, sb + S_PS + PS_PASS, 1, par0);
            else values(vf, std::integral_constant<uint32_t, (NV > 1 ? ORDER_R : 0x76543210)>(),
                        [&](int s) { if (s >= (NV > 1 ? 2 : 1) && s + NV + (NV > 1 ? 1 : 2) < 8) ldv(s + NV + (NV > 1 ? 1 : 2)); }, sb + S_PS + PS_PASS, 1, par0);
            arrive_if(ln == 0, sb + S_RELV);
        };
        if (LAST0 > 0 && ch == 3) {
            pass2(std::integral_constant<int, LAST0>(), std::integral_constant<int, LAST1>(), std::integral_constant<int, LAST2>());
#pragma unroll
            for (int m = 0; m < 60; m++) { uint32_t& r = m % 10 < 8 ? Wq[m / 10].a[(m % 10) / 4][m % 2 + 2 * ((m % 10) / 2 % 2)] : Wq[m / 10].c[m % 2]; r = 0; opaque(r); }
        } else pass2(std::integral_constant<int, KPRE>(), std::integral_constant<int, 0>(), std::integral_constant<int, KPRE2>());
        TST(11);
        CSTAMP(23);
    }
    sts32_if(td == 255, sb + S_GATE, 6);
    TSTAMP(3);
}

typedef CUresult (*EncodeFn)(CUtensorMap*, CUtensorMapDataType, cuuint32_t, void*, const cuuint64_t*, const cuuint64_t*, const cuuint32_t*,
                             const cuuint32_t*, CUtensorMapInterleave, CUtensorMapSwizzle, CUtensorMapL2promotion, CUtensorMapFloatOOBfill);

void make_map(EncodeFn enc, CUtensorMap* m, const void* base, uint64_t cols, uint64_t rows, uint32_t box_cols, uint32_t box_rows, bool swizzle) {
    cuuint64_t dims[2] = {cols, rows};
    cuuint64_t strides[1] = {cols * 2};
    cuuint32_t box[2] = {box_cols, box_rows};
    cuuint32_t es[2] = {1, 1};
    enc(m, CU_TENSOR_MAP_DATA_TYPE_BFLOAT16, 2, const_cast<void*>(base), dims, strides, box, es, CU_TENSOR_MAP_INTERLEAVE_NONE,
        swizzle ? CU_TENSOR_MAP_SWIZZLE_128B : CU_TENSOR_MAP_SWIZZLE_NONE, swizzle ? CU_TENSOR_MAP_L2_PROMOTION_NONE : WPROMO, CU_TENSOR_MAP_FLOAT_OOB_FILL_NONE);
}

}

extern "C" void kernel_launch(void* const* d_in, const int* in_sizes, int n_in, void* d_out, int out_size) {
    (void)in_sizes; (void)n_in; (void)out_size;
    static EncodeFn enc = nullptr;
    if (!enc) {
        void* f = nullptr;
        cudaDriverEntryPointQueryResult q;
        cudaGetDriverEntryPoint("cuTensorMapEncodeTiled", &f, cudaEnableDefault, &q);
        enc = (EncodeFn)f;
        cudaFuncSetAttribute(fused_kernel, cudaFuncAttributeMaxDynamicSharedMemorySize, SMEM_BYTES);
    }
    Params P;
    P.x = (const __nv_bfloat16*)d_in[0]; P.k = (const __nv_bfloat16*)d_in[1]; P.v = (const __nv_bfloat16*)d_in[2];
    P.wr = (const __nv_bfloat16*)d_in[6];
    P.out = (__nv_bfloat16*)d_out;
    Maps M;
    {
        cuuint64_t dims[4] = {64, 8, 3, (cuuint64_t)KV_BATCH_KEYS / 2}, strides[3] = {384, 128, 3072};
        cuuint32_t box[4] = {64, 8, 3, 2}, es[4] = {1, 1, 1, 1};
        enc(&M.k, CU_TENSOR_MAP_DATA_TYPE_BFLOAT16, 4, d_in[1], dims, strides, box, es, CU_TENSOR_MAP_INTERLEAVE_NONE, CU_TENSOR_MAP_SWIZZLE_128B,
            CU_TENSOR_MAP_L2_PROMOTION_NONE, CU_TENSOR_MAP_FLOAT_OOB_FILL_NONE);
    }
    make_map(enc, &M.v, P.v, 64, (uint64_t)12 * KV_BATCH_KEYS, 64, 96, true);
    make_map(enc, &M.vu, P.v, 64, (uint64_t)12 * KV_BATCH_KEYS, 64, 48, true);
    make_map(enc, &M.wq, d_in[3], 6144, 640, 192, 40, false);
    make_map(enc, &M.wo, d_in[4], 640, 6144, 80, 96, false);
    make_map(enc, &M.wg, d_in[7], 1536, 640, 96, 80, false);
    make_map(enc, &M.wu, d_in[8], 1536, 640, 96, 80, false);
    make_map(enc, &M.wd, d_in[9], 640, 1536, 80, 96, false);
    fused_kernel<<<NCTA, NTHR, SMEM_BYTES, cudaStreamPerThread>>>(P, M);
}
```

```cpp
#include <cuda_runtime.h>
#include <cuda.h>
#include <cuda_bf16.h>
#include <stdint.h>
#include <type_traits>

namespace {

constexpr int NCTA = 128;
constexpr int NTHR = 384;
constexpr int UNIT = 6144;
constexpr int SLOT = 12288;
#define TAU 4000
#define TAUW 3850
#define TAU0 3850
#define PF0 2
#define PFMAP 1
#define ZPOS 1
#define LOOK1 0
#define LOOK2 0
#define SLACK 4000
#define SLACK0 2000
#define TSH 0
#define HOP1_NS 200
#define RELR_AT 0
#define PSLEEP 0
#define KRE_EARLY 6
#define PFTOP 2
#define RFR_XS 2
#define TMIN 2400
#define T_LEAD 0
#define WIN_W 3
#define WIN_S 4
#define WIN_U 10
#define RFR_ON 1
#define KRE_N1 0
#define KRE_TAU1 2500
#define RFR_TAU 25600
#define VPF 4
#define KRE_GATE 0
#define KRE_GATE3 KRE_GATE
#define JFREE 16
#define TFREE 0
#define KRE_TAU 3000
#define KRE_TAU3 KRE_TAU
#define HDEPTH 3
#define LAST0 3
#define ORDER_L 0x76543210
#define ORDER_R 0x76543210
#define LAST_LATE 0xaa8
#define LAST1 4
#define LAST2 3
#define FSTEP 4
#define SPEC 1
#define PV1PIPE 0
#define HOPA0 6
#define HOPA1 6
#define WPROMO CU_TENSOR_MAP_L2_PROMOTION_NONE
#define KPRE 1
#define KPRE2 3
#define DELAY_G 2
#define DELAY_L 2
#define DELAY_E3 0
#define DELAY_C 1
#define DELAY_D 0
#define DELAY_E 1
#define REG_LO "40"
#define REG_HI "232"
#define SPIN_LOG 17
constexpr int SPIN_LIMIT = 1 << SPIN_LOG;

__host__ __device__ constexpr uint32_t pairL(uint32_t region, uint32_t c, uint32_t g) { return (g & 1) | ((g >> 1) << 2) | (c << 5) | (region << 6); }
__host__ __device__ constexpr uint32_t pairG(uint32_t d, uint32_t c, uint32_t i) { return (i & 1) | ((i >> 1) << 2) | (d << 4) | (c << 5) | (3u << 6); }
constexpr uint32_t RA = 0, RC = 1, RE = 2, HALF = 16384, COPY = 4096, PMASK = 0x59;
constexpr uint32_t XS = 0;
constexpr uint32_t XS2 = XS + 128 * 7680;
constexpr uint32_t XSEND = XS2 + 128 * 768;
__device__ uint4 g_s[XSEND / 16];
__device__ uint4 g_x[(4u << 20) / 16];
#define SWEEPS(k, n) do {} while (0)

constexpr uint32_t S_WD = 16 * SLOT;
constexpr uint32_t S_DUMMY = S_WD + 15360;
constexpr uint32_t S_BAR = S_DUMMY + 4096;
constexpr uint32_t S_FV = S_BAR, S_FK = S_FV + 64, S_RING = S_FK + 64, S_DBAR = S_RING + 48, S_WFULL = S_DBAR + 32, S_QRDY = S_WFULL + 88;
constexpr uint32_t S_RELK = S_QRDY + 8, S_RELV = S_RELK + 8, S_RELR = S_RELV + 8, S_RELW = S_RELR + 8, S_SCO = S_RELW + 24;
constexpr uint32_t S_OS1 = S_SCO + 8;
constexpr uint32_t S_ZERO = S_OS1 + 8;
constexpr uint32_t S_KF = S_ZERO + 8;
constexpr uint32_t S_TOK = S_KF + 8;
constexpr uint32_t S_SIDE = S_TOK + 80, S_GATE = S_SIDE + 4;
constexpr uint32_t S_STAT = S_GATE + 12, S_SWR = S_STAT + 16;
constexpr uint32_t S_XCAR = S_STAT + 32;
constexpr uint32_t S_CSQ = S_XCAR + 320;
constexpr uint32_t S_CSGU = S_CSQ + 768;
constexpr uint32_t S_RED = S_CSGU + 768;
constexpr uint32_t S_L0 = S_RED;
constexpr uint32_t S_OS = S_RED + 5120;
constexpr uint32_t S_PS = S_OS + 1536;
constexpr uint32_t PS_MAX = 512, PS_PASS = 544;
constexpr uint32_t S_QS = S_PS + 2 * PS_PASS;
constexpr uint32_t S_XB = S_QS + 1536;
constexpr uint32_t S_XA = S_XB + 768;
constexpr uint32_t S_HS = S_XA + 768;
constexpr uint32_t S_X0 = S_HS + 768;
constexpr uint32_t S_SC = S_X0 + 640;
constexpr uint32_t S_TM = S_SC + 512;
constexpr int SMEM_BYTES = S_TM + 256;
static_assert(SMEM_BYTES <= 232448 && S_STAT % 16 == 0 && S_RED % 16 == 0 && S_XB % 16 == 0 && S_HS % 16 == 0 && S_PS % 16 == 0 && S_QS % 16 == 0, "smem");
static_assert(S_SCO == S_BAR + 44 * 8 && S_RELK == S_BAR + 38 * 8, "barriers");
constexpr uint32_t ST_WQ = 3 * SLOT, ST_WG = 8 * SLOT, ST_WO = 11 * SLOT;

__device__ __forceinline__ uint32_t smem_u32(const void* p) { return (uint32_t)__cvta_generic_to_shared(p); }
__device__ __forceinline__ void mbar_init(uint32_t bar, uint32_t cnt) { asm volatile("mbarrier.init.shared::cta.b64 [%0], %1;" :: "r"(bar), "r"(cnt) : "memory"); }
__device__ __forceinline__ void mbar_expect(uint32_t bar, uint32_t bytes) { asm volatile("mbarrier.arrive.expect_tx.shared::cta.b64 _, [%0], %1;" :: "r"(bar), "r"(bytes) : "memory"); }
__device__ __forceinline__ void mbar_arrive(uint32_t bar) { asm volatile("mbarrier.arrive.shared::cta.b64 _, [%0];" :: "r"(bar) : "memory"); }
__device__ __forceinline__ bool mbar_try(uint32_t bar, uint32_t parity) {
    uint32_t ok;
    asm volatile("{\n .reg .pred p;\n mbarrier.try_wait.parity.shared::cta.b64 p, [%1], %2;\n selp.u32 %0, 1, 0, p;\n}" : "=r"(ok) : "r"(bar), "r"(parity) : "memory");
    return ok != 0;
}
__device__ __forceinline__ bool mbar_test(uint32_t bar, uint32_t parity) {
    uint32_t ok;
    asm volatile("{\n .reg .pred p;\n mbarrier.test_wait.parity.shared::cta.b64 p, [%1], %2;\n selp.u32 %0, 1, 0, p;\n}" : "=r"(ok) : "r"(bar), "r"(parity) : "memory");
    return ok != 0;
}
__device__ __forceinline__ void mbar_wait(uint32_t bar, uint32_t parity) {
    int n = 0;
    while (!mbar_try(bar, parity) && ++n < SPIN_LIMIT) {}
}
__device__ __forceinline__ unsigned long long gtime() { unsigned long long t; asm volatile("mov.u64 %0, %globaltimer;" : "=l"(t)); return t; }
__device__ __forceinline__ uint32_t gtime32() { uint32_t t; asm volatile("mov.u32 %0, %globaltimer_lo;" : "=r"(t)); return t; }
__device__ __forceinline__ void bar_main() { asm volatile("bar.sync 1, 256;" ::: "memory"); }

__device__ __forceinline__ void mma16816(float (&c)[4], uint32_t a0, uint32_t a1, uint32_t a2, uint32_t a3, uint32_t b0, uint32_t b1) {
    asm("mma.sync.aligned.m16n8k16.row.col.f32.bf16.bf16.f32 {%0,%1,%2,%3}, {%4,%5,%6,%7}, {%8,%9}, {%0,%1,%2,%3};"
        : "+f"(c[0]), "+f"(c[1]), "+f"(c[2]), "+f"(c[3]) : "r"(a0), "r"(a1), "r"(a2), "r"(a3), "r"(b0), "r"(b1));
}
__device__ __forceinline__ void mmaA(float (&c)[4], const uint32_t (&a)[4], uint32_t b0, uint32_t b1) { mma16816(c, a[0], a[1], a[2], a[3], b0, b1); }
__device__ __forceinline__ void mmaAv(float (&c)[4], const uint32_t (&a)[4], uint32_t b0, uint32_t b1) {
    asm volatile("mma.sync.aligned.m16n8k16.row.col.f32.bf16.bf16.f32 {%0,%1,%2,%3}, {%4,%5,%6,%7}, {%8,%9}, {%0,%1,%2,%3};"
        : "+f"(c[0]), "+f"(c[1]), "+f"(c[2]), "+f"(c[3]) : "r"(a[0]), "r"(a[1]), "r"(a[2]), "r"(a[3]), "r"(b0), "r"(b1) : "memory");
}
__device__ __forceinline__ void mma8(float (&c)[4], uint32_t a0, uint32_t a1, uint32_t b0) {
    asm("mma.sync.aligned.m16n8k8.row.col.f32.bf16.bf16.f32 {%0,%1,%2,%3}, {%4,%5}, {%6}, {%0,%1,%2,%3};"
        : "+f"(c[0]), "+f"(c[1]), "+f"(c[2]), "+f"(c[3]) : "r"(a0), "r"(a1), "r"(b0));
}
struct W80 { uint32_t a[2][4], c[2]; };
template <int N> __device__ __forceinline__ void mul80(float (&acc)[N][4], const W80 (&W)[N], const uint4& b, uint32_t b4) {
#pragma unroll
    for (int m = 0; m < N; m++) mmaA(acc[m], W[m].a[0], b.x, b.y);
#pragma unroll
    for (int m = 0; m < N; m++) mmaA(acc[m], W[m].a[1], b.z, b.w);
#pragma unroll
    for (int m = 0; m < N; m++) mma8(acc[m], W[m].c[0], W[m].c[1], b4);
}
__device__ __forceinline__ void ldsm2t(uint32_t (&r)[2], uint32_t addr) {
    asm volatile("ldmatrix.sync.aligned.m8n8.x2.trans.shared.b16 {%0,%1}, [%2];" : "=r"(r[0]), "=r"(r[1]) : "r"(addr) : "memory");
}
__device__ __forceinline__ void mmaV(float (&c)[4], const uint4& a, uint32_t b0, uint32_t b1) { mma16816(c, a.x, a.y, a.z, a.w, b0, b1); }
__device__ __forceinline__ void ldsm4(uint32_t (&r)[4], uint32_t addr) {
    asm volatile("ldmatrix.sync.aligned.m8n8.x4.shared.b16 {%0,%1,%2,%3}, [%4];" : "=r"(r[0]), "=r"(r[1]), "=r"(r[2]), "=r"(r[3]) : "r"(addr) : "memory");
}
__device__ __forceinline__ void ldsm4t(uint32_t (&r)[4], uint32_t addr) {
    asm volatile("ldmatrix.sync.aligned.m8n8.x4.trans.shared.b16 {%0,%1,%2,%3}, [%4];" : "=r"(r[0]), "=r"(r[1]), "=r"(r[2]), "=r"(r[3]) : "r"(addr) : "memory");
}
__device__ __forceinline__ uint32_t lds16(uint32_t a) { uint16_t v; asm volatile("ld.shared.u16 %0, [%1];" : "=h"(v) : "r"(a) : "memory"); return v; }
__device__ __forceinline__ uint32_t lds32(uint32_t a) { uint32_t v; asm volatile("ld.shared.u32 %0, [%1];" : "=r"(v) : "r"(a) : "memory"); return v; }
__device__ __forceinline__ float ldsf(uint32_t a) { return __uint_as_float(lds32(a)); }
__device__ __forceinline__ uint2 lds64(uint32_t a) { uint2 v; asm volatile("ld.shared.v2.u32 {%0,%1}, [%2];" : "=r"(v.x), "=r"(v.y) : "r"(a) : "memory"); return v; }
__device__ __forceinline__ uint4 lds128(uint32_t a) { uint4 v; asm volatile("ld.shared.v4.u32 {%0,%1,%2,%3}, [%4];" : "=r"(v.x), "=r"(v.y), "=r"(v.z), "=r"(v.w) : "r"(a) : "memory"); return v; }
__device__ __forceinline__ int ldsvol(uint32_t a) { int v; asm volatile("ld.volatile.shared.u32 %0, [%1];" : "=r"(v) : "r"(a) : "memory"); return v; }
__device__ __forceinline__ void stsvol(uint32_t a, int v) { asm volatile("st.volatile.shared.u32 [%0], %1;" :: "r"(a), "r"(v) : "memory"); }
__device__ __forceinline__ void sts_hi16(uint32_t a, float v) { asm volatile("{\n .reg .b16 lo, hi;\n mov.b32 {lo, hi}, %1;\n st.shared.u16 [%0], hi;\n}" :: "r"(a), "r"(__float_as_uint(v)) : "memory"); }
__device__ __forceinline__ void sts16(uint32_t a, uint32_t v) { asm volatile("st.shared.u16 [%0], %1;" :: "r"(a), "r"(v) : "memory"); }
__device__ __forceinline__ void sts32(uint32_t a, uint32_t v) { asm volatile("st.shared.u32 [%0], %1;" :: "r"(a), "r"(v) : "memory"); }
__device__ __forceinline__ void stsf(uint32_t a, float v) { sts32(a, __float_as_uint(v)); }
__device__ __forceinline__ void sts64(uint32_t a, uint32_t x, uint32_t y) { asm volatile("st.shared.v2.u32 [%0], {%1,%2};" :: "r"(a), "r"(x), "r"(y) : "memory"); }

__device__ __forceinline__ void sts_hi16_if(bool p, uint32_t a, float v) {
    asm volatile("{\n .reg .pred p;\n .reg .b16 lo, hi;\n setp.ne.u32 p, %2, 0;\n mov.b32 {lo, hi}, %1;\n @p st.shared.u16 [%0], hi;\n}" :: "r"(a), "r"(__float_as_uint(v)), "r"((uint32_t)p) : "memory");
}
__device__ __forceinline__ void sts32_if(bool p, uint32_t a, uint32_t v) {
    asm volatile("{\n .reg .pred p;\n setp.ne.u32 p, %2, 0;\n @p st.shared.u32 [%0], %1;\n}" :: "r"(a), "r"(v), "r"((uint32_t)p) : "memory");
}
__device__ __forceinline__ void sts64_if(bool p, uint32_t a, float x, float y) {
    asm volatile("{\n .reg .pred p;\n setp.ne.u32 p, %3, 0;\n @p st.shared.v2.f32 [%0], {%1,%2};\n}" :: "r"(a), "f"(x), "f"(y), "r"((uint32_t)p) : "memory");
}
__device__ __forceinline__ void arrive_if(bool p, uint32_t bar) {
    asm volatile("{\n .reg .pred p;\n setp.ne.u32 p, %1, 0;\n @p mbarrier.arrive.shared::cta.b64 _, [%0];\n}" :: "r"(bar), "r"((uint32_t)p) : "memory");
}
__device__ __forceinline__ void opaque(uint32_t& v) { asm volatile("" : "+r"(v)); }
__device__ __forceinline__ void keep(uint32_t& v) { asm volatile("" : "+r"(v)); }
__device__ __forceinline__ void keep(float& v) { asm volatile("" : "+f"(v)); }
template <class T> __device__ __forceinline__ void keep(T*& v) { asm volatile("" : "+l"(v)); }

__device__ __forceinline__ uint32_t ldp32(const char* p) { uint32_t v; asm volatile("ld.relaxed.gpu.global.u32 %0, [%1];" : "=r"(v) : "l"(p) : "memory"); return v; }
__device__ __forceinline__ uint2 ldp64(const char* p) {
    uint2 v; asm volatile("{\n .reg .b64 d;\n ld.relaxed.gpu.global.b64 d, [%2];\n mov.b64 {%0,%1}, d;\n}" : "=r"(v.x), "=r"(v.y) : "l"(p) : "memory"); return v;
}
__device__ __forceinline__ uint32_t tagw(float f, uint32_t par) { return (__float_as_uint(f) & ~1u) | par; }
__device__ __forceinline__ void stp32(char* p, float a, uint32_t par) { asm volatile("st.relaxed.gpu.global.u32 [%0], %1;" :: "l"(p), "r"(tagw(a, par)) : "memory"); }
__device__ __forceinline__ void stp64(char* p, float a, float b, uint32_t par) {
    asm volatile("{\n .reg .b64 d;\n mov.b64 d, {%1,%2};\n st.relaxed.gpu.global.b64 [%0], d;\n}" :: "l"(p), "r"(tagw(a, par)), "r"(tagw(b, par)) : "memory");
}
__device__ __forceinline__ void stp32_if(bool p, char* d, float a, uint32_t par) {
    asm volatile("{\n .reg .pred p;\n setp.ne.u32 p, %2, 0;\n @p st.relaxed.gpu.global.u32 [%0], %1;\n @p st.relaxed.gpu.global.u32 [%0+4096], %1;\n}" :: "l"(d), "r"(tagw(a, par)), "r"((uint32_t)p) : "memory");
}
__device__ __forceinline__ void stp64_if(bool p, char* d, uint32_t lo, uint32_t hi) {
    asm volatile("{\n .reg .pred p;\n .reg .b64 d;\n setp.ne.u32 p, %3, 0;\n mov.b64 d, {%1,%2};\n @p st.relaxed.gpu.global.b64 [%0], d;\n @p st.relaxed.gpu.global.b64 [%0+4096], d;\n}" :: "l"(d), "r"(lo), "r"(hi), "r"((uint32_t)p) : "memory");
}
__device__ __forceinline__ uint32_t chk2(uint32_t a, uint32_t b, uint32_t par) { uint32_t r; asm("lop3.b32 %0, %1, %2, %3, 0x7E;" : "=r"(r) : "r"(a), "r"(b), "r"(par)); return r; }
__device__ __forceinline__ uint32_t or3(uint32_t a, uint32_t b, uint32_t c) { uint32_t r; asm("lop3.b32 %0, %1, %2, %3, 0xFE;" : "=r"(r) : "r"(a), "r"(b), "r"(c)); return r; }
__device__ __forceinline__ uint32_t chk8(const uint32_t (&v)[8], uint32_t par) { return or3(chk2(v[0], v[1], par), chk2(v[2], v[3], par), or3(chk2(v[4], v[5], par), chk2(v[6], v[7], par), 0)); }
__device__ __forceinline__ uint32_t chk8(const uint2 (&v)[8], uint32_t par) { return or3(chk2(v[0].x, v[1].x, par), chk2(v[2].x, v[3].x, par), or3(chk2(v[4].x, v[5].x, par), chk2(v[6].x, v[7].x, par), 0)); }
__device__ __forceinline__ uint32_t chk8y(const uint2 (&v)[8], uint32_t par) { return or3(chk2(v[0].y, v[1].y, par), chk2(v[2].y, v[3].y, par), or3(chk2(v[4].y, v[5].y, par), chk2(v[6].y, v[7].y, par), 0)); }
__device__ __forceinline__ uint32_t chk4(const uint2 (&v)[4], uint32_t par) { return or3(chk2(v[0].x, v[0].y, par), chk2(v[1].x, v[1].y, par), or3(chk2(v[2].x, v[2].y, par), chk2(v[3].x, v[3].y, par), 0)); }
__device__ __forceinline__ float asf(uint32_t v) { return __uint_as_float(v); }
__device__ __forceinline__ float sum8(const uint32_t (&v)[8]) { return ((asf(v[0]) + asf(v[1])) + (asf(v[2]) + asf(v[3]))) + ((asf(v[4]) + asf(v[5])) + (asf(v[6]) + asf(v[7]))); }
__device__ __forceinline__ float sum8x(const uint2 (&v)[8]) { return ((asf(v[0].x) + asf(v[1].x)) + (asf(v[2].x) + asf(v[3].x))) + ((asf(v[4].x) + asf(v[5].x)) + (asf(v[6].x) + asf(v[7].x))); }
__device__ __forceinline__ float sum8y(const uint2 (&v)[8]) { return ((asf(v[0].y) + asf(v[1].y)) + (asf(v[2].y) + asf(v[3].y))) + ((asf(v[4].y) + asf(v[5].y)) + (asf(v[6].y) + asf(v[7].y))); }

__device__ __forceinline__ uint32_t pack2(float lo, float hi) { uint32_t r; asm("cvt.rn.bf16x2.f32 %0, %1, %2;" : "=r"(r) : "f"(hi), "f"(lo)); return r; }
__device__ __forceinline__ float bfr(float x) { return __uint_as_float(pack2(0.0f, x)); }
__device__ __forceinline__ float ex2(float x) { float r; asm("ex2.approx.ftz.f32 %0, %1;" : "=f"(r) : "f"(x)); return r; }
__device__ __forceinline__ float rcp(float x) { float r; asm("rcp.approx.ftz.f32 %0, %1;" : "=f"(r) : "f"(x)); return r; }
__device__ __forceinline__ float sqrt_(float x) { float r; asm("sqrt.approx.ftz.f32 %0, %1;" : "=f"(r) : "f"(x)); return r; }
__device__ __forceinline__ float bf_lo(uint32_t v) { return __uint_as_float(v << 16); }
__device__ __forceinline__ float bf_hi(uint32_t v) { return __uint_as_float(v & 0xffff0000u); }
__device__ __forceinline__ float sel4(int k, float a, float b, float c, float d) { return (k & 2) ? ((k & 1) ? d : c) : ((k & 1) ? b : a); }
constexpr float LOG2E = 1.4426950408889634f;
constexpr uint32_t ONES = 0x3f803f80u;

__device__ __forceinline__ void ln_stats(float sum, float sq, float& mean, float& den) {
    const float m = sum * (1.0f / 640.0f);
    const float var = fmaxf(fmaf(sq, 1.0f / 640.0f, -m * m), 0.0f);
    mean = bfr(m);
    den = bfr(sqrt_(bfr(bfr(var) + 1e-5f)));
}
__device__ __forceinline__ float sigmoidf_(float x) { return rcp(1.0f + ex2(-x * LOG2E)); }

#define TSTAMP(k) do {} while (0)
#define TST(k) do {} while (0)

#define CSTAMP(k) do {} while (0)
template <int N> __device__ __forceinline__ uint32_t lag(uint32_t sb, uint32_t z = 0) {
#pragma unroll
    for (int k = 0; k < N; k++) z = ldsvol(sb + S_ZERO + z);
    return z;
}
__device__ __forceinline__ void warm_mma(uint32_t& a, uint32_t& b) {
    asm volatile("mma.sync.aligned.m16n8k8.row.col.f16.f16.f16.f16 {%0,%1}, {%0,%1}, {%0}, {%0,%1};" : "+r"(a), "+r"(b) :: "memory");
}
#define KWNS2 20
#define KWNS 200
template <int STRIDE>
__device__ __forceinline__ float gather8(const char* p, uint32_t par) {
    uint32_t v[8];
    int guard = 0;
    do {
#pragma unroll
        for (int s = 0; s < 8; s++) v[s] = ldp32(p + s * STRIDE);
    } while ((chk8(v, par) & 1) && ++guard < SPIN_LIMIT);
    return sum8(v);
}
template <class F>
__device__ __forceinline__ void gather16(const char* p, uint32_t par, int k, F use) {
    uint32_t v[8], u[8];
    int guard = 0;
    bool again;
    do {
#pragma unroll
        for (int s = 0; s < 8; s++) v[s] = ldp32(p + s * 512);
#pragma unroll
        for (int s = 0; s < 8; s++) u[s] = ldp32(p + HALF + s * 512);
        const uint32_t stale = use(sum8(v) + sum8(u), ((v[0] ^ par) & 1) * 8);
        again = __any_sync(~0u, (or3(chk8(v, par), chk8(u, par), stale) & 1) != 0);
    } while (again & (++guard < SPIN_LIMIT));
    SWEEPS(k, guard - 1);
}

struct Params {
    const __nv_bfloat16 *x, *k, *v, *wr;
    __nv_bfloat16* out;
};
struct Maps { CUtensorMap k, v, vu, wq, wo, wg, wu, wd; };

constexpr int KV_BATCH_KEYS = 32 * 4096;

__device__ __forceinline__ void tma2d(uint32_t dst, const CUtensorMap* m, int c0, int c1, uint32_t bar, uint32_t bytes, uint64_t pol) {
    asm volatile("{\n .reg .pred p;\n elect.sync _|p, 0xffffffff;\n"
                 " @p mbarrier.arrive.expect_tx.shared::cta.b64 _, [%2], %6;\n"
                 " @p cp.async.bulk.tensor.2d.shared::cluster.global.mbarrier::complete_tx::bytes.L2::cache_hint [%0], [%1, {%3, %4}], [%2], %5;\n}"
                 :: "r"(dst), "l"(m), "r"(bar), "r"(c0), "r"(c1), "l"(pol), "r"(bytes) : "memory");
}
__device__ __forceinline__ void scrap_copy(uint32_t dst, const char* src, uint32_t bar) {
    asm volatile("{\n .reg .pred p;\n elect.sync _|p, 0xffffffff;\n"
                 " @p mbarrier.arrive.expect_tx.shared::cta.b64 _, [%2], 12288;\n"
                 " @p cp.async.bulk.shared::cluster.global.mbarrier::complete_tx::bytes [%0], [%1], 4096, [%2];\n"
                 " @p cp.async.bulk.shared::cluster.global.mbarrier::complete_tx::bytes [%0], [%1+4096], 4096, [%2];\n"
                 " @p cp.async.bulk.shared::cluster.global.mbarrier::complete_tx::bytes [%0], [%1+8192], 4096, [%2];\n}"
                 :: "r"(dst), "l"(src), "r"(bar) : "memory");
}
__device__ __forceinline__ void prefetch_l2(const void* p, uint32_t bytes) {
    asm volatile("{\n .reg .pred p;\n elect.sync _|p, 0xffffffff;\n @p cp.async.bulk.prefetch.L2.global [%0], %1;\n}" :: "l"(p), "r"(bytes) : "memory");
}
__device__ __forceinline__ uint64_t pol_first() { uint64_t p; asm("createpolicy.fractional.L2::evict_first.b64 %0, 1.0;" : "=l"(p)); return p; }
__device__ __forceinline__ uint64_t pol_normal() { uint64_t p; asm("createpolicy.fractional.L2::evict_normal.b64 %0, 1.0;" : "=l"(p)); return p; }
__device__ __forceinline__ bool utest(uint32_t bar, uint32_t parity) { return __all_sync(~0u, mbar_test(bar, parity)); }
__device__ __forceinline__ void uwait(uint32_t bar, uint32_t parity) {
    int n = 0;
    while (!__all_sync(~0u, mbar_try(bar, parity)) && ++n < SPIN_LIMIT) {}
}
template <int A, int B, int CNT> __device__ __forceinline__ void init_bars(uint32_t sb) {
#pragma unroll 1
    for (int k = A; k < B; k++)
        asm volatile("{\n .reg .pred p;\n elect.sync _|p, 0xffffffff;\n @p mbarrier.init.shared::cta.b64 [%0], %1;\n}" :: "r"(sb + S_BAR + 8 * k), "n"(CNT) : "memory");
}
__device__ __forceinline__ int first_key() { return (blockIdx.x >> 2) * 4096 + 3072 + (blockIdx.x & 3) * 256; }
__device__ __forceinline__ void load_tile(const CUtensorMap* m, uint32_t dst, uint32_t bar, uint32_t bytes, int key, uint64_t pol) { tma2d(dst, m, 0, 3 * key, bar, bytes, pol); }
__device__ __forceinline__ const char* unit_ptr(const Params& P, int n) {
    return (const char*)((n & 16) ? P.v : P.k) + (size_t)(first_key() + (n >> 5) * KV_BATCH_KEYS + (n & 15) * 16) * 384;
}
#define LSTAMP(k) do {} while (0)

__device__ __forceinline__ uint32_t k_place(uint32_t b, uint32_t s) { return s + 3 + 5 * (b & 1); }
__device__ __forceinline__ uint32_t v_place(uint32_t b, uint32_t s) { return s < 3 ? s : s + 8 - 8 * (b & 1); }
__device__ __forceinline__ void k_load(const Maps& M, uint32_t dst, uint32_t bar, int key8, uint64_t pol) {
    asm volatile("{\n .reg .pred p;\n elect.sync _|p, 0xffffffff;\n"
                 " @p mbarrier.arrive.expect_tx.shared::cta.b64 _, [%2], 6144;\n"
                 " @p cp.async.bulk.tensor.4d.shared::cluster.global.mbarrier::complete_tx::bytes.L2::cache_hint [%0], [%1, {0, 0, 0, %3}], [%2], %4;\n}"
                 :: "r"(dst), "l"(&M.k), "r"(bar), "r"(key8), "l"(pol) : "memory");
}
__device__ __forceinline__ int unit_key8(uint32_t n) { return first_key() / 8 + (n >> 4) * (KV_BATCH_KEYS / 8) + 2 * (n & 15); }
__device__ __forceinline__ void ring_load(const Maps& M, uint32_t sb, uint32_t b, uint32_t u, uint32_t pos) {
    if (u < 16) k_load(M, sb + pos * UNIT, sb + S_RING + 8 * pos, unit_key8(16 * b + u), pol_normal());
    else load_tile(&M.vu, sb + pos * UNIT, sb + S_FV + 4 * (pos & 6), UNIT, first_key() + b * KV_BATCH_KEYS + 16 * pos, pol_first());
}
__device__ __forceinline__ uint32_t token(bool p, uint32_t a, uint32_t n) {
    uint32_t v;
    asm volatile("{\n .reg .pred p;\n setp.ne.u32 p, %2, 0;\n mov.u32 %0, 0;\n @p atom.shared.exch.b32 %0, [%1], %3;\n}" : "=r"(v) : "r"(a), "r"((uint32_t)p), "r"(n) : "memory");
    return v;
}
__device__ __forceinline__ void place_load(const Maps& M, uint32_t sb, uint32_t n) {
    k_load(M, sb + k_place(n >> 4, 0) * SLOT + (n & 15) * UNIT, sb + S_FK + 4 * (n & 14), unit_key8(n), pol_first());
}
__device__ __forceinline__ void v_load(const Maps& M, uint32_t sb, uint32_t b, uint32_t s) {
    load_tile(&M.v, sb + v_place(b, s) * SLOT, sb + S_FV + 8 * s, SLOT, first_key() + b * KV_BATCH_KEYS + 32 * s, pol_first());
}
__device__ __forceinline__ bool due(uint32_t t) { return __all_sync(~0u, (int)(gtime32() * 16 - t) >= 0); }
__device__ __forceinline__ bool reached(uint32_t a, int v) { return __all_sync(~0u, ldsvol(a) >= v); }

__device__ __forceinline__ void stream_warp(const Params& P, const Maps& M, uint32_t sb, uint32_t lane) {
    const uint64_t pol = pol_first();
    const int bid = blockIdx.x, g = bid >> 3, i = bid & 7;
    const uint32_t wf = sb + S_WFULL;
    if (PF0 > 0 && !PFTOP) prefetch_l2(unit_ptr(P, 0), PF0 * UNIT);
    uint32_t tn = __shfl_sync(~0u, gtime32(), 0) * 16 - T_LEAD;
    auto pace = [&](uint32_t dt) {
        int k = 0;
        uint32_t now;
        do now = __shfl_sync(~0u, gtime32(), 0) * 16; while ((int)(now - tn) < 0 && ++k < SPIN_LIMIT);
        if ((int)(now - tn) > SLACK0) tn = now - SLACK0;
        tn += dt;
    };
#pragma unroll
    for (int k = 0; k < 10; k++) {
        if (k < 2) {
            if (k == 0) init_bars<26, 27, 1>(sb); else init_bars<27, 37, 1>(sb);
            asm volatile("fence.mbarrier_init.release.cluster;" ::: "memory");
            if (k == 1) { asm volatile("bar.arrive 2, %0;" :: "n"(NTHR) : "memory"); asm volatile("bar.sync 3, 128;" ::: "memory"); }
        }
        if (k >= WIN_W) uwait(wf + 8 * (k - WIN_W), 0);
        pace(TAUW * 5 / 2);
        if (k < 4) tma2d(sb + ST_WQ + 15360 * k, &M.wq, 384 * g + 192 * (k >> 1), 80 * i + 40 * (k & 1), wf + 8 * k, 15360, pol);
        else if (k < 6) tma2d(sb + ST_WG + 15360 * (k - 4), k == 4 ? &M.wg : &M.wu, 96 * g, 80 * i, wf + 8 * k, 15360, pol);
        else tma2d(sb + ST_WO + 15360 * (k - 6), &M.wo, 80 * i, 384 * g + 96 * (k - 6), wf + 8 * k, 15360, pol);
    }
#pragma unroll 1
    for (int n = 0; n < 16; n++) {
        if (n == 0 || n == 5 || n == 11) uwait(sb + S_RELW + (n == 0 ? 0 : n == 5 ? 8 : 16), 0);
        uwait(n < WIN_S ? wf + 8 * (10 - WIN_S + n) : sb + S_FV + 8 * ((n - WIN_S) ^ 8), 0);
        pace(max(min(2 * n + 2 - PF0, 2), 0) * TAU0);
        if (n < 8) { place_load(M, sb, 2 * n); place_load(M, sb, 2 * n + 1); }
        else if (n < 11) { ring_load(M, sb, 0, 2 * n, 2 * n - 16); ring_load(M, sb, 0, 2 * n + 1, 2 * n - 15); }
        else v_load(M, sb, 0, n - 8);
        if (n == 7) { pace(TAUW * 5 / 2); tma2d(sb + S_WD, &M.wd, 80 * i, 96 * g, wf + 80, 15360, pol); }
    }
    int nd = 0;
    uint32_t q[4];
#pragma unroll
    for (int r = 0; r < 4; r++) q[r] = sb + S_FV + 8 * (7 - r);
    tn -= TSH;
    uint32_t td = tn;
    uint32_t pos = 2;
#pragma unroll 1
    for (int m = 16; m < 64; m++) {
        const int b = m >> 4, j = m & 15;
        const char* src = unit_ptr(P, 2 * m);
        const uint32_t tok = sb + S_TOK + (j < 3 ? 4 * pos : j < 11 ? 24 + 4 * pos : 16 + 4 * j) + 4 * lane;
        static_assert(WIN_U <= 12, "a ring position has at most one token of the timetable");
        int k = 0;
        while (true) {
            const uint2 c = lds64(sb + S_KF);
            if (__all_sync(~0u, mbar_test(q[WIN_S - 1] & ~1u, q[WIN_S - 1] & 1) & (min((int)c.x + 1, (int)c.y) >= 16 * b + min(2 * j + 2 - WIN_U, 16))) || ++k >= SPIN_LIMIT) break;
        }
        uint32_t now;
        while (true) {
            now = __shfl_sync(~0u, gtime32(), 0) * 16;
            if ((int)(now - td) >= 0 || ++k >= SPIN_LIMIT) break;
            if (PSLEEP > 0 && (int)(td - now) > 16 * PSLEEP * 2) __nanosleep(PSLEEP);
        }
        const uint32_t mine = __ballot_sync(~0u, token(lane < (j < 11 ? 2 : 1), tok, 2 * m + lane) == 2 * m + lane);
        q[3] = q[2]; q[2] = q[1]; q[1] = q[0]; q[0] = sb + S_QRDY;
        if (j < 11) {
            if (mine & 1) ring_load(M, sb, b, 2 * j, pos); else prefetch_l2(src, UNIT);
            if (mine & 2) ring_load(M, sb, b, 2 * j + 1, pos + 1); else prefetch_l2(src + UNIT, UNIT);
            if (j >= 8) q[0] = (sb + S_FV + 8 * (j - 8)) | (b & 1);
        } else if (mine) { v_load(M, sb, b, j - 8); q[0] = (sb + S_FV + 8 * (j - 8)) | (b & 1); }
        else if (j - 8 >= VPF) prefetch_l2(src, SLOT);
        else {
            scrap_copy(sb + S_DUMMY, src, sb + S_DBAR + 8 * (nd & 3));
            q[0] = (sb + S_DBAR + 8 * (nd & 3)) | ((nd >> 2) & 1);
            nd++;
        }
        pos = j == 15 ? 2 : pos == 4 ? 0 : pos + 2;
        if ((int)(now - tn) > SLACK) tn = now - SLACK;
        tn += 2 * TAU;
        td = (int)(tn - now) > 2 * TMIN ? tn : now + 2 * TMIN;
        if (m >= 48 + JFREE) td = now + TFREE;
    }
#pragma unroll 1
    for (int m = max(nd - 4, 0); m < nd; m++) uwait(sb + S_DBAR + 8 * (m & 3), (m >> 2) & 1);
}

__host__ __device__ constexpr uint64_t bit_list(uint32_t m) { uint64_t r = 0; int n = 0; for (int k = 0; k < 12; k++) if ((m >> k) & 1) r |= (uint64_t)k << (4 * n++); return r; }
__device__ __forceinline__ float scaled(float s) { return bfr(bfr(s) * 0.07216878364870322f); }
__device__ __forceinline__ void probs(float s, uint32_t ps, uint32_t src, uint32_t ln) {
    const uint32_t q8 = ln >> 2, t4 = ln & 3;
    int key = __float_as_int(s);
    key ^= (key >> 31) & 0x7fffffff;
    key = __reduce_max_sync(~0u, key);
    key ^= (key >> 31) & 0x7fffffff;
    const float ml = __int_as_float(key) * LOG2E;
    sts16(ps + 64 * src + (q8 >> 1) * 16 + t4 * 4 + (q8 & 1) * 2, pack2(ex2(fmaf(s, LOG2E, -ml)), 0.f));
    stsf(ps + PS_MAX + 4 * src, ml);
}
template <int H> __device__ __forceinline__ uint32_t b_pos(uint32_t e) { const uint32_t h = e >= H, k = e - H * h; return h * 192 + (k & 6) * 24 + (k >> 3) * 4 + (k & 1) * 2; }
__device__ __forceinline__ uint32_t a_pos(uint32_t e) { const uint32_t h = e >= 40, k = e - 40 * h; return (k & 6) * 24 + (k >> 3) * 8 + h * 4 + (k & 1) * 2; }
__device__ __forceinline__ uint32_t q_pos(uint32_t d) { const uint32_t s = 3 * ((d >> 4) & 3) + (d >> 6); return s * 32 + (d & 6) * 4 + ((d >> 3) & 1) * 4 + (d & 1) * 2; }
__device__ __forceinline__ uint32_t k_off(uint32_t ln) { return (ln & 8) * 384 + (ln & 7) * 128 + (((ln & 7) ^ (ln >> 4)) << 4); }

#define HSTAMP(k) do {} while (0)
__device__ __forceinline__ char* xwindow() { return reinterpret_cast<char*>((reinterpret_cast<uintptr_t>(g_x) + (2u << 20) - 1) & ~(uintptr_t)((2u << 20) - 1)); }

struct XPtr {
    uint32_t lo, hi;
    __device__ __forceinline__ explicit XPtr(char* p) : lo((uint32_t)(uintptr_t)p), hi((uint32_t)((uintptr_t)p >> 32)) {}
    __device__ __forceinline__ XPtr(uint32_t l, uint32_t h) : lo(l), hi(h) {}
    __device__ __forceinline__ XPtr operator+(uint32_t o) const { return XPtr(lo + o, hi); }
    __device__ __forceinline__ operator char*() const { uint64_t p; asm("mov.b64 %0, {%1, %2};" : "=l"(p) : "r"(lo), "r"(hi)); return (char*)p; }
};
__device__ __forceinline__ void keep(XPtr& v) { keep(v.lo); }

__device__ __forceinline__ void side_warp(uint32_t sb) {
    const uint32_t bid = blockIdx.x, g = bid >> 3, i = bid & 7, P = pairG(0, 0, i);
    char* p = xwindow() + P * 8192 + (g >> 3) * HALF + (g & 7) * 512 + 448;
    uint32_t best[2] = {~0u, ~0u};
    asm volatile("st.relaxed.gpu.global.b32 [%0], 1;" :: "l"(p) : "memory");
    asm volatile("st.relaxed.gpu.global.b32 [%0], 1;" :: "l"(p + COPY) : "memory");
#pragma unroll 1
    for (int r = 0; r < 64; r++) {
        if (r >= 4 && !(r & 1) && min(best[0], best[1]) < 380 && max(best[0], best[1]) > min(best[0], best[1]) + 80) break;
        uint32_t c0, c1, v;
        asm volatile("mov.u32 %0, %clock;" : "=r"(c0) :: "memory");
        asm volatile("atom.relaxed.gpu.global.exch.b32 %0, [%1], 0;" : "=r"(v) : "l"(p + (r & 1) * COPY) : "memory");
        asm volatile("{\n .reg .pred q;\n setp.eq.u32 q, %1, 0x13579bdf;\n mov.u32 %0, 0;\n @!q mov.u32 %0, %clock;\n}" : "=r"(c1) : "r"(v) : "memory");
        if (r & 1) best[1] = min(best[1], c1 - c0); else best[0] = min(best[0], c1 - c0);
    }
    stsvol(sb + S_SIDE, 1 + ((best[1] < best[0]) ^ (__popc(P & PMASK) & 1)));
}

template <int N>
__device__ __forceinline__ void hop_a(const char* src, uint32_t par, uint32_t dst, bool st, int k) {
    uint2 v[N][4];
    float e[4], rl;
    int guard = 0;
    bool again;
    do {
#pragma unroll
        for (int s = 0; s < 4 * N; s++) v[s / 4][s % 4] = ldp64(src + (s / 4) * 256 + (s % 4) * 1024);
        again = __any_sync(~0u, ((chk4(v[0], par) | chk4(v[N - 1], par)) & 1) != 0);
        const int M = max(max((int)v[0][0].x, (int)v[0][1].x), max((int)v[0][2].x, (int)v[0][3].x)) - 254;
#pragma unroll
        for (int s = 0; s < 4; s++) e[s] = __int_as_float(max((int)v[0][s].x - M, 0) << 22);
        rl = rcp(fmaf(e[0], asf(v[0][0].y), e[1] * asf(v[0][1].y)) + fmaf(e[2], asf(v[0][2].y), e[3] * asf(v[0][3].y)));
#pragma unroll
        for (int s = 0; s < 4; s++) e[s] = __shfl_sync(~0u, e[s], 24);
        keep(rl);
    } while (again & (++guard < SPIN_LIMIT));
    rl = __shfl_sync(~0u, rl, 24);
#pragma unroll
    for (int n = 0; n < N; n++) {
        const float o0 = fmaf(e[0], asf(v[n][0].x), e[1] * asf(v[n][1].x)) + fmaf(e[2], asf(v[n][2].x), e[3] * asf(v[n][3].x));
        const float o1 = fmaf(e[0], asf(v[n][0].y), e[1] * asf(v[n][1].y)) + fmaf(e[2], asf(v[n][2].y), e[3] * asf(v[n][3].y));
        sts32_if(st, dst + 192 * n, pack2(o0 * rl, o1 * rl));
    }
    SWEEPS(k, guard - 1);
    __syncwarp();
}

__device__ __forceinline__ void score_warp(const Maps& M, uint32_t sb, uint32_t h, uint32_t ln) {
    const uint32_t lane0 = ln;
    uwait(sb + S_QRDY, 0);
    const uint32_t q8 = ln >> 2;
    const uint32_t k0 = k_off(ln);
    uint32_t pos = h + 6, bar = sb + S_FK, par = 0, phases = 0;
    uint2 q = lds64(sb + S_QS + 8 * ln), qh = lds64(sb + S_QS + 8 * ln + 256);
    auto first_round = [&](uint32_t b, uint32_t ln) {
        uwait(sb + S_RELR, b & 1);
        const uint32_t u = h + 2 * ln, p = u < 4 ? u + 2 : u - 4;
        uint32_t todo = __ballot_sync(~0u, token(ln < 3, sb + S_TOK + 4 * p, 32 * b + 32 + u) == 32 * b + 32 + u);
#pragma unroll 1
        for (uint32_t r = h; todo; todo >>= 1, r += 2) if (todo & 1) ring_load(M, sb, b + 1, r, r < 4 ? r + 2 : r - 4);
    };
#pragma unroll 1
    for (uint32_t n = h; n < 64; n += 2) {
        HSTAMP(0);
        const uint32_t ua = sb + pos * UNIT;
        if (!__all_sync(~0u, mbar_try(bar, par))) uwait(bar, par);
        HSTAMP(1);
        float acc[2][4] = {};
        uint32_t mine = 0;
        const uint32_t id = n + (n & 48) + 6;
#pragma unroll
        for (int s = 0; s < 12; s++) {
            uint32_t kf[4];
            ldsm4(kf, (k0 ^ (32 * (s / 3))) + (ua + 1024 * (s % 3)));
            if (s == 11) {
                __syncwarp();
                mine = token(ln == 0 && n >= 16, sb + S_TOK + 24 + 4 * pos, id);
                stsvol(sb + S_KF + 4 * h, n + 1);
            }
            const bool m = q8 == (s & 7);
            mmaA(acc[s & 1], kf, m ? (s < 8 ? q.x : qh.x) : 0u, m ? (s < 8 ? q.y : qh.y) : 0u);
        }
        const uint32_t pos0 = pos;
        const bool last = (n & 14) == 14;
        pos = last ? h + 2 : n >= 16 && pos >= 4 ? h : pos + 2;
        bar = n >= 14 ? sb + S_RING + 8 * pos : bar + 8;
        par = n >= 14 ? (phases >> pos) & 1 : 0;
        phases ^= n >= 14 ? 1u << pos : 0;
        const float w0 = (acc[0][0] + acc[0][1]) + (acc[1][0] + acc[1][1]), w1 = (acc[0][2] + acc[0][3]) + (acc[1][2] + acc[1][3]);
        HSTAMP(2);
        if (__any_sync(~0u, mine == id)) ring_load(M, sb, n >> 4, (n & 15) + 6, pos0);
        HSTAMP(3);
        float s = ((ln & 1) ? w1 : w0) + __shfl_xor_sync(~0u, (ln & 1) ? w0 : w1, 1);
        s += __shfl_xor_sync(~0u, s, 2);
        sts_hi16(sb + S_SC + (((n & 12) >> 1) + h) * 64 + (n & 2) * 2 + (ln & 29) * 2, scaled(s));
        if (last) {
            __syncwarp();
            arrive_if(ln == 0, sb + S_SCO);
            const uint32_t b = n >> 4, ln = lane0 + lag<1>(sb);
            if (b > 0) {
                uwait(sb + S_RELK, (b - 1) & 1);
                if (h == 0) LSTAMP(64 + 2 * b);
                const uint32_t sl = 3 + h + 2 * ln, idv = 32 * b + 16 + 2 * sl;
                uint32_t todo = __ballot_sync(~0u, token(sl < 8, sb + S_TOK + 48 + 4 * sl, idv) == idv);
#pragma unroll 1
                for (uint32_t r = 3 + h; todo; todo >>= 1, r += 2) if (todo & 1) v_load(M, sb, b, r);
                const uint32_t g = blockIdx.x >> 3, pr = pairL(RA, 1, g), side = ldsvol(sb + S_SIDE);
                const char* src = xwindow() + pr * 8192 + ((side ^ 1 ^ __popc(pr & PMASK)) & 1) * COPY + h * HALF + 8 * min(ln, 24u);
                uwait(sb + S_RELV, (b - 1) & 1);
                __nanosleep(HOP1_NS);
#pragma unroll 1
                for (uint32_t r = 0; r < 4; r += 2) {
                    hop_a<2>(src + 256 * r, b & 1, sb + S_OS + 192 * (4 * h + r) + 96 + 4 * ln, ln < 24, 25);
                    if (r == RELR_AT && b < 3) first_round(b, ln);
                }
                arrive_if(ln == 0, sb + S_OS1);
            } else first_round(0, ln);
            q = lds64(sb + S_QS + 24 * ((n + 2) & 48) + 8 * ln); qh = lds64(sb + S_QS + 24 * ((n + 2) & 48) + 8 * ln + 256);
        }
    }
}

__global__ void __launch_bounds__(NTHR, 1)
fused_kernel(const Params P, const __grid_constant__ Maps M) {
    extern __shared__ __align__(1024) unsigned char smem[];
    const uint32_t sb = smem_u32(smem);
    const int tid = threadIdx.x, bid = blockIdx.x;
    if (PFTOP && tid == 0) {
        if (PFTOP == 2) asm volatile("prefetch.tensormap [%0];" :: "l"(&M.wq) : "memory");
        asm volatile("cp.async.bulk.prefetch.L2.global [%0], %1;" :: "l"(unit_ptr(P, 0)), "r"(PF0 * UNIT) : "memory");
    }
    const int w = __shfl_sync(~0u, tid >> 5, 0), lane = tid & 31;

    if (w >= 8) {
        asm volatile("setmaxnreg.dec.sync.aligned.u32 " REG_LO ";");
        if (w == 8) {
            stream_warp(P, M, sb, lane);
        } else {
            if (PFMAP && w == 11 && lane < 8) asm volatile("prefetch.tensormap [%0];" :: "l"(&M.k + lane) : "memory");
            if (w == 9) { init_bars<0, 3, 2>(sb); init_bars<3, 8, 1>(sb); init_bars<16, 22, 1>(sb); }
            else if (w == 10) { init_bars<8, 16, 2>(sb); init_bars<22, 26, 1>(sb); }
            else { init_bars<37, 38, 1>(sb); init_bars<38, 40, 8>(sb); init_bars<40, 41, 1>(sb); init_bars<41, 44, 8>(sb); init_bars<44, 46, 2>(sb); stsvol(sb + S_ZERO + 4 * lane, 0); }
            asm volatile("fence.mbarrier_init.release.cluster;" ::: "memory");
            asm volatile("bar.arrive 3, 128;" ::: "memory");
            asm volatile("bar.sync 2, %0;" :: "n"(NTHR) : "memory");
            if (w < 11) score_warp(M, sb, w - 9, lane);
            else {
                if (lane == 0) side_warp(sb);
                __syncwarp();
                uint32_t a = 0, b = 0;
                int k = 0;
                while (ldsvol(sb + S_GATE) == 0 && ++k < SPIN_LIMIT) { warm_mma(a, b); __nanosleep(KWNS); }
                uint4* d = reinterpret_cast<uint4*>(reinterpret_cast<char*>(g_s) + XS + bid * 7680) + lane;
                const uint4 z = make_uint4(0, 0, 0, 0);
#pragma unroll 1
                for (int u = 0; u < 15; u++) d[32 * u] = z;
                d = reinterpret_cast<uint4*>(reinterpret_cast<char*>(g_s) + XS2 + bid * 768) + lane;
                d[0] = z;
                if (lane < 16) d[32] = z;
                const uint32_t side = (ldsvol(sb + S_SIDE) & 1) ^ 1, g = bid >> 3, i = bid & 7;
                const XPtr gx(xwindow());
                auto nearp = [&](uint32_t pr) { return gx.lo + pr * 8192 + ((side ^ __popc(pr & PMASK)) & 1) * COPY; };
                const uint32_t own = (i >> 2) * HALF + (i & 3) * 1024 + (lane & 7) * 128;
                const uint32_t pAC = nearp(pairL(lane >> 4, (lane >> 3) & 1, g)) + own, pE = nearp(pairL(RE, (lane >> 3) & 1, g)) + own;
                const uint32_t pG = nearp(pairG((lane >> 2) & 1, (lane >> 3) & 1, i)) + min(lane & 3, 2) * 128;
                uint32_t tr = 0, tk = 0, ph = 0, src = g + (lane >> 4), seen = 0, n = 16, cs = 0;
                bool go = false, first = true;
                while (n < 64 && ++k < SPIN_LIMIT) {
                    const uint32_t now = __shfl_sync(~0u, gtime32(), 0) * 16;
                    if (!go && utest((n & 15) < KRE_EARLY ? sb + S_RELK : sb + S_RELV, ((n >> 4) & 1) ^ 1)) { go = true; if ((int)(now - tk) > 0 || !(n & 15)) tk = now; }
                    if (go && (int)(now - tk) >= 0) {
                        place_load(M, sb, (n & 16) ? n : (n & 48) | ((n + 10) & 15));
                        tk += n >= 48 ? KRE_TAU3 : (n & 15) < KRE_N1 ? KRE_TAU1 : KRE_TAU;
                        n++;
                        go = (n & 15) != 0 && (n & 15) != KRE_EARLY;
                        if (!(n & 15)) LSTAMP(63 + (n >> 3));
                    } else if (first || (int)(now - tr) >= 0) {
                        first = false;
                        tr = now + RFR_TAU;
                        b |= seen & a;
                        warm_mma(a, b);
                        if (RFR_ON) seen = ldp32(XPtr(ph == 0 ? pAC : ph == 1 && lane < 16 ? pE : pG + (src & 8) * (HALF / 8) + (src & 7) * 512, gx.hi));
                        if (RFR_XS && (++cs & (RFR_XS - 1)) < 2) {
                            const uint32_t l = lane + 32 * (cs & 1);
                            *reinterpret_cast<volatile uint32_t*>(reinterpret_cast<char*>(g_s) + (l < 60 ? XS + bid * 7680 + 128 * l : XS2 + bid * 768 + 128 * (l - 60))) = 0;
                        }
                        src += ph == 0 ? 0 : ph == 1 ? 2 : 1;
                        ph = ph == 2 ? 0 : ph + 1;
                    } else __nanosleep(KWNS2);
                }
                while (ldsvol(sb + S_GATE) < 6 && ++k < SPIN_LIMIT) { warm_mma(a, b); __nanosleep(KWNS); }
                if (a | b) stsvol(sb + S_GATE, 6);
            }
        }
        return;
    }
    asm volatile("setmaxnreg.inc.sync.aligned.u32 " REG_HI ";");

    const int g = bid >> 3, i = bid & 7;
    const int g8 = lane >> 2, t = lane & 3;
    char* const gs = reinterpret_cast<char*>(g_s);
    const XPtr gx(xwindow());

    auto zero_words = [&] {
        const uint4 z = make_uint4(0, 0, 0, 0);
        const uint32_t c = (tid >> 6) & 1, cp = (tid >> 7) * COPY, k = (tid & 63) * 16;
        *reinterpret_cast<uint4*>((char*)(gx + pairL(RA, c, g) * 8192 + (i >> 2) * HALF + (i & 3) * 1024 + cp + k)) = z;
        *reinterpret_cast<uint4*>((char*)(gx + pairL(RC, c, g) * 8192 + (i >> 2) * HALF + (i & 3) * 1024 + cp + k)) = z;
        *reinterpret_cast<uint4*>((char*)(gx + pairL(RE, c, g) * 8192 + (i >> 2) * HALF + (i & 3) * 1024 + cp + k)) = z;
        if ((tid & 31) < 24) *reinterpret_cast<uint4*>((char*)(gx + pairG((tid >> 5) & 1, c, i) * 8192 + (g >> 3) * HALF + (g & 7) * 512 + cp + (tid & 31) * 16)) = z;
    };
    if (ZPOS == 0) zero_words();
    W80 Wq[6], Wgu[3];
    uint32_t Wo[5][3][4];
    if (w < 4) {
        const uint32_t* xp = reinterpret_cast<const uint32_t*>(P.x + 640 * w);
        float sum = 0.f, sq = 0.f;
#pragma unroll
        for (int u = 0; u < 10; u++) { uint32_t v = xp[lane + 32 * u]; float a = bf_lo(v), b = bf_hi(v); sum += a + b; sq += a * a + b * b; }
#pragma unroll
        for (int o = 16; o > 0; o >>= 1) { sum += __shfl_xor_sync(~0u, sum, o); sq += __shfl_xor_sync(~0u, sq, o); }
        float mean, den; ln_stats(sum, sq, mean, den);
        if (lane < 20) {
            const uint2 v = reinterpret_cast<const uint2*>(P.x + 640 * w + 80 * i)[lane];
            sts64(sb + S_X0 + 160 * w + 8 * lane, v.x, v.y);
            sts32(sb + S_L0 + 384 * w + b_pos<40>(4 * lane), pack2(__fdiv_rn(bfr(bf_lo(v.x) - mean), den), __fdiv_rn(bfr(bf_hi(v.x) - mean), den)));
            sts32(sb + S_L0 + 384 * w + b_pos<40>(4 * lane + 2), pack2(__fdiv_rn(bfr(bf_lo(v.y) - mean), den), __fdiv_rn(bfr(bf_hi(v.y) - mean), den)));
        }
    } else if (w == 4) {
        const uint32_t* xp = reinterpret_cast<const uint32_t*>(P.wr);
        float sum = 0.f;
#pragma unroll
        for (int u = 0; u < 10; u++) { uint32_t v = xp[lane + 32 * u]; sum += bf_lo(v) + bf_hi(v); }
#pragma unroll
        for (int o = 16; o > 0; o >>= 1) sum += __shfl_xor_sync(~0u, sum, o);
        if (lane == 0) stsf(sb + S_SWR, sum);
        if (lane < 20) {
            const uint2 v = reinterpret_cast<const uint2*>(P.wr + 80 * i)[lane];
            sts32(sb + S_XA + 576 + a_pos(4 * lane), v.x); sts32(sb + S_XA + 576 + a_pos(4 * lane + 2), v.y);
            sts32(sb + S_XA + a_pos(4 * lane), ONES); sts32(sb + S_XA + a_pos(4 * lane + 2), ONES);
        }
    }
    asm volatile("bar.sync 2, %0;" :: "n"(NTHR) : "memory");
    auto frag = [](uint32_t (&a)[4], uint32_t p, int pitch) {
        const uint32_t r0 = lds32(p), r1 = lds32(p + pitch), r2 = lds32(p + 2 * pitch), r3 = lds32(p + 3 * pitch);
        a[0] = __byte_perm(r0, r1, 0x5410); a[1] = __byte_perm(r0, r1, 0x7632);
        a[2] = __byte_perm(r2, r3, 0x5410); a[3] = __byte_perm(r2, r3, 0x7632);
    };
    mbar_wait(sb + S_WFULL + 16 * (w >> 2), 0);
    mbar_wait(sb + S_WFULL + 16 * (w >> 2) + 8, 0);
    {
        const uint32_t p = sb + ST_WQ + (w >> 2) * 30720 + (2 * t) * 384 + (48 * (w & 3) + 2 * g8) * 2;
#pragma unroll
        for (int r = 0; r < 10; r++)
#pragma unroll
            for (int m = 0; m < 3; m++) {
                const uint32_t q = p + ((r & 1) * 40 + (r >> 1) * 8) * 384 + 32 * m, r0 = lds32(q), r1 = lds32(q + 384);
                (r < 8 ? Wq[2 * m].a[(r >> 2) & 1][r & 3] : Wq[2 * m].c[r & 1]) = __byte_perm(r0, r1, 0x5410);
                (r < 8 ? Wq[2 * m + 1].a[(r >> 2) & 1][r & 3] : Wq[2 * m + 1].c[r & 1]) = __byte_perm(r0, r1, 0x7632);
            }
    }
    __syncwarp();
    if (lane == 0) mbar_arrive(sb + S_RELW);
    TSTAMP(1);
    {
        char* d = gs + XS + bid * 7680 + (w >> 2) * 3840 + (48 * (w & 3) + 2 * g8) * 4;
        float acc[6][4] = {};
        mul80(acc, Wq, lds128(sb + S_L0 + 48 * lane), lds32(sb + S_L0 + 48 * lane + 16));
#pragma unroll
        for (int m = 0; m < 6; m += 2) stp64(d + t * 768 + 32 * m, acc[m][0] + acc[m][3], acc[m + 1][0] + acc[m + 1][3], 1);
        float sum[6][4] = {};
        mul80(sum, Wq, make_uint4(ONES, ONES, ONES, ONES), ONES);
        if (t == 0)
#pragma unroll
            for (int m = 0; m < 6; m += 2) stp64(d + 4 * 768 + 32 * m, sum[m][0] + sum[m][3], sum[m + 1][0] + sum[m + 1][3], 1);
    }
    mbar_wait(sb + S_WFULL + 32, 0);
    mbar_wait(sb + S_WFULL + 40, 0);
    const uint32_t oct = 3 * (w >> 1) + (w & 1), oct2 = 3 * (w >> 1) + 2;
    {
        const uint32_t p = sb + ST_WG + ((lane & 7) + 40 * ((lane >> 3) & 1) + 8 * (lane >> 4)) * 192;
#pragma unroll
        for (int T = 0; T < 3; T++) {
            const uint32_t q = p + (T < 2 ? T * 15360 + 16 * oct : (w & 1) * 15360 + 16 * oct2);
            ldsm4t(Wgu[T].a[0], q); ldsm4t(Wgu[T].a[1], q + 16 * 192); ldsm2t(Wgu[T].c, q + 32 * 192);
        }
        float sum[3][4] = {};
        mul80(sum, Wgu, make_uint4(ONES, ONES, ONES, ONES), ONES);
        if (t < 3) stp32(gs + XS2 + bid * 768 + (t < 2 ? 64 * oct + 4 * t : 64 * oct2 + 4 * (w & 1)) + 8 * g8,
                         sel4(t, sum[0][0] + sum[0][3], sum[1][0] + sum[1][3], sum[2][0] + sum[2][3], 0.f), 1);
    }
    __syncwarp();
    if (lane == 0) mbar_arrive(sb + S_RELW + 8);
    const char* srcS = gs + XS + g * 8 * 7680 + (i >> 2) * 3840 + min(tid, 191) * 4;
    uint32_t vs[5][8];
#pragma unroll
    for (int b = 0; b < 5; b++)
#pragma unroll
        for (int s = 0; s < 8; s++) vs[b][s] = LOOK1 ? ldp32(srcS + b * 768 + s * 7680) : 0;
    uint32_t cs2[8];
#pragma unroll
    for (int s = 0; s < 8; s++) cs2[s] = LOOK2 ? ldp32(gs + XS2 + (g * 8 + s) * 768 + min(tid, 191) * 4) : 0;
    __syncwarp();
    mbar_wait(sb + S_WFULL + 48 + 8 * (w >> 1), 0);
    {
        const uint32_t po = sb + ST_WO + (48 * w + 12 * t) * 160 + 4 * g8;
#pragma unroll
        for (int s = 0; s < 3; s++)
#pragma unroll
            for (int m = 0; m < 5; m++) frag(Wo[m][s], po + 4 * s * 160 + 32 * m, 160);
    }
    __syncwarp();
    if (lane == 0) mbar_arrive(sb + S_RELW + 16);
    if (ZPOS == 1) zero_words();
    if (tid < 192) {
        int guard = 0;
        while (((or3(chk8(vs[0], 1), chk8(vs[1], 1), chk8(vs[2], 1)) | chk8(vs[3], 1) | chk8(vs[4], 1)) & 1) && ++guard < SPIN_LIMIT) {
#pragma unroll
            for (int b = 0; b < 5; b++)
#pragma unroll
                for (int s = 0; s < 8; s++) vs[b][s] = ldp32(srcS + b * 768 + s * 7680);
        }
        const uint32_t qpos = sb + S_QS + q_pos(tid);
#pragma unroll
        for (int b = 0; b < 4; b++) {
            sts_hi16(qpos + 384 * b, bfr(sum8(vs[b])));
        }
        stsf(sb + S_CSQ + 4 * tid, sum8(vs[4]));
    }
    if (tid < 192) stsf(sb + S_CSGU + 4 * tid, (chk8(cs2, 1) & 1) ? gather8<768>(gs + XS2 + g * 8 * 768 + tid * 4, 1) : sum8(cs2));
    __syncwarp();
    bar_main();
    arrive_if(tid == 0, sb + S_QRDY);
    if (ZPOS == 2) zero_words();
    TSTAMP(2);

    uint32_t side;
    { int k = 0; while ((side = ldsvol(sb + S_SIDE)) == 0 && ++k < SPIN_LIMIT) {} }
    const uint32_t td = __shfl_sync(~0u, tid, lane);
    const uint32_t wp = __shfl_sync(~0u, tid >> 5, 0);
    const uint32_t cc = wp >= 3;
    auto uni = [](uint32_t v) { return __shfl_sync(~0u, v, 0); };
    auto pin = [&](uint32_t v) { return __shfl_sync(~0u, v, td); };
    auto nearp = [&](uint32_t P) { return gx.lo + P * 8192 + ((side ^ 1 ^ __popc(P & PMASK)) & 1) * COPY; };
    constexpr uint32_t COL = 32 * 8192;
    const uint32_t ownL = gx.lo + (i >> 2) * HALF + (i & 3) * 1024, ownG = gx.lo + (g >> 3) * HALF + (g & 7) * 512;
    const uint32_t uPubA = uni(ownL + pairL(RA, 0, g) * 8192 + (wp >> 1) * 256 + (wp & 1) * 96), uPolA = uni(nearp(pairL(RA, 0, g)) + (wp >> 2) * HALF + (wp & 3) * 256);
    const uint32_t uPubB = uni(ownG + pairG(0, cc, i) * 8192), uPolB = uni(nearp(pairG(0, cc, i)));
    const uint32_t uPubC = uni(ownL + pairL(RC, 0, g) * 8192), uPolC = uni(nearp(pairL(RC, wp < 6 ? cc : wp - 6, g)));
    const uint32_t uPubD = uni(ownG + pairG(1, 0, i) * 8192 + (wp < 7 ? 32 * wp : 256)), uPolD = uni(nearp(pairG(1, cc, i)));
    const uint32_t uPubE = uni(ownL + pairL(RE, 0, g) * 8192), uPolE = uni(nearp(pairL(RE, i >> 2, g)));
    const uint32_t uOS = uni(sb + S_OS + 192 * wp);
    auto xp = [&](uint32_t lo) { return (char*)XPtr(lo, gx.hi); };
#define IDS() __syncwarp(); const uint32_t z0_ = lag<1>(sb), z_ = td + z0_; const uint32_t ln = z_ & 31, q8 = ln >> 2, t4 = z_ & 3, n96 = z_ - 96 * cc, n80 = min(n96, 79u); (void)q8; (void)t4; (void)n80; (void)ln

    auto vaddr = [&](uint32_t (&voff)[3]) {
        const uint32_t ln = td & 31;
        const uint32_t key3 = 3 * ((ln & 7) + 2 * (ln & 8) + ((ln >> 1) & 8));
#pragma unroll
        for (int T = 0; T < 3; T++) {
            const uint32_t u = 3 * wp + T, r = key3 + (u >> 3);
            voff[T] = r * 128 + (((u ^ r) & 7) << 4);
        }
    };
    auto values = [&](uint32_t (&vf)[8][3][4], auto order, auto step, uint32_t ps, uint32_t col, uint32_t par) {
        const uint32_t ln = td & 31, q8 = ln >> 2, t4 = td & 3;
        const uint4 p = lds128(ps + 16 * ln);
        float acc[3][4] = {}, f0 = 0.f, f1 = 0.f, r3 = 0.f;
        int M = 0;
#pragma unroll
        for (int k = 0; k < 8; k++) {
            step(k);
            const int s = (order.value >> (4 * k)) & 7;
            const bool m = (q8 >> 1) == (s >> 1);
            const uint32_t b0 = m ? ((s & 1) ? p.z : p.x) : 0u, b1 = m ? ((s & 1) ? p.w : p.y) : 0u;
#pragma unroll
            for (int T = 0; T < 3; T++) mmaA(acc[T], vf[s][T], b0, b1);
            if (k == FSTEP) {
                const uint2 mp = lds64(ps + PS_MAX + 8 * t4);
                M = __reduce_max_sync(~0u, __float2int_ru(fmaxf(asf(mp.x), asf(mp.y))));
                f0 = ex2(asf(mp.x) - (float)M); f1 = ex2(asf(mp.y) - (float)M);
                float l[4] = {};
                mma16816(l, ONES, ONES, ONES, ONES, p.x, p.y); mma16816(l, ONES, ONES, ONES, ONES, p.z, p.w);
                r3 = fmaf(f0, l[0], f1 * l[1]);
            }
        }
        CSTAMP(25);
        char* pubA = xp(uPubA + col * COL + 32 * t4 + 4 * q8);
        const float r0 = fmaf(f0, acc[0][0], f1 * acc[0][3]), r1 = fmaf(f0, acc[1][0], f1 * acc[1][3]), r2 = fmaf(f0, acc[2][0], f1 * acc[2][3]);
        const bool hi = t4 & 2, od = t4 & 1;
        const float u0 = (hi ? r2 : r0) + __shfl_xor_sync(~0u, hi ? r0 : r2, 2), u1 = (hi ? r3 : r1) + __shfl_xor_sync(~0u, hi ? r1 : r3, 2);
        const float o = (od ? u1 : u0) + __shfl_xor_sync(~0u, od ? u0 : u1, 1);
        stp32_if(t4 < 3 || ((wp & 1) && q8 < 2), pubA, ln == 3 ? __int_as_float(2 * M) : o, par);
    };

#pragma unroll 1
    for (int ch = 0; ch < 5; ch++) {
        const uint32_t par0 = (ch + 1) & 1, par1 = ch & 1;
        uint32_t voff[3], vf[8][3][4];
        if (ch < 4) {
            vaddr(voff);
            mbar_wait(sb + S_SCO, par1);
            if (ch == 0) mbar_wait(sb + S_WFULL + 80, 0);
            TST(0);
            auto ldw = [&](int s) {
                mbar_wait(sb + S_FV + 8 * s, par1);
#pragma unroll
                for (int T = 0; T < 3; T++) ldsm4t(vf[s][T], voff[T] + (sb + v_place(ch, s) * SLOT));
            };
            probs(bf_lo(lds16(sb + S_SC + 2 * td)), sb + S_PS, wp, td & 31);
            ldw(0); ldw(1); ldw(2);
            bar_main();
            arrive_if(td == 0, sb + S_RELR);
            values(vf, std::integral_constant<uint32_t, 0x76543210>(), [&](int s) {
                if (s >= 3) ldw(s);
            }, sb + S_PS, 0, par0);
            TST(1);
            CSTAMP(5);
            if (ch > 0) mbar_wait(sb + S_OS1, par0);
        } else {
#pragma unroll
            for (int s = 0; s < 36; s++) { vf[s / 12][(s / 4) % 3][s & 3] = 0; opaque(vf[s / 12][(s / 4) % 3][s & 3]); }
        }
        const bool has0 = ch < 4, has1 = ch > 0;
        const bool actc = wp < 6 && (cc ? has1 : has0);
        const uint32_t parc = cc ? par1 : par0;
        const uint32_t pub0 = has0 ? par0 : 0;
        uint32_t rr, pubB;
        {
            IDS();
            const uint32_t c = ch == 4;
            const uint32_t osa = pin(uOS + 96 * c + 4 * ln), oa = pin(uOS + 48 * (q8 & 2) + 24 * t4), ra = pin(sb + S_RED + 640 * wp + 320 * (t4 & 1) + 8 * q8);
            rr = pin(sb + S_RED + 320 * cc + 4 * n80); pubB = pin(uPubB + 4 * n80);
            hop_a<1>(xp(uPolA + c * COL + 8 * min(ln, 24u) + lag<DELAY_L>(sb, z0_)), pub0, osa, ln < 24, 5 * ch);
            TST(2);
            CSTAMP(6);
            float acc[5][4] = {};
            const uint2 b0 = lds64(oa), b1 = lds64(oa + 8), b2 = lds64(oa + 16);
#pragma unroll
            for (int m = 0; m < 5; m++) mmaA(acc[m], Wo[m][0], b0.x, b0.y);
#pragma unroll
            for (int m = 0; m < 5; m++) mmaA(acc[m], Wo[m][1], b1.x, b1.y);
#pragma unroll
            for (int m = 0; m < 5; m++) mmaA(acc[m], Wo[m][2], b2.x, b2.y);
#pragma unroll
            for (int m = 0; m < 5; m++) { stsf(ra + 64 * m, acc[m][0]); stsf(ra + 64 * m + 4, acc[m][2]); }
        }
        CSTAMP(7);
        uint32_t xr, fl, pubC, pubC2;
        auto prepC = [&](uint32_t ln) {
            const uint32_t q8 = ln >> 2, t4 = ln & 3;
            xr = pin(sb + S_XB + 48 * (ln & 15));
            pubC = pin(uPubC + (t4 & 1) * COL + 192 * (wp >> 1) + 64 * (wp & 1) + 8 * q8);
            pubC2 = pin(uPubC + (t4 & 1) * COL + ((t4 & 2) ? 192 * (wp >> 1) + 128 + 4 * (wp & 1) + 8 * q8 : 768 + 2 * ((q8 + 1) & 6)));
            fl = pin(((t4 & 1) ? par1 : pub0) | (t4 >= 2 || (wp == 7 && q8 < 4 && q8 != 2 - t4) ? 2 : 0));
        };
        auto stats = [&](uint32_t xa, const uint4& b, uint32_t b4) {
            float a[4] = {};
            const uint4 p0 = lds128(xa), p1 = lds128(xa + 16);
            const uint2 p2 = lds64(xa + 32);
            mmaV(a, p0, b.x, b.y); mmaV(a, p1, b.z, b.w); mma8(a, p2.x, p2.y, b4);
            return a[0] + a[3];
        };
        {
            auto gate_up = [&](auto with_stats) {
                bar_main();
                TST(3);
                CSTAMP(11);
                const uint4 b = lds128(xr);
                const uint32_t b4 = lds32(xr + 16);
                float acc[3][4] = {}, st = 0.f;
                if (with_stats.value) st = stats(xr + (S_XA - S_XB), b, b4);
                mul80(acc, Wgu, b, b4);
                stp64_if(!(td & 2), xp(pubC), tagw(acc[0][0] + acc[0][3], fl & 1), tagw(acc[1][0] + acc[1][3], fl & 1));
                stp32_if(fl > 1, xp(pubC2), !with_stats.value || (td & 2) ? acc[2][0] + acc[2][3] : st, fl & 1);
            };
            if (wp == 7) {
                bar_main();
                IDS();
                prepC(ln);
                gate_up(std::true_type());
            } else {
                if (actc) {
                    bar_main();
                    CSTAMP(8);
                    uint32_t r[8];
#pragma unroll
                    for (int s = 0; s < 8; s++) r[s] = lds32(rr + 640 * s);
                    stp32_if(true, xp(pubB), sum8(r), parc);
                    CSTAMP(9);
                    IDS();
                    prepC(ln);
                    const uint32_t n4 = 4 * n80;
                    const uint32_t xas = pin(sb + S_XA + 192 + 192 * cc + a_pos(n80)), xbs = pin(sb + S_XB + 384 * cc + b_pos<40>(n80));
                    const float x0 = cc ? ldsf(sb + S_XCAR + n4) : bf_lo(lds16(sb + S_X0 + 160 * (ch & 3) + n4 / 2));
                    gather16(xp(uPolB + n4 + lag<DELAY_G>(sb, z0_)), parc, 5 * ch + 1, [&](float y, uint32_t) {
                        const uint32_t x = pack2(x0 + bfr(y), 0.f);
                        sts16(xbs, x);
                        sts16(xas, x);
                        return 0u;
                    });
                    CSTAMP(10);
                } else {
                    bar_main();
                    IDS();
                    prepC(ln);
                }
                gate_up(std::false_type());
            }
        }
        CSTAMP(12);
        float mean = 0.f, den = 1.f;
        {
            IDS();
            const uint32_t wh = pin((((ln & 7) + 48 * ((ln >> 3) & 1) + 8 * (ln >> 4)) * 160 + (wp < 7 ? 16 * wp : 128)) | ((384 * cc + b_pos<48>(n96)) << 16));
            const uint32_t pubD = pin(uPubD + (t4 & 1) * COL + 16 * (t4 & 2) + 4 * q8 + (fl & 1)), ha = xr + (S_HS - S_XB);
            auto down = [&](const uint32_t (&W)[3][4], const uint4& h0, const uint2& h1) {
                float a0[4] = {}, a1[4] = {}, a2[4] = {};
                mmaA(a0, W[0], h0.x, h0.y); mmaA(a1, W[1], h0.z, h0.w); mmaA(a2, W[2], h1.x, h1.y);
                return ((a0[0] + a0[3]) + (a1[0] + a1[3])) + (a2[0] + a2[3]);
            };
            if (wp < 6) {
                uint32_t Wd[3][4];
                auto ldd = [&](uint32_t z) {
#pragma unroll
                    for (int s = 0; s < 3; s++) ldsm4t(Wd[s], ((wh ^ z) & 0xffff) + (sb + S_WD + s * 2560));
                };
                if (actc) {
                    const uint32_t src0 = uPolC + lag<DELAY_C>(sb, z0_);
                    const char* srcv = xp(src0 + 8 * n96);
                    const char* src = xp(src0 + (ln & 1) * HALF);
                    float gt, up;
                    int guard = 0;
                    bool again;
                    do {
                        uint2 v[8], st[4];
#pragma unroll
                        for (int s = 0; s < 4; s++) st[s] = ldp64(src + 768 + s * 1024);
#pragma unroll
                        for (int s = 0; s < 8; s++) v[s] = ldp64(srcv + (s >> 2) * HALF + (s & 3) * 1024);
                        float sx = (asf(st[0].x) + asf(st[1].x)) + (asf(st[2].x) + asf(st[3].x)), sq = (asf(st[0].y) + asf(st[1].y)) + (asf(st[2].y) + asf(st[3].y));
                        sx += __shfl_xor_sync(~0u, sx, 1); sq += __shfl_xor_sync(~0u, sq, 1);
                        const uint32_t z = ((st[0].x ^ parc) & 1) * 16;
                        const uint2 cs = lds64(sb + S_CSGU - 768 * cc + 8 * td + z);
                        again = __any_sync(~0u, (or3(chk4(st, parc), chk8(v, parc), chk8y(v, parc)) & 1) != 0);
                        ln_stats(sx, sq, mean, den);
                        const float rd = rcp(den);
                        gt = fmaf(-mean, asf(cs.x), sum8x(v)); up = fmaf(-mean, asf(cs.y), sum8y(v));
                        ldd(z);
                        gt *= rd; up *= rd;
                        keep(gt); keep(up);
                    } while (again & (++guard < SPIN_LIMIT));
                    CSTAMP(13);
                    SWEEPS(5 * ch + 2, guard - 1);
                    gt = bfr(gt);
                    const uint32_t h = pack2(bfr(gt * sigmoidf_(gt)) * bfr(up), 0.f);
                    sts16((wh >> 16) + (sb + S_HS), h);
                    CSTAMP(14);
                    if (ch == 3) CSTAMP(0);
                } else ldd(0);
                bar_main();
                TST(4);
                CSTAMP(15);
                const uint4 h0 = lds128(ha);
                const uint2 h1 = lds64(ha + 16);
                stp32_if(!(td & 2), xp(pubD & ~1u), down(Wd, h0, h1), pubD & 1);
            } else {
                stsvol(sb + S_GATE, ch + 1);
                uint32_t Wd[2][3][4];
#pragma unroll
                for (int s = 0; s < 6; s++) ldsm4t(Wd[s / 3][s % 3], (wh & 0xffff) + (sb + S_WD + (s / 3) * 16 + (s % 3) * 2560));
                uint32_t v = 0;
                if (wp == 6 ? has0 : has1) {
                    const uint32_t par = wp == 6 ? par0 : par1;
                    const char* src = xp(uPolC + 768 + (ln & 4) * (HALF / 4) + (ln & 3) * 1024 + 4 * min(ln >> 3, 2u) + lag<DELAY_C>(sb, z0_));
                    int guard = 0;
                    do v = ldp32(src); while (__any_sync(~0u, (v ^ par) & 1) && ++guard < SPIN_LIMIT);
                }
                bar_main();
                const uint4 h0 = lds128(ha);
                const uint2 h1 = lds64(ha + 16);
                const float d0 = down(Wd[0], h0, h1), d1 = down(Wd[1], h0, h1);
                stp32_if(true, xp(pubD & ~1u), (td & 2) ? d1 : d0, pubD & 1);
                if (wp == 6 ? has0 : has1) {
                    float sx = asf(v);
                    sx += __shfl_xor_sync(~0u, sx, 1); sx += __shfl_xor_sync(~0u, sx, 2); sx += __shfl_xor_sync(~0u, sx, 4);
                    const float sq = __shfl_sync(~0u, sx, 8), xw = __shfl_sync(~0u, sx, 16);
                    ln_stats(sx, sq, mean, den);
                    const float r = bfr(fmaf(-mean, ldsf(sb + S_SWR), xw) * rcp(den));
                    sts32_if(ln == 0, sb + S_STAT + 4 * (wp - 6), __float_as_uint(bfr(sigmoidf_(r))) | (ch + 1));
                }
            }
        }
        CSTAMP(16);
        {
            IDS();
            const uint32_t pubE = pin(uPubE + (t4 < 3 ? (wp >> 2) * COL + 192 * (wp & 3) + 64 * t4 + 8 * q8 : (q8 >> 2) * COL + 768 + 4 * (q8 & 1)));
            xr = pin(sb + S_XB + 48 * (ln & 7));
            uint32_t x2 = 0;
            auto hop_d = [&](auto col) {
                const uint32_t xbs = pin(sb + S_XB + 384 * col.value + b_pos<40>(n80)), xas = col.value ? 0 : pin(sb + S_XA + 192 + a_pos(n80));
                const float x1 = bf_lo(lds16(xbs));
                const float lnx = __uint_as_float(pin(__float_as_uint(bfr(__fdiv_rn(bfr(x1 - mean), den)))));
                gather16(xp(uPolD + 4 * n80 + lag<DELAY_D>(sb, z0_)), col.value ? par1 : par0, 5 * ch + 3, [&](float y, uint32_t z) {
                    const uint32_t gate = ldsvol(sb + S_STAT + 4 * col.value + z);
                    x2 = pack2(x1 + bfr(lnx + bfr(bfr(y) * bf_hi(gate))), 0.f);
                    if (col.value) keep(x2); else { sts16(xbs, x2); sts16(xas, x2); }
                    return (uint32_t)((gate & 7) != ch + 1);
                });
                CSTAMP(17);
            };
            auto qproj = [&](auto with_stats) {
                bar_main();
                TST(5);
                CSTAMP(19);
                const uint32_t t4 = td & 3;
                const uint4 b = lds128(xr);
                const uint32_t b4 = lds32(xr + 16);
                float acc[6][4] = {}, st = 0.f;
                if (with_stats.value) st = stats(xr + (S_XA - S_XB), b, b4);
                mul80(acc, Wq, b, b4);
                const float v0 = sel4(t4, acc[0][0] + acc[0][3], acc[2][0] + acc[2][3], acc[4][0] + acc[4][3], acc[4][0] + acc[4][3]);
                const float v1 = sel4(t4, acc[1][0] + acc[1][3], acc[3][0] + acc[3][3], acc[5][0] + acc[5][3], acc[5][0] + acc[5][3]);
                if (with_stats.value) stp32_if((td & 11) == 3, xp(pubE), st, par0);
                stp64_if(t4 < 3, xp(pubE), tagw(v0, par0), tagw(v1, par0));
            };
            if (wp == 7) {
                if (!has0) break;
                qproj(std::true_type());
            } else {
                if (actc && !cc) hop_d(std::integral_constant<int, 0>());
                else {
                    if (actc && g == 0) {
                        const uint32_t po = pin(1280 * (ch - 1) + 160 * i + 2 * n80);
                        hop_d(std::integral_constant<int, 1>());
                        *reinterpret_cast<unsigned short*>(reinterpret_cast<char*>(P.out) + po) = (unsigned short)x2;
                    }
                    if (!has0) break;
                }
                qproj(std::false_type());
                sts32_if(td < 80, sb + S_XCAR + 4 * td, x2 << 16);
            }
        }
        CSTAMP(20);
        auto pass2 = [&](auto d0, auto d1, auto d2) {
            constexpr int D0 = d0.value, D1 = d1.value, D = D0 + D1 + d2.value;
            IDS();
            const uint32_t ua = sb + k_place(ch, wp & 6) * SLOT + (wp & 1) * UNIT, k0 = k_off(ln);
            uint32_t kf[12][2][4];
            auto ldk = [&](int s) { const uint32_t a = (k0 ^ (32 * (s / 3))) + (ua + 1024 * (s % 3)); ldsm4(kf[s][0], a); ldsm4(kf[s][1], a + SLOT); };
            auto ldv1 = [&](int k) { ldsm4t(vf[k / 3][k % 3], voff[k % 3] + (sb + v_place(ch, k / 3) * SLOT)); };
            auto ldv = [&](int s) { ldv1(3 * s); ldv1(3 * s + 1); ldv1(3 * s + 2); };
            constexpr uint32_t LATE = LAST_LATE;
            constexpr uint64_t EARLY_LIST = bit_list(~LATE), LATE_LIST = bit_list(LATE);
            auto early = [&](int k) {
                if (D1 == 0) ldk(k);
                else if (k < 3) { ldv1(9 + 2 * k); ldv1(10 + 2 * k); }
                else ldk((EARLY_LIST >> (4 * (k - 3))) & 15);
            };
            if (D1 > 0) vaddr(voff);
            if (!(mbar_try(sb + S_FK + 8 * (wp & 6), par1) & mbar_try(sb + S_FK + 8 * (wp | 1), par1))) { mbar_wait(sb + S_FK + 8 * (wp & 6), par1); mbar_wait(sb + S_FK + 8 * (wp | 1), par1); }
#pragma unroll
            for (int s = 0; s < D0; s++) early(s);
            if (wp < 6) {
                const uint32_t qsa = pin(sb + S_QS + 384 * ch + q_pos(td));
                const uint32_t src0 = uPolE + lag<(D1 > 0 ? DELAY_E3 : DELAY_E)>(sb, z0_);
                const char* srcv = xp(src0 + 4 * td);
                const char* src = xp(src0 + (ln & 1) * HALF);
                uint32_t v[8]; uint2 st[4];
                auto look = [&] {
#pragma unroll
                    for (int s = 0; s < 4; s++) st[s] = ldp64(src + 768 + s * 1024);
#pragma unroll
                    for (int s = 0; s < 8; s++) v[s] = ldp32(srcv + (s >> 2) * HALF + (s & 3) * 1024);
                };
                if (D1 > 0) {
                    look();
                    __syncwarp();
#pragma unroll
                    for (int s = D0; s < D0 + D1; s++) early(s);
                }
                int guard = 0;
                while (true) {
                    if (D1 == 0) look();
                    float sx = (asf(st[0].x) + asf(st[1].x)) + (asf(st[2].x) + asf(st[3].x)), sq = (asf(st[0].y) + asf(st[1].y)) + (asf(st[2].y) + asf(st[3].y));
                    sx += __shfl_xor_sync(~0u, sx, 1); sq += __shfl_xor_sync(~0u, sq, 1);
                    const float cs = ldsf(sb + S_CSQ + 4 * td + ((st[0].x ^ par0) & 1) * 4);
                    const bool again = __any_sync(~0u, ((chk8(v, par0) | chk4(st, par0)) & 1) != 0);
                    ln_stats(sx, sq, mean, den);
                    const uint32_t q = pack2(fmaf(-mean, cs, sum8(v)) * rcp(den), 0.f);
                    sts16(qsa, q);
                    if (!(again & (++guard < SPIN_LIMIT))) break;
                    if (D1 > 0) look();
                }
                SWEEPS(5 * ch + 4, guard - 1);
                CSTAMP(22);
            } else {
#pragma unroll
                for (int s = D0; s < D0 + D1; s++) early(s);
            }
#pragma unroll
            for (int s = D0 + D1; s < D; s++) early(s);
            bar_main();
            TST(6);
            CSTAMP(1);
            uint2 q = lds64(sb + S_QS + 384 * ch + 8 * ln);
            float acc[2][4] = {};
            constexpr int V0 = 13 - D, NV = D1 > 0 ? 2 : (2 * (D - 1)) / 3;
            static_assert(D1 == 0 || LAST0 == 0 || D - 3 + __builtin_popcount(LATE) == 12, "plan");
#pragma unroll
            for (int s = 0; s < 12; s++) {
                const bool m = q8 == (s & 7);
                const uint32_t b0 = m ? q.x : 0u, b1 = m ? q.y : 0u;
                if (s == 7) q = lds64(sb + S_QS + 384 * ch + 8 * ln + 256);
                mmaA(acc[0], kf[s][0], b0, b1);
                mmaA(acc[1], kf[s][1], b0, b1);
                if (D1 > 0) {
                    if (s >= 1 && s <= __builtin_popcount(LATE)) ldk((LATE_LIST >> (4 * (s - 1))) & 15);
                } else {
                    if (s >= 1 && s + D - 1 < 12) ldk(s + D - 1);
                    if (s >= 1 && s + D - 1 == 11) { __syncwarp(); arrive_if(ln == 0, sb + S_RELK); }
                    if (s == V0) vaddr(voff);
                    if (s >= V0 && 2 * (s - V0) < 3 * NV) ldv1(9 + 2 * (s - V0));
                    if (s >= V0 && 2 * (s - V0) + 1 < 3 * NV) ldv1(10 + 2 * (s - V0));
                }
            }
            CSTAMP(24);
            {
                const float v0 = acc[0][0] + acc[0][1], v1 = acc[0][2] + acc[0][3], v2 = acc[1][0] + acc[1][1], v3 = acc[1][2] + acc[1][3];
                const bool hi = t4 & 2, od = t4 & 1;
                const float u0 = (hi ? v2 : v0) + __shfl_xor_sync(~0u, hi ? v0 : v2, 2), u1 = (hi ? v3 : v1) + __shfl_xor_sync(~0u, hi ? v1 : v3, 2);
                const float s = (od ? u1 : u0) + __shfl_xor_sync(~0u, od ? u0 : u1, 1);
                CSTAMP(2);
                probs(scaled(s), sb + S_PS + PS_PASS, wp, ln);
                CSTAMP(3);
            }
            bar_main();
            TST(10);
            CSTAMP(4);
            if (D1 > 0) values(vf, std::integral_constant<uint32_t, ORDER_L>(), [&](int s) { if (s < 3) ldv(s + 5); }, sb + S_PS + PS_PASS, 1, par0);
            else values(vf, std::integral_constant<uint32_t, (NV > 1 ? ORDER_R : 0x76543210)>(),
                        [&](int s) { if (s >= (NV > 1 ? 2 : 1) && s + NV + (NV > 1 ? 1 : 2) < 8) ldv(s + NV + (NV > 1 ? 1 : 2)); }, sb + S_PS + PS_PASS, 1, par0);
            arrive_if(ln == 0, sb + S_RELV);
        };
        if (LAST0 > 0 && ch == 3) {
            pass2(std::integral_constant<int, LAST0>(), std::integral_constant<int, LAST1>(), std::integral_constant<int, LAST2>());
#pragma unroll
            for (int m = 0; m < 60; m++) { uint32_t& r = m % 10 < 8 ? Wq[m / 10].a[(m % 10) / 4][m % 2 + 2 * ((m % 10) / 2 % 2)] : Wq[m / 10].c[m % 2]; r = 0; opaque(r); }
        } else pass2(std::integral_constant<int, KPRE>(), std::integral_constant<int, 0>(), std::integral_constant<int, KPRE2>());
        TST(11);
        CSTAMP(23);
    }
    sts32_if(td == 255, sb + S_GATE, 6);
    TSTAMP(3);
}

typedef CUresult (*EncodeFn)(CUtensorMap*, CUtensorMapDataType, cuuint32_t, void*, const cuuint64_t*, const cuuint64_t*, const cuuint32_t*,
                             const cuuint32_t*, CUtensorMapInterleave, CUtensorMapSwizzle, CUtensorMapL2promotion, CUtensorMapFloatOOBfill);

void make_map(EncodeFn enc, CUtensorMap* m, const void* base, uint64_t cols, uint64_t rows, uint32_t box_cols, uint32_t box_rows, bool swizzle) {
    cuuint64_t dims[2] = {cols, rows};
    cuuint64_t strides[1] = {cols * 2};
    cuuint32_t box[2] = {box_cols, box_rows};
    cuuint32_t es[2] = {1, 1};
    enc(m, CU_TENSOR_MAP_DATA_TYPE_BFLOAT16, 2, const_cast<void*>(base), dims, strides, box, es, CU_TENSOR_MAP_INTERLEAVE_NONE,
        swizzle ? CU_TENSOR_MAP_SWIZZLE_128B : CU_TENSOR_MAP_SWIZZLE_NONE, swizzle ? CU_TENSOR_MAP_L2_PROMOTION_NONE : WPROMO, CU_TENSOR_MAP_FLOAT_OOB_FILL_NONE);
}

}

extern "C" void kernel_launch(void* const* d_in, const int* in_sizes, int n_in, void* d_out, int out_size) {
    (void)in_sizes; (void)n_in; (void)out_size;
    static EncodeFn enc = nullptr;
    if (!enc) {
        void* f = nullptr;
        cudaDriverEntryPointQueryResult q;
        cudaGetDriverEntryPoint("cuTensorMapEncodeTiled", &f, cudaEnableDefault, &q);
        enc = (EncodeFn)f;
        cudaFuncSetAttribute(fused_kernel, cudaFuncAttributeMaxDynamicSharedMemorySize, SMEM_BYTES);
    }
    Params P;
    P.x = (const __nv_bfloat16*)d_in[0]; P.k = (const __nv_bfloat16*)d_in[1]; P.v = (const __nv_bfloat16*)d_in[2];
    P.wr = (const __nv_bfloat16*)d_in[6];
    P.out = (__nv_bfloat16*)d_out;
    Maps M;
    {
        cuuint64_t dims[4] = {64, 8, 3, (cuuint64_t)KV_BATCH_KEYS / 2}, strides[3] = {384, 128, 3072};
        cuuint32_t box[4] = {64, 8, 3, 2}, es[4] = {1, 1, 1, 1};
        enc(&M.k, CU_TENSOR_MAP_DATA_TYPE_BFLOAT16, 4, d_in[1], dims, strides, box, es, CU_TENSOR_MAP_INTERLEAVE_NONE, CU_TENSOR_MAP_SWIZZLE_128B,
            CU_TENSOR_MAP_L2_PROMOTION_NONE, CU_TENSOR_MAP_FLOAT_OOB_FILL_NONE);
    }
    make_map(enc, &M.v, P.v, 64, (uint64_t)12 * KV_BATCH_KEYS, 64, 96, true);
    make_map(enc, &M.vu, P.v, 64, (uint64_t)12 * KV_BATCH_KEYS, 64, 48, true);
    make_map(enc, &M.wq, d_in[3], 6144, 640, 192, 40, false);
    make_map(enc, &M.wo, d_in[4], 640, 6144, 80, 96, false);
    make_map(enc, &M.wg, d_in[7], 1536, 640, 96, 80, false);
    make_map(enc, &M.wu, d_in[8], 1536, 640, 96, 80, false);
    make_map(enc, &M.wd, d_in[9], 640, 1536, 80, 96, false);
    fused_kernel<<<NCTA, NTHR, SMEM_BYTES, cudaStreamPerThread>>>(P, M);
}
```

```cpp
#include <cuda_runtime.h>
#include <cuda.h>
#include <cuda_bf16.h>
#include <stdint.h>
#include <type_traits>

namespace {

constexpr int NCTA = 128;
constexpr int NTHR = 384;
constexpr int UNIT = 6144;
constexpr int SLOT = 12288;
#define TAU 4000
#define TAUW 3850
#define TAU0 3850
#define PF0 2
#define PFMAP 1
#define ZPOS 1
#define LOOK1 0
#define LOOK2 0
#define SLACK 4000
#define SLACK0 2000
#define TSH 0
#define HOP1_NS 200
#define RELR_AT 0
#define PSLEEP 0
#define KRE_EARLY 6
#define PFTOP 2
#define RFR_XS 2
#define TMIN 2400
#define T_LEAD 0
#define WIN_W 3
#define WIN_S 4
#define WIN_U 10
#define RFR_ON 1
#define KRE_N1 0
#define KRE_TAU1 2500
#define RFR_TAU 25600
#define VPF 4
#define KRE_GATE 0
#define KRE_GATE3 KRE_GATE
#define JFREE 16
#define TFREE 0
#define KRE_TAU 3000
#define KRE_TAU3 KRE_TAU
#define HDEPTH 3
#define LAST0 3
#define ORDER_L 0x76543210
#define ORDER_R 0x76543210
#define LAST_LATE 0xaa8
#define LAST1 4
#define LAST2 3
#define FSTEP 4
#define SPEC 1
#define PV1PIPE 0
#define HOPA0 6
#define HOPA1 6
#define WPROMO CU_TENSOR_MAP_L2_PROMOTION_NONE
#define KPRE 1
#define KPRE2 3
#define DELAY_G 2
#define DELAY_L 2
#define DELAY_E3 0
#define DELAY_C 1
#define DELAY_D 0
#define DELAY_E 1
#define REG_LO "40"
#define REG_HI "232"
#define SPIN_LOG 17
constexpr int SPIN_LIMIT = 1 << SPIN_LOG;

__host__ __device__ constexpr uint32_t pairL(uint32_t region, uint32_t c, uint32_t g) { return (g & 1) | ((g >> 1) << 2) | (c << 5) | (region << 6); }
__host__ __device__ constexpr uint32_t pairG(uint32_t d, uint32_t c, uint32_t i) { return (i & 1) | ((i >> 1) << 2) | (d << 4) | (c << 5) | (3u << 6); }
constexpr uint32_t RA = 0, RC = 1, RE = 2, HALF = 16384, COPY = 4096, PMASK = 0x59;
constexpr uint32_t XS = 0;
constexpr uint32_t XS2 = XS + 128 * 7680;
constexpr uint32_t XSEND = XS2 + 128 * 768;
__device__ uint4 g_s[XSEND / 16];
__device__ uint4 g_x[(4u << 20) / 16];
#define SWEEPS(k, n) do {} while (0)

constexpr uint32_t S_WD = 16 * SLOT;
constexpr uint32_t S_DUMMY = S_WD + 15360;
constexpr uint32_t S_BAR = S_DUMMY + 4096;
constexpr uint32_t S_FV = S_BAR, S_FK = S_FV + 64, S_RING = S_FK + 64, S_DBAR = S_RING + 48, S_WFULL = S_DBAR + 32, S_QRDY = S_WFULL + 88;
constexpr uint32_t S_RELK = S_QRDY + 8, S_RELV = S_RELK + 8, S_RELR = S_RELV + 8, S_RELW = S_RELR + 8, S_SCO = S_RELW + 24;
constexpr uint32_t S_OS1 = S_SCO + 8;
constexpr uint32_t S_ZERO = S_OS1 + 8;
constexpr uint32_t S_KF = S_ZERO + 8;
constexpr uint32_t S_TOK = S_KF + 8;
constexpr uint32_t S_SIDE = S_TOK + 80, S_GATE = S_SIDE + 4;
constexpr uint32_t S_STAT = S_GATE + 12, S_SWR = S_STAT + 16;
constexpr uint32_t S_LN = S_STAT + 32;
constexpr uint32_t S_XCAR = S_LN + 64;
constexpr uint32_t S_CSQ = S_XCAR + 320;
constexpr uint32_t S_CSGU = S_CSQ + 768;
constexpr uint32_t S_RED = S_CSGU + 768;
constexpr uint32_t S_L0 = S_RED;
constexpr uint32_t S_OS = S_RED + 5120;
constexpr uint32_t S_PS = S_OS + 1536;
constexpr uint32_t PS_MAX = 512, PS_PASS = 544;
constexpr uint32_t S_QS = S_PS + 2 * PS_PASS;
constexpr uint32_t S_XB = S_QS + 1536;
constexpr uint32_t S_XA = S_XB + 768;
constexpr uint32_t S_HS = S_XA + 768;
constexpr uint32_t S_X0 = S_HS + 768;
constexpr uint32_t S_SC = S_X0 + 640;
constexpr uint32_t S_TM = S_SC + 512;
constexpr int SMEM_BYTES = S_TM + 256;
static_assert(SMEM_BYTES <= 232448 && S_STAT % 16 == 0 && S_RED % 16 == 0 && S_XB % 16 == 0 && S_HS % 16 == 0 && S_PS % 16 == 0 && S_QS % 16 == 0, "smem");
static_assert(S_SCO == S_BAR + 44 * 8 && S_RELK == S_BAR + 38 * 8, "barriers");
constexpr uint32_t ST_WQ = 3 * SLOT, ST_WG = 8 * SLOT, ST_WO = 11 * SLOT;

__device__ __forceinline__ uint32_t smem_u32(const void* p) { return (uint32_t)__cvta_generic_to_shared(p); }
__device__ __forceinline__ void mbar_init(uint32_t bar, uint32_t cnt) { asm volatile("mbarrier.init.shared::cta.b64 [%0], %1;" :: "r"(bar), "r"(cnt) : "memory"); }
__device__ __forceinline__ void mbar_expect(uint32_t bar, uint32_t bytes) { asm volatile("mbarrier.arrive.expect_tx.shared::cta.b64 _, [%0], %1;" :: "r"(bar), "r"(bytes) : "memory"); }
__device__ __forceinline__ void mbar_arrive(uint32_t bar) { asm volatile("mbarrier.arrive.shared::cta.b64 _, [%0];" :: "r"(bar) : "memory"); }
__device__ __forceinline__ bool mbar_try(uint32_t bar, uint32_t parity) {
    uint32_t ok;
    asm volatile("{\n .reg .pred p;\n mbarrier.try_wait.parity.shared::cta.b64 p, [%1], %2;\n selp.u32 %0, 1, 0, p;\n}" : "=r"(ok) : "r"(bar), "r"(parity) : "memory");
    return ok != 0;
}
__device__ __forceinline__ bool mbar_test(uint32_t bar, uint32_t parity) {
    uint32_t ok;
    asm volatile("{\n .reg .pred p;\n mbarrier.test_wait.parity.shared::cta.b64 p, [%1], %2;\n selp.u32 %0, 1, 0, p;\n}" : "=r"(ok) : "r"(bar), "r"(parity) : "memory");
    return ok != 0;
}
__device__ __forceinline__ void mbar_wait(uint32_t bar, uint32_t parity) {
    int n = 0;
    while (!mbar_try(bar, parity) && ++n < SPIN_LIMIT) {}
}
__device__ __forceinline__ unsigned long long gtime() { unsigned long long t; asm volatile("mov.u64 %0, %globaltimer;" : "=l"(t)); return t; }
__device__ __forceinline__ uint32_t gtime32() { uint32_t t; asm volatile("mov.u32 %0, %globaltimer_lo;" : "=r"(t)); return t; }
__device__ __forceinline__ void bar_main() { asm volatile("bar.sync 1, 256;" ::: "memory"); }

__device__ __forceinline__ void mma16816(float (&c)[4], uint32_t a0, uint32_t a1, uint32_t a2, uint32_t a3, uint32_t b0, uint32_t b1) {
    asm("mma.sync.aligned.m16n8k16.row.col.f32.bf16.bf16.f32 {%0,%1,%2,%3}, {%4,%5,%6,%7}, {%8,%9}, {%0,%1,%2,%3};"
        : "+f"(c[0]), "+f"(c[1]), "+f"(c[2]), "+f"(c[3]) : "r"(a0), "r"(a1), "r"(a2), "r"(a3), "r"(b0), "r"(b1));
}
__device__ __forceinline__ void mmaA(float (&c)[4], const uint32_t (&a)[4], uint32_t b0, uint32_t b1) { mma16816(c, a[0], a[1], a[2], a[3], b0, b1); }
__device__ __forceinline__ void mmaAv(float (&c)[4], const uint32_t (&a)[4], uint32_t b0, uint32_t b1) {
    asm volatile("mma.sync.aligned.m16n8k16.row.col.f32.bf16.bf16.f32 {%0,%1,%2,%3}, {%4,%5,%6,%7}, {%8,%9}, {%0,%1,%2,%3};"
        : "+f"(c[0]), "+f"(c[1]), "+f"(c[2]), "+f"(c[3]) : "r"(a[0]), "r"(a[1]), "r"(a[2]), "r"(a[3]), "r"(b0), "r"(b1) : "memory");
}
__device__ __forceinline__ void mma8(float (&c)[4], uint32_t a0, uint32_t a1, uint32_t b0) {
    asm("mma.sync.aligned.m16n8k8.row.col.f32.bf16.bf16.f32 {%0,%1,%2,%3}, {%4,%5}, {%6}, {%0,%1,%2,%3};"
        : "+f"(c[0]), "+f"(c[1]), "+f"(c[2]), "+f"(c[3]) : "r"(a0), "r"(a1), "r"(b0));
}
struct W80 { uint32_t a[2][4], c[2]; };
template <int N> __device__ __forceinline__ void mul80(float (&acc)[N][4], const W80 (&W)[N], const uint4& b, uint32_t b4) {
#pragma unroll
    for (int m = 0; m < N; m++) mmaA(acc[m], W[m].a[0], b.x, b.y);
#pragma unroll
    for (int m = 0; m < N; m++) mmaA(acc[m], W[m].a[1], b.z, b.w);
#pragma unroll
    for (int m = 0; m < N; m++) mma8(acc[m], W[m].c[0], W[m].c[1], b4);
}
__device__ __forceinline__ void ldsm2t(uint32_t (&r)[2], uint32_t addr) {
    asm volatile("ldmatrix.sync.aligned.m8n8.x2.trans.shared.b16 {%0,%1}, [%2];" : "=r"(r[0]), "=r"(r[1]) : "r"(addr) : "memory");
}
__device__ __forceinline__ void mmaV(float (&c)[4], const uint4& a, uint32_t b0, uint32_t b1) { mma16816(c, a.x, a.y, a.z, a.w, b0, b1); }
__device__ __forceinline__ void ldsm4(uint32_t (&r)[4], uint32_t addr) {
    asm volatile("ldmatrix.sync.aligned.m8n8.x4.shared.b16 {%0,%1,%2,%3}, [%4];" : "=r"(r[0]), "=r"(r[1]), "=r"(r[2]), "=r"(r[3]) : "r"(addr) : "memory");
}
__device__ __forceinline__ void ldsm4t(uint32_t (&r)[4], uint32_t addr) {
    asm volatile("ldmatrix.sync.aligned.m8n8.x4.trans.shared.b16 {%0,%1,%2,%3}, [%4];" : "=r"(r[0]), "=r"(r[1]), "=r"(r[2]), "=r"(r[3]) : "r"(addr) : "memory");
}
__device__ __forceinline__ uint32_t lds16(uint32_t a) { uint16_t v; asm volatile("ld.shared.u16 %0, [%1];" : "=h"(v) : "r"(a) : "memory"); return v; }
__device__ __forceinline__ uint32_t lds32(uint32_t a) { uint32_t v; asm volatile("ld.shared.u32 %0, [%1];" : "=r"(v) : "r"(a) : "memory"); return v; }
__device__ __forceinline__ float ldsf(uint32_t a) { return __uint_as_float(lds32(a)); }
__device__ __forceinline__ uint2 lds64(uint32_t a) { uint2 v; asm volatile("ld.shared.v2.u32 {%0,%1}, [%2];" : "=r"(v.x), "=r"(v.y) : "r"(a) : "memory"); return v; }
__device__ __forceinline__ uint4 lds128(uint32_t a) { uint4 v; asm volatile("ld.shared.v4.u32 {%0,%1,%2,%3}, [%4];" : "=r"(v.x), "=r"(v.y), "=r"(v.z), "=r"(v.w) : "r"(a) : "memory"); return v; }
__device__ __forceinline__ int ldsvol(uint32_t a) { int v; asm volatile("ld.volatile.shared.u32 %0, [%1];" : "=r"(v) : "r"(a) : "memory"); return v; }
__device__ __forceinline__ uint2 ldsvol64(uint32_t a) { uint2 v; asm volatile("{\n .reg .b64 d;\n ld.volatile.shared.b64 d, [%2];\n mov.b64 {%0,%1}, d;\n}" : "=r"(v.x), "=r"(v.y) : "r"(a) : "memory"); return v; }
__device__ __forceinline__ void stsvol64(uint32_t a, uint32_t x, uint32_t y) { asm volatile("{\n .reg .b64 d;\n mov.b64 d, {%1,%2};\n st.volatile.shared.b64 [%0], d;\n}" :: "r"(a), "r"(x), "r"(y) : "memory"); }
__device__ __forceinline__ void stsvol(uint32_t a, int v) { asm volatile("st.volatile.shared.u32 [%0], %1;" :: "r"(a), "r"(v) : "memory"); }
__device__ __forceinline__ void sts_hi16(uint32_t a, float v) { asm volatile("{\n .reg .b16 lo, hi;\n mov.b32 {lo, hi}, %1;\n st.shared.u16 [%0], hi;\n}" :: "r"(a), "r"(__float_as_uint(v)) : "memory"); }
__device__ __forceinline__ void sts16(uint32_t a, uint32_t v) { asm volatile("st.shared.u16 [%0], %1;" :: "r"(a), "r"(v) : "memory"); }
__device__ __forceinline__ void sts32(uint32_t a, uint32_t v) { asm volatile("st.shared.u32 [%0], %1;" :: "r"(a), "r"(v) : "memory"); }
__device__ __forceinline__ void stsf(uint32_t a, float v) { sts32(a, __float_as_uint(v)); }
__device__ __forceinline__ void sts64(uint32_t a, uint32_t x, uint32_t y) { asm volatile("st.shared.v2.u32 [%0], {%1,%2};" :: "r"(a), "r"(x), "r"(y) : "memory"); }

__device__ __forceinline__ void sts_hi16_if(bool p, uint32_t a, float v) {
    asm volatile("{\n .reg .pred p;\n .reg .b16 lo, hi;\n setp.ne.u32 p, %2, 0;\n mov.b32 {lo, hi}, %1;\n @p st.shared.u16 [%0], hi;\n}" :: "r"(a), "r"(__float_as_uint(v)), "r"((uint32_t)p) : "memory");
}
__device__ __forceinline__ void sts32_if(bool p, uint32_t a, uint32_t v) {
    asm volatile("{\n .reg .pred p;\n setp.ne.u32 p, %2, 0;\n @p st.shared.u32 [%0], %1;\n}" :: "r"(a), "r"(v), "r"((uint32_t)p) : "memory");
}
__device__ __forceinline__ void sts64_if(bool p, uint32_t a, float x, float y) {
    asm volatile("{\n .reg .pred p;\n setp.ne.u32 p, %3, 0;\n @p st.shared.v2.f32 [%0], {%1,%2};\n}" :: "r"(a), "f"(x), "f"(y), "r"((uint32_t)p) : "memory");
}
__device__ __forceinline__ void arrive_if(bool p, uint32_t bar) {
    asm volatile("{\n .reg .pred p;\n setp.ne.u32 p, %1, 0;\n @p mbarrier.arrive.shared::cta.b64 _, [%0];\n}" :: "r"(bar), "r"((uint32_t)p) : "memory");
}
__device__ __forceinline__ void opaque(uint32_t& v) { asm volatile("" : "+r"(v)); }
__device__ __forceinline__ void keep(uint32_t& v) { asm volatile("" : "+r"(v)); }
__device__ __forceinline__ void keep(float& v) { asm volatile("" : "+f"(v)); }
template <class T> __device__ __forceinline__ void keep(T*& v) { asm volatile("" : "+l"(v)); }

__device__ __forceinline__ uint32_t ldp32(const char* p) { uint32_t v; asm volatile("ld.relaxed.gpu.global.u32 %0, [%1];" : "=r"(v) : "l"(p) : "memory"); return v; }
__device__ __forceinline__ uint2 ldp64(const char* p) {
    uint2 v; asm volatile("{\n .reg .b64 d;\n ld.relaxed.gpu.global.b64 d, [%2];\n mov.b64 {%0,%1}, d;\n}" : "=r"(v.x), "=r"(v.y) : "l"(p) : "memory"); return v;
}
__device__ __forceinline__ uint32_t tagw(float f, uint32_t par) { return (__float_as_uint(f) & ~1u) | par; }
__device__ __forceinline__ void stp32(char* p, float a, uint32_t par) { asm volatile("st.relaxed.gpu.global.u32 [%0], %1;" :: "l"(p), "r"(tagw(a, par)) : "memory"); }
__device__ __forceinline__ void stp64(char* p, float a, float b, uint32_t par) {
    asm volatile("{\n .reg .b64 d;\n mov.b64 d, {%1,%2};\n st.relaxed.gpu.global.b64 [%0], d;\n}" :: "l"(p), "r"(tagw(a, par)), "r"(tagw(b, par)) : "memory");
}
__device__ __forceinline__ void stp32_if(bool p, char* d, float a, uint32_t par) {
    asm volatile("{\n .reg .pred p;\n setp.ne.u32 p, %2, 0;\n @p st.relaxed.gpu.global.u32 [%0], %1;\n @p st.relaxed.gpu.global.u32 [%0+4096], %1;\n}" :: "l"(d), "r"(tagw(a, par)), "r"((uint32_t)p) : "memory");
}
__device__ __forceinline__ void stp64_if(bool p, char* d, uint32_t lo, uint32_t hi) {
    asm volatile("{\n .reg .pred p;\n .reg .b64 d;\n setp.ne.u32 p, %3, 0;\n mov.b64 d, {%1,%2};\n @p st.relaxed.gpu.global.b64 [%0], d;\n @p st.relaxed.gpu.global.b64 [%0+4096], d;\n}" :: "l"(d), "r"(lo), "r"(hi), "r"((uint32_t)p) : "memory");
}
__device__ __forceinline__ uint32_t chk2(uint32_t a, uint32_t b, uint32_t par) { uint32_t r; asm("lop3.b32 %0, %1, %2, %3, 0x7E;" : "=r"(r) : "r"(a), "r"(b), "r"(par)); return r; }
__device__ __forceinline__ uint32_t or3(uint32_t a, uint32_t b, uint32_t c) { uint32_t r; asm("lop3.b32 %0, %1, %2, %3, 0xFE;" : "=r"(r) : "r"(a), "r"(b), "r"(c)); return r; }
__device__ __forceinline__ uint32_t chk8(const uint32_t (&v)[8], uint32_t par) { return or3(chk2(v[0], v[1], par), chk2(v[2], v[3], par), or3(chk2(v[4], v[5], par), chk2(v[6], v[7], par), 0)); }
__device__ __forceinline__ uint32_t chk8(const uint2 (&v)[8], uint32_t par) { return or3(chk2(v[0].x, v[1].x, par), chk2(v[2].x, v[3].x, par), or3(chk2(v[4].x, v[5].x, par), chk2(v[6].x, v[7].x, par), 0)); }
__device__ __forceinline__ uint32_t chk8y(const uint2 (&v)[8], uint32_t par) { return or3(chk2(v[0].y, v[1].y, par), chk2(v[2].y, v[3].y, par), or3(chk2(v[4].y, v[5].y, par), chk2(v[6].y, v[7].y, par), 0)); }
__device__ __forceinline__ uint32_t chk4(const uint2 (&v)[4], uint32_t par) { return or3(chk2(v[0].x, v[0].y, par), chk2(v[1].x, v[1].y, par), or3(chk2(v[2].x, v[2].y, par), chk2(v[3].x, v[3].y, par), 0)); }
__device__ __forceinline__ float asf(uint32_t v) { return __uint_as_float(v); }
__device__ __forceinline__ float sum8(const uint32_t (&v)[8]) { return ((asf(v[0]) + asf(v[1])) + (asf(v[2]) + asf(v[3]))) + ((asf(v[4]) + asf(v[5])) + (asf(v[6]) + asf(v[7]))); }
__device__ __forceinline__ float sum8x(const uint2 (&v)[8]) { return ((asf(v[0].x) + asf(v[1].x)) + (asf(v[2].x) + asf(v[3].x))) + ((asf(v[4].x) + asf(v[5].x)) + (asf(v[6].x) + asf(v[7].x))); }
__device__ __forceinline__ float sum8y(const uint2 (&v)[8]) { return ((asf(v[0].y) + asf(v[1].y)) + (asf(v[2].y) + asf(v[3].y))) + ((asf(v[4].y) + asf(v[5].y)) + (asf(v[6].y) + asf(v[7].y))); }

__device__ __forceinline__ uint32_t pack2(float lo, float hi) { uint32_t r; asm("cvt.rn.bf16x2.f32 %0, %1, %2;" : "=r"(r) : "f"(hi), "f"(lo)); return r; }
__device__ __forceinline__ float bfr(float x) { return __uint_as_float(pack2(0.0f, x)); }
__device__ __forceinline__ float ex2(float x) { float r; asm("ex2.approx.ftz.f32 %0, %1;" : "=f"(r) : "f"(x)); return r; }
__device__ __forceinline__ float rcp(float x) { float r; asm("rcp.approx.ftz.f32 %0, %1;" : "=f"(r) : "f"(x)); return r; }
__device__ __forceinline__ float sqrt_(float x) { float r; asm("sqrt.approx.ftz.f32 %0, %1;" : "=f"(r) : "f"(x)); return r; }
__device__ __forceinline__ float bf_lo(uint32_t v) { return __uint_as_float(v << 16); }
__device__ __forceinline__ float bf_hi(uint32_t v) { return __uint_as_float(v & 0xffff0000u); }
__device__ __forceinline__ float sel4(int k, float a, float b, float c, float d) { return (k & 2) ? ((k & 1) ? d : c) : ((k & 1) ? b : a); }
constexpr float LOG2E = 1.4426950408889634f;
constexpr uint32_t ONES = 0x3f803f80u;

__device__ __forceinline__ void ln_stats(float sum, float sq, float& mean, float& den) {
    const float m = sum * (1.0f / 640.0f);
    const float var = fmaxf(fmaf(sq, 1.0f / 640.0f, -m * m), 0.0f);
    mean = bfr(m);
    den = bfr(sqrt_(bfr(bfr(var) + 1e-5f)));
}
__device__ __forceinline__ float sigmoidf_(float x) { return rcp(1.0f + ex2(-x * LOG2E)); }

#define TSTAMP(k) do {} while (0)
#define TST(k) do {} while (0)

#define CSTAMP(k) do {} while (0)
template <int N> __device__ __forceinline__ uint32_t lag(uint32_t sb, uint32_t z = 0) {
#pragma unroll
    for (int k = 0; k < N; k++) z = ldsvol(sb + S_ZERO + z);
    return z;
}
__device__ __forceinline__ void warm_mma(uint32_t& a, uint32_t& b) {
    asm volatile("mma.sync.aligned.m16n8k8.row.col.f16.f16.f16.f16 {%0,%1}, {%0,%1}, {%0}, {%0,%1};" : "+r"(a), "+r"(b) :: "memory");
}
#define KWNS2 20
#define KWNS 200
template <int STRIDE>
__device__ __forceinline__ float gather8(const char* p, uint32_t par) {
    uint32_t v[8];
    int guard = 0;
    do {
#pragma unroll
        for (int s = 0; s < 8; s++) v[s] = ldp32(p + s * STRIDE);
    } while ((chk8(v, par) & 1) && ++guard < SPIN_LIMIT);
    return sum8(v);
}
template <class F>
__device__ __forceinline__ void gather16(const char* p, uint32_t par, int k, F use) {
    uint32_t v[8], u[8];
    int guard = 0;
    bool again;
    do {
#pragma unroll
        for (int s = 0; s < 8; s++) v[s] = ldp32(p + s * 512);
#pragma unroll
        for (int s = 0; s < 8; s++) u[s] = ldp32(p + HALF + s * 512);
        const uint32_t stale = use(sum8(v) + sum8(u), ((v[0] ^ par) & 1) * 8);
        again = __any_sync(~0u, (or3(chk8(v, par), chk8(u, par), stale) & 1) != 0);
    } while (again & (++guard < SPIN_LIMIT));
    SWEEPS(k, guard - 1);
}

struct Params {
    const __nv_bfloat16 *x, *k, *v, *wr;
    __nv_bfloat16* out;
};
struct Maps { CUtensorMap k, v, vu, wq, wo, wg, wu, wd; };

constexpr int KV_BATCH_KEYS = 32 * 4096;

__device__ __forceinline__ void tma2d(uint32_t dst, const CUtensorMap* m, int c0, int c1, uint32_t bar, uint32_t bytes, uint64_t pol) {
    asm volatile("{\n .reg .pred p;\n elect.sync _|p, 0xffffffff;\n"
                 " @p mbarrier.arrive.expect_tx.shared::cta.b64 _, [%2], %6;\n"
                 " @p cp.async.bulk.tensor.2d.shared::cluster.global.mbarrier::complete_tx::bytes.L2::cache_hint [%0], [%1, {%3, %4}], [%2], %5;\n}"
                 :: "r"(dst), "l"(m), "r"(bar), "r"(c0), "r"(c1), "l"(pol), "r"(bytes) : "memory");
}
__device__ __forceinline__ void scrap_copy(uint32_t dst, const char* src, uint32_t bar) {
    asm volatile("{\n .reg .pred p;\n elect.sync _|p, 0xffffffff;\n"
                 " @p mbarrier.arrive.expect_tx.shared::cta.b64 _, [%2], 12288;\n"
                 " @p cp.async.bulk.shared::cluster.global.mbarrier::complete_tx::bytes [%0], [%1], 4096, [%2];\n"
                 " @p cp.async.bulk.shared::cluster.global.mbarrier::complete_tx::bytes [%0], [%1+4096], 4096, [%2];\n"
                 " @p cp.async.bulk.shared::cluster.global.mbarrier::complete_tx::bytes [%0], [%1+8192], 4096, [%2];\n}"
                 :: "r"(dst), "l"(src), "r"(bar) : "memory");
}
__device__ __forceinline__ void prefetch_l2(const void* p, uint32_t bytes) {
    asm volatile("{\n .reg .pred p;\n elect.sync _|p, 0xffffffff;\n @p cp.async.bulk.prefetch.L2.global [%0], %1;\n}" :: "l"(p), "r"(bytes) : "memory");
}
__device__ __forceinline__ uint64_t pol_first() { uint64_t p; asm("createpolicy.fractional.L2::evict_first.b64 %0, 1.0;" : "=l"(p)); return p; }
__device__ __forceinline__ uint64_t pol_normal() { uint64_t p; asm("createpolicy.fractional.L2::evict_normal.b64 %0, 1.0;" : "=l"(p)); return p; }
__device__ __forceinline__ bool utest(uint32_t bar, uint32_t parity) { return __all_sync(~0u, mbar_test(bar, parity)); }
__device__ __forceinline__ void uwait(uint32_t bar, uint32_t parity) {
    int n = 0;
    while (!__all_sync(~0u, mbar_try(bar, parity)) && ++n < SPIN_LIMIT) {}
}
template <int A, int B, int CNT> __device__ __forceinline__ void init_bars(uint32_t sb) {
#pragma unroll 1
    for (int k = A; k < B; k++)
        asm volatile("{\n .reg .pred p;\n elect.sync _|p, 0xffffffff;\n @p mbarrier.init.shared::cta.b64 [%0], %1;\n}" :: "r"(sb + S_BAR + 8 * k), "n"(CNT) : "memory");
}
__device__ __forceinline__ int first_key() { return (blockIdx.x >> 2) * 4096 + 3072 + (blockIdx.x & 3) * 256; }
__device__ __forceinline__ void load_tile(const CUtensorMap* m, uint32_t dst, uint32_t bar, uint32_t bytes, int key, uint64_t pol) { tma2d(dst, m, 0, 3 * key, bar, bytes, pol); }
__device__ __forceinline__ const char* unit_ptr(const Params& P, int n) {
    return (const char*)((n & 16) ? P.v : P.k) + (size_t)(first_key() + (n >> 5) * KV_BATCH_KEYS + (n & 15) * 16) * 384;
}
#define LSTAMP(k) do {} while (0)

__device__ __forceinline__ uint32_t k_place(uint32_t b, uint32_t s) { return s + 3 + 5 * (b & 1); }
__device__ __forceinline__ uint32_t v_place(uint32_t b, uint32_t s) { return s < 3 ? s : s + 8 - 8 * (b & 1); }
__device__ __forceinline__ void k_load(const Maps& M, uint32_t dst, uint32_t bar, int key8, uint64_t pol) {
    asm volatile("{\n .reg .pred p;\n elect.sync _|p, 0xffffffff;\n"
                 " @p mbarrier.arrive.expect_tx.shared::cta.b64 _, [%2], 6144;\n"
                 " @p cp.async.bulk.tensor.4d.shared::cluster.global.mbarrier::complete_tx::bytes.L2::cache_hint [%0], [%1, {0, 0, 0, %3}], [%2], %4;\n}"
                 :: "r"(dst), "l"(&M.k), "r"(bar), "r"(key8), "l"(pol) : "memory");
}
__device__ __forceinline__ int unit_key8(uint32_t n) { return first_key() / 8 + (n >> 4) * (KV_BATCH_KEYS / 8) + 2 * (n & 15); }
__device__ __forceinline__ void ring_load(const Maps& M, uint32_t sb, uint32_t b, uint32_t u, uint32_t pos) {
    if (u < 16) k_load(M, sb + pos * UNIT, sb + S_RING + 8 * pos, unit_key8(16 * b + u), pol_normal());
    else load_tile(&M.vu, sb + pos * UNIT, sb + S_FV + 4 * (pos & 6), UNIT, first_key() + b * KV_BATCH_KEYS + 16 * pos, pol_first());
}
__device__ __forceinline__ uint32_t token(bool p, uint32_t a, uint32_t n) {
    uint32_t v;
    asm volatile("{\n .reg .pred p;\n setp.ne.u32 p, %2, 0;\n mov.u32 %0, 0;\n @p atom.shared.exch.b32 %0, [%1], %3;\n}" : "=r"(v) : "r"(a), "r"((uint32_t)p), "r"(n) : "memory");
    return v;
}
__device__ __forceinline__ void place_load(const Maps& M, uint32_t sb, uint32_t n) {
    k_load(M, sb + k_place(n >> 4, 0) * SLOT + (n & 15) * UNIT, sb + S_FK + 4 * (n & 14), unit_key8(n), pol_first());
}
__device__ __forceinline__ void v_load(const Maps& M, uint32_t sb, uint32_t b, uint32_t s) {
    load_tile(&M.v, sb + v_place(b, s) * SLOT, sb + S_FV + 8 * s, SLOT, first_key() + b * KV_BATCH_KEYS + 32 * s, pol_first());
}
__device__ __forceinline__ bool due(uint32_t t) { return __all_sync(~0u, (int)(gtime32() * 16 - t) >= 0); }
__device__ __forceinline__ bool reached(uint32_t a, int v) { return __all_sync(~0u, ldsvol(a) >= v); }

__device__ __forceinline__ void stream_warp(const Params& P, const Maps& M, uint32_t sb, uint32_t lane) {
    const uint64_t pol = pol_first();
    const int bid = blockIdx.x, g = bid >> 3, i = bid & 7;
    const uint32_t wf = sb + S_WFULL;
    if (PF0 > 0 && !PFTOP) prefetch_l2(unit_ptr(P, 0), PF0 * UNIT);
    uint32_t tn = __shfl_sync(~0u, gtime32(), 0) * 16 - T_LEAD;
    auto pace = [&](uint32_t dt) {
        int k = 0;
        uint32_t now;
        do now = __shfl_sync(~0u, gtime32(), 0) * 16; while ((int)(now - tn) < 0 && ++k < SPIN_LIMIT);
        if ((int)(now - tn) > SLACK0) tn = now - SLACK0;
        tn += dt;
    };
#pragma unroll
    for (int k = 0; k < 10; k++) {
        if (k < 2) {
            if (k == 0) init_bars<26, 27, 1>(sb); else init_bars<27, 37, 1>(sb);
            asm volatile("fence.mbarrier_init.release.cluster;" ::: "memory");
            if (k == 1) { asm volatile("bar.arrive 2, %0;" :: "n"(NTHR) : "memory"); asm volatile("bar.sync 3, 128;" ::: "memory"); }
        }
        if (k >= WIN_W) uwait(wf + 8 * (k - WIN_W), 0);
        pace(TAUW * 5 / 2);
        if (k < 4) tma2d(sb + ST_WQ + 15360 * k, &M.wq, 384 * g + 192 * (k >> 1), 80 * i + 40 * (k & 1), wf + 8 * k, 15360, pol);
        else if (k < 6) tma2d(sb + ST_WG + 15360 * (k - 4), k == 4 ? &M.wg : &M.wu, 96 * g, 80 * i, wf + 8 * k, 15360, pol);
        else tma2d(sb + ST_WO + 15360 * (k - 6), &M.wo, 80 * i, 384 * g + 96 * (k - 6), wf + 8 * k, 15360, pol);
    }
#pragma unroll 1
    for (int n = 0; n < 16; n++) {
        if (n == 0 || n == 5 || n == 11) uwait(sb + S_RELW + (n == 0 ? 0 : n == 5 ? 8 : 16), 0);
        uwait(n < WIN_S ? wf + 8 * (10 - WIN_S + n) : sb + S_FV + 8 * ((n - WIN_S) ^ 8), 0);
        pace(max(min(2 * n + 2 - PF0, 2), 0) * TAU0);
        if (n < 8) { place_load(M, sb, 2 * n); place_load(M, sb, 2 * n + 1); }
        else if (n < 11) { ring_load(M, sb, 0, 2 * n, 2 * n - 16); ring_load(M, sb, 0, 2 * n + 1, 2 * n - 15); }
        else v_load(M, sb, 0, n - 8);
        if (n == 7) { pace(TAUW * 5 / 2); tma2d(sb + S_WD, &M.wd, 80 * i, 96 * g, wf + 80, 15360, pol); }
    }
    int nd = 0;
    uint32_t q[4];
#pragma unroll
    for (int r = 0; r < 4; r++) q[r] = sb + S_FV + 8 * (7 - r);
    tn -= TSH;
    uint32_t td = tn;
    uint32_t pos = 2;
#pragma unroll 1
    for (int m = 16; m < 64; m++) {
        const int b = m >> 4, j = m & 15;
        const char* src = unit_ptr(P, 2 * m);
        const uint32_t tok = sb + S_TOK + (j < 3 ? 4 * pos : j < 11 ? 24 + 4 * pos : 16 + 4 * j) + 4 * lane;
        static_assert(WIN_U <= 12, "a ring position has at most one token of the timetable");
        int k = 0;
        while (true) {
            const uint2 c = lds64(sb + S_KF);
            if (__all_sync(~0u, mbar_test(q[WIN_S - 1] & ~1u, q[WIN_S - 1] & 1) & (min((int)c.x + 1, (int)c.y) >= 16 * b + min(2 * j + 2 - WIN_U, 16))) || ++k >= SPIN_LIMIT) break;
        }
        uint32_t now;
        while (true) {
            now = __shfl_sync(~0u, gtime32(), 0) * 16;
            if ((int)(now - td) >= 0 || ++k >= SPIN_LIMIT) break;
            if (PSLEEP > 0 && (int)(td - now) > 16 * PSLEEP * 2) __nanosleep(PSLEEP);
        }
        const uint32_t mine = __ballot_sync(~0u, token(lane < (j < 11 ? 2 : 1), tok, 2 * m + lane) == 2 * m + lane);
        q[3] = q[2]; q[2] = q[1]; q[1] = q[0]; q[0] = sb + S_QRDY;
        if (j < 11) {
            if (mine & 1) ring_load(M, sb, b, 2 * j, pos); else prefetch_l2(src, UNIT);
            if (mine & 2) ring_load(M, sb, b, 2 * j + 1, pos + 1); else prefetch_l2(src + UNIT, UNIT);
            if (j >= 8) q[0] = (sb + S_FV + 8 * (j - 8)) | (b & 1);
        } else if (mine) { v_load(M, sb, b, j - 8); q[0] = (sb + S_FV + 8 * (j - 8)) | (b & 1); }
        else if (j - 8 >= VPF) prefetch_l2(src, SLOT);
        else {
            scrap_copy(sb + S_DUMMY, src, sb + S_DBAR + 8 * (nd & 3));
            q[0] = (sb + S_DBAR + 8 * (nd & 3)) | ((nd >> 2) & 1);
            nd++;
        }
        pos = j == 15 ? 2 : pos == 4 ? 0 : pos + 2;
        if ((int)(now - tn) > SLACK) tn = now - SLACK;
        tn += 2 * TAU;
        td = (int)(tn - now) > 2 * TMIN ? tn : now + 2 * TMIN;
        if (m >= 48 + JFREE) td = now + TFREE;
    }
#pragma unroll 1
    for (int m = max(nd - 4, 0); m < nd; m++) uwait(sb + S_DBAR + 8 * (m & 3), (m >> 2) & 1);
}

__host__ __device__ constexpr uint64_t bit_list(uint32_t m) { uint64_t r = 0; int n = 0; for (int k = 0; k < 12; k++) if ((m >> k) & 1) r |= (uint64_t)k << (4 * n++); return r; }
__device__ __forceinline__ float scaled(float s) { return bfr(bfr(s) * 0.07216878364870322f); }
__device__ __forceinline__ void probs(float s, uint32_t ps, uint32_t src, uint32_t ln) {
    const uint32_t q8 = ln >> 2, t4 = ln & 3;
    int key = __float_as_int(s);
    key ^= (key >> 31) & 0x7fffffff;
    key = __reduce_max_sync(~0u, key);
    key ^= (key >> 31) & 0x7fffffff;
    const float ml = __int_as_float(key) * LOG2E;
    sts16(ps + 64 * src + (q8 >> 1) * 16 + t4 * 4 + (q8 & 1) * 2, pack2(ex2(fmaf(s, LOG2E, -ml)), 0.f));
    stsf(ps + PS_MAX + 4 * src, ml);
}
template <int H> __device__ __forceinline__ uint32_t b_pos(uint32_t e) { const uint32_t h = e >= H, k = e - H * h; return h * 192 + (k & 6) * 24 + (k >> 3) * 4 + (k & 1) * 2; }
__device__ __forceinline__ uint32_t a_pos(uint32_t e) { const uint32_t h = e >= 40, k = e - 40 * h; return (k & 6) * 24 + (k >> 3) * 8 + h * 4 + (k & 1) * 2; }
__device__ __forceinline__ uint32_t q_pos(uint32_t d) { const uint32_t s = 3 * ((d >> 4) & 3) + (d >> 6); return s * 32 + (d & 6) * 4 + ((d >> 3) & 1) * 4 + (d & 1) * 2; }
__device__ __forceinline__ uint32_t k_off(uint32_t ln) { return (ln & 8) * 384 + (ln & 7) * 128 + (((ln & 7) ^ (ln >> 4)) << 4); }

#define HSTAMP(k) do {} while (0)
__device__ __forceinline__ char* xwindow() { return reinterpret_cast<char*>((reinterpret_cast<uintptr_t>(g_x) + (2u << 20) - 1) & ~(uintptr_t)((2u << 20) - 1)); }

struct XPtr {
    uint32_t lo, hi;
    __device__ __forceinline__ explicit XPtr(char* p) : lo((uint32_t)(uintptr_t)p), hi((uint32_t)((uintptr_t)p >> 32)) {}
    __device__ __forceinline__ XPtr(uint32_t l, uint32_t h) : lo(l), hi(h) {}
    __device__ __forceinline__ XPtr operator+(uint32_t o) const { return XPtr(lo + o, hi); }
    __device__ __forceinline__ operator char*() const { uint64_t p; asm("mov.b64 %0, {%1, %2};" : "=l"(p) : "r"(lo), "r"(hi)); return (char*)p; }
};
__device__ __forceinline__ void keep(XPtr& v) { keep(v.lo); }

__device__ __forceinline__ void side_warp(uint32_t sb) {
    const uint32_t bid = blockIdx.x, g = bid >> 3, i = bid & 7, P = pairG(0, 0, i);
    char* p = xwindow() + P * 8192 + (g >> 3) * HALF + (g & 7) * 512 + 448;
    uint32_t best[2] = {~0u, ~0u};
    asm volatile("st.relaxed.gpu.global.b32 [%0], 1;" :: "l"(p) : "memory");
    asm volatile("st.relaxed.gpu.global.b32 [%0], 1;" :: "l"(p + COPY) : "memory");
#pragma unroll 1
    for (int r = 0; r < 64; r++) {
        if (r >= 4 && !(r & 1) && min(best[0], best[1]) < 380 && max(best[0], best[1]) > min(best[0], best[1]) + 80) break;
        uint32_t c0, c1, v;
        asm volatile("mov.u32 %0, %clock;" : "=r"(c0) :: "memory");
        asm volatile("atom.relaxed.gpu.global.exch.b32 %0, [%1], 0;" : "=r"(v) : "l"(p + (r & 1) * COPY) : "memory");
        asm volatile("{\n .reg .pred q;\n setp.eq.u32 q, %1, 0x13579bdf;\n mov.u32 %0, 0;\n @!q mov.u32 %0, %clock;\n}" : "=r"(c1) : "r"(v) : "memory");
        if (r & 1) best[1] = min(best[1], c1 - c0); else best[0] = min(best[0], c1 - c0);
    }
    stsvol(sb + S_SIDE, 1 + ((best[1] < best[0]) ^ (__popc(P & PMASK) & 1)));
}

template <int N>
__device__ __forceinline__ void hop_a(const char* src, uint32_t par, uint32_t dst, bool st, int k) {
    uint2 v[N][4];
    float e[4], rl;
    int guard = 0;
    bool again;
    do {
#pragma unroll
        for (int s = 0; s < 4 * N; s++) v[s / 4][s % 4] = ldp64(src + (s / 4) * 256 + (s % 4) * 1024);
        again = __any_sync(~0u, ((chk4(v[0], par) | chk4(v[N - 1], par)) & 1) != 0);
        const int M = max(max((int)v[0][0].x, (int)v[0][1].x), max((int)v[0][2].x, (int)v[0][3].x)) - 254;
#pragma unroll
        for (int s = 0; s < 4; s++) e[s] = __int_as_float(max((int)v[0][s].x - M, 0) << 22);
        rl = rcp(fmaf(e[0], asf(v[0][0].y), e[1] * asf(v[0][1].y)) + fmaf(e[2], asf(v[0][2].y), e[3] * asf(v[0][3].y)));
#pragma unroll
        for (int s = 0; s < 4; s++) e[s] = __shfl_sync(~0u, e[s], 24);
        keep(rl);
    } while (again & (++guard < SPIN_LIMIT));
    rl = __shfl_sync(~0u, rl, 24);
#pragma unroll
    for (int n = 0; n < N; n++) {
        const float o0 = fmaf(e[0], asf(v[n][0].x), e[1] * asf(v[n][1].x)) + fmaf(e[2], asf(v[n][2].x), e[3] * asf(v[n][3].x));
        const float o1 = fmaf(e[0], asf(v[n][0].y), e[1] * asf(v[n][1].y)) + fmaf(e[2], asf(v[n][2].y), e[3] * asf(v[n][3].y));
        sts32_if(st, dst + 192 * n, pack2(o0 * rl, o1 * rl));
    }
    SWEEPS(k, guard - 1);
    __syncwarp();
}

__device__ __forceinline__ void score_warp(const Maps& M, uint32_t sb, uint32_t h, uint32_t ln) {
    const uint32_t lane0 = ln;
    uwait(sb + S_QRDY, 0);
    const uint32_t q8 = ln >> 2;
    const uint32_t k0 = k_off(ln);
    uint32_t pos = h + 6, bar = sb + S_FK, par = 0, phases = 0;
    uint2 q = lds64(sb + S_QS + 8 * ln), qh = lds64(sb + S_QS + 8 * ln + 256);
    auto first_round = [&](uint32_t b, uint32_t ln) {
        uwait(sb + S_RELR, b & 1);
        const uint32_t u = h + 2 * ln, p = u < 4 ? u + 2 : u - 4;
        uint32_t todo = __ballot_sync(~0u, token(ln < 3, sb + S_TOK + 4 * p, 32 * b + 32 + u) == 32 * b + 32 + u);
#pragma unroll 1
        for (uint32_t r = h; todo; todo >>= 1, r += 2) if (todo & 1) ring_load(M, sb, b + 1, r, r < 4 ? r + 2 : r - 4);
    };
#pragma unroll 1
    for (uint32_t n = h; n < 64; n += 2) {
        HSTAMP(0);
        const uint32_t ua = sb + pos * UNIT;
        if (!__all_sync(~0u, mbar_try(bar, par))) uwait(bar, par);
        HSTAMP(1);
        float acc[2][4] = {};
        uint32_t mine = 0;
        const uint32_t id = n + (n & 48) + 6;
#pragma unroll
        for (int s = 0; s < 12; s++) {
            uint32_t kf[4];
            ldsm4(kf, (k0 ^ (32 * (s / 3))) + (ua + 1024 * (s % 3)));
            if (s == 11) {
                __syncwarp();
                mine = token(ln == 0 && n >= 16, sb + S_TOK + 24 + 4 * pos, id);
                stsvol(sb + S_KF + 4 * h, n + 1);
            }
            const bool m = q8 == (s & 7);
            mmaA(acc[s & 1], kf, m ? (s < 8 ? q.x : qh.x) : 0u, m ? (s < 8 ? q.y : qh.y) : 0u);
        }
        const uint32_t pos0 = pos;
        const bool last = (n & 14) == 14;
        pos = last ? h + 2 : n >= 16 && pos >= 4 ? h : pos + 2;
        bar = n >= 14 ? sb + S_RING + 8 * pos : bar + 8;
        par = n >= 14 ? (phases >> pos) & 1 : 0;
        phases ^= n >= 14 ? 1u << pos : 0;
        const float w0 = (acc[0][0] + acc[0][1]) + (acc[1][0] + acc[1][1]), w1 = (acc[0][2] + acc[0][3]) + (acc[1][2] + acc[1][3]);
        HSTAMP(2);
        if (__any_sync(~0u, mine == id)) ring_load(M, sb, n >> 4, (n & 15) + 6, pos0);
        HSTAMP(3);
        float s = ((ln & 1) ? w1 : w0) + __shfl_xor_sync(~0u, (ln & 1) ? w0 : w1, 1);
        s += __shfl_xor_sync(~0u, s, 2);
        sts_hi16(sb + S_SC + (((n & 12) >> 1) + h) * 64 + (n & 2) * 2 + (ln & 29) * 2, scaled(s));
        if (last) {
            __syncwarp();
            arrive_if(ln == 0, sb + S_SCO);
            const uint32_t b = n >> 4, ln = lane0 + lag<1>(sb);
            if (b > 0) {
                uwait(sb + S_RELK, (b - 1) & 1);
                if (h == 0) LSTAMP(64 + 2 * b);
                const uint32_t sl = 3 + h + 2 * ln, idv = 32 * b + 16 + 2 * sl;
                uint32_t todo = __ballot_sync(~0u, token(sl < 8, sb + S_TOK + 48 + 4 * sl, idv) == idv);
#pragma unroll 1
                for (uint32_t r = 3 + h; todo; todo >>= 1, r += 2) if (todo & 1) v_load(M, sb, b, r);
                const uint32_t g = blockIdx.x >> 3, pr = pairL(RA, 1, g), side = ldsvol(sb + S_SIDE);
                const char* src = xwindow() + pr * 8192 + ((side ^ 1 ^ __popc(pr & PMASK)) & 1) * COPY + h * HALF + 8 * min(ln, 24u);
                uwait(sb + S_RELV, (b - 1) & 1);
                __nanosleep(HOP1_NS);
#pragma unroll 1
                for (uint32_t r = 0; r < 4; r += 2) {
                    hop_a<2>(src + 256 * r, b & 1, sb + S_OS + 192 * (4 * h + r) + 96 + 4 * ln, ln < 24, 25);
                    if (r == RELR_AT && b < 3) first_round(b, ln);
                }
                arrive_if(ln == 0, sb + S_OS1);
            } else first_round(0, ln);
            q = lds64(sb + S_QS + 24 * ((n + 2) & 48) + 8 * ln); qh = lds64(sb + S_QS + 24 * ((n + 2) & 48) + 8 * ln + 256);
        }
    }
}

__global__ void __launch_bounds__(NTHR, 1)
fused_kernel(const Params P, const __grid_constant__ Maps M) {
    extern __shared__ __align__(1024) unsigned char smem[];
    const uint32_t sb = smem_u32(smem);
    const int tid = threadIdx.x, bid = blockIdx.x;
    if (PFTOP && tid == 0) {
        if (PFTOP == 2) asm volatile("prefetch.tensormap [%0];" :: "l"(&M.wq) : "memory");
        asm volatile("cp.async.bulk.prefetch.L2.global [%0], %1;" :: "l"(unit_ptr(P, 0)), "r"(PF0 * UNIT) : "memory");
    }
    const int w = __shfl_sync(~0u, tid >> 5, 0), lane = tid & 31;

    if (w >= 8) {
        asm volatile("setmaxnreg.dec.sync.aligned.u32 " REG_LO ";");
        if (w == 8) {
            stream_warp(P, M, sb, lane);
        } else {
            if (PFMAP && w == 11 && lane < 8) asm volatile("prefetch.tensormap [%0];" :: "l"(&M.k + lane) : "memory");
            if (w == 9) { init_bars<0, 3, 2>(sb); init_bars<3, 8, 1>(sb); init_bars<16, 22, 1>(sb); }
            else if (w == 10) { init_bars<8, 16, 2>(sb); init_bars<22, 26, 1>(sb); }
            else { init_bars<37, 38, 1>(sb); init_bars<38, 40, 8>(sb); init_bars<40, 41, 1>(sb); init_bars<41, 44, 8>(sb); init_bars<44, 46, 2>(sb); stsvol(sb + S_ZERO + 4 * lane, 0); if (lane < 16) stsvol(sb + S_LN + 4 * lane, 0); }
            asm volatile("fence.mbarrier_init.release.cluster;" ::: "memory");
            asm volatile("bar.arrive 3, 128;" ::: "memory");
            asm volatile("bar.sync 2, %0;" :: "n"(NTHR) : "memory");
            if (w < 11) score_warp(M, sb, w - 9, lane);
            else {
                if (lane == 0) side_warp(sb);
                __syncwarp();
                uint32_t a = 0, b = 0;
                int k = 0;
                while (ldsvol(sb + S_GATE) == 0 && ++k < SPIN_LIMIT) { warm_mma(a, b); __nanosleep(KWNS); }
                uint4* d = reinterpret_cast<uint4*>(reinterpret_cast<char*>(g_s) + XS + bid * 7680) + lane;
                const uint4 z = make_uint4(0, 0, 0, 0);
#pragma unroll 1
                for (int u = 0; u < 15; u++) d[32 * u] = z;
                d = reinterpret_cast<uint4*>(reinterpret_cast<char*>(g_s) + XS2 + bid * 768) + lane;
                d[0] = z;
                if (lane < 16) d[32] = z;
                const uint32_t side = (ldsvol(sb + S_SIDE) & 1) ^ 1, g = bid >> 3, i = bid & 7;
                const XPtr gx(xwindow());
                auto nearp = [&](uint32_t pr) { return gx.lo + pr * 8192 + ((side ^ __popc(pr & PMASK)) & 1) * COPY; };
                const uint32_t own = (i >> 2) * HALF + (i & 3) * 1024 + (lane & 7) * 128;
                const uint32_t pAC = nearp(pairL(lane >> 4, (lane >> 3) & 1, g)) + own, pE = nearp(pairL(RE, (lane >> 3) & 1, g)) + own;
                const uint32_t pG = nearp(pairG((lane >> 2) & 1, (lane >> 3) & 1, i)) + min(lane & 3, 2) * 128;
                uint32_t tr = 0, tk = 0, ph = 0, src = g + (lane >> 4), seen = 0, n = 16, cs = 0;
                bool go = false, first = true;
                while (n < 64 && ++k < SPIN_LIMIT) {
                    const uint32_t now = __shfl_sync(~0u, gtime32(), 0) * 16;
                    if (!go && utest((n & 15) < KRE_EARLY ? sb + S_RELK : sb + S_RELV, ((n >> 4) & 1) ^ 1)) { go = true; if ((int)(now - tk) > 0 || !(n & 15)) tk = now; }
                    if (go && (int)(now - tk) >= 0) {
                        place_load(M, sb, (n & 16) ? n : (n & 48) | ((n + 10) & 15));
                        tk += n >= 48 ? KRE_TAU3 : (n & 15) < KRE_N1 ? KRE_TAU1 : KRE_TAU;
                        n++;
                        go = (n & 15) != 0 && (n & 15) != KRE_EARLY;
                        if (!(n & 15)) LSTAMP(63 + (n >> 3));
                    } else if (first || (int)(now - tr) >= 0) {
                        first = false;
                        tr = now + RFR_TAU;
                        b |= seen & a;
                        warm_mma(a, b);
                        if (RFR_ON) seen = ldp32(XPtr(ph == 0 ? pAC : ph == 1 && lane < 16 ? pE : pG + (src & 8) * (HALF / 8) + (src & 7) * 512, gx.hi));
                        if (RFR_XS && (++cs & (RFR_XS - 1)) < 2) {
                            const uint32_t l = lane + 32 * (cs & 1);
                            *reinterpret_cast<volatile uint32_t*>(reinterpret_cast<char*>(g_s) + (l < 60 ? XS + bid * 7680 + 128 * l : XS2 + bid * 768 + 128 * (l - 60))) = 0;
                        }
                        src += ph == 0 ? 0 : ph == 1 ? 2 : 1;
                        ph = ph == 2 ? 0 : ph + 1;
                    } else __nanosleep(KWNS2);
                }
                while (ldsvol(sb + S_GATE) < 6 && ++k < SPIN_LIMIT) { warm_mma(a, b); __nanosleep(KWNS); }
                if (a | b) stsvol(sb + S_GATE, 6);
            }
        }
        return;
    }
    asm volatile("setmaxnreg.inc.sync.aligned.u32 " REG_HI ";");

    const int g = bid >> 3, i = bid & 7;
    const int g8 = lane >> 2, t = lane & 3;
    char* const gs = reinterpret_cast<char*>(g_s);
    const XPtr gx(xwindow());

    auto zero_words = [&] {
        const uint4 z = make_uint4(0, 0, 0, 0);
        const uint32_t c = (tid >> 6) & 1, cp = (tid >> 7) * COPY, k = (tid & 63) * 16;
        *reinterpret_cast<uint4*>((char*)(gx + pairL(RA, c, g) * 8192 + (i >> 2) * HALF + (i & 3) * 1024 + cp + k)) = z;
        *reinterpret_cast<uint4*>((char*)(gx + pairL(RC, c, g) * 8192 + (i >> 2) * HALF + (i & 3) * 1024 + cp + k)) = z;
        *reinterpret_cast<uint4*>((char*)(gx + pairL(RE, c, g) * 8192 + (i >> 2) * HALF + (i & 3) * 1024 + cp + k)) = z;
        if ((tid & 31) < 24) *reinterpret_cast<uint4*>((char*)(gx + pairG((tid >> 5) & 1, c, i) * 8192 + (g >> 3) * HALF + (g & 7) * 512 + cp + (tid & 31) * 16)) = z;
    };
    if (ZPOS == 0) zero_words();
    W80 Wq[6], Wgu[3];
    uint32_t Wo[5][3][4];
    if (w < 4) {
        const uint32_t* xp = reinterpret_cast<const uint32_t*>(P.x + 640 * w);
        float sum = 0.f, sq = 0.f;
#pragma unroll
        for (int u = 0; u < 10; u++) { uint32_t v = xp[lane + 32 * u]; float a = bf_lo(v), b = bf_hi(v); sum += a + b; sq += a * a + b * b; }
#pragma unroll
        for (int o = 16; o > 0; o >>= 1) { sum += __shfl_xor_sync(~0u, sum, o); sq += __shfl_xor_sync(~0u, sq, o); }
        float mean, den; ln_stats(sum, sq, mean, den);
        if (lane < 20) {
            const uint2 v = reinterpret_cast<const uint2*>(P.x + 640 * w + 80 * i)[lane];
            sts64(sb + S_X0 + 160 * w + 8 * lane, v.x, v.y);
            sts32(sb + S_L0 + 384 * w + b_pos<40>(4 * lane), pack2(__fdiv_rn(bfr(bf_lo(v.x) - mean), den), __fdiv_rn(bfr(bf_hi(v.x) - mean), den)));
            sts32(sb + S_L0 + 384 * w + b_pos<40>(4 * lane + 2), pack2(__fdiv_rn(bfr(bf_lo(v.y) - mean), den), __fdiv_rn(bfr(bf_hi(v.y) - mean), den)));
        }
    } else if (w == 4) {
        const uint32_t* xp = reinterpret_cast<const uint32_t*>(P.wr);
        float sum = 0.f;
#pragma unroll
        for (int u = 0; u < 10; u++) { uint32_t v = xp[lane + 32 * u]; sum += bf_lo(v) + bf_hi(v); }
#pragma unroll
        for (int o = 16; o > 0; o >>= 1) sum += __shfl_xor_sync(~0u, sum, o);
        if (lane == 0) stsf(sb + S_SWR, sum);
        if (lane < 20) {
            const uint2 v = reinterpret_cast<const uint2*>(P.wr + 80 * i)[lane];
            sts32(sb + S_XA + 576 + a_pos(4 * lane), v.x); sts32(sb + S_XA + 576 + a_pos(4 * lane + 2), v.y);
            sts32(sb + S_XA + a_pos(4 * lane), ONES); sts32(sb + S_XA + a_pos(4 * lane + 2), ONES);
        }
    }
    asm volatile("bar.sync 2, %0;" :: "n"(NTHR) : "memory");
    auto frag = [](uint32_t (&a)[4], uint32_t p, int pitch) {
        const uint32_t r0 = lds32(p), r1 = lds32(p + pitch), r2 = lds32(p + 2 * pitch), r3 = lds32(p + 3 * pitch);
        a[0] = __byte_perm(r0, r1, 0x5410); a[1] = __byte_perm(r0, r1, 0x7632);
        a[2] = __byte_perm(r2, r3, 0x5410); a[3] = __byte_perm(r2, r3, 0x7632);
    };
    mbar_wait(sb + S_WFULL + 16 * (w >> 2), 0);
    mbar_wait(sb + S_WFULL + 16 * (w >> 2) + 8, 0);
    {
        const uint32_t p = sb + ST_WQ + (w >> 2) * 30720 + (2 * t) * 384 + (48 * (w & 3) + 2 * g8) * 2;
#pragma unroll
        for (int r = 0; r < 10; r++)
#pragma unroll
            for (int m = 0; m < 3; m++) {
                const uint32_t q = p + ((r & 1) * 40 + (r >> 1) * 8) * 384 + 32 * m, r0 = lds32(q), r1 = lds32(q + 384);
                (r < 8 ? Wq[2 * m].a[(r >> 2) & 1][r & 3] : Wq[2 * m].c[r & 1]) = __byte_perm(r0, r1, 0x5410);
                (r < 8 ? Wq[2 * m + 1].a[(r >> 2) & 1][r & 3] : Wq[2 * m + 1].c[r & 1]) = __byte_perm(r0, r1, 0x7632);
            }
    }
    __syncwarp();
    if (lane == 0) mbar_arrive(sb + S_RELW);
    TSTAMP(1);
    {
        char* d = gs + XS + bid * 7680 + (w >> 2) * 3840 + (48 * (w & 3) + 2 * g8) * 4;
        float acc[6][4] = {};
        mul80(acc, Wq, lds128(sb + S_L0 + 48 * lane), lds32(sb + S_L0 + 48 * lane + 16));
#pragma unroll
        for (int m = 0; m < 6; m += 2) stp64(d + t * 768 + 32 * m, acc[m][0] + acc[m][3], acc[m + 1][0] + acc[m + 1][3], 1);
        float sum[6][4] = {};
        mul80(sum, Wq, make_uint4(ONES, ONES, ONES, ONES), ONES);
        if (t == 0)
#pragma unroll
            for (int m = 0; m < 6; m += 2) stp64(d + 4 * 768 + 32 * m, sum[m][0] + sum[m][3], sum[m + 1][0] + sum[m + 1][3], 1);
    }
    mbar_wait(sb + S_WFULL + 32, 0);
    mbar_wait(sb + S_WFULL + 40, 0);
    const uint32_t oct = 3 * (w >> 1) + (w & 1), oct2 = 3 * (w >> 1) + 2;
    {
        const uint32_t p = sb + ST_WG + ((lane & 7) + 40 * ((lane >> 3) & 1) + 8 * (lane >> 4)) * 192;
#pragma unroll
        for (int T = 0; T < 3; T++) {
            const uint32_t q = p + (T < 2 ? T * 15360 + 16 * oct : (w & 1) * 15360 + 16 * oct2);
            ldsm4t(Wgu[T].a[0], q); ldsm4t(Wgu[T].a[1], q + 16 * 192); ldsm2t(Wgu[T].c, q + 32 * 192);
        }
        float sum[3][4] = {};
        mul80(sum, Wgu, make_uint4(ONES, ONES, ONES, ONES), ONES);
        if (t < 3) stp32(gs + XS2 + bid * 768 + (t < 2 ? 64 * oct + 4 * t : 64 * oct2 + 4 * (w & 1)) + 8 * g8,
                         sel4(t, sum[0][0] + sum[0][3], sum[1][0] + sum[1][3], sum[2][0] + sum[2][3], 0.f), 1);
    }
    __syncwarp();
    if (lane == 0) mbar_arrive(sb + S_RELW + 8);
    const char* srcS = gs + XS + g * 8 * 7680 + (i >> 2) * 3840 + min(tid, 191) * 4;
    uint32_t vs[5][8];
#pragma unroll
    for (int b = 0; b < 5; b++)
#pragma unroll
        for (int s = 0; s < 8; s++) vs[b][s] = LOOK1 ? ldp32(srcS + b * 768 + s * 7680) : 0;
    uint32_t cs2[8];
#pragma unroll
    for (int s = 0; s < 8; s++) cs2[s] = LOOK2 ? ldp32(gs + XS2 + (g * 8 + s) * 768 + min(tid, 191) * 4) : 0;
    __syncwarp();
    mbar_wait(sb + S_WFULL + 48 + 8 * (w >> 1), 0);
    {
        const uint32_t po = sb + ST_WO + (48 * w + 12 * t) * 160 + 4 * g8;
#pragma unroll
        for (int s = 0; s < 3; s++)
#pragma unroll
            for (int m = 0; m < 5; m++) frag(Wo[m][s], po + 4 * s * 160 + 32 * m, 160);
    }
    __syncwarp();
    if (lane == 0) mbar_arrive(sb + S_RELW + 16);
    if (ZPOS == 1) zero_words();
    if (tid < 192) {
        int guard = 0;
        while (((or3(chk8(vs[0], 1), chk8(vs[1], 1), chk8(vs[2], 1)) | chk8(vs[3], 1) | chk8(vs[4], 1)) & 1) && ++guard < SPIN_LIMIT) {
#pragma unroll
            for (int b = 0; b < 5; b++)
#pragma unroll
                for (int s = 0; s < 8; s++) vs[b][s] = ldp32(srcS + b * 768 + s * 7680);
        }
        const uint32_t qpos = sb + S_QS + q_pos(tid);
#pragma unroll
        for (int b = 0; b < 4; b++) {
            sts_hi16(qpos + 384 * b, bfr(sum8(vs[b])));
        }
        stsf(sb + S_CSQ + 4 * tid, sum8(vs[4]));
    }
    if (tid < 192) stsf(sb + S_CSGU + 4 * tid, (chk8(cs2, 1) & 1) ? gather8<768>(gs + XS2 + g * 8 * 768 + tid * 4, 1) : sum8(cs2));
    __syncwarp();
    bar_main();
    arrive_if(tid == 0, sb + S_QRDY);
    if (ZPOS == 2) zero_words();
    TSTAMP(2);

    uint32_t side;
    { int k = 0; while ((side = ldsvol(sb + S_SIDE)) == 0 && ++k < SPIN_LIMIT) {} }
    const uint32_t td = __shfl_sync(~0u, tid, lane);
    const uint32_t wp = __shfl_sync(~0u, tid >> 5, 0);
    const uint32_t cc = wp >= 3;
    auto uni = [](uint32_t v) { return __shfl_sync(~0u, v, 0); };
    auto pin = [&](uint32_t v) { return __shfl_sync(~0u, v, td); };
    auto nearp = [&](uint32_t P) { return gx.lo + P * 8192 + ((side ^ 1 ^ __popc(P & PMASK)) & 1) * COPY; };
    constexpr uint32_t COL = 32 * 8192;
    const uint32_t ownL = gx.lo + (i >> 2) * HALF + (i & 3) * 1024, ownG = gx.lo + (g >> 3) * HALF + (g & 7) * 512;
    const uint32_t uPubA = uni(ownL + pairL(RA, 0, g) * 8192 + (wp >> 1) * 256 + (wp & 1) * 96), uPolA = uni(nearp(pairL(RA, 0, g)) + (wp >> 2) * HALF + (wp & 3) * 256);
    const uint32_t uPubB = uni(ownG + pairG(0, cc, i) * 8192), uPolB = uni(nearp(pairG(0, cc, i)));
    const uint32_t uPubC = uni(ownL + pairL(RC, 0, g) * 8192), uPolC = uni(nearp(pairL(RC, wp < 6 ? cc : wp - 6, g)));
    const uint32_t uPubD = uni(ownG + pairG(1, 0, i) * 8192 + (wp < 7 ? 32 * wp : 256)), uPolD = uni(nearp(pairG(1, cc, i)));
    const uint32_t uPubE = uni(ownL + pairL(RE, 0, g) * 8192), uPolE = uni(nearp(pairL(RE, i >> 2, g)));
    const uint32_t uOS = uni(sb + S_OS + 192 * wp);
    auto xp = [&](uint32_t lo) { return (char*)XPtr(lo, gx.hi); };
#define IDS() __syncwarp(); const uint32_t z0_ = lag<1>(sb), z_ = td + z0_; const uint32_t ln = z_ & 31, q8 = ln >> 2, t4 = z_ & 3, n96 = z_ - 96 * cc, n80 = min(n96, 79u); (void)q8; (void)t4; (void)n80; (void)ln

    auto vaddr = [&](uint32_t (&voff)[3]) {
        const uint32_t ln = td & 31;
        const uint32_t key3 = 3 * ((ln & 7) + 2 * (ln & 8) + ((ln >> 1) & 8));
#pragma unroll
        for (int T = 0; T < 3; T++) {
            const uint32_t u = 3 * wp + T, r = key3 + (u >> 3);
            voff[T] = r * 128 + (((u ^ r) & 7) << 4);
        }
    };
    auto values = [&](uint32_t (&vf)[8][3][4], auto order, auto step, uint32_t ps, uint32_t col, uint32_t par) {
        const uint32_t ln = td & 31, q8 = ln >> 2, t4 = td & 3;
        const uint4 p = lds128(ps + 16 * ln);
        float acc[3][4] = {}, f0 = 0.f, f1 = 0.f, r3 = 0.f;
        int M = 0;
#pragma unroll
        for (int k = 0; k < 8; k++) {
            step(k);
            const int s = (order.value >> (4 * k)) & 7;
            const bool m = (q8 >> 1) == (s >> 1);
            const uint32_t b0 = m ? ((s & 1) ? p.z : p.x) : 0u, b1 = m ? ((s & 1) ? p.w : p.y) : 0u;
#pragma unroll
            for (int T = 0; T < 3; T++) mmaA(acc[T], vf[s][T], b0, b1);
            if (k == FSTEP) {
                const uint2 mp = lds64(ps + PS_MAX + 8 * t4);
                M = __reduce_max_sync(~0u, __float2int_ru(fmaxf(asf(mp.x), asf(mp.y))));
                f0 = ex2(asf(mp.x) - (float)M); f1 = ex2(asf(mp.y) - (float)M);
                float l[4] = {};
                mma16816(l, ONES, ONES, ONES, ONES, p.x, p.y); mma16816(l, ONES, ONES, ONES, ONES, p.z, p.w);
                r3 = fmaf(f0, l[0], f1 * l[1]);
            }
        }
        CSTAMP(25);
        char* pubA = xp(uPubA + col * COL + 32 * t4 + 4 * q8);
        const float r0 = fmaf(f0, acc[0][0], f1 * acc[0][3]), r1 = fmaf(f0, acc[1][0], f1 * acc[1][3]), r2 = fmaf(f0, acc[2][0], f1 * acc[2][3]);
        const bool hi = t4 & 2, od = t4 & 1;
        const float u0 = (hi ? r2 : r0) + __shfl_xor_sync(~0u, hi ? r0 : r2, 2), u1 = (hi ? r3 : r1) + __shfl_xor_sync(~0u, hi ? r1 : r3, 2);
        const float o = (od ? u1 : u0) + __shfl_xor_sync(~0u, od ? u0 : u1, 1);
        stp32_if(t4 < 3 || ((wp & 1) && q8 < 2), pubA, ln == 3 ? __int_as_float(2 * M) : o, par);
    };

#pragma unroll 1
    for (int ch = 0; ch < 5; ch++) {
        const uint32_t par0 = (ch + 1) & 1, par1 = ch & 1;
        uint32_t voff[3], vf[8][3][4];
        if (ch < 4) {
            vaddr(voff);
            mbar_wait(sb + S_SCO, par1);
            if (ch == 0) mbar_wait(sb + S_WFULL + 80, 0);
            TST(0);
            auto ldw = [&](int s) {
                mbar_wait(sb + S_FV + 8 * s, par1);
#pragma unroll
                for (int T = 0; T < 3; T++) ldsm4t(vf[s][T], voff[T] + (sb + v_place(ch, s) * SLOT));
            };
            probs(bf_lo(lds16(sb + S_SC + 2 * td)), sb + S_PS, wp, td & 31);
            ldw(0); ldw(1); ldw(2);
            bar_main();
            arrive_if(td == 0, sb + S_RELR);
            values(vf, std::integral_constant<uint32_t, 0x76543210>(), [&](int s) {
                if (s >= 3) ldw(s);
            }, sb + S_PS, 0, par0);
            TST(1);
            CSTAMP(5);
            if (ch > 0) mbar_wait(sb + S_OS1, par0);
        } else {
#pragma unroll
            for (int s = 0; s < 36; s++) { vf[s / 12][(s / 4) % 3][s & 3] = 0; opaque(vf[s / 12][(s / 4) % 3][s & 3]); }
        }
        const bool has0 = ch < 4, has1 = ch > 0;
        const bool actc = wp < 6 && (cc ? has1 : has0);
        const uint32_t parc = cc ? par1 : par0;
        const uint32_t pub0 = has0 ? par0 : 0;
        uint32_t rr, pubB;
        {
            IDS();
            const uint32_t c = ch == 4;
            const uint32_t osa = pin(uOS + 96 * c + 4 * ln), oa = pin(uOS + 48 * (q8 & 2) + 24 * t4), ra = pin(sb + S_RED + 640 * wp + 320 * (t4 & 1) + 8 * q8);
            rr = pin(sb + S_RED + 320 * cc + 4 * n80); pubB = pin(uPubB + 4 * n80);
            hop_a<1>(xp(uPolA + c * COL + 8 * min(ln, 24u) + lag<DELAY_L>(sb, z0_)), pub0, osa, ln < 24, 5 * ch);
            TST(2);
            CSTAMP(6);
            float acc[5][4] = {};
            const uint2 b0 = lds64(oa), b1 = lds64(oa + 8), b2 = lds64(oa + 16);
#pragma unroll
            for (int m = 0; m < 5; m++) mmaA(acc[m], Wo[m][0], b0.x, b0.y);
#pragma unroll
            for (int m = 0; m < 5; m++) mmaA(acc[m], Wo[m][1], b1.x, b1.y);
#pragma unroll
            for (int m = 0; m < 5; m++) mmaA(acc[m], Wo[m][2], b2.x, b2.y);
#pragma unroll
            for (int m = 0; m < 5; m++) { stsf(ra + 64 * m, acc[m][0]); stsf(ra + 64 * m + 4, acc[m][2]); }
        }
        CSTAMP(7);
        uint32_t xr, fl, pubC, pubC2;
        auto prepC = [&](uint32_t ln) {
            const uint32_t q8 = ln >> 2, t4 = ln & 3;
            xr = pin(sb + S_XB + 48 * (ln & 15));
            pubC = pin(uPubC + (t4 & 1) * COL + 192 * (wp >> 1) + 64 * (wp & 1) + 8 * q8);
            pubC2 = pin(uPubC + (t4 & 1) * COL + ((t4 & 2) ? 192 * (wp >> 1) + 128 + 4 * (wp & 1) + 8 * q8 : 768 + 2 * ((q8 + 1) & 6)));
            fl = pin(((t4 & 1) ? par1 : pub0) | (t4 >= 2 || (wp == 7 && q8 < 4 && q8 != 2 - t4) ? 2 : 0));
        };
        auto stats = [&](uint32_t xa, const uint4& b, uint32_t b4) {
            float a0[4] = {}, a1[4] = {}, a2[4] = {};
            const uint4 p0 = lds128(xa), p1 = lds128(xa + 16);
            const uint2 p2 = lds64(xa + 32);
            mmaV(a0, p0, b.x, b.y); mmaV(a1, p1, b.z, b.w); mma8(a2, p2.x, p2.y, b4);
            return ((a0[0] + a0[3]) + (a1[0] + a1[3])) + (a2[0] + a2[3]);
        };
        auto give_ln = [&](uint32_t src0, uint32_t par, uint32_t dst, uint32_t ln, float& mean, float& den, auto also) {
            const char* src = xp(src0 + 768 + (ln & 1) * HALF);
            uint2 st[4];
            int guard = 0;
            bool again;
            do {
#pragma unroll
                for (int s = 0; s < 4; s++) st[s] = ldp64(src + s * 1024);
                again = __any_sync(~0u, ((chk4(st, par) | also()) & 1) != 0);
            } while (again & (++guard < SPIN_LIMIT));
            float sx = (asf(st[0].x) + asf(st[1].x)) + (asf(st[2].x) + asf(st[3].x)), sq = (asf(st[0].y) + asf(st[1].y)) + (asf(st[2].y) + asf(st[3].y));
            sx += __shfl_xor_sync(~0u, sx, 1); sq += __shfl_xor_sync(~0u, sq, 1);
            ln_stats(sx, sq, mean, den);
            stsvol64(dst, __byte_perm(__float_as_uint(den), __float_as_uint(mean), 0x7632), (__float_as_uint(rcp(den)) & ~7u) | (ch + 1));
        };
        auto take_ln = [&](uint2& c, uint32_t a) { int k = 0; while (__any_sync(~0u, (c.y & 7) != ch + 1) && ++k < SPIN_LIMIT) c = ldsvol64(a); };
        {
            auto gate_up = [&](auto with_stats) {
                bar_main();
                TST(3);
                CSTAMP(11);
                const uint4 b = lds128(xr);
                uint32_t b4 = lds32(xr + 16);
                float acc[3][4] = {};
                if (with_stats.value) {
                    stp32_if(fl > 1 && !(td & 2), xp(pubC2), stats(xr + (S_XA - S_XB), b, b4), fl & 1);
                    __syncwarp();
                    b4 = lds32(xr + 16);
                }
                mul80(acc, Wgu, b, b4);
                stp64_if(!(td & 2), xp(pubC), tagw(acc[0][0] + acc[0][3], fl & 1), tagw(acc[1][0] + acc[1][3], fl & 1));
                stp32_if(td & 2, xp(pubC2), acc[2][0] + acc[2][3], fl & 1);
            };
            if (wp == 7) {
                bar_main();
                IDS();
                prepC(ln);
                gate_up(std::true_type());
            } else {
                if (actc) {
                    bar_main();
                    CSTAMP(8);
                    uint32_t r[8];
#pragma unroll
                    for (int s = 0; s < 8; s++) r[s] = lds32(rr + 640 * s);
                    stp32_if(true, xp(pubB), sum8(r), parc);
                    CSTAMP(9);
                    IDS();
                    prepC(ln);
                    const uint32_t n4 = 4 * n80;
                    const uint32_t xas = pin(sb + S_XA + 192 + 192 * cc + a_pos(n80)), xbs = pin(sb + S_XB + 384 * cc + b_pos<40>(n80));
                    const float x0 = cc ? ldsf(sb + S_XCAR + n4) : bf_lo(lds16(sb + S_X0 + 160 * (ch & 3) + n4 / 2));
                    gather16(xp(uPolB + n4 + lag<DELAY_G>(sb, z0_)), parc, 5 * ch + 1, [&](float y, uint32_t) {
                        const uint32_t x = pack2(x0 + bfr(y), 0.f);
                        sts16(xbs, x);
                        sts16(xas, x);
                        return 0u;
                    });
                    CSTAMP(10);
                } else {
                    bar_main();
                    IDS();
                    prepC(ln);
                }
                gate_up(std::false_type());
            }
        }
        CSTAMP(12);
        float mean = 0.f, den = 1.f;
        {
            IDS();
            const uint32_t wh = pin((((ln & 7) + 48 * ((ln >> 3) & 1) + 8 * (ln >> 4)) * 160 + (wp < 7 ? 16 * wp : 128)) | ((384 * cc + b_pos<48>(n96)) << 16));
            const uint32_t pubD = pin(uPubD + (t4 & 1) * COL + 16 * (t4 & 2) + 4 * q8 + (fl & 1)), ha = xr + (S_HS - S_XB);
            auto down = [&](const uint32_t (&W)[3][4], const uint4& h0, const uint2& h1) {
                float a0[4] = {}, a1[4] = {}, a2[4] = {};
                mmaA(a0, W[0], h0.x, h0.y); mmaA(a1, W[1], h0.z, h0.w); mmaA(a2, W[2], h1.x, h1.y);
                return ((a0[0] + a0[3]) + (a1[0] + a1[3])) + (a2[0] + a2[3]);
            };
            if (wp < 6) {
                uint32_t Wd[3][4];
                auto ldd = [&](uint32_t z) {
#pragma unroll
                    for (int s = 0; s < 3; s++) ldsm4t(Wd[s], ((wh ^ z) & 0xffff) + (sb + S_WD + s * 2560));
                };
                ldd(0);
                if (actc) {
                    const char* srcv = xp(uPolC + lag<DELAY_C>(sb, z0_) + 8 * n96);
                    const uint2 cs = lds64(sb + S_CSGU + 8 * n96);
                    float pg, pu;
                    uint2 c;
                    int guard = 0;
                    bool again;
                    do {
                        uint2 v[8];
#pragma unroll
                        for (int s = 0; s < 8; s++) v[s] = ldp64(srcv + (s >> 2) * HALF + (s & 3) * 1024);
                        c = ldsvol64(sb + S_LN + 8 * cc + ((v[0].x ^ parc) & 1) * 32);
                        again = __any_sync(~0u, ((chk8(v, parc) | chk8y(v, parc)) & 1) != 0);
                        pg = sum8x(v); pu = sum8y(v);
                        keep(pg); keep(pu);
                    } while (again & (++guard < SPIN_LIMIT));
                    CSTAMP(13);
                    SWEEPS(5 * ch + 2, guard - 1);
                    take_ln(c, sb + S_LN + 8 * cc);
                    mean = bf_hi(c.x); den = bf_lo(c.x);
                    const float gt = bfr(fmaf(-mean, asf(cs.x), pg) * asf(c.y)), up = fmaf(-mean, asf(cs.y), pu) * asf(c.y);
                    const uint32_t h = pack2(bfr(gt * sigmoidf_(gt)) * bfr(up), 0.f);
                    sts16((wh >> 16) + (sb + S_HS), h);
                    CSTAMP(14);
                    if (ch == 3) CSTAMP(0);
                }
                bar_main();
                TST(4);
                CSTAMP(15);
                const uint4 h0 = lds128(ha);
                const uint2 h1 = lds64(ha + 16);
                stp32_if(!(td & 2), xp(pubD & ~1u), down(Wd, h0, h1), pubD & 1);
            } else {
                uint32_t v = 0;
                if (wp == 6 ? has0 : has1) {
                    const uint32_t par = wp == 6 ? par0 : par1;
                    const char* src = xp(uPolC + 776 + (ln & 4) * (HALF / 4) + (ln & 3) * 1024);
                    give_ln(uPolC, par, sb + S_LN + 8 * (wp - 6), ln, mean, den, [&] { v = ldp32(src); return v ^ par; });
                }
                stsvol(sb + S_GATE, ch + 1);
                uint32_t Wd[2][3][4];
#pragma unroll
                for (int s = 0; s < 6; s++) ldsm4t(Wd[s / 3][s % 3], (wh & 0xffff) + (sb + S_WD + (s / 3) * 16 + (s % 3) * 2560));
                bar_main();
                const uint4 h0 = lds128(ha);
                const uint2 h1 = lds64(ha + 16);
                const float d0 = down(Wd[0], h0, h1), d1 = down(Wd[1], h0, h1);
                stp32_if(true, xp(pubD & ~1u), (td & 2) ? d1 : d0, pubD & 1);
                if (wp == 6 ? has0 : has1) {
                    float xw = asf(v);
                    xw += __shfl_xor_sync(~0u, xw, 1); xw += __shfl_xor_sync(~0u, xw, 2); xw += __shfl_xor_sync(~0u, xw, 4);
                    const float r = bfr(fmaf(-mean, ldsf(sb + S_SWR), xw) * rcp(den));
                    sts32_if(ln == 0, sb + S_STAT + 4 * (wp - 6), __float_as_uint(bfr(sigmoidf_(r))) | (ch + 1));
                }
            }
        }
        CSTAMP(16);
        {
            IDS();
            const uint32_t pubE = pin(uPubE + (t4 < 3 ? (wp >> 2) * COL + 192 * (wp & 3) + 64 * t4 + 8 * q8 : (q8 >> 2) * COL + 768 + 4 * (q8 & 1)));
            xr = pin(sb + S_XB + 48 * (ln & 7));
            uint32_t x2 = 0;
            auto hop_d = [&](auto col) {
                const uint32_t xbs = pin(sb + S_XB + 384 * col.value + b_pos<40>(n80)), xas = col.value ? 0 : pin(sb + S_XA + 192 + a_pos(n80));
                const float x1 = bf_lo(lds16(xbs));
                const float lnx = __uint_as_float(pin(__float_as_uint(bfr(__fdiv_rn(bfr(x1 - mean), den)))));
                gather16(xp(uPolD + 4 * n80 + lag<DELAY_D>(sb, z0_)), col.value ? par1 : par0, 5 * ch + 3, [&](float y, uint32_t z) {
                    const uint32_t gate = ldsvol(sb + S_STAT + 4 * col.value + z);
                    x2 = pack2(x1 + bfr(lnx + bfr(bfr(y) * bf_hi(gate))), 0.f);
                    if (col.value) keep(x2); else { sts16(xbs, x2); sts16(xas, x2); }
                    return (uint32_t)((gate & 7) != ch + 1);
                });
                CSTAMP(17);
            };
            auto qproj = [&](auto with_stats) {
                bar_main();
                TST(5);
                CSTAMP(19);
                const uint32_t t4 = td & 3;
                const uint4 b = lds128(xr);
                uint32_t b4 = lds32(xr + 16);
                float acc[6][4] = {};
                if (with_stats.value) {
                    stp32_if((td & 11) == 3, xp(pubE), stats(xr + (S_XA - S_XB), b, b4), par0);
                    __syncwarp();
                    b4 = lds32(xr + 16);
                }
                mul80(acc, Wq, b, b4);
                const float v0 = sel4(t4, acc[0][0] + acc[0][3], acc[2][0] + acc[2][3], acc[4][0] + acc[4][3], acc[4][0] + acc[4][3]);
                const float v1 = sel4(t4, acc[1][0] + acc[1][3], acc[3][0] + acc[3][3], acc[5][0] + acc[5][3], acc[5][0] + acc[5][3]);
                stp64_if(t4 < 3, xp(pubE), tagw(v0, par0), tagw(v1, par0));
            };
            if (wp == 7) {
                if (!has0) break;
                qproj(std::true_type());
            } else {
                if (actc && !cc) hop_d(std::integral_constant<int, 0>());
                else {
                    if (actc && g == 0) {
                        const uint32_t po = pin(1280 * (ch - 1) + 160 * i + 2 * n80);
                        hop_d(std::integral_constant<int, 1>());
                        *reinterpret_cast<unsigned short*>(reinterpret_cast<char*>(P.out) + po) = (unsigned short)x2;
                    }
                    if (!has0) break;
                }
                qproj(std::false_type());
                sts32_if(td < 80, sb + S_XCAR + 4 * td, x2 << 16);
            }
        }
        CSTAMP(20);
        auto pass2 = [&](auto d0, auto d1, auto d2) {
            constexpr int D0 = d0.value, D1 = d1.value, D = D0 + D1 + d2.value;
            IDS();
            const uint32_t ua = sb + k_place(ch, wp & 6) * SLOT + (wp & 1) * UNIT, k0 = k_off(ln);
            uint32_t kf[12][2][4];
            auto ldk = [&](int s) { const uint32_t a = (k0 ^ (32 * (s / 3))) + (ua + 1024 * (s % 3)); ldsm4(kf[s][0], a); ldsm4(kf[s][1], a + SLOT); };
            auto ldv1 = [&](int k) { ldsm4t(vf[k / 3][k % 3], voff[k % 3] + (sb + v_place(ch, k / 3) * SLOT)); };
            auto ldv = [&](int s) { ldv1(3 * s); ldv1(3 * s + 1); ldv1(3 * s + 2); };
            constexpr uint32_t LATE = LAST_LATE;
            constexpr uint64_t EARLY_LIST = bit_list(~LATE), LATE_LIST = bit_list(LATE);
            auto early = [&](int k) {
                if (D1 == 0) ldk(k);
                else if (k < 3) { ldv1(9 + 2 * k); ldv1(10 + 2 * k); }
                else ldk((EARLY_LIST >> (4 * (k - 3))) & 15);
            };
            if (wp == 6) give_ln(uPolE, par0, sb + S_LN + 16, ln, mean, den, [] { return 0u; });
            if (D1 > 0) vaddr(voff);
            if (!(mbar_try(sb + S_FK + 8 * (wp & 6), par1) & mbar_try(sb + S_FK + 8 * (wp | 1), par1))) { mbar_wait(sb + S_FK + 8 * (wp & 6), par1); mbar_wait(sb + S_FK + 8 * (wp | 1), par1); }
#pragma unroll
            for (int s = 0; s < D0; s++) early(s);
            if (wp < 6) {
                const uint32_t qsa = pin(sb + S_QS + 384 * ch + q_pos(td));
                const char* srcv = xp(uPolE + lag<(D1 > 0 ? DELAY_E3 : DELAY_E)>(sb, z0_) + 4 * td);
                const float cs = ldsf(sb + S_CSQ + 4 * td);
                uint32_t v[8];
                auto look = [&] {
#pragma unroll
                    for (int s = 0; s < 8; s++) v[s] = ldp32(srcv + (s >> 2) * HALF + (s & 3) * 1024);
                };
                if (D1 > 0) {
                    look();
                    __syncwarp();
#pragma unroll
                    for (int s = D0; s < D0 + D1; s++) early(s);
                }
                float qs;
                uint2 c;
                int guard = 0;
                while (true) {
                    if (D1 == 0) look();
                    c = ldsvol64(sb + S_LN + 16 + ((v[0] ^ par0) & 1) * 32);
                    const bool again = __any_sync(~0u, (chk8(v, par0) & 1) != 0);
                    qs = sum8(v);
                    keep(qs);
                    if (!(again & (++guard < SPIN_LIMIT))) break;
                    if (D1 > 0) look();
                }
                take_ln(c, sb + S_LN + 16);
                const uint32_t q = pack2(fmaf(-bf_hi(c.x), cs, qs) * asf(c.y), 0.f);
                sts16(qsa, q);
                SWEEPS(5 * ch + 4, guard - 1);
                CSTAMP(22);
            } else {
#pragma unroll
                for (int s = D0; s < D0 + D1; s++) early(s);
            }
#pragma unroll
            for (int s = D0 + D1; s < D; s++) early(s);
            bar_main();
            TST(6);
            CSTAMP(1);
            uint2 q = lds64(sb + S_QS + 384 * ch + 8 * ln);
            float acc[2][4] = {};
            constexpr int V0 = 13 - D, NV = D1 > 0 ? 2 : (2 * (D - 1)) / 3;
            static_assert(D1 == 0 || LAST0 == 0 || D - 3 + __builtin_popcount(LATE) == 12, "plan");
#pragma unroll
            for (int s = 0; s < 12; s++) {
                const bool m = q8 == (s & 7);
                const uint32_t b0 = m ? q.x : 0u, b1 = m ? q.y : 0u;
                if (s == 7) q = lds64(sb + S_QS + 384 * ch + 8 * ln + 256);
                mmaA(acc[0], kf[s][0], b0, b1);
                mmaA(acc[1], kf[s][1], b0, b1);
                if (D1 > 0) {
                    if (s >= 1 && s <= __builtin_popcount(LATE)) ldk((LATE_LIST >> (4 * (s - 1))) & 15);
                } else {
                    if (s >= 1 && s + D - 1 < 12) ldk(s + D - 1);
                    if (s >= 1 && s + D - 1 == 11) { __syncwarp(); arrive_if(ln == 0, sb + S_RELK); }
                    if (s == V0) vaddr(voff);
                    if (s >= V0 && 2 * (s - V0) < 3 * NV) ldv1(9 + 2 * (s - V0));
                    if (s >= V0 && 2 * (s - V0) + 1 < 3 * NV) ldv1(10 + 2 * (s - V0));
                }
            }
            CSTAMP(24);
            {
                const float v0 = acc[0][0] + acc[0][1], v1 = acc[0][2] + acc[0][3], v2 = acc[1][0] + acc[1][1], v3 = acc[1][2] + acc[1][3];
                const bool hi = t4 & 2, od = t4 & 1;
                const float u0 = (hi ? v2 : v0) + __shfl_xor_sync(~0u, hi ? v0 : v2, 2), u1 = (hi ? v3 : v1) + __shfl_xor_sync(~0u, hi ? v1 : v3, 2);
                const float s = (od ? u1 : u0) + __shfl_xor_sync(~0u, od ? u0 : u1, 1);
                CSTAMP(2);
                probs(scaled(s), sb + S_PS + PS_PASS, wp, ln);
                CSTAMP(3);
            }
            bar_main();
            TST(10);
            CSTAMP(4);
            if (D1 > 0) values(vf, std::integral_constant<uint32_t, ORDER_L>(), [&](int s) { if (s < 3) ldv(s + 5); }, sb + S_PS + PS_PASS, 1, par0);
            else values(vf, std::integral_constant<uint32_t, (NV > 1 ? ORDER_R : 0x76543210)>(),
                        [&](int s) { if (s >= (NV > 1 ? 2 : 1) && s + NV + (NV > 1 ? 1 : 2) < 8) ldv(s + NV + (NV > 1 ? 1 : 2)); }, sb + S_PS + PS_PASS, 1, par0);
            arrive_if(ln == 0, sb + S_RELV);
        };
        if (LAST0 > 0 && ch == 3) {
            pass2(std::integral_constant<int, LAST0>(), std::integral_constant<int, LAST1>(), std::integral_constant<int, LAST2>());
#pragma unroll
            for (int m = 0; m < 60; m++) { uint32_t& r = m % 10 < 8 ? Wq[m / 10].a[(m % 10) / 4][m % 2 + 2 * ((m % 10) / 2 % 2)] : Wq[m / 10].c[m % 2]; r = 0; opaque(r); }
        } else pass2(std::integral_constant<int, KPRE>(), std::integral_constant<int, 0>(), std::integral_constant<int, KPRE2>());
        TST(11);
        CSTAMP(23);
    }
    sts32_if(td == 255, sb + S_GATE, 6);
    TSTAMP(3);
}

typedef CUresult (*EncodeFn)(CUtensorMap*, CUtensorMapDataType, cuuint32_t, void*, const cuuint64_t*, const cuuint64_t*, const cuuint32_t*,
                             const cuuint32_t*, CUtensorMapInterleave, CUtensorMapSwizzle, CUtensorMapL2promotion, CUtensorMapFloatOOBfill);

void make_map(EncodeFn enc, CUtensorMap* m, const void* base, uint64_t cols, uint64_t rows, uint32_t box_cols, uint32_t box_rows, bool swizzle) {
    cuuint64_t dims[2] = {cols, rows};
    cuuint64_t strides[1] = {cols * 2};
    cuuint32_t box[2] = {box_cols, box_rows};
    cuuint32_t es[2] = {1, 1};
    enc(m, CU_TENSOR_MAP_DATA_TYPE_BFLOAT16, 2, const_cast<void*>(base), dims, strides, box, es, CU_TENSOR_MAP_INTERLEAVE_NONE,
        swizzle ? CU_TENSOR_MAP_SWIZZLE_128B : CU_TENSOR_MAP_SWIZZLE_NONE, swizzle ? CU_TENSOR_MAP_L2_PROMOTION_NONE : WPROMO, CU_TENSOR_MAP_FLOAT_OOB_FILL_NONE);
}

}

extern "C" void kernel_launch(void* const* d_in, const int* in_sizes, int n_in, void* d_out, int out_size) {
    (void)in_sizes; (void)n_in; (void)out_size;
    static EncodeFn enc = nullptr;
    if (!enc) {
        void* f = nullptr;
        cudaDriverEntryPointQueryResult q;
        cudaGetDriverEntryPoint("cuTensorMapEncodeTiled", &f, cudaEnableDefault, &q);
        enc = (EncodeFn)f;
        cudaFuncSetAttribute(fused_kernel, cudaFuncAttributeMaxDynamicSharedMemorySize, SMEM_BYTES);
    }
    Params P;
    P.x = (const __nv_bfloat16*)d_in[0]; P.k = (const __nv_bfloat16*)d_in[1]; P.v = (const __nv_bfloat16*)d_in[2];
    P.wr = (const __nv_bfloat16*)d_in[6];
    P.out = (__nv_bfloat16*)d_out;
    Maps M;
    {
        cuuint64_t dims[4] = {64, 8, 3, (cuuint64_t)KV_BATCH_KEYS / 2}, strides[3] = {384, 128, 3072};
        cuuint32_t box[4] = {64, 8, 3, 2}, es[4] = {1, 1, 1, 1};
        enc(&M.k, CU_TENSOR_MAP_DATA_TYPE_BFLOAT16, 4, d_in[1], dims, strides, box, es, CU_TENSOR_MAP_INTERLEAVE_NONE, CU_TENSOR_MAP_SWIZZLE_128B,
            CU_TENSOR_MAP_L2_PROMOTION_NONE, CU_TENSOR_MAP_FLOAT_OOB_FILL_NONE);
    }
    make_map(enc, &M.v, P.v, 64, (uint64_t)12 * KV_BATCH_KEYS, 64, 96, true);
    make_map(enc, &M.vu, P.v, 64, (uint64_t)12 * KV_BATCH_KEYS, 64, 48, true);
    make_map(enc, &M.wq, d_in[3], 6144, 640, 192, 40, false);
    make_map(enc, &M.wo, d_in[4], 640, 6144, 80, 96, false);
    make_map(enc, &M.wg, d_in[7], 1536, 640, 96, 80, false);
    make_map(enc, &M.wu, d_in[8], 1536, 640, 96, 80, false);
    make_map(enc, &M.wd, d_in[9], 640, 1536, 80, 96, false);
    fused_kernel<<<NCTA, NTHR, SMEM_BYTES, cudaStreamPerThread>>>(P, M);
}
```

```cpp
#include <cuda_runtime.h>
#include <cuda.h>
#include <cuda_bf16.h>
#include <stdint.h>
#include <type_traits>

namespace {

constexpr int NCTA = 128;
constexpr int NTHR = 384;
constexpr int UNIT = 6144;
constexpr int SLOT = 12288;
#define TAU 4000
#define TAUW 3850
#define TAU0 3850
#define PF0 2
#define PFMAP 1
#define ZPOS 1
#define LOOK1 0
#define LOOK2 0
#define SLACK 4000
#define SLACK0 2000
#define TSH 0
#define HOP1_NS 200
#define RELR_AT 0
#define PSLEEP 0
#define KRE_EARLY 6
#define PFTOP 2
#define RFR_XS 2
#define TMIN 2400
#define T_LEAD 0
#define WIN_W 3
#define WIN_S 4
#define WIN_U 10
#define RFR_ON 1
#define KRE_N1 0
#define KRE_TAU1 2500
#define RFR_TAU 25600
#define VPF 4
#define KRE_GATE 0
#define KRE_GATE3 KRE_GATE
#define JFREE 16
#define TFREE 0
#define KRE_TAU 3000
#define KRE_TAU3 KRE_TAU
#define HDEPTH 3
#define LAST0 3
#define ORDER_L 0x76543210
#define ORDER_R 0x76543210
#define LAST_LATE 0xaa8
#define LAST1 4
#define LAST2 3
#define FSTEP 4
#define SPEC 1
#define PV1PIPE 0
#define HOPA0 6
#define HOPA1 6
#define WPROMO CU_TENSOR_MAP_L2_PROMOTION_NONE
#define KPRE 1
#define KPRE2 3
#define DELAY_G 2
#define DELAY_L 2
#define DELAY_E3 0
#define DELAY_C 3
#define DELAY_D 0
#define DELAY_E 1
#define REG_LO "40"
#define REG_HI "232"
#define SPIN_LOG 17
constexpr int SPIN_LIMIT = 1 << SPIN_LOG;

__host__ __device__ constexpr uint32_t pairL(uint32_t region, uint32_t c, uint32_t g) { return (g & 1) | ((g >> 1) << 2) | (c << 5) | (region << 6); }
__host__ __device__ constexpr uint32_t pairG(uint32_t d, uint32_t c, uint32_t i) { return (i & 1) | ((i >> 1) << 2) | (d << 4) | (c << 5) | (3u << 6); }
constexpr uint32_t RA = 0, RC = 1, RE = 2, HALF = 16384, COPY = 4096, PMASK = 0x59;
constexpr uint32_t XS = 0;
constexpr uint32_t XS2 = XS + 128 * 7680;
constexpr uint32_t XSEND = XS2 + 128 * 768;
__device__ uint4 g_s[XSEND / 16];
__device__ uint4 g_x[(4u << 20) / 16];
#define SWEEPS(k, n) do {} while (0)

constexpr uint32_t S_WD = 16 * SLOT;
constexpr uint32_t S_DUMMY = S_WD + 15360;
constexpr uint32_t S_BAR = S_DUMMY + 4096;
constexpr uint32_t S_FV = S_BAR, S_FK = S_FV + 64, S_RING = S_FK + 64, S_DBAR = S_RING + 48, S_WFULL = S_DBAR + 32, S_QRDY = S_WFULL + 88;
constexpr uint32_t S_RELK = S_QRDY + 8, S_RELV = S_RELK + 8, S_RELR = S_RELV + 8, S_RELW = S_RELR + 8, S_SCO = S_RELW + 24;
constexpr uint32_t S_OS1 = S_SCO + 8;
constexpr uint32_t S_ZERO = S_OS1 + 8;
constexpr uint32_t S_KF = S_ZERO + 8;
constexpr uint32_t S_TOK = S_KF + 8;
constexpr uint32_t S_SIDE = S_TOK + 80, S_GATE = S_SIDE + 4;
constexpr uint32_t S_STAT = S_GATE + 12, S_SWR = S_STAT + 16;
constexpr uint32_t S_LN = S_STAT + 32;
constexpr uint32_t S_XCAR = S_LN + 64;
constexpr uint32_t S_CSQ = S_XCAR + 320;
constexpr uint32_t S_CSGU = S_CSQ + 768;
constexpr uint32_t S_RED = S_CSGU + 768;
constexpr uint32_t S_L0 = S_RED;
constexpr uint32_t S_OS = S_RED + 5120;
constexpr uint32_t S_PS = S_OS + 1536;
constexpr uint32_t PS_MAX = 512, PS_PASS = 544;
constexpr uint32_t S_QS = S_PS + 2 * PS_PASS;
constexpr uint32_t S_XB = S_QS + 1536;
constexpr uint32_t S_XA = S_XB + 768;
constexpr uint32_t S_HS = S_XA + 768;
constexpr uint32_t S_X0 = S_HS + 768;
constexpr uint32_t S_SC = S_X0 + 640;
constexpr uint32_t S_TM = S_SC + 512;
constexpr int SMEM_BYTES = S_TM + 256;
static_assert(SMEM_BYTES <= 232448 && S_STAT % 16 == 0 && S_RED % 16 == 0 && S_XB % 16 == 0 && S_HS % 16 == 0 && S_PS % 16 == 0 && S_QS % 16 == 0, "smem");
static_assert(S_SCO == S_BAR + 44 * 8 && S_RELK == S_BAR + 38 * 8, "barriers");
constexpr uint32_t ST_WQ = 3 * SLOT, ST_WG = 8 * SLOT, ST_WO = 11 * SLOT;

__device__ __forceinline__ uint32_t smem_u32(const void* p) { return (uint32_t)__cvta_generic_to_shared(p); }
__device__ __forceinline__ void mbar_init(uint32_t bar, uint32_t cnt) { asm volatile("mbarrier.init.shared::cta.b64 [%0], %1;" :: "r"(bar), "r"(cnt) : "memory"); }
__device__ __forceinline__ void mbar_expect(uint32_t bar, uint32_t bytes) { asm volatile("mbarrier.arrive.expect_tx.shared::cta.b64 _, [%0], %1;" :: "r"(bar), "r"(bytes) : "memory"); }
__device__ __forceinline__ void mbar_arrive(uint32_t bar) { asm volatile("mbarrier.arrive.shared::cta.b64 _, [%0];" :: "r"(bar) : "memory"); }
__device__ __forceinline__ bool mbar_try(uint32_t bar, uint32_t parity) {
    uint32_t ok;
    asm volatile("{\n .reg .pred p;\n mbarrier.try_wait.parity.shared::cta.b64 p, [%1], %2;\n selp.u32 %0, 1, 0, p;\n}" : "=r"(ok) : "r"(bar), "r"(parity) : "memory");
    return ok != 0;
}
__device__ __forceinline__ bool mbar_test(uint32_t bar, uint32_t parity) {
    uint32_t ok;
    asm volatile("{\n .reg .pred p;\n mbarrier.test_wait.parity.shared::cta.b64 p, [%1], %2;\n selp.u32 %0, 1, 0, p;\n}" : "=r"(ok) : "r"(bar), "r"(parity) : "memory");
    return ok != 0;
}
__device__ __forceinline__ void mbar_wait(uint32_t bar, uint32_t parity) {
    int n = 0;
    while (!mbar_try(bar, parity) && ++n < SPIN_LIMIT) {}
}
__device__ __forceinline__ unsigned long long gtime() { unsigned long long t; asm volatile("mov.u64 %0, %globaltimer;" : "=l"(t)); return t; }
__device__ __forceinline__ uint32_t gtime32() { uint32_t t; asm volatile("mov.u32 %0, %globaltimer_lo;" : "=r"(t)); return t; }
__device__ __forceinline__ void bar_main() { asm volatile("bar.sync 1, 256;" ::: "memory"); }

__device__ __forceinline__ void mma16816(float (&c)[4], uint32_t a0, uint32_t a1, uint32_t a2, uint32_t a3, uint32_t b0, uint32_t b1) {
    asm("mma.sync.aligned.m16n8k16.row.col.f32.bf16.bf16.f32 {%0,%1,%2,%3}, {%4,%5,%6,%7}, {%8,%9}, {%0,%1,%2,%3};"
        : "+f"(c[0]), "+f"(c[1]), "+f"(c[2]), "+f"(c[3]) : "r"(a0), "r"(a1), "r"(a2), "r"(a3), "r"(b0), "r"(b1));
}
__device__ __forceinline__ void mmaA(float (&c)[4], const uint32_t (&a)[4], uint32_t b0, uint32_t b1) { mma16816(c, a[0], a[1], a[2], a[3], b0, b1); }
__device__ __forceinline__ void mmaAv(float (&c)[4], const uint32_t (&a)[4], uint32_t b0, uint32_t b1) {
    asm volatile("mma.sync.aligned.m16n8k16.row.col.f32.bf16.bf16.f32 {%0,%1,%2,%3}, {%4,%5,%6,%7}, {%8,%9}, {%0,%1,%2,%3};"
        : "+f"(c[0]), "+f"(c[1]), "+f"(c[2]), "+f"(c[3]) : "r"(a[0]), "r"(a[1]), "r"(a[2]), "r"(a[3]), "r"(b0), "r"(b1) : "memory");
}
__device__ __forceinline__ void mma8(float (&c)[4], uint32_t a0, uint32_t a1, uint32_t b0) {
    asm("mma.sync.aligned.m16n8k8.row.col.f32.bf16.bf16.f32 {%0,%1,%2,%3}, {%4,%5}, {%6}, {%0,%1,%2,%3};"
        : "+f"(c[0]), "+f"(c[1]), "+f"(c[2]), "+f"(c[3]) : "r"(a0), "r"(a1), "r"(b0));
}
struct W80 { uint32_t a[2][4], c[2]; };
template <int N> __device__ __forceinline__ void mul80(float (&acc)[N][4], const W80 (&W)[N], const uint4& b, uint32_t b4) {
#pragma unroll
    for (int m = 0; m < N; m++) mmaA(acc[m], W[m].a[0], b.x, b.y);
#pragma unroll
    for (int m = 0; m < N; m++) mmaA(acc[m], W[m].a[1], b.z, b.w);
#pragma unroll
    for (int m = 0; m < N; m++) mma8(acc[m], W[m].c[0], W[m].c[1], b4);
}
__device__ __forceinline__ void ldsm2t(uint32_t (&r)[2], uint32_t addr) {
    asm volatile("ldmatrix.sync.aligned.m8n8.x2.trans.shared.b16 {%0,%1}, [%2];" : "=r"(r[0]), "=r"(r[1]) : "r"(addr) : "memory");
}
__device__ __forceinline__ void mmaV(float (&c)[4], const uint4& a, uint32_t b0, uint32_t b1) { mma16816(c, a.x, a.y, a.z, a.w, b0, b1); }
__device__ __forceinline__ void ldsm4(uint32_t (&r)[4], uint32_t addr) {
    asm volatile("ldmatrix.sync.aligned.m8n8.x4.shared.b16 {%0,%1,%2,%3}, [%4];" : "=r"(r[0]), "=r"(r[1]), "=r"(r[2]), "=r"(r[3]) : "r"(addr) : "memory");
}
__device__ __forceinline__ void ldsm4t(uint32_t (&r)[4], uint32_t addr) {
    asm volatile("ldmatrix.sync.aligned.m8n8.x4.trans.shared.b16 {%0,%1,%2,%3}, [%4];" : "=r"(r[0]), "=r"(r[1]), "=r"(r[2]), "=r"(r[3]) : "r"(addr) : "memory");
}
__device__ __forceinline__ uint32_t lds16(uint32_t a) { uint16_t v; asm volatile("ld.shared.u16 %0, [%1];" : "=h"(v) : "r"(a) : "memory"); return v; }
__device__ __forceinline__ uint32_t lds32(uint32_t a) { uint32_t v; asm volatile("ld.shared.u32 %0, [%1];" : "=r"(v) : "r"(a) : "memory"); return v; }
__device__ __forceinline__ float ldsf(uint32_t a) { return __uint_as_float(lds32(a)); }
__device__ __forceinline__ uint2 lds64(uint32_t a) { uint2 v; asm volatile("ld.shared.v2.u32 {%0,%1}, [%2];" : "=r"(v.x), "=r"(v.y) : "r"(a) : "memory"); return v; }
__device__ __forceinline__ uint4 lds128(uint32_t a) { uint4 v; asm volatile("ld.shared.v4.u32 {%0,%1,%2,%3}, [%4];" : "=r"(v.x), "=r"(v.y), "=r"(v.z), "=r"(v.w) : "r"(a) : "memory"); return v; }
__device__ __forceinline__ int ldsvol(uint32_t a) { int v; asm volatile("ld.volatile.shared.u32 %0, [%1];" : "=r"(v) : "r"(a) : "memory"); return v; }
__device__ __forceinline__ uint2 ldsvol64(uint32_t a) { uint2 v; asm volatile("{\n .reg .b64 d;\n ld.volatile.shared.b64 d, [%2];\n mov.b64 {%0,%1}, d;\n}" : "=r"(v.x), "=r"(v.y) : "r"(a) : "memory"); return v; }
__device__ __forceinline__ void stsvol64(uint32_t a, uint32_t x, uint32_t y) { asm volatile("{\n .reg .b64 d;\n mov.b64 d, {%1,%2};\n st.volatile.shared.b64 [%0], d;\n}" :: "r"(a), "r"(x), "r"(y) : "memory"); }
__device__ __forceinline__ void stsvol(uint32_t a, int v) { asm volatile("st.volatile.shared.u32 [%0], %1;" :: "r"(a), "r"(v) : "memory"); }
__device__ __forceinline__ void sts_hi16(uint32_t a, float v) { asm volatile("{\n .reg .b16 lo, hi;\n mov.b32 {lo, hi}, %1;\n st.shared.u16 [%0], hi;\n}" :: "r"(a), "r"(__float_as_uint(v)) : "memory"); }
__device__ __forceinline__ void sts16(uint32_t a, uint32_t v) { asm volatile("st.shared.u16 [%0], %1;" :: "r"(a), "r"(v) : "memory"); }
__device__ __forceinline__ void sts32(uint32_t a, uint32_t v) { asm volatile("st.shared.u32 [%0], %1;" :: "r"(a), "r"(v) : "memory"); }
__device__ __forceinline__ void stsf(uint32_t a, float v) { sts32(a, __float_as_uint(v)); }
__device__ __forceinline__ void sts64(uint32_t a, uint32_t x, uint32_t y) { asm volatile("st.shared.v2.u32 [%0], {%1,%2};" :: "r"(a), "r"(x), "r"(y) : "memory"); }

__device__ __forceinline__ void sts_hi16_if(bool p, uint32_t a, float v) {
    asm volatile("{\n .reg .pred p;\n .reg .b16 lo, hi;\n setp.ne.u32 p, %2, 0;\n mov.b32 {lo, hi}, %1;\n @p st.shared.u16 [%0], hi;\n}" :: "r"(a), "r"(__float_as_uint(v)), "r"((uint32_t)p) : "memory");
}
__device__ __forceinline__ void sts32_if(bool p, uint32_t a, uint32_t v) {
    asm volatile("{\n .reg .pred p;\n setp.ne.u32 p, %2, 0;\n @p st.shared.u32 [%0], %1;\n}" :: "r"(a), "r"(v), "r"((uint32_t)p) : "memory");
}
__device__ __forceinline__ void sts64_if(bool p, uint32_t a, float x, float y) {
    asm volatile("{\n .reg .pred p;\n setp.ne.u32 p, %3, 0;\n @p st.shared.v2.f32 [%0], {%1,%2};\n}" :: "r"(a), "f"(x), "f"(y), "r"((uint32_t)p) : "memory");
}
__device__ __forceinline__ void arrive_if(bool p, uint32_t bar) {
    asm volatile("{\n .reg .pred p;\n setp.ne.u32 p, %1, 0;\n @p mbarrier.arrive.shared::cta.b64 _, [%0];\n}" :: "r"(bar), "r"((uint32_t)p) : "memory");
}
__device__ __forceinline__ void opaque(uint32_t& v) { asm volatile("" : "+r"(v)); }
__device__ __forceinline__ void keep(uint32_t& v) { asm volatile("" : "+r"(v)); }
__device__ __forceinline__ void keep(float& v) { asm volatile("" : "+f"(v)); }
template <class T> __device__ __forceinline__ void keep(T*& v) { asm volatile("" : "+l"(v)); }

__device__ __forceinline__ uint32_t ldp32(const char* p) { uint32_t v; asm volatile("ld.relaxed.gpu.global.u32 %0, [%1];" : "=r"(v) : "l"(p) : "memory"); return v; }
__device__ __forceinline__ uint2 ldp64(const char* p) {
    uint2 v; asm volatile("{\n .reg .b64 d;\n ld.relaxed.gpu.global.b64 d, [%2];\n mov.b64 {%0,%1}, d;\n}" : "=r"(v.x), "=r"(v.y) : "l"(p) : "memory"); return v;
}
__device__ __forceinline__ uint32_t tagw(float f, uint32_t par) { return (__float_as_uint(f) & ~1u) | par; }
__device__ __forceinline__ void stp32(char* p, float a, uint32_t par) { asm volatile("st.relaxed.gpu.global.u32 [%0], %1;" :: "l"(p), "r"(tagw(a, par)) : "memory"); }
__device__ __forceinline__ void stp64(char* p, float a, float b, uint32_t par) {
    asm volatile("{\n .reg .b64 d;\n mov.b64 d, {%1,%2};\n st.relaxed.gpu.global.b64 [%0], d;\n}" :: "l"(p), "r"(tagw(a, par)), "r"(tagw(b, par)) : "memory");
}
__device__ __forceinline__ void stp32_if(bool p, char* d, float a, uint32_t par) {
    asm volatile("{\n .reg .pred p;\n setp.ne.u32 p, %2, 0;\n @p st.relaxed.gpu.global.u32 [%0], %1;\n @p st.relaxed.gpu.global.u32 [%0+4096], %1;\n}" :: "l"(d), "r"(tagw(a, par)), "r"((uint32_t)p) : "memory");
}
__device__ __forceinline__ void stp64_if(bool p, char* d, uint32_t lo, uint32_t hi) {
    asm volatile("{\n .reg .pred p;\n .reg .b64 d;\n setp.ne.u32 p, %3, 0;\n mov.b64 d, {%1,%2};\n @p st.relaxed.gpu.global.b64 [%0], d;\n @p st.relaxed.gpu.global.b64 [%0+4096], d;\n}" :: "l"(d), "r"(lo), "r"(hi), "r"((uint32_t)p) : "memory");
}
__device__ __forceinline__ uint32_t chk2(uint32_t a, uint32_t b, uint32_t par) { uint32_t r; asm("lop3.b32 %0, %1, %2, %3, 0x7E;" : "=r"(r) : "r"(a), "r"(b), "r"(par)); return r; }
__device__ __forceinline__ uint32_t or3(uint32_t a, uint32_t b, uint32_t c) { uint32_t r; asm("lop3.b32 %0, %1, %2, %3, 0xFE;" : "=r"(r) : "r"(a), "r"(b), "r"(c)); return r; }
__device__ __forceinline__ uint32_t chk8(const uint32_t (&v)[8], uint32_t par) { return or3(chk2(v[0], v[1], par), chk2(v[2], v[3], par), or3(chk2(v[4], v[5], par), chk2(v[6], v[7], par), 0)); }
__device__ __forceinline__ uint32_t chk8(const uint2 (&v)[8], uint32_t par) { return or3(chk2(v[0].x, v[1].x, par), chk2(v[2].x, v[3].x, par), or3(chk2(v[4].x, v[5].x, par), chk2(v[6].x, v[7].x, par), 0)); }
__device__ __forceinline__ uint32_t chk8y(const uint2 (&v)[8], uint32_t par) { return or3(chk2(v[0].y, v[1].y, par), chk2(v[2].y, v[3].y, par), or3(chk2(v[4].y, v[5].y, par), chk2(v[6].y, v[7].y, par), 0)); }
__device__ __forceinline__ uint32_t chk4(const uint2 (&v)[4], uint32_t par) { return or3(chk2(v[0].x, v[0].y, par), chk2(v[1].x, v[1].y, par), or3(chk2(v[2].x, v[2].y, par), chk2(v[3].x, v[3].y, par), 0)); }
__device__ __forceinline__ float asf(uint32_t v) { return __uint_as_float(v); }
__device__ __forceinline__ float sum8(const uint32_t (&v)[8]) { return ((asf(v[0]) + asf(v[1])) + (asf(v[2]) + asf(v[3]))) + ((asf(v[4]) + asf(v[5])) + (asf(v[6]) + asf(v[7]))); }
__device__ __forceinline__ float sum8x(const uint2 (&v)[8]) { return ((asf(v[0].x) + asf(v[1].x)) + (asf(v[2].x) + asf(v[3].x))) + ((asf(v[4].x) + asf(v[5].x)) + (asf(v[6].x) + asf(v[7].x))); }
__device__ __forceinline__ float sum8y(const uint2 (&v)[8]) { return ((asf(v[0].y) + asf(v[1].y)) + (asf(v[2].y) + asf(v[3].y))) + ((asf(v[4].y) + asf(v[5].y)) + (asf(v[6].y) + asf(v[7].y))); }

__device__ __forceinline__ uint32_t pack2(float lo, float hi) { uint32_t r; asm("cvt.rn.bf16x2.f32 %0, %1, %2;" : "=r"(r) : "f"(hi), "f"(lo)); return r; }
__device__ __forceinline__ float bfr(float x) { return __uint_as_float(pack2(0.0f, x)); }
__device__ __forceinline__ float ex2(float x) { float r; asm("ex2.approx.ftz.f32 %0, %1;" : "=f"(r) : "f"(x)); return r; }
__device__ __forceinline__ float rcp(float x) { float r; asm("rcp.approx.ftz.f32 %0, %1;" : "=f"(r) : "f"(x)); return r; }
__device__ __forceinline__ float sqrt_(float x) { float r; asm("sqrt.approx.ftz.f32 %0, %1;" : "=f"(r) : "f"(x)); return r; }
__device__ __forceinline__ float bf_lo(uint32_t v) { return __uint_as_float(v << 16); }
__device__ __forceinline__ float bf_hi(uint32_t v) { return __uint_as_float(v & 0xffff0000u); }
__device__ __forceinline__ float sel4(int k, float a, float b, float c, float d) { return (k & 2) ? ((k & 1) ? d : c) : ((k & 1) ? b : a); }
constexpr float LOG2E = 1.4426950408889634f;
constexpr uint32_t ONES = 0x3f803f80u;

__device__ __forceinline__ void ln_stats(float sum, float sq, float& mean, float& den) {
    const float m = sum * (1.0f / 640.0f);
    const float var = fmaxf(fmaf(sq, 1.0f / 640.0f, -m * m), 0.0f);
    mean = bfr(m);
    den = bfr(sqrt_(bfr(bfr(var) + 1e-5f)));
}
__device__ __forceinline__ float sigmoidf_(float x) { return rcp(1.0f + ex2(-x * LOG2E)); }

#define TSTAMP(k) do {} while (0)
#define TST(k) do {} while (0)

#define CSTAMP(k) do {} while (0)
template <int N> __device__ __forceinline__ uint32_t lag(uint32_t sb, uint32_t z = 0) {
#pragma unroll
    for (int k = 0; k < N; k++) z = ldsvol(sb + S_ZERO + z);
    return z;
}
__device__ __forceinline__ void warm_mma(uint32_t& a, uint32_t& b) {
    asm volatile("mma.sync.aligned.m16n8k8.row.col.f16.f16.f16.f16 {%0,%1}, {%0,%1}, {%0}, {%0,%1};" : "+r"(a), "+r"(b) :: "memory");
}
#define KWNS2 20
#define KWNS 200
template <int STRIDE>
__device__ __forceinline__ float gather8(const char* p, uint32_t par) {
    uint32_t v[8];
    int guard = 0;
    do {
#pragma unroll
        for (int s = 0; s < 8; s++) v[s] = ldp32(p + s * STRIDE);
    } while ((chk8(v, par) & 1) && ++guard < SPIN_LIMIT);
    return sum8(v);
}
template <class F>
__device__ __forceinline__ void gather16(const char* p, uint32_t par, int k, F use) {
    uint32_t v[8], u[8];
    int guard = 0;
    bool again;
    do {
#pragma unroll
        for (int s = 0; s < 8; s++) v[s] = ldp32(p + s * 512);
#pragma unroll
        for (int s = 0; s < 8; s++) u[s] = ldp32(p + HALF + s * 512);
        const uint32_t stale = use(sum8(v) + sum8(u), ((v[0] ^ par) & 1) * 8);
        again = __any_sync(~0u, (or3(chk8(v, par), chk8(u, par), stale) & 1) != 0);
    } while (again & (++guard < SPIN_LIMIT));
    SWEEPS(k, guard - 1);
}

struct Params {
    const __nv_bfloat16 *x, *k, *v, *wr;
    __nv_bfloat16* out;
};
struct Maps { CUtensorMap k, v, vu, wq, wo, wg, wu, wd; };

constexpr int KV_BATCH_KEYS = 32 * 4096;

__device__ __forceinline__ void tma2d(uint32_t dst, const CUtensorMap* m, int c0, int c1, uint32_t bar, uint32_t bytes, uint64_t pol) {
    asm volatile("{\n .reg .pred p;\n elect.sync _|p, 0xffffffff;\n"
                 " @p mbarrier.arrive.expect_tx.shared::cta.b64 _, [%2], %6;\n"
                 " @p cp.async.bulk.tensor.2d.shared::cluster.global.mbarrier::complete_tx::bytes.L2::cache_hint [%0], [%1, {%3, %4}], [%2], %5;\n}"
                 :: "r"(dst), "l"(m), "r"(bar), "r"(c0), "r"(c1), "l"(pol), "r"(bytes) : "memory");
}
__device__ __forceinline__ void scrap_copy(uint32_t dst, const char* src, uint32_t bar) {
    asm volatile("{\n .reg .pred p;\n elect.sync _|p, 0xffffffff;\n"
                 " @p mbarrier.arrive.expect_tx.shared::cta.b64 _, [%2], 12288;\n"
                 " @p cp.async.bulk.shared::cluster.global.mbarrier::complete_tx::bytes [%0], [%1], 4096, [%2];\n"
                 " @p cp.async.bulk.shared::cluster.global.mbarrier::complete_tx::bytes [%0], [%1+4096], 4096, [%2];\n"
                 " @p cp.async.bulk.shared::cluster.global.mbarrier::complete_tx::bytes [%0], [%1+8192], 4096, [%2];\n}"
                 :: "r"(dst), "l"(src), "r"(bar) : "memory");
}
__device__ __forceinline__ void prefetch_l2(const void* p, uint32_t bytes) {
    asm volatile("{\n .reg .pred p;\n elect.sync _|p, 0xffffffff;\n @p cp.async.bulk.prefetch.L2.global [%0], %1;\n}" :: "l"(p), "r"(bytes) : "memory");
}
__device__ __forceinline__ uint64_t pol_first() { uint64_t p; asm("createpolicy.fractional.L2::evict_first.b64 %0, 1.0;" : "=l"(p)); return p; }
__device__ __forceinline__ uint64_t pol_normal() { uint64_t p; asm("createpolicy.fractional.L2::evict_normal.b64 %0, 1.0;" : "=l"(p)); return p; }
__device__ __forceinline__ bool utest(uint32_t bar, uint32_t parity) { return __all_sync(~0u, mbar_test(bar, parity)); }
__device__ __forceinline__ void uwait(uint32_t bar, uint32_t parity) {
    int n = 0;
    while (!__all_sync(~0u, mbar_try(bar, parity)) && ++n < SPIN_LIMIT) {}
}
template <int A, int B, int CNT> __device__ __forceinline__ void init_bars(uint32_t sb) {
#pragma unroll 1
    for (int k = A; k < B; k++)
        asm volatile("{\n .reg .pred p;\n elect.sync _|p, 0xffffffff;\n @p mbarrier.init.shared::cta.b64 [%0], %1;\n}" :: "r"(sb + S_BAR + 8 * k), "n"(CNT) : "memory");
}
__device__ __forceinline__ int first_key() { return (blockIdx.x >> 2) * 4096 + 3072 + (blockIdx.x & 3) * 256; }
__device__ __forceinline__ void load_tile(const CUtensorMap* m, uint32_t dst, uint32_t bar, uint32_t bytes, int key, uint64_t pol) { tma2d(dst, m, 0, 3 * key, bar, bytes, pol); }
__device__ __forceinline__ const char* unit_ptr(const Params& P, int n) {
    return (const char*)((n & 16) ? P.v : P.k) + (size_t)(first_key() + (n >> 5) * KV_BATCH_KEYS + (n & 15) * 16) * 384;
}
#define LSTAMP(k) do {} while (0)

__device__ __forceinline__ uint32_t k_place(uint32_t b, uint32_t s) { return s + 3 + 5 * (b & 1); }
__device__ __forceinline__ uint32_t v_place(uint32_t b, uint32_t s) { return s < 3 ? s : s + 8 - 8 * (b & 1); }
__device__ __forceinline__ void k_load(const Maps& M, uint32_t dst, uint32_t bar, int key8, uint64_t pol) {
    asm volatile("{\n .reg .pred p;\n elect.sync _|p, 0xffffffff;\n"
                 " @p mbarrier.arrive.expect_tx.shared::cta.b64 _, [%2], 6144;\n"
                 " @p cp.async.bulk.tensor.4d.shared::cluster.global.mbarrier::complete_tx::bytes.L2::cache_hint [%0], [%1, {0, 0, 0, %3}], [%2], %4;\n}"
                 :: "r"(dst), "l"(&M.k), "r"(bar), "r"(key8), "l"(pol) : "memory");
}
__device__ __forceinline__ int unit_key8(uint32_t n) { return first_key() / 8 + (n >> 4) * (KV_BATCH_KEYS / 8) + 2 * (n & 15); }
__device__ __forceinline__ void ring_load(const Maps& M, uint32_t sb, uint32_t b, uint32_t u, uint32_t pos) {
    if (u < 16) k_load(M, sb + pos * UNIT, sb + S_RING + 8 * pos, unit_key8(16 * b + u), pol_normal());
    else load_tile(&M.vu, sb + pos * UNIT, sb + S_FV + 4 * (pos & 6), UNIT, first_key() + b * KV_BATCH_KEYS + 16 * pos, pol_first());
}
__device__ __forceinline__ uint32_t token(bool p, uint32_t a, uint32_t n) {
    uint32_t v;
    asm volatile("{\n .reg .pred p;\n setp.ne.u32 p, %2, 0;\n mov.u32 %0, 0;\n @p atom.shared.exch.b32 %0, [%1], %3;\n}" : "=r"(v) : "r"(a), "r"((uint32_t)p), "r"(n) : "memory");
    return v;
}
__device__ __forceinline__ void place_load(const Maps& M, uint32_t sb, uint32_t n) {
    k_load(M, sb + k_place(n >> 4, 0) * SLOT + (n & 15) * UNIT, sb + S_FK + 4 * (n & 14), unit_key8(n), pol_first());
}
__device__ __forceinline__ void v_load(const Maps& M, uint32_t sb, uint32_t b, uint32_t s) {
    load_tile(&M.v, sb + v_place(b, s) * SLOT, sb + S_FV + 8 * s, SLOT, first_key() + b * KV_BATCH_KEYS + 32 * s, pol_first());
}
__device__ __forceinline__ bool due(uint32_t t) { return __all_sync(~0u, (int)(gtime32() * 16 - t) >= 0); }
__device__ __forceinline__ bool reached(uint32_t a, int v) { return __all_sync(~0u, ldsvol(a) >= v); }

__device__ __forceinline__ void stream_warp(const Params& P, const Maps& M, uint32_t sb, uint32_t lane) {
    const uint64_t pol = pol_first();
    const int bid = blockIdx.x, g = bid >> 3, i = bid & 7;
    const uint32_t wf = sb + S_WFULL;
    if (PF0 > 0 && !PFTOP) prefetch_l2(unit_ptr(P, 0), PF0 * UNIT);
    uint32_t tn = __shfl_sync(~0u, gtime32(), 0) * 16 - T_LEAD;
    auto pace = [&](uint32_t dt) {
        int k = 0;
        uint32_t now;
        do now = __shfl_sync(~0u, gtime32(), 0) * 16; while ((int)(now - tn) < 0 && ++k < SPIN_LIMIT);
        if ((int)(now - tn) > SLACK0) tn = now - SLACK0;
        tn += dt;
    };
#pragma unroll
    for (int k = 0; k < 10; k++) {
        if (k < 2) {
            if (k == 0) init_bars<26, 27, 1>(sb); else init_bars<27, 37, 1>(sb);
            asm volatile("fence.mbarrier_init.release.cluster;" ::: "memory");
            if (k == 1) { asm volatile("bar.arrive 2, %0;" :: "n"(NTHR) : "memory"); asm volatile("bar.sync 3, 128;" ::: "memory"); }
        }
        if (k >= WIN_W) uwait(wf + 8 * (k - WIN_W), 0);
        pace(TAUW * 5 / 2);
        if (k < 4) tma2d(sb + ST_WQ + 15360 * k, &M.wq, 384 * g + 192 * (k >> 1), 80 * i + 40 * (k & 1), wf + 8 * k, 15360, pol);
        else if (k < 6) tma2d(sb + ST_WG + 15360 * (k - 4), k == 4 ? &M.wg : &M.wu, 96 * g, 80 * i, wf + 8 * k, 15360, pol);
        else tma2d(sb + ST_WO + 15360 * (k - 6), &M.wo, 80 * i, 384 * g + 96 * (k - 6), wf + 8 * k, 15360, pol);
    }
#pragma unroll 1
    for (int n = 0; n < 16; n++) {
        if (n == 0 || n == 5 || n == 11) uwait(sb + S_RELW + (n == 0 ? 0 : n == 5 ? 8 : 16), 0);
        uwait(n < WIN_S ? wf + 8 * (10 - WIN_S + n) : sb + S_FV + 8 * ((n - WIN_S) ^ 8), 0);
        pace(max(min(2 * n + 2 - PF0, 2), 0) * TAU0);
        if (n < 8) { place_load(M, sb, 2 * n); place_load(M, sb, 2 * n + 1); }
        else if (n < 11) { ring_load(M, sb, 0, 2 * n, 2 * n - 16); ring_load(M, sb, 0, 2 * n + 1, 2 * n - 15); }
        else v_load(M, sb, 0, n - 8);
        if (n == 7) { pace(TAUW * 5 / 2); tma2d(sb + S_WD, &M.wd, 80 * i, 96 * g, wf + 80, 15360, pol); }
    }
    int nd = 0;
    uint32_t q[4];
#pragma unroll
    for (int r = 0; r < 4; r++) q[r] = sb + S_FV + 8 * (7 - r);
    tn -= TSH;
    uint32_t td = tn;
    uint32_t pos = 2;
#pragma unroll 1
    for (int m = 16; m < 64; m++) {
        const int b = m >> 4, j = m & 15;
        const char* src = unit_ptr(P, 2 * m);
        const uint32_t tok = sb + S_TOK + (j < 3 ? 4 * pos : j < 11 ? 24 + 4 * pos : 16 + 4 * j) + 4 * lane;
        static_assert(WIN_U <= 12, "a ring position has at most one token of the timetable");
        int k = 0;
        while (true) {
            const uint2 c = lds64(sb + S_KF);
            if (__all_sync(~0u, mbar_test(q[WIN_S - 1] & ~1u, q[WIN_S - 1] & 1) & (min((int)c.x + 1, (int)c.y) >= 16 * b + min(2 * j + 2 - WIN_U, 16))) || ++k >= SPIN_LIMIT) break;
        }
        uint32_t now;
        while (true) {
            now = __shfl_sync(~0u, gtime32(), 0) * 16;
            if ((int)(now - td) >= 0 || ++k >= SPIN_LIMIT) break;
            if (PSLEEP > 0 && (int)(td - now) > 16 * PSLEEP * 2) __nanosleep(PSLEEP);
        }
        const uint32_t mine = __ballot_sync(~0u, token(lane < (j < 11 ? 2 : 1), tok, 2 * m + lane) == 2 * m + lane);
        q[3] = q[2]; q[2] = q[1]; q[1] = q[0]; q[0] = sb + S_QRDY;
        if (j < 11) {
            if (mine & 1) ring_load(M, sb, b, 2 * j, pos); else prefetch_l2(src, UNIT);
            if (mine & 2) ring_load(M, sb, b, 2 * j + 1, pos + 1); else prefetch_l2(src + UNIT, UNIT);
            if (j >= 8) q[0] = (sb + S_FV + 8 * (j - 8)) | (b & 1);
        } else if (mine) { v_load(M, sb, b, j - 8); q[0] = (sb + S_FV + 8 * (j - 8)) | (b & 1); }
        else if (j - 8 >= VPF) prefetch_l2(src, SLOT);
        else {
            scrap_copy(sb + S_DUMMY, src, sb + S_DBAR + 8 * (nd & 3));
            q[0] = (sb + S_DBAR + 8 * (nd & 3)) | ((nd >> 2) & 1);
            nd++;
        }
        pos = j == 15 ? 2 : pos == 4 ? 0 : pos + 2;
        if ((int)(now - tn) > SLACK) tn = now - SLACK;
        tn += 2 * TAU;
        td = (int)(tn - now) > 2 * TMIN ? tn : now + 2 * TMIN;
        if (m >= 48 + JFREE) td = now + TFREE;
    }
#pragma unroll 1
    for (int m = max(nd - 4, 0); m < nd; m++) uwait(sb + S_DBAR + 8 * (m & 3), (m >> 2) & 1);
}

__host__ __device__ constexpr uint64_t bit_list(uint32_t m) { uint64_t r = 0; int n = 0; for (int k = 0; k < 12; k++) if ((m >> k) & 1) r |= (uint64_t)k << (4 * n++); return r; }
__device__ __forceinline__ float scaled(float s) { return bfr(bfr(s) * 0.07216878364870322f); }
__device__ __forceinline__ void probs(float s, uint32_t ps, uint32_t src, uint32_t ln) {
    const uint32_t q8 = ln >> 2, t4 = ln & 3;
    int key = __float_as_int(s);
    key ^= (key >> 31) & 0x7fffffff;
    key = __reduce_max_sync(~0u, key);
    key ^= (key >> 31) & 0x7fffffff;
    const float ml = __int_as_float(key) * LOG2E;
    sts16(ps + 64 * src + (q8 >> 1) * 16 + t4 * 4 + (q8 & 1) * 2, pack2(ex2(fmaf(s, LOG2E, -ml)), 0.f));
    stsf(ps + PS_MAX + 4 * src, ml);
}
template <int H> __device__ __forceinline__ uint32_t b_pos(uint32_t e) { const uint32_t h = e >= H, k = e - H * h; return h * 192 + (k & 6) * 24 + (k >> 3) * 4 + (k & 1) * 2; }
__device__ __forceinline__ uint32_t a_pos(uint32_t e) { const uint32_t h = e >= 40, k = e - 40 * h; return (k & 6) * 24 + (k >> 3) * 8 + h * 4 + (k & 1) * 2; }
__device__ __forceinline__ uint32_t q_pos(uint32_t d) { const uint32_t s = 3 * ((d >> 4) & 3) + (d >> 6); return s * 32 + (d & 6) * 4 + ((d >> 3) & 1) * 4 + (d & 1) * 2; }
__device__ __forceinline__ uint32_t k_off(uint32_t ln) { return (ln & 8) * 384 + (ln & 7) * 128 + (((ln & 7) ^ (ln >> 4)) << 4); }

#define HSTAMP(k) do {} while (0)
__device__ __forceinline__ char* xwindow() { return reinterpret_cast<char*>((reinterpret_cast<uintptr_t>(g_x) + (2u << 20) - 1) & ~(uintptr_t)((2u << 20) - 1)); }

struct XPtr {
    uint32_t lo, hi;
    __device__ __forceinline__ explicit XPtr(char* p) : lo((uint32_t)(uintptr_t)p), hi((uint32_t)((uintptr_t)p >> 32)) {}
    __device__ __forceinline__ XPtr(uint32_t l, uint32_t h) : lo(l), hi(h) {}
    __device__ __forceinline__ XPtr operator+(uint32_t o) const { return XPtr(lo + o, hi); }
    __device__ __forceinline__ operator char*() const { uint64_t p; asm("mov.b64 %0, {%1, %2};" : "=l"(p) : "r"(lo), "r"(hi)); return (char*)p; }
};
__device__ __forceinline__ void keep(XPtr& v) { keep(v.lo); }

__device__ __forceinline__ void side_warp(uint32_t sb) {
    const uint32_t bid = blockIdx.x, g = bid >> 3, i = bid & 7, P = pairG(0, 0, i);
    char* p = xwindow() + P * 8192 + (g >> 3) * HALF + (g & 7) * 512 + 448;
    uint32_t best[2] = {~0u, ~0u};
    asm volatile("st.relaxed.gpu.global.b32 [%0], 1;" :: "l"(p) : "memory");
    asm volatile("st.relaxed.gpu.global.b32 [%0], 1;" :: "l"(p + COPY) : "memory");
#pragma unroll 1
    for (int r = 0; r < 64; r++) {
        if (r >= 4 && !(r & 1) && min(best[0], best[1]) < 380 && max(best[0], best[1]) > min(best[0], best[1]) + 80) break;
        uint32_t c0, c1, v;
        asm volatile("mov.u32 %0, %clock;" : "=r"(c0) :: "memory");
        asm volatile("atom.relaxed.gpu.global.exch.b32 %0, [%1], 0;" : "=r"(v) : "l"(p + (r & 1) * COPY) : "memory");
        asm volatile("{\n .reg .pred q;\n setp.eq.u32 q, %1, 0x13579bdf;\n mov.u32 %0, 0;\n @!q mov.u32 %0, %clock;\n}" : "=r"(c1) : "r"(v) : "memory");
        if (r & 1) best[1] = min(best[1], c1 - c0); else best[0] = min(best[0], c1 - c0);
    }
    stsvol(sb + S_SIDE, 1 + ((best[1] < best[0]) ^ (__popc(P & PMASK) & 1)));
}

template <int N>
__device__ __forceinline__ void hop_a(const char* src, uint32_t par, uint32_t dst, bool st, int k) {
    uint2 v[N][4];
    float e[4], rl;
    int guard = 0;
    bool again;
    do {
#pragma unroll
        for (int s = 0; s < 4 * N; s++) v[s / 4][s % 4] = ldp64(src + (s / 4) * 256 + (s % 4) * 1024);
        again = __any_sync(~0u, ((chk4(v[0], par) | chk4(v[N - 1], par)) & 1) != 0);
        const int M = max(max((int)v[0][0].x, (int)v[0][1].x), max((int)v[0][2].x, (int)v[0][3].x)) - 254;
#pragma unroll
        for (int s = 0; s < 4; s++) e[s] = __int_as_float(max((int)v[0][s].x - M, 0) << 22);
        rl = rcp(fmaf(e[0], asf(v[0][0].y), e[1] * asf(v[0][1].y)) + fmaf(e[2], asf(v[0][2].y), e[3] * asf(v[0][3].y)));
#pragma unroll
        for (int s = 0; s < 4; s++) e[s] = __shfl_sync(~0u, e[s], 24);
        keep(rl);
    } while (again & (++guard < SPIN_LIMIT));
    rl = __shfl_sync(~0u, rl, 24);
#pragma unroll
    for (int n = 0; n < N; n++) {
        const float o0 = fmaf(e[0], asf(v[n][0].x), e[1] * asf(v[n][1].x)) + fmaf(e[2], asf(v[n][2].x), e[3] * asf(v[n][3].x));
        const float o1 = fmaf(e[0], asf(v[n][0].y), e[1] * asf(v[n][1].y)) + fmaf(e[2], asf(v[n][2].y), e[3] * asf(v[n][3].y));
        sts32_if(st, dst + 192 * n, pack2(o0 * rl, o1 * rl));
    }
    SWEEPS(k, guard - 1);
    __syncwarp();
}

__device__ __forceinline__ void score_warp(const Maps& M, uint32_t sb, uint32_t h, uint32_t ln) {
    const uint32_t lane0 = ln;
    uwait(sb + S_QRDY, 0);
    const uint32_t q8 = ln >> 2;
    const uint32_t k0 = k_off(ln);
    uint32_t pos = h + 6, bar = sb + S_FK, par = 0, phases = 0;
    uint2 q = lds64(sb + S_QS + 8 * ln), qh = lds64(sb + S_QS + 8 * ln + 256);
    auto first_round = [&](uint32_t b, uint32_t ln) {
        uwait(sb + S_RELR, b & 1);
        const uint32_t u = h + 2 * ln, p = u < 4 ? u + 2 : u - 4;
        uint32_t todo = __ballot_sync(~0u, token(ln < 3, sb + S_TOK + 4 * p, 32 * b + 32 + u) == 32 * b + 32 + u);
#pragma unroll 1
        for (uint32_t r = h; todo; todo >>= 1, r += 2) if (todo & 1) ring_load(M, sb, b + 1, r, r < 4 ? r + 2 : r - 4);
    };
#pragma unroll 1
    for (uint32_t n = h; n < 64; n += 2) {
        HSTAMP(0);
        const uint32_t ua = sb + pos * UNIT;
        if (!__all_sync(~0u, mbar_try(bar, par))) uwait(bar, par);
        HSTAMP(1);
        float acc[2][4] = {};
        uint32_t mine = 0;
        const uint32_t id = n + (n & 48) + 6;
#pragma unroll
        for (int s = 0; s < 12; s++) {
            uint32_t kf[4];
            ldsm4(kf, (k0 ^ (32 * (s / 3))) + (ua + 1024 * (s % 3)));
            if (s == 11) {
                __syncwarp();
                mine = token(ln == 0 && n >= 16, sb + S_TOK + 24 + 4 * pos, id);
                stsvol(sb + S_KF + 4 * h, n + 1);
            }
            const bool m = q8 == (s & 7);
            mmaA(acc[s & 1], kf, m ? (s < 8 ? q.x : qh.x) : 0u, m ? (s < 8 ? q.y : qh.y) : 0u);
        }
        const uint32_t pos0 = pos;
        const bool last = (n & 14) == 14;
        pos = last ? h + 2 : n >= 16 && pos >= 4 ? h : pos + 2;
        bar = n >= 14 ? sb + S_RING + 8 * pos : bar + 8;
        par = n >= 14 ? (phases >> pos) & 1 : 0;
        phases ^= n >= 14 ? 1u << pos : 0;
        const float w0 = (acc[0][0] + acc[0][1]) + (acc[1][0] + acc[1][1]), w1 = (acc[0][2] + acc[0][3]) + (acc[1][2] + acc[1][3]);
        HSTAMP(2);
        if (__any_sync(~0u, mine == id)) ring_load(M, sb, n >> 4, (n & 15) + 6, pos0);
        HSTAMP(3);
        float s = ((ln & 1) ? w1 : w0) + __shfl_xor_sync(~0u, (ln & 1) ? w0 : w1, 1);
        s += __shfl_xor_sync(~0u, s, 2);
        sts_hi16(sb + S_SC + (((n & 12) >> 1) + h) * 64 + (n & 2) * 2 + (ln & 29) * 2, scaled(s));
        if (last) {
            __syncwarp();
            arrive_if(ln == 0, sb + S_SCO);
            const uint32_t b = n >> 4, ln = lane0 + lag<1>(sb);
            if (b > 0) {
                uwait(sb + S_RELK, (b - 1) & 1);
                if (h == 0) LSTAMP(64 + 2 * b);
                const uint32_t sl = 3 + h + 2 * ln, idv = 32 * b + 16 + 2 * sl;
                uint32_t todo = __ballot_sync(~0u, token(sl < 8, sb + S_TOK + 48 + 4 * sl, idv) == idv);
#pragma unroll 1
                for (uint32_t r = 3 + h; todo; todo >>= 1, r += 2) if (todo & 1) v_load(M, sb, b, r);
                const uint32_t g = blockIdx.x >> 3, pr = pairL(RA, 1, g), side = ldsvol(sb + S_SIDE);
                const char* src = xwindow() + pr * 8192 + ((side ^ 1 ^ __popc(pr & PMASK)) & 1) * COPY + h * HALF + 8 * min(ln, 24u);
                uwait(sb + S_RELV, (b - 1) & 1);
                __nanosleep(HOP1_NS);
#pragma unroll 1
                for (uint32_t r = 0; r < 4; r += 2) {
                    hop_a<2>(src + 256 * r, b & 1, sb + S_OS + 192 * (4 * h + r) + 96 + 4 * ln, ln < 24, 25);
                    if (r == RELR_AT && b < 3) first_round(b, ln);
                }
                arrive_if(ln == 0, sb + S_OS1);
            } else first_round(0, ln);
            q = lds64(sb + S_QS + 24 * ((n + 2) & 48) + 8 * ln); qh = lds64(sb + S_QS + 24 * ((n + 2) & 48) + 8 * ln + 256);
        }
    }
}

__global__ void __launch_bounds__(NTHR, 1)
fused_kernel(const Params P, const __grid_constant__ Maps M) {
    extern __shared__ __align__(1024) unsigned char smem[];
    const uint32_t sb = smem_u32(smem);
    const int tid = threadIdx.x, bid = blockIdx.x;
    if (PFTOP && tid == 0) {
        if (PFTOP == 2) asm volatile("prefetch.tensormap [%0];" :: "l"(&M.wq) : "memory");
        asm volatile("cp.async.bulk.prefetch.L2.global [%0], %1;" :: "l"(unit_ptr(P, 0)), "r"(PF0 * UNIT) : "memory");
    }
    const int w = __shfl_sync(~0u, tid >> 5, 0), lane = tid & 31;

    if (w >= 8) {
        asm volatile("setmaxnreg.dec.sync.aligned.u32 " REG_LO ";");
        if (w == 8) {
            stream_warp(P, M, sb, lane);
        } else {
            if (PFMAP && w == 11 && lane < 8) asm volatile("prefetch.tensormap [%0];" :: "l"(&M.k + lane) : "memory");
            if (w == 9) { init_bars<0, 3, 2>(sb); init_bars<3, 8, 1>(sb); init_bars<16, 22, 1>(sb); }
            else if (w == 10) { init_bars<8, 16, 2>(sb); init_bars<22, 26, 1>(sb); }
            else { init_bars<37, 38, 1>(sb); init_bars<38, 40, 8>(sb); init_bars<40, 41, 1>(sb); init_bars<41, 44, 8>(sb); init_bars<44, 46, 2>(sb); stsvol(sb + S_ZERO + 4 * lane, 0); if (lane < 16) stsvol(sb + S_LN + 4 * lane, 0); }
            asm volatile("fence.mbarrier_init.release.cluster;" ::: "memory");
            asm volatile("bar.arrive 3, 128;" ::: "memory");
            asm volatile("bar.sync 2, %0;" :: "n"(NTHR) : "memory");
            if (w < 11) score_warp(M, sb, w - 9, lane);
            else {
                if (lane == 0) side_warp(sb);
                __syncwarp();
                uint32_t a = 0, b = 0;
                int k = 0;
                while (ldsvol(sb + S_GATE) == 0 && ++k < SPIN_LIMIT) { warm_mma(a, b); __nanosleep(KWNS); }
                uint4* d = reinterpret_cast<uint4*>(reinterpret_cast<char*>(g_s) + XS + bid * 7680) + lane;
                const uint4 z = make_uint4(0, 0, 0, 0);
#pragma unroll 1
                for (int u = 0; u < 15; u++) d[32 * u] = z;
                d = reinterpret_cast<uint4*>(reinterpret_cast<char*>(g_s) + XS2 + bid * 768) + lane;
                d[0] = z;
                if (lane < 16) d[32] = z;
                const uint32_t side = (ldsvol(sb + S_SIDE) & 1) ^ 1, g = bid >> 3, i = bid & 7;
                const XPtr gx(xwindow());
                auto nearp = [&](uint32_t pr) { return gx.lo + pr * 8192 + ((side ^ __popc(pr & PMASK)) & 1) * COPY; };
                const uint32_t own = (i >> 2) * HALF + (i & 3) * 1024 + (lane & 7) * 128;
                const uint32_t pAC = nearp(pairL(lane >> 4, (lane >> 3) & 1, g)) + own, pE = nearp(pairL(RE, (lane >> 3) & 1, g)) + own;
                const uint32_t pG = nearp(pairG((lane >> 2) & 1, (lane >> 3) & 1, i)) + min(lane & 3, 2) * 128;
                uint32_t tr = 0, tk = 0, ph = 0, src = g + (lane >> 4), seen = 0, n = 16, cs = 0;
                bool go = false, first = true;
                while (n < 64 && ++k < SPIN_LIMIT) {
                    const uint32_t now = __shfl_sync(~0u, gtime32(), 0) * 16;
                    if (!go && utest((n & 15) < KRE_EARLY ? sb + S_RELK : sb + S_RELV, ((n >> 4) & 1) ^ 1)) { go = true; if ((int)(now - tk) > 0 || !(n & 15)) tk = now; }
                    if (go && (int)(now - tk) >= 0) {
                        place_load(M, sb, (n & 16) ? n : (n & 48) | ((n + 10) & 15));
                        tk += n >= 48 ? KRE_TAU3 : (n & 15) < KRE_N1 ? KRE_TAU1 : KRE_TAU;
                        n++;
                        go = (n & 15) != 0 && (n & 15) != KRE_EARLY;
                        if (!(n & 15)) LSTAMP(63 + (n >> 3));
                    } else if (first || (int)(now - tr) >= 0) {
                        first = false;
                        tr = now + RFR_TAU;
                        b |= seen & a;
                        warm_mma(a, b);
                        if (RFR_ON) seen = ldp32(XPtr(ph == 0 ? pAC : ph == 1 && lane < 16 ? pE : pG + (src & 8) * (HALF / 8) + (src & 7) * 512, gx.hi));
                        if (RFR_XS && (++cs & (RFR_XS - 1)) < 2) {
                            const uint32_t l = lane + 32 * (cs & 1);
                            *reinterpret_cast<volatile uint32_t*>(reinterpret_cast<char*>(g_s) + (l < 60 ? XS + bid * 7680 + 128 * l : XS2 + bid * 768 + 128 * (l - 60))) = 0;
                        }
                        src += ph == 0 ? 0 : ph == 1 ? 2 : 1;
                        ph = ph == 2 ? 0 : ph + 1;
                    } else __nanosleep(KWNS2);
                }
                while (ldsvol(sb + S_GATE) < 6 && ++k < SPIN_LIMIT) { warm_mma(a, b); __nanosleep(KWNS); }
                if (a | b) stsvol(sb + S_GATE, 6);
            }
        }
        return;
    }
    asm volatile("setmaxnreg.inc.sync.aligned.u32 " REG_HI ";");

    const int g = bid >> 3, i = bid & 7;
    const int g8 = lane >> 2, t = lane & 3;
    char* const gs = reinterpret_cast<char*>(g_s);
    const XPtr gx(xwindow());

    auto zero_words = [&] {
        const uint4 z = make_uint4(0, 0, 0, 0);
        const uint32_t c = (tid >> 6) & 1, cp = (tid >> 7) * COPY, k = (tid & 63) * 16;
        *reinterpret_cast<uint4*>((char*)(gx + pairL(RA, c, g) * 8192 + (i >> 2) * HALF + (i & 3) * 1024 + cp + k)) = z;
        *reinterpret_cast<uint4*>((char*)(gx + pairL(RC, c, g) * 8192 + (i >> 2) * HALF + (i & 3) * 1024 + cp + k)) = z;
        *reinterpret_cast<uint4*>((char*)(gx + pairL(RE, c, g) * 8192 + (i >> 2) * HALF + (i & 3) * 1024 + cp + k)) = z;
        if ((tid & 31) < 24) *reinterpret_cast<uint4*>((char*)(gx + pairG((tid >> 5) & 1, c, i) * 8192 + (g >> 3) * HALF + (g & 7) * 512 + cp + (tid & 31) * 16)) = z;
    };
    if (ZPOS == 0) zero_words();
    W80 Wq[6], Wgu[3];
    uint32_t Wo[5][3][4];
    if (w < 4) {
        const uint32_t* xp = reinterpret_cast<const uint32_t*>(P.x + 640 * w);
        float sum = 0.f, sq = 0.f;
#pragma unroll
        for (int u = 0; u < 10; u++) { uint32_t v = xp[lane + 32 * u]; float a = bf_lo(v), b = bf_hi(v); sum += a + b; sq += a * a + b * b; }
#pragma unroll
        for (int o = 16; o > 0; o >>= 1) { sum += __shfl_xor_sync(~0u, sum, o); sq += __shfl_xor_sync(~0u, sq, o); }
        float mean, den; ln_stats(sum, sq, mean, den);
        if (lane < 20) {
            const uint2 v = reinterpret_cast<const uint2*>(P.x + 640 * w + 80 * i)[lane];
            sts64(sb + S_X0 + 160 * w + 8 * lane, v.x, v.y);
            sts32(sb + S_L0 + 384 * w + b_pos<40>(4 * lane), pack2(__fdiv_rn(bfr(bf_lo(v.x) - mean), den), __fdiv_rn(bfr(bf_hi(v.x) - mean), den)));
            sts32(sb + S_L0 + 384 * w + b_pos<40>(4 * lane + 2), pack2(__fdiv_rn(bfr(bf_lo(v.y) - mean), den), __fdiv_rn(bfr(bf_hi(v.y) - mean), den)));
        }
    } else if (w == 4) {
        const uint32_t* xp = reinterpret_cast<const uint32_t*>(P.wr);
        float sum = 0.f;
#pragma unroll
        for (int u = 0; u < 10; u++) { uint32_t v = xp[lane + 32 * u]; sum += bf_lo(v) + bf_hi(v); }
#pragma unroll
        for (int o = 16; o > 0; o >>= 1) sum += __shfl_xor_sync(~0u, sum, o);
        if (lane == 0) stsf(sb + S_SWR, sum);
        if (lane < 20) {
            const uint2 v = reinterpret_cast<const uint2*>(P.wr + 80 * i)[lane];
            sts32(sb + S_XA + 576 + a_pos(4 * lane), v.x); sts32(sb + S_XA + 576 + a_pos(4 * lane + 2), v.y);
            sts32(sb + S_XA + a_pos(4 * lane), ONES); sts32(sb + S_XA + a_pos(4 * lane + 2), ONES);
        }
    }
    asm volatile("bar.sync 2, %0;" :: "n"(NTHR) : "memory");
    auto frag = [](uint32_t (&a)[4], uint32_t p, int pitch) {
        const uint32_t r0 = lds32(p), r1 = lds32(p + pitch), r2 = lds32(p + 2 * pitch), r3 = lds32(p + 3 * pitch);
        a[0] = __byte_perm(r0, r1, 0x5410); a[1] = __byte_perm(r0, r1, 0x7632);
        a[2] = __byte_perm(r2, r3, 0x5410); a[3] = __byte_perm(r2, r3, 0x7632);
    };
    mbar_wait(sb + S_WFULL + 16 * (w >> 2), 0);
    mbar_wait(sb + S_WFULL + 16 * (w >> 2) + 8, 0);
    {
        const uint32_t p = sb + ST_WQ + (w >> 2) * 30720 + (2 * t) * 384 + (48 * (w & 3) + 2 * g8) * 2;
#pragma unroll
        for (int r = 0; r < 10; r++)
#pragma unroll
            for (int m = 0; m < 3; m++) {
                const uint32_t q = p + ((r & 1) * 40 + (r >> 1) * 8) * 384 + 32 * m, r0 = lds32(q), r1 = lds32(q + 384);
                (r < 8 ? Wq[2 * m].a[(r >> 2) & 1][r & 3] : Wq[2 * m].c[r & 1]) = __byte_perm(r0, r1, 0x5410);
                (r < 8 ? Wq[2 * m + 1].a[(r >> 2) & 1][r & 3] : Wq[2 * m + 1].c[r & 1]) = __byte_perm(r0, r1, 0x7632);
            }
    }
    __syncwarp();
    if (lane == 0) mbar_arrive(sb + S_RELW);
    TSTAMP(1);
    {
        char* d = gs + XS + bid * 7680 + (w >> 2) * 3840 + (48 * (w & 3) + 2 * g8) * 4;
        float acc[6][4] = {};
        mul80(acc, Wq, lds128(sb + S_L0 + 48 * lane), lds32(sb + S_L0 + 48 * lane + 16));
#pragma unroll
        for (int m = 0; m < 6; m += 2) stp64(d + t * 768 + 32 * m, acc[m][0] + acc[m][3], acc[m + 1][0] + acc[m + 1][3], 1);
        float sum[6][4] = {};
        mul80(sum, Wq, make_uint4(ONES, ONES, ONES, ONES), ONES);
        if (t == 0)
#pragma unroll
            for (int m = 0; m < 6; m += 2) stp64(d + 4 * 768 + 32 * m, sum[m][0] + sum[m][3], sum[m + 1][0] + sum[m + 1][3], 1);
    }
    mbar_wait(sb + S_WFULL + 32, 0);
    mbar_wait(sb + S_WFULL + 40, 0);
    const uint32_t oct = 3 * (w >> 1) + (w & 1), oct2 = 3 * (w >> 1) + 2;
    {
        const uint32_t p = sb + ST_WG + ((lane & 7) + 40 * ((lane >> 3) & 1) + 8 * (lane >> 4)) * 192;
#pragma unroll
        for (int T = 0; T < 3; T++) {
            const uint32_t q = p + (T < 2 ? T * 15360 + 16 * oct : (w & 1) * 15360 + 16 * oct2);
            ldsm4t(Wgu[T].a[0], q); ldsm4t(Wgu[T].a[1], q + 16 * 192); ldsm2t(Wgu[T].c, q + 32 * 192);
        }
        float sum[3][4] = {};
        mul80(sum, Wgu, make_uint4(ONES, ONES, ONES, ONES), ONES);
        if (t < 3) stp32(gs + XS2 + bid * 768 + (t < 2 ? 64 * oct + 4 * t : 64 * oct2 + 4 * (w & 1)) + 8 * g8,
                         sel4(t, sum[0][0] + sum[0][3], sum[1][0] + sum[1][3], sum[2][0] + sum[2][3], 0.f), 1);
    }
    __syncwarp();
    if (lane == 0) mbar_arrive(sb + S_RELW + 8);
    const char* srcS = gs + XS + g * 8 * 7680 + (i >> 2) * 3840 + min(tid, 191) * 4;
    uint32_t vs[5][8];
#pragma unroll
    for (int b = 0; b < 5; b++)
#pragma unroll
        for (int s = 0; s < 8; s++) vs[b][s] = LOOK1 ? ldp32(srcS + b * 768 + s * 7680) : 0;
    uint32_t cs2[8];
#pragma unroll
    for (int s = 0; s < 8; s++) cs2[s] = LOOK2 ? ldp32(gs + XS2 + (g * 8 + s) * 768 + min(tid, 191) * 4) : 0;
    __syncwarp();
    mbar_wait(sb + S_WFULL + 48 + 8 * (w >> 1), 0);
    {
        const uint32_t po = sb + ST_WO + (48 * w + 12 * t) * 160 + 4 * g8;
#pragma unroll
        for (int s = 0; s < 3; s++)
#pragma unroll
            for (int m = 0; m < 5; m++) frag(Wo[m][s], po + 4 * s * 160 + 32 * m, 160);
    }
    __syncwarp();
    if (lane == 0) mbar_arrive(sb + S_RELW + 16);
    if (ZPOS == 1) zero_words();
    if (tid < 192) {
        int guard = 0;
        while (((or3(chk8(vs[0], 1), chk8(vs[1], 1), chk8(vs[2], 1)) | chk8(vs[3], 1) | chk8(vs[4], 1)) & 1) && ++guard < SPIN_LIMIT) {
#pragma unroll
            for (int b = 0; b < 5; b++)
#pragma unroll
                for (int s = 0; s < 8; s++) vs[b][s] = ldp32(srcS + b * 768 + s * 7680);
        }
        const uint32_t qpos = sb + S_QS + q_pos(tid);
#pragma unroll
        for (int b = 0; b < 4; b++) {
            sts_hi16(qpos + 384 * b, bfr(sum8(vs[b])));
        }
        stsf(sb + S_CSQ + 4 * tid, sum8(vs[4]));
    }
    if (tid < 192) stsf(sb + S_CSGU + 4 * tid, (chk8(cs2, 1) & 1) ? gather8<768>(gs + XS2 + g * 8 * 768 + tid * 4, 1) : sum8(cs2));
    __syncwarp();
    bar_main();
    arrive_if(tid == 0, sb + S_QRDY);
    if (ZPOS == 2) zero_words();
    TSTAMP(2);

    uint32_t side;
    { int k = 0; while ((side = ldsvol(sb + S_SIDE)) == 0 && ++k < SPIN_LIMIT) {} }
    const uint32_t td = __shfl_sync(~0u, tid, lane);
    const uint32_t wp = __shfl_sync(~0u, tid >> 5, 0);
    const uint32_t cc = wp >= 3;
    auto uni = [](uint32_t v) { return __shfl_sync(~0u, v, 0); };
    auto pin = [&](uint32_t v) { return __shfl_sync(~0u, v, td); };
    auto nearp = [&](uint32_t P) { return gx.lo + P * 8192 + ((side ^ 1 ^ __popc(P & PMASK)) & 1) * COPY; };
    constexpr uint32_t COL = 32 * 8192;
    const uint32_t ownL = gx.lo + (i >> 2) * HALF + (i & 3) * 1024, ownG = gx.lo + (g >> 3) * HALF + (g & 7) * 512;
    const uint32_t uPubA = uni(ownL + pairL(RA, 0, g) * 8192 + (wp >> 1) * 256 + (wp & 1) * 96), uPolA = uni(nearp(pairL(RA, 0, g)) + (wp >> 2) * HALF + (wp & 3) * 256);
    const uint32_t uPubB = uni(ownG + pairG(0, cc, i) * 8192), uPolB = uni(nearp(pairG(0, cc, i)));
    const uint32_t uPubC = uni(ownL + pairL(RC, 0, g) * 8192), uPolC = uni(nearp(pairL(RC, wp < 6 ? cc : 0, g)));
    const uint32_t uPubD = uni(ownG + pairG(1, 0, i) * 8192 + (wp < 7 ? 32 * wp : 256)), uPolD = uni(nearp(pairG(1, cc, i)));
    const uint32_t uPubE = uni(ownL + pairL(RE, 0, g) * 8192), uPolE = uni(nearp(pairL(RE, i >> 2, g)));
    const uint32_t uOS = uni(sb + S_OS + 192 * wp);
    auto xp = [&](uint32_t lo) { return (char*)XPtr(lo, gx.hi); };
#define IDS() __syncwarp(); const uint32_t z0_ = lag<1>(sb), z_ = td + z0_; const uint32_t ln = z_ & 31, q8 = ln >> 2, t4 = z_ & 3, n96 = z_ - 96 * cc, n80 = min(n96, 79u); (void)q8; (void)t4; (void)n80; (void)ln

    auto vaddr = [&](uint32_t (&voff)[3]) {
        const uint32_t ln = td & 31;
        const uint32_t key3 = 3 * ((ln & 7) + 2 * (ln & 8) + ((ln >> 1) & 8));
#pragma unroll
        for (int T = 0; T < 3; T++) {
            const uint32_t u = 3 * wp + T, r = key3 + (u >> 3);
            voff[T] = r * 128 + (((u ^ r) & 7) << 4);
        }
    };
    auto values = [&](uint32_t (&vf)[8][3][4], float (&acc)[3][4], auto order, auto step, uint32_t ps, uint32_t col, uint32_t par) {
        const uint32_t ln = td & 31, q8 = ln >> 2, t4 = td & 3;
        const uint4 p = lds128(ps + 16 * ln);
        float f0 = 0.f, f1 = 0.f, r3 = 0.f;
#pragma unroll
        for (int k = 0; k < 12; k++) acc[k / 4][k % 4] = 0.f;
        int M = 0;
#pragma unroll
        for (int k = 0; k < 8; k++) {
            step(k);
            const int s = (order.value >> (4 * k)) & 7;
            const bool m = (q8 >> 1) == (s >> 1);
            const uint32_t b0 = m ? ((s & 1) ? p.z : p.x) : 0u, b1 = m ? ((s & 1) ? p.w : p.y) : 0u;
#pragma unroll
            for (int T = 0; T < 3; T++) mmaA(acc[T], vf[s][T], b0, b1);
            if (k == FSTEP) {
                const uint2 mp = lds64(ps + PS_MAX + 8 * t4);
                M = __reduce_max_sync(~0u, __float2int_ru(fmaxf(asf(mp.x), asf(mp.y))));
                f0 = ex2(asf(mp.x) - (float)M); f1 = ex2(asf(mp.y) - (float)M);
                float l[4] = {};
                mma16816(l, ONES, ONES, ONES, ONES, p.x, p.y); mma16816(l, ONES, ONES, ONES, ONES, p.z, p.w);
                r3 = fmaf(f0, l[0], f1 * l[1]);
            }
        }
        CSTAMP(25);
        char* pubA = xp(uPubA + col * COL + 32 * t4 + 4 * q8);
        const float r0 = fmaf(f0, acc[0][0], f1 * acc[0][3]), r1 = fmaf(f0, acc[1][0], f1 * acc[1][3]), r2 = fmaf(f0, acc[2][0], f1 * acc[2][3]);
        const bool hi = t4 & 2, od = t4 & 1;
        const float u0 = (hi ? r2 : r0) + __shfl_xor_sync(~0u, hi ? r0 : r2, 2), u1 = (hi ? r3 : r1) + __shfl_xor_sync(~0u, hi ? r1 : r3, 2);
        const float o = (od ? u1 : u0) + __shfl_xor_sync(~0u, od ? u0 : u1, 1);
        stp32_if(t4 < 3 || ((wp & 1) && q8 < 2), pubA, ln == 3 ? __int_as_float(2 * M) : o, par);
    };

    uint32_t left[36] = {};
#pragma unroll 1
    for (int ch = 0; ch < 5; ch++) {
        const uint32_t par0 = (ch + 1) & 1, par1 = ch & 1;
        uint32_t voff[3], vf[8][3][4];
        float acc_[3][4];
        if (ch < 4) {
            vaddr(voff);
            mbar_wait(sb + S_SCO, par1);
            if (ch == 0) mbar_wait(sb + S_WFULL + 80, 0);
            TST(0);
            auto ldw = [&](int s) {
                mbar_wait(sb + S_FV + 8 * s, par1);
#pragma unroll
                for (int T = 0; T < 3; T++) ldsm4t(vf[s][T], voff[T] + (sb + v_place(ch, s) * SLOT));
            };
            probs(bf_lo(lds16(sb + S_SC + 2 * td)), sb + S_PS, wp, td & 31);
            ldw(0); ldw(1); ldw(2);
            bar_main();
            arrive_if(td == 0, sb + S_RELR);
            values(vf, acc_, std::integral_constant<uint32_t, 0x76543210>(), [&](int s) {
                if (s >= 3) ldw(s);
            }, sb + S_PS, 0, par0);
            TST(1);
            CSTAMP(5);
            if (ch > 0) mbar_wait(sb + S_OS1, par0);
        } else {
#pragma unroll
            for (int s = 0; s < 36; s++) vf[s / 12][(s / 4) % 3][s & 3] = left[s];
        }
        const bool has0 = ch < 4, has1 = ch > 0;
        const bool actc = wp < 6 && (cc ? has1 : has0);
        const uint32_t parc = cc ? par1 : par0;
        const uint32_t pub0 = has0 ? par0 : 0;
        uint32_t rr, pubB;
        {
            IDS();
            const uint32_t c = ch == 4;
            const uint32_t osa = pin(uOS + 96 * c + 4 * ln), oa = pin(uOS + 48 * (q8 & 2) + 24 * t4), ra = pin(sb + S_RED + 640 * wp + 320 * (t4 & 1) + 8 * q8);
            rr = pin(sb + S_RED + 320 * cc + 4 * n80); pubB = pin(uPubB + 4 * n80);
            hop_a<1>(xp(uPolA + c * COL + 8 * min(ln, 24u) + lag<DELAY_L>(sb, z0_)), pub0, osa, ln < 24, 5 * ch);
            TST(2);
            CSTAMP(6);
            float acc[5][4] = {};
            const uint2 b0 = lds64(oa), b1 = lds64(oa + 8), b2 = lds64(oa + 16);
#pragma unroll
            for (int m = 0; m < 5; m++) mmaA(acc[m], Wo[m][0], b0.x, b0.y);
#pragma unroll
            for (int m = 0; m < 5; m++) mmaA(acc[m], Wo[m][1], b1.x, b1.y);
#pragma unroll
            for (int m = 0; m < 5; m++) mmaA(acc[m], Wo[m][2], b2.x, b2.y);
#pragma unroll
            for (int m = 0; m < 5; m++) { stsf(ra + 64 * m, acc[m][0]); stsf(ra + 64 * m + 4, acc[m][2]); }
        }
        CSTAMP(7);
        uint32_t xr, fl, pubC, pubC2;
        auto prepC = [&](uint32_t ln) {
            const uint32_t q8 = ln >> 2, t4 = ln & 3;
            xr = pin(sb + S_XB + 48 * (ln & 15));
            pubC = pin(uPubC + (t4 & 1) * COL + 192 * (wp >> 1) + 64 * (wp & 1) + 8 * q8);
            pubC2 = pin(uPubC + (t4 & 1) * COL + ((t4 & 2) ? 192 * (wp >> 1) + 128 + 4 * (wp & 1) + 8 * q8 : 768 + 2 * ((q8 + 1) & 6)));
            fl = pin(((t4 & 1) ? par1 : pub0) | (t4 >= 2 || (wp == 7 && q8 < 4 && q8 != 2 - t4) ? 2 : 0));
        };
        auto stats = [&](uint32_t xa, const uint4& b, uint32_t b4) {
            float a0[4] = {}, a1[4] = {}, a2[4] = {};
            const uint4 p0 = lds128(xa), p1 = lds128(xa + 16);
            const uint2 p2 = lds64(xa + 32);
            mmaV(a0, p0, b.x, b.y); mmaV(a1, p1, b.z, b.w); mma8(a2, p2.x, p2.y, b4);
            return ((a0[0] + a0[3]) + (a1[0] + a1[3])) + (a2[0] + a2[3]);
        };
        auto give_ln = [&](uint32_t src0, uint32_t par, uint32_t dst, uint32_t ln, float& mean, float& den, auto also) {
            const char* src = xp(src0 + 768 + (ln & 1) * HALF);
            uint2 st[4];
            int guard = 0;
            bool again;
            do {
#pragma unroll
                for (int s = 0; s < 4; s++) st[s] = ldp64(src + s * 1024);
                again = __any_sync(~0u, ((chk4(st, par) | also()) & 1) != 0);
            } while (again & (++guard < SPIN_LIMIT));
            float sx = (asf(st[0].x) + asf(st[1].x)) + (asf(st[2].x) + asf(st[3].x)), sq = (asf(st[0].y) + asf(st[1].y)) + (asf(st[2].y) + asf(st[3].y));
            sx += __shfl_xor_sync(~0u, sx, 1); sq += __shfl_xor_sync(~0u, sq, 1);
            ln_stats(sx, sq, mean, den);
            stsvol64(dst, __byte_perm(__float_as_uint(den), __float_as_uint(mean), 0x7632), (__float_as_uint(rcp(den)) & ~7u) | (ch + 1));
        };
        auto take_ln = [&](uint2& c, uint32_t a) { int k = 0; while (__any_sync(~0u, (c.y & 7) != ch + 1) && ++k < SPIN_LIMIT) c = ldsvol64(a); };
        {
            auto gate_up = [&](auto with_stats) {
                bar_main();
                TST(3);
                CSTAMP(11);
                const uint4 b = lds128(xr);
                uint32_t b4 = lds32(xr + 16);
                float acc[3][4] = {};
                if (with_stats.value) {
                    stp32_if(fl > 1 && !(td & 2), xp(pubC2), stats(xr + (S_XA - S_XB), b, b4), fl & 1);
                    __syncwarp();
                    b4 = lds32(xr + 16);
                }
                mul80(acc, Wgu, b, b4);
                stp64_if(!(td & 2), xp(pubC), tagw(acc[0][0] + acc[0][3], fl & 1), tagw(acc[1][0] + acc[1][3], fl & 1));
                stp32_if(td & 2, xp(pubC2), acc[2][0] + acc[2][3], fl & 1);
            };
            if (wp == 7) {
                bar_main();
                IDS();
                prepC(ln);
                sts32(sb + S_ZERO + 4, or3(pubC, pubC2, fl));
                gate_up(std::true_type());
            } else {
                if (actc) {
                    bar_main();
                    CSTAMP(8);
                    uint32_t r[8];
#pragma unroll
                    for (int s = 0; s < 8; s++) r[s] = lds32(rr + 640 * s);
                    stp32_if(true, xp(pubB), sum8(r), parc);
                    CSTAMP(9);
                    IDS();
                    prepC(ln);
                    const uint32_t n4 = 4 * n80;
                    const uint32_t xas = pin(sb + S_XA + 192 + 192 * cc + a_pos(n80)), xbs = pin(sb + S_XB + 384 * cc + b_pos<40>(n80));
                    const float x0 = cc ? ldsf(sb + S_XCAR + n4) : bf_lo(lds16(sb + S_X0 + 160 * (ch & 3) + n4 / 2));
                    gather16(xp(uPolB + n4 + lag<DELAY_G>(sb, z0_)), parc, 5 * ch + 1, [&](float y, uint32_t) {
                        const uint32_t x = pack2(x0 + bfr(y), 0.f);
                        sts16(xbs, x);
                        sts16(xas, x);
                        return 0u;
                    });
                    CSTAMP(10);
                } else {
                    bar_main();
                    IDS();
                    prepC(ln);
                }
                gate_up(std::false_type());
            }
        }
        CSTAMP(12);
        float mean = 0.f, den = 1.f;
        {
            IDS();
            const uint32_t wh = pin((((ln & 7) + 48 * ((ln >> 3) & 1) + 8 * (ln >> 4)) * 160 + (wp < 7 ? 16 * wp : 128)) | ((384 * cc + b_pos<48>(n96)) << 16));
            const uint32_t pubD = pin(uPubD + (t4 & 1) * COL + 16 * (t4 & 2) + 4 * q8 + (fl & 1)), ha = xr + (S_HS - S_XB);
            auto down = [&](const uint32_t (&W)[3][4], const uint4& h0, const uint2& h1) {
                float a0[4] = {}, a1[4] = {}, a2[4] = {};
                mmaA(a0, W[0], h0.x, h0.y); mmaA(a1, W[1], h0.z, h0.w); mmaA(a2, W[2], h1.x, h1.y);
                return ((a0[0] + a0[3]) + (a1[0] + a1[3])) + (a2[0] + a2[3]);
            };
            if (wp < 6) {
                uint32_t Wd[3][4];
                auto ldd = [&](uint32_t z) {
#pragma unroll
                    for (int s = 0; s < 3; s++) ldsm4t(Wd[s], ((wh ^ z) & 0xffff) + (sb + S_WD + s * 2560));
                };
                ldd(0);
                if (actc) {
                    const char* srcv = xp(uPolC + lag<DELAY_C>(sb, z0_) + 8 * n96);
                    const uint2 cs = lds64(sb + S_CSGU + 8 * n96);
                    float pg, pu;
                    uint2 c;
                    int guard = 0;
                    bool again;
                    do {
                        uint2 v[8];
#pragma unroll
                        for (int s = 0; s < 8; s++) v[s] = ldp64(srcv + (s >> 2) * HALF + (s & 3) * 1024);
                        c = ldsvol64(sb + S_LN + 8 * cc + ((v[0].x ^ parc) & 1) * 32);
                        again = __any_sync(~0u, ((chk8(v, parc) | chk8y(v, parc)) & 1) != 0);
                        pg = sum8x(v); pu = sum8y(v);
                        keep(pg); keep(pu);
                    } while (again & (++guard < SPIN_LIMIT));
                    CSTAMP(13);
                    SWEEPS(5 * ch + 2, guard - 1);
                    take_ln(c, sb + S_LN + 8 * cc);
                    mean = bf_hi(c.x); den = bf_lo(c.x);
                    const float gt = bfr(fmaf(-mean, asf(cs.x), pg) * asf(c.y)), up = fmaf(-mean, asf(cs.y), pu) * asf(c.y);
                    const uint32_t h = pack2(bfr(gt * sigmoidf_(gt)) * bfr(up), 0.f);
                    sts16((wh >> 16) + (sb + S_HS), h);
                    CSTAMP(14);
                    if (ch == 3) CSTAMP(0);
                }
                bar_main();
                TST(4);
                CSTAMP(15);
                const uint4 h0 = lds128(ha);
                const uint2 h1 = lds64(ha + 16);
                stp32_if(!(td & 2), xp(pubD & ~1u), down(Wd, h0, h1), pubD & 1);
            } else {
                uint32_t v = 0;
                const uint32_t col = wp == 7 || !has0;
                const bool serve = wp == 6 || (has0 && has1);
                if (serve) {
                    const uint32_t par = col ? par1 : par0;
                    const char* src = xp(uPolC + col * COL + 776 + (td & 4) * (HALF / 4) + (td & 3) * 1024);
                    give_ln(uPolC + col * COL, par, sb + S_LN + 8 * col, td, mean, den, [&] { v = ldp32(src); return v ^ par; });
                }
                stsvol(sb + S_GATE, ch + 1);
                uint32_t Wd[2][3][4];
#pragma unroll
                for (int s = 0; s < 6; s++) ldsm4t(Wd[s / 3][s % 3], (wh & 0xffff) + (sb + S_WD + (s / 3) * 16 + (s % 3) * 2560));
                bar_main();
                const uint4 h0 = lds128(ha);
                const uint2 h1 = lds64(ha + 16);
                const float d0 = down(Wd[0], h0, h1), d1 = down(Wd[1], h0, h1);
                stp32_if(true, xp(pubD & ~1u), (td & 2) ? d1 : d0, pubD & 1);
                if (serve) {
                    float xw = asf(v);
                    xw += __shfl_xor_sync(~0u, xw, 1); xw += __shfl_xor_sync(~0u, xw, 2); xw += __shfl_xor_sync(~0u, xw, 4);
                    const float r = bfr(fmaf(-mean, ldsf(sb + S_SWR), xw) * rcp(den));
                    sts32(sb + S_STAT + 4 * col, __float_as_uint(bfr(sigmoidf_(r))) | (ch + 1));
                }
            }
        }
        CSTAMP(16);
        {
            IDS();
            const uint32_t pubE = pin(uPubE + (t4 < 3 ? (wp >> 2) * COL + 192 * (wp & 3) + 64 * t4 + 8 * q8 : (q8 >> 2) * COL + 768 + 4 * (q8 & 1)));
            xr = pin(sb + S_XB + 48 * (ln & 7));
            uint32_t x2 = 0;
            auto hop_d = [&](auto col) {
                const uint32_t xbs = pin(sb + S_XB + 384 * col.value + b_pos<40>(n80)), xas = col.value ? 0 : pin(sb + S_XA + 192 + a_pos(n80));
                const float x1 = bf_lo(lds16(xbs));
                const float lnx = __uint_as_float(pin(__float_as_uint(bfr(__fdiv_rn(bfr(x1 - mean), den)))));
                gather16(xp(uPolD + 4 * n80 + lag<DELAY_D>(sb, z0_)), col.value ? par1 : par0, 5 * ch + 3, [&](float y, uint32_t z) {
                    const uint32_t gate = ldsvol(sb + S_STAT + 4 * col.value + z);
                    x2 = pack2(x1 + bfr(lnx + bfr(bfr(y) * bf_hi(gate))), 0.f);
                    if (col.value) keep(x2); else { sts16(xbs, x2); sts16(xas, x2); }
                    return (uint32_t)((gate & 7) != ch + 1);
                });
                CSTAMP(17);
            };
            auto qproj = [&](auto with_stats) {
                bar_main();
                TST(5);
                CSTAMP(19);
                const uint32_t t4 = td & 3;
                const uint4 b = lds128(xr);
                uint32_t b4 = lds32(xr + 16);
                float acc[6][4] = {};
                if (with_stats.value) {
                    stp32_if((td & 11) == 3, xp(pubE), stats(xr + (S_XA - S_XB), b, b4), par0);
                    __syncwarp();
                    b4 = lds32(xr + 16);
                }
                mul80(acc, Wq, b, b4);
                const float v0 = sel4(t4, acc[0][0] + acc[0][3], acc[2][0] + acc[2][3], acc[4][0] + acc[4][3], acc[4][0] + acc[4][3]);
                const float v1 = sel4(t4, acc[1][0] + acc[1][3], acc[3][0] + acc[3][3], acc[5][0] + acc[5][3], acc[5][0] + acc[5][3]);
                stp64_if(t4 < 3, xp(pubE), tagw(v0, par0), tagw(v1, par0));
            };
            if (wp == 7) {
                if (!has0) break;
                qproj(std::true_type());
            } else {
                if (actc && !cc) hop_d(std::integral_constant<int, 0>());
                else {
                    if (actc && g == 0) {
                        const uint32_t po = pin(1280 * (ch - 1) + 160 * i + 2 * n80);
                        hop_d(std::integral_constant<int, 1>());
                        *reinterpret_cast<unsigned short*>(reinterpret_cast<char*>(P.out) + po) = (unsigned short)x2;
                    }
                    if (!has0) break;
                }
                qproj(std::false_type());
                sts32_if(td < 80, sb + S_XCAR + 4 * td, x2 << 16);
            }
        }
        CSTAMP(20);
        auto pass2 = [&](auto d0, auto d1, auto d2) {
            constexpr int D0 = d0.value, D1 = d1.value, D = D0 + D1 + d2.value;
            IDS();
            const uint32_t ua = sb + k_place(ch, wp & 6) * SLOT + (wp & 1) * UNIT, k0 = k_off(ln);
            uint32_t kf[12][2][4];
            auto ldk = [&](int s) { const uint32_t a = (k0 ^ (32 * (s / 3))) + (ua + 1024 * (s % 3)); ldsm4(kf[s][0], a); ldsm4(kf[s][1], a + SLOT); };
            auto ldv1 = [&](int k) { ldsm4t(vf[k / 3][k % 3], voff[k % 3] + (sb + v_place(ch, k / 3) * SLOT)); };
            auto ldv = [&](int s) { ldv1(3 * s); ldv1(3 * s + 1); ldv1(3 * s + 2); };
            constexpr uint32_t LATE = LAST_LATE;
            constexpr uint64_t EARLY_LIST = bit_list(~LATE), LATE_LIST = bit_list(LATE);
            auto early = [&](int k) {
                if (D1 == 0) ldk(k);
                else if (k < 3) { ldv1(9 + 2 * k); ldv1(10 + 2 * k); }
                else ldk((EARLY_LIST >> (4 * (k - 3))) & 15);
            };
            if (wp == 6) give_ln(uPolE, par0, sb + S_LN + 16, td, mean, den, [] { return 0u; });
            if (D1 > 0) vaddr(voff);
            if (!(mbar_try(sb + S_FK + 8 * (wp & 6), par1) & mbar_try(sb + S_FK + 8 * (wp | 1), par1))) { mbar_wait(sb + S_FK + 8 * (wp & 6), par1); mbar_wait(sb + S_FK + 8 * (wp | 1), par1); }
#pragma unroll
            for (int s = 0; s < D0; s++) early(s);
            if (wp < 6) {
                const uint32_t qsa = pin(sb + S_QS + 384 * ch + q_pos(td));
                const char* srcv = xp(uPolE + lag<(D1 > 0 ? DELAY_E3 : DELAY_E)>(sb, z0_) + 4 * td);
                const float cs = ldsf(sb + S_CSQ + 4 * td);
                uint32_t v[8];
                auto look = [&] {
#pragma unroll
                    for (int s = 0; s < 8; s++) v[s] = ldp32(srcv + (s >> 2) * HALF + (s & 3) * 1024);
                };
                if (D1 > 0) {
                    look();
                    __syncwarp();
#pragma unroll
                    for (int s = D0; s < D0 + D1; s++) early(s);
                }
                float qs;
                uint2 c;
                int guard = 0;
                while (true) {
                    if (D1 == 0) look();
                    c = ldsvol64(sb + S_LN + 16 + ((v[0] ^ par0) & 1) * 32);
                    const bool again = __any_sync(~0u, (chk8(v, par0) & 1) != 0);
                    qs = sum8(v);
                    keep(qs);
                    if (!(again & (++guard < SPIN_LIMIT))) break;
                    if (D1 > 0) look();
                }
                take_ln(c, sb + S_LN + 16);
                const uint32_t q = pack2(fmaf(-bf_hi(c.x), cs, qs) * asf(c.y), 0.f);
                sts16(qsa, q);
                SWEEPS(5 * ch + 4, guard - 1);
                CSTAMP(22);
            } else {
#pragma unroll
                for (int s = D0; s < D0 + D1; s++) early(s);
            }
#pragma unroll
            for (int s = D0 + D1; s < D; s++) early(s);
            bar_main();
            TST(6);
            CSTAMP(1);
            uint2 q = lds64(sb + S_QS + 384 * ch + 8 * ln);
            float acc[2][4] = {};
            constexpr int V0 = 13 - D, NV = D1 > 0 ? 2 : (2 * (D - 1)) / 3;
            static_assert(D1 == 0 || LAST0 == 0 || D - 3 + __builtin_popcount(LATE) == 12, "plan");
#pragma unroll
            for (int s = 0; s < 12; s++) {
                const bool m = q8 == (s & 7);
                const uint32_t b0 = m ? q.x : 0u, b1 = m ? q.y : 0u;
                if (s == 7) q = lds64(sb + S_QS + 384 * ch + 8 * ln + 256);
                mmaA(acc[0], kf[s][0], b0, b1);
                mmaA(acc[1], kf[s][1], b0, b1);
                if (D1 > 0) {
                    if (s >= 1 && s <= __builtin_popcount(LATE)) ldk((LATE_LIST >> (4 * (s - 1))) & 15);
                } else {
                    if (s >= 1 && s + D - 1 < 12) ldk(s + D - 1);
                    if (s >= 1 && s + D - 1 == 11) { __syncwarp(); arrive_if(ln == 0, sb + S_RELK); }
                    if (s == V0) vaddr(voff);
                    if (s >= V0 && 2 * (s - V0) < 3 * NV) ldv1(9 + 2 * (s - V0));
                    if (s >= V0 && 2 * (s - V0) + 1 < 3 * NV) ldv1(10 + 2 * (s - V0));
                }
            }
            CSTAMP(24);
            {
                const float v0 = acc[0][0] + acc[0][1], v1 = acc[0][2] + acc[0][3], v2 = acc[1][0] + acc[1][1], v3 = acc[1][2] + acc[1][3];
                const bool hi = t4 & 2, od = t4 & 1;
                const float u0 = (hi ? v2 : v0) + __shfl_xor_sync(~0u, hi ? v0 : v2, 2), u1 = (hi ? v3 : v1) + __shfl_xor_sync(~0u, hi ? v1 : v3, 2);
                const float s = (od ? u1 : u0) + __shfl_xor_sync(~0u, od ? u0 : u1, 1);
                CSTAMP(2);
                probs(scaled(s), sb + S_PS + PS_PASS, wp, ln);
                CSTAMP(3);
            }
            bar_main();
            TST(10);
            CSTAMP(4);
            if (D1 > 0) values(vf, acc_, std::integral_constant<uint32_t, ORDER_L>(), [&](int s) { if (s < 3) ldv(s + 5); }, sb + S_PS + PS_PASS, 1, par0);
            else values(vf, acc_, std::integral_constant<uint32_t, (NV > 1 ? ORDER_R : 0x76543210)>(),
                        [&](int s) { if (s >= (NV > 1 ? 2 : 1) && s + NV + (NV > 1 ? 1 : 2) < 8) ldv(s + NV + (NV > 1 ? 1 : 2)); }, sb + S_PS + PS_PASS, 1, par0);
            arrive_if(ln == 0, sb + S_RELV);
        };
        if (LAST0 > 0 && ch == 3) {
            pass2(std::integral_constant<int, LAST0>(), std::integral_constant<int, LAST1>(), std::integral_constant<int, LAST2>());
#pragma unroll
            for (int m = 0; m < 48; m++) Wq[m / 8].a[(m / 4) % 2][m % 4] = vf[3 + m / 12][(m / 4) % 3][m % 4];
#pragma unroll
            for (int m = 0; m < 12; m++) Wq[m / 2].c[m % 2] = vf[7][m / 4][m % 4];
#pragma unroll
            for (int m = 0; m < 36; m++) left[m] = m < 12 ? __float_as_uint(acc_[m / 4][m % 4]) : vf[m / 12][(m / 4) % 3][m % 4];
        } else {
            pass2(std::integral_constant<int, KPRE>(), std::integral_constant<int, 0>(), std::integral_constant<int, KPRE2>());
#pragma unroll
            for (int m = 0; m < 36; m++) left[m] = m < 12 ? __float_as_uint(acc_[m / 4][m % 4]) : vf[4 + m / 12][(m / 4) % 3][m % 4];
        }
        TST(11);
        CSTAMP(23);
    }
    sts32_if(td == 255, sb + S_GATE, 6);
    TSTAMP(3);
}

typedef CUresult (*EncodeFn)(CUtensorMap*, CUtensorMapDataType, cuuint32_t, void*, const cuuint64_t*, const cuuint64_t*, const cuuint32_t*,
                             const cuuint32_t*, CUtensorMapInterleave, CUtensorMapSwizzle, CUtensorMapL2promotion, CUtensorMapFloatOOBfill);

void make_map(EncodeFn enc, CUtensorMap* m, const void* base, uint64_t cols, uint64_t rows, uint32_t box_cols, uint32_t box_rows, bool swizzle) {
    cuuint64_t dims[2] = {cols, rows};
    cuuint64_t strides[1] = {cols * 2};
    cuuint32_t box[2] = {box_cols, box_rows};
    cuuint32_t es[2] = {1, 1};
    enc(m, CU_TENSOR_MAP_DATA_TYPE_BFLOAT16, 2, const_cast<void*>(base), dims, strides, box, es, CU_TENSOR_MAP_INTERLEAVE_NONE,
        swizzle ? CU_TENSOR_MAP_SWIZZLE_128B : CU_TENSOR_MAP_SWIZZLE_NONE, swizzle ? CU_TENSOR_MAP_L2_PROMOTION_NONE : WPROMO, CU_TENSOR_MAP_FLOAT_OOB_FILL_NONE);
}

}

extern "C" void kernel_launch(void* const* d_in, const int* in_sizes, int n_in, void* d_out, int out_size) {
    (void)in_sizes; (void)n_in; (void)out_size;
    static EncodeFn enc = nullptr;
    if (!enc) {
        void* f = nullptr;
        cudaDriverEntryPointQueryResult q;
        cudaGetDriverEntryPoint("cuTensorMapEncodeTiled", &f, cudaEnableDefault, &q);
        enc = (EncodeFn)f;
        cudaFuncSetAttribute(fused_kernel, cudaFuncAttributeMaxDynamicSharedMemorySize, SMEM_BYTES);
    }
    Params P;
    P.x = (const __nv_bfloat16*)d_in[0]; P.k = (const __nv_bfloat16*)d_in[1]; P.v = (const __nv_bfloat16*)d_in[2];
    P.wr = (const __nv_bfloat16*)d_in[6];
    P.out = (__nv_bfloat16*)d_out;
    Maps M;
    {
        cuuint64_t dims[4] = {64, 8, 3, (cuuint64_t)KV_BATCH_KEYS / 2}, strides[3] = {384, 128, 3072};
        cuuint32_t box[4] = {64, 8, 3, 2}, es[4] = {1, 1, 1, 1};
        enc(&M.k, CU_TENSOR_MAP_DATA_TYPE_BFLOAT16, 4, d_in[1], dims, strides, box, es, CU_TENSOR_MAP_INTERLEAVE_NONE, CU_TENSOR_MAP_SWIZZLE_128B,
            CU_TENSOR_MAP_L2_PROMOTION_NONE, CU_TENSOR_MAP_FLOAT_OOB_FILL_NONE);
    }
    make_map(enc, &M.v, P.v, 64, (uint64_t)12 * KV_BATCH_KEYS, 64, 96, true);
    make_map(enc, &M.vu, P.v, 64, (uint64_t)12 * KV_BATCH_KEYS, 64, 48, true);
    make_map(enc, &M.wq, d_in[3], 6144, 640, 192, 40, false);
    make_map(enc, &M.wo, d_in[4], 640, 6144, 80, 96, false);
    make_map(enc, &M.wg, d_in[7], 1536, 640, 96, 80, false);
    make_map(enc, &M.wu, d_in[8], 1536, 640, 96, 80, false);
    make_map(enc, &M.wd, d_in[9], 640, 1536, 80, 96, false);
    fused_kernel<<<NCTA, NTHR, SMEM_BYTES, cudaStreamPerThread>>>(P, M);
}
```

```cpp
#include <cuda_runtime.h>
#include <cuda.h>
#include <cuda_bf16.h>
#include <stdint.h>
#include <type_traits>

namespace {

constexpr int NCTA = 128;
constexpr int NTHR = 384;
constexpr int UNIT = 6144;
constexpr int SLOT = 12288;
#define TAU 4000
#define TAUW 3850
#define TAU0 3850
#define PF0 2
#define PFMAP 1
#define ZPOS 1
#define LOOK1 0
#define LOOK2 0
#define SLACK 4000
#define SLACK0 2000
#define TSH 0
#define HOP1_NS 200
#define RELR_AT 0
#define PSLEEP 0
#define KRE_EARLY 6
#define PFTOP 2
#define RFR_XS 2
#define TMIN 2400
#define T_LEAD 0
#define WIN_W 3
#define WIN_S 4
#define WIN_U 10
#define RFR_ON 1
#define KRE_N1 0
#define KRE_TAU1 2500
#define RFR_TAU 25600
#define VPF 4
#define KRE_GATE 0
#define KRE_GATE3 KRE_GATE
#define JFREE 16
#define TFREE 0
#define KRE_TAU 3000
#define KRE_TAU3 KRE_TAU
#define HDEPTH 3
#define LAST0 4
#define ORDER_L 0x76543210
#define ORDER_R 0x76543210
#define LOOK_FIRST 0
#define LAST_LATE 0xaa8
#define LAST1 4
#define LAST2 2
#define FSTEP 4
#define SPEC 1
#define PV1PIPE 0
#define HOPA0 6
#define HOPA1 6
#define WPROMO CU_TENSOR_MAP_L2_PROMOTION_NONE
#define KPRE 1
#define KPRE2 3
#define DELAY_G 2
#define DELAY_L 2
#define DELAY_E3 0
#define DELAY_C 3
#define DELAY_D 0
#define DELAY_E 1
#define REG_LO "40"
#define REG_HI "232"
#define SPIN_LOG 17
constexpr int SPIN_LIMIT = 1 << SPIN_LOG;

__host__ __device__ constexpr uint32_t pairL(uint32_t region, uint32_t c, uint32_t g) { return (g & 1) | ((g >> 1) << 2) | (c << 5) | (region << 6); }
__host__ __device__ constexpr uint32_t pairG(uint32_t d, uint32_t c, uint32_t i) { return (i & 1) | ((i >> 1) << 2) | (d << 4) | (c << 5) | (3u << 6); }
constexpr uint32_t RA = 0, RC = 1, RE = 2, HALF = 16384, COPY = 4096, PMASK = 0x59;
constexpr uint32_t XS = 0;
constexpr uint32_t XS2 = XS + 128 * 7680;
constexpr uint32_t XSEND = XS2 + 128 * 768;
__device__ uint4 g_s[XSEND / 16];
__device__ uint4 g_x[(4u << 20) / 16];
#define SWEEPS(k, n) do {} while (0)

constexpr uint32_t S_WD = 16 * SLOT;
constexpr uint32_t S_DUMMY = S_WD + 15360;
constexpr uint32_t S_BAR = S_DUMMY + 4096;
constexpr uint32_t S_FV = S_BAR, S_FK = S_FV + 64, S_RING = S_FK + 64, S_DBAR = S_RING + 48, S_WFULL = S_DBAR + 32, S_QRDY = S_WFULL + 88;
constexpr uint32_t S_RELK = S_QRDY + 8, S_RELV = S_RELK + 8, S_RELR = S_RELV + 8, S_RELW = S_RELR + 8, S_SCO = S_RELW + 24;
constexpr uint32_t S_OS1 = S_SCO + 8;
constexpr uint32_t S_ZERO = S_OS1 + 8;
constexpr uint32_t S_KF = S_ZERO + 8;
constexpr uint32_t S_TOK = S_KF + 8;
constexpr uint32_t S_SIDE = S_TOK + 80, S_GATE = S_SIDE + 4;
constexpr uint32_t S_STAT = S_GATE + 12, S_SWR = S_STAT + 16;
constexpr uint32_t S_LN = S_STAT + 32;
constexpr uint32_t S_XCAR = S_LN + 64;
constexpr uint32_t S_CSQ = S_XCAR + 320;
constexpr uint32_t S_CSGU = S_CSQ + 768;
constexpr uint32_t S_RED = S_CSGU + 768;
constexpr uint32_t S_L0 = S_RED;
constexpr uint32_t S_OS = S_RED + 5120;
constexpr uint32_t S_PS = S_OS + 1536;
constexpr uint32_t PS_MAX = 512, PS_PASS = 544;
constexpr uint32_t S_QS = S_PS + 2 * PS_PASS;
constexpr uint32_t S_XB = S_QS + 1536;
constexpr uint32_t S_XA = S_XB + 768;
constexpr uint32_t S_HS = S_XA + 768;
constexpr uint32_t S_X0 = S_HS + 768;
constexpr uint32_t S_SC = S_X0 + 640;
constexpr uint32_t S_TM = S_SC + 512;
constexpr int SMEM_BYTES = S_TM + 256;
static_assert(SMEM_BYTES <= 232448 && S_STAT % 16 == 0 && S_RED % 16 == 0 && S_XB % 16 == 0 && S_HS % 16 == 0 && S_PS % 16 == 0 && S_QS % 16 == 0, "smem");
static_assert(S_SCO == S_BAR + 44 * 8 && S_RELK == S_BAR + 38 * 8, "barriers");
constexpr uint32_t ST_WQ = 3 * SLOT, ST_WG = 8 * SLOT, ST_WO = 11 * SLOT;

__device__ __forceinline__ uint32_t smem_u32(const void* p) { return (uint32_t)__cvta_generic_to_shared(p); }
__device__ __forceinline__ void mbar_init(uint32_t bar, uint32_t cnt) { asm volatile("mbarrier.init.shared::cta.b64 [%0], %1;" :: "r"(bar), "r"(cnt) : "memory"); }
__device__ __forceinline__ void mbar_expect(uint32_t bar, uint32_t bytes) { asm volatile("mbarrier.arrive.expect_tx.shared::cta.b64 _, [%0], %1;" :: "r"(bar), "r"(bytes) : "memory"); }
__device__ __forceinline__ void mbar_arrive(uint32_t bar) { asm volatile("mbarrier.arrive.shared::cta.b64 _, [%0];" :: "r"(bar) : "memory"); }
__device__ __forceinline__ bool mbar_try(uint32_t bar, uint32_t parity) {
    uint32_t ok;
    asm volatile("{\n .reg .pred p;\n mbarrier.try_wait.parity.shared::cta.b64 p, [%1], %2;\n selp.u32 %0, 1, 0, p;\n}" : "=r"(ok) : "r"(bar), "r"(parity) : "memory");
    return ok != 0;
}
__device__ __forceinline__ bool mbar_test(uint32_t bar, uint32_t parity) {
    uint32_t ok;
    asm volatile("{\n .reg .pred p;\n mbarrier.test_wait.parity.shared::cta.b64 p, [%1], %2;\n selp.u32 %0, 1, 0, p;\n}" : "=r"(ok) : "r"(bar), "r"(parity) : "memory");
    return ok != 0;
}
__device__ __forceinline__ void mbar_wait(uint32_t bar, uint32_t parity) {
    int n = 0;
    while (!mbar_try(bar, parity) && ++n < SPIN_LIMIT) {}
}
__device__ __forceinline__ unsigned long long gtime() { unsigned long long t; asm volatile("mov.u64 %0, %globaltimer;" : "=l"(t)); return t; }
__device__ __forceinline__ uint32_t gtime32() { uint32_t t; asm volatile("mov.u32 %0, %globaltimer_lo;" : "=r"(t)); return t; }
__device__ __forceinline__ void bar_main() { asm volatile("bar.sync 1, 256;" ::: "memory"); }

__device__ __forceinline__ void mma16816(float (&c)[4], uint32_t a0, uint32_t a1, uint32_t a2, uint32_t a3, uint32_t b0, uint32_t b1) {
    asm("mma.sync.aligned.m16n8k16.row.col.f32.bf16.bf16.f32 {%0,%1,%2,%3}, {%4,%5,%6,%7}, {%8,%9}, {%0,%1,%2,%3};"
        : "+f"(c[0]), "+f"(c[1]), "+f"(c[2]), "+f"(c[3]) : "r"(a0), "r"(a1), "r"(a2), "r"(a3), "r"(b0), "r"(b1));
}
__device__ __forceinline__ void mmaA(float (&c)[4], const uint32_t (&a)[4], uint32_t b0, uint32_t b1) { mma16816(c, a[0], a[1], a[2], a[3], b0, b1); }
__device__ __forceinline__ void mmaAv(float (&c)[4], const uint32_t (&a)[4], uint32_t b0, uint32_t b1) {
    asm volatile("mma.sync.aligned.m16n8k16.row.col.f32.bf16.bf16.f32 {%0,%1,%2,%3}, {%4,%5,%6,%7}, {%8,%9}, {%0,%1,%2,%3};"
        : "+f"(c[0]), "+f"(c[1]), "+f"(c[2]), "+f"(c[3]) : "r"(a[0]), "r"(a[1]), "r"(a[2]), "r"(a[3]), "r"(b0), "r"(b1) : "memory");
}
__device__ __forceinline__ void mma8(float (&c)[4], uint32_t a0, uint32_t a1, uint32_t b0) {
    asm("mma.sync.aligned.m16n8k8.row.col.f32.bf16.bf16.f32 {%0,%1,%2,%3}, {%4,%5}, {%6}, {%0,%1,%2,%3};"
        : "+f"(c[0]), "+f"(c[1]), "+f"(c[2]), "+f"(c[3]) : "r"(a0), "r"(a1), "r"(b0));
}
struct W80 { uint32_t a[2][4], c[2]; };
template <int N> __device__ __forceinline__ void mul80(float (&acc)[N][4], const W80 (&W)[N], const uint4& b, uint32_t b4) {
#pragma unroll
    for (int m = 0; m < N; m++) mmaA(acc[m], W[m].a[0], b.x, b.y);
#pragma unroll
    for (int m = 0; m < N; m++) mmaA(acc[m], W[m].a[1], b.z, b.w);
#pragma unroll
    for (int m = 0; m < N; m++) mma8(acc[m], W[m].c[0], W[m].c[1], b4);
}
__device__ __forceinline__ void ldsm2t(uint32_t (&r)[2], uint32_t addr) {
    asm volatile("ldmatrix.sync.aligned.m8n8.x2.trans.shared.b16 {%0,%1}, [%2];" : "=r"(r[0]), "=r"(r[1]) : "r"(addr) : "memory");
}
__device__ __forceinline__ void mmaV(float (&c)[4], const uint4& a, uint32_t b0, uint32_t b1) { mma16816(c, a.x, a.y, a.z, a.w, b0, b1); }
__device__ __forceinline__ void ldsm4(uint32_t (&r)[4], uint32_t addr) {
    asm volatile("ldmatrix.sync.aligned.m8n8.x4.shared.b16 {%0,%1,%2,%3}, [%4];" : "=r"(r[0]), "=r"(r[1]), "=r"(r[2]), "=r"(r[3]) : "r"(addr) : "memory");
}
__device__ __forceinline__ void ldsm4t(uint32_t (&r)[4], uint32_t addr) {
    asm volatile("ldmatrix.sync.aligned.m8n8.x4.trans.shared.b16 {%0,%1,%2,%3}, [%4];" : "=r"(r[0]), "=r"(r[1]), "=r"(r[2]), "=r"(r[3]) : "r"(addr) : "memory");
}
__device__ __forceinline__ uint32_t lds16(uint32_t a) { uint16_t v; asm volatile("ld.shared.u16 %0, [%1];" : "=h"(v) : "r"(a) : "memory"); return v; }
__device__ __forceinline__ uint32_t lds32(uint32_t a) { uint32_t v; asm volatile("ld.shared.u32 %0, [%1];" : "=r"(v) : "r"(a) : "memory"); return v; }
__device__ __forceinline__ float ldsf(uint32_t a) { return __uint_as_float(lds32(a)); }
__device__ __forceinline__ uint2 lds64(uint32_t a) { uint2 v; asm volatile("ld.shared.v2.u32 {%0,%1}, [%2];" : "=r"(v.x), "=r"(v.y) : "r"(a) : "memory"); return v; }
__device__ __forceinline__ uint4 lds128(uint32_t a) { uint4 v; asm volatile("ld.shared.v4.u32 {%0,%1,%2,%3}, [%4];" : "=r"(v.x), "=r"(v.y), "=r"(v.z), "=r"(v.w) : "r"(a) : "memory"); return v; }
__device__ __forceinline__ int ldsvol(uint32_t a) { int v; asm volatile("ld.volatile.shared.u32 %0, [%1];" : "=r"(v) : "r"(a) : "memory"); return v; }
__device__ __forceinline__ uint2 ldsvol64(uint32_t a) { uint2 v; asm volatile("{\n .reg .b64 d;\n ld.volatile.shared.b64 d, [%2];\n mov.b64 {%0,%1}, d;\n}" : "=r"(v.x), "=r"(v.y) : "r"(a) : "memory"); return v; }
__device__ __forceinline__ void stsvol64(uint32_t a, uint32_t x, uint32_t y) { asm volatile("{\n .reg .b64 d;\n mov.b64 d, {%1,%2};\n st.volatile.shared.b64 [%0], d;\n}" :: "r"(a), "r"(x), "r"(y) : "memory"); }
__device__ __forceinline__ void stsvol(uint32_t a, int v) { asm volatile("st.volatile.shared.u32 [%0], %1;" :: "r"(a), "r"(v) : "memory"); }
__device__ __forceinline__ void sts_hi16(uint32_t a, float v) { asm volatile("{\n .reg .b16 lo, hi;\n mov.b32 {lo, hi}, %1;\n st.shared.u16 [%0], hi;\n}" :: "r"(a), "r"(__float_as_uint(v)) : "memory"); }
__device__ __forceinline__ void sts16(uint32_t a, uint32_t v) { asm volatile("st.shared.u16 [%0], %1;" :: "r"(a), "r"(v) : "memory"); }
__device__ __forceinline__ void sts32(uint32_t a, uint32_t v) { asm volatile("st.shared.u32 [%0], %1;" :: "r"(a), "r"(v) : "memory"); }
__device__ __forceinline__ void stsf(uint32_t a, float v) { sts32(a, __float_as_uint(v)); }
__device__ __forceinline__ void sts64(uint32_t a, uint32_t x, uint32_t y) { asm volatile("st.shared.v2.u32 [%0], {%1,%2};" :: "r"(a), "r"(x), "r"(y) : "memory"); }

__device__ __forceinline__ void sts_hi16_if(bool p, uint32_t a, float v) {
    asm volatile("{\n .reg .pred p;\n .reg .b16 lo, hi;\n setp.ne.u32 p, %2, 0;\n mov.b32 {lo, hi}, %1;\n @p st.shared.u16 [%0], hi;\n}" :: "r"(a), "r"(__float_as_uint(v)), "r"((uint32_t)p) : "memory");
}
__device__ __forceinline__ void sts32_if(bool p, uint32_t a, uint32_t v) {
    asm volatile("{\n .reg .pred p;\n setp.ne.u32 p, %2, 0;\n @p st.shared.u32 [%0], %1;\n}" :: "r"(a), "r"(v), "r"((uint32_t)p) : "memory");
}
__device__ __forceinline__ void sts64_if(bool p, uint32_t a, float x, float y) {
    asm volatile("{\n .reg .pred p;\n setp.ne.u32 p, %3, 0;\n @p st.shared.v2.f32 [%0], {%1,%2};\n}" :: "r"(a), "f"(x), "f"(y), "r"((uint32_t)p) : "memory");
}
__device__ __forceinline__ void arrive_if(bool p, uint32_t bar) {
    asm volatile("{\n .reg .pred p;\n setp.ne.u32 p, %1, 0;\n @p mbarrier.arrive.shared::cta.b64 _, [%0];\n}" :: "r"(bar), "r"((uint32_t)p) : "memory");
}
__device__ __forceinline__ void opaque(uint32_t& v) { asm volatile("" : "+r"(v)); }
__device__ __forceinline__ void keep(uint32_t& v) { asm volatile("" : "+r"(v)); }
__device__ __forceinline__ void keep(float& v) { asm volatile("" : "+f"(v)); }
template <class T> __device__ __forceinline__ void keep(T*& v) { asm volatile("" : "+l"(v)); }

__device__ __forceinline__ uint32_t ldp32(const char* p) { uint32_t v; asm volatile("ld.relaxed.gpu.global.u32 %0, [%1];" : "=r"(v) : "l"(p) : "memory"); return v; }
__device__ __forceinline__ uint2 ldp64(const char* p) {
    uint2 v; asm volatile("{\n .reg .b64 d;\n ld.relaxed.gpu.global.b64 d, [%2];\n mov.b64 {%0,%1}, d;\n}" : "=r"(v.x), "=r"(v.y) : "l"(p) : "memory"); return v;
}
__device__ __forceinline__ uint32_t tagw(float f, uint32_t par) { return (__float_as_uint(f) & ~1u) | par; }
__device__ __forceinline__ void stp32(char* p, float a, uint32_t par) { asm volatile("st.relaxed.gpu.global.u32 [%0], %1;" :: "l"(p), "r"(tagw(a, par)) : "memory"); }
__device__ __forceinline__ void stp64(char* p, float a, float b, uint32_t par) {
    asm volatile("{\n .reg .b64 d;\n mov.b64 d, {%1,%2};\n st.relaxed.gpu.global.b64 [%0], d;\n}" :: "l"(p), "r"(tagw(a, par)), "r"(tagw(b, par)) : "memory");
}
__device__ __forceinline__ void stp32_if(bool p, char* d, float a, uint32_t par) {
    asm volatile("{\n .reg .pred p;\n setp.ne.u32 p, %2, 0;\n @p st.relaxed.gpu.global.u32 [%0], %1;\n @p st.relaxed.gpu.global.u32 [%0+4096], %1;\n}" :: "l"(d), "r"(tagw(a, par)), "r"((uint32_t)p) : "memory");
}
__device__ __forceinline__ void stp64_if(bool p, char* d, uint32_t lo, uint32_t hi) {
    asm volatile("{\n .reg .pred p;\n .reg .b64 d;\n setp.ne.u32 p, %3, 0;\n mov.b64 d, {%1,%2};\n @p st.relaxed.gpu.global.b64 [%0], d;\n @p st.relaxed.gpu.global.b64 [%0+4096], d;\n}" :: "l"(d), "r"(lo), "r"(hi), "r"((uint32_t)p) : "memory");
}
__device__ __forceinline__ uint32_t chk2(uint32_t a, uint32_t b, uint32_t par) { uint32_t r; asm("lop3.b32 %0, %1, %2, %3, 0x7E;" : "=r"(r) : "r"(a), "r"(b), "r"(par)); return r; }
__device__ __forceinline__ uint32_t or3(uint32_t a, uint32_t b, uint32_t c) { uint32_t r; asm("lop3.b32 %0, %1, %2, %3, 0xFE;" : "=r"(r) : "r"(a), "r"(b), "r"(c)); return r; }
__device__ __forceinline__ uint32_t chk8(const uint32_t (&v)[8], uint32_t par) { return or3(chk2(v[0], v[1], par), chk2(v[2], v[3], par), or3(chk2(v[4], v[5], par), chk2(v[6], v[7], par), 0)); }
__device__ __forceinline__ uint32_t chk8(const uint2 (&v)[8], uint32_t par) { return or3(chk2(v[0].x, v[1].x, par), chk2(v[2].x, v[3].x, par), or3(chk2(v[4].x, v[5].x, par), chk2(v[6].x, v[7].x, par), 0)); }
__device__ __forceinline__ uint32_t chk8y(const uint2 (&v)[8], uint32_t par) { return or3(chk2(v[0].y, v[1].y, par), chk2(v[2].y, v[3].y, par), or3(chk2(v[4].y, v[5].y, par), chk2(v[6].y, v[7].y, par), 0)); }
__device__ __forceinline__ uint32_t chk4(const uint2 (&v)[4], uint32_t par) { return or3(chk2(v[0].x, v[0].y, par), chk2(v[1].x, v[1].y, par), or3(chk2(v[2].x, v[2].y, par), chk2(v[3].x, v[3].y, par), 0)); }
__device__ __forceinline__ float asf(uint32_t v) { return __uint_as_float(v); }
__device__ __forceinline__ float sum8(const uint32_t (&v)[8]) { return ((asf(v[0]) + asf(v[1])) + (asf(v[2]) + asf(v[3]))) + ((asf(v[4]) + asf(v[5])) + (asf(v[6]) + asf(v[7]))); }
__device__ __forceinline__ float sum8x(const uint2 (&v)[8]) { return ((asf(v[0].x) + asf(v[1].x)) + (asf(v[2].x) + asf(v[3].x))) + ((asf(v[4].x) + asf(v[5].x)) + (asf(v[6].x) + asf(v[7].x))); }
__device__ __forceinline__ float sum8y(const uint2 (&v)[8]) { return ((asf(v[0].y) + asf(v[1].y)) + (asf(v[2].y) + asf(v[3].y))) + ((asf(v[4].y) + asf(v[5].y)) + (asf(v[6].y) + asf(v[7].y))); }

__device__ __forceinline__ uint32_t pack2(float lo, float hi) { uint32_t r; asm("cvt.rn.bf16x2.f32 %0, %1, %2;" : "=r"(r) : "f"(hi), "f"(lo)); return r; }
__device__ __forceinline__ float bfr(float x) { return __uint_as_float(pack2(0.0f, x)); }
__device__ __forceinline__ float ex2(float x) { float r; asm("ex2.approx.ftz.f32 %0, %1;" : "=f"(r) : "f"(x)); return r; }
__device__ __forceinline__ float rcp(float x) { float r; asm("rcp.approx.ftz.f32 %0, %1;" : "=f"(r) : "f"(x)); return r; }
__device__ __forceinline__ float sqrt_(float x) { float r; asm("sqrt.approx.ftz.f32 %0, %1;" : "=f"(r) : "f"(x)); return r; }
__device__ __forceinline__ float bf_lo(uint32_t v) { return __uint_as_float(v << 16); }
__device__ __forceinline__ float bf_hi(uint32_t v) { return __uint_as_float(v & 0xffff0000u); }
__device__ __forceinline__ float sel4(int k, float a, float b, float c, float d) { return (k & 2) ? ((k & 1) ? d : c) : ((k & 1) ? b : a); }
constexpr float LOG2E = 1.4426950408889634f;
constexpr uint32_t ONES = 0x3f803f80u;

__device__ __forceinline__ void ln_stats(float sum, float sq, float& mean, float& den) {
    const float m = sum * (1.0f / 640.0f);
    const float var = fmaxf(fmaf(sq, 1.0f / 640.0f, -m * m), 0.0f);
    mean = bfr(m);
    den = bfr(sqrt_(bfr(bfr(var) + 1e-5f)));
}
__device__ __forceinline__ float sigmoidf_(float x) { return rcp(1.0f + ex2(-x * LOG2E)); }

#define TSTAMP(k) do {} while (0)
#define TST(k) do {} while (0)

#define CSTAMP(k) do {} while (0)
template <int N> __device__ __forceinline__ uint32_t lag(uint32_t sb, uint32_t z = 0) {
#pragma unroll
    for (int k = 0; k < N; k++) z = ldsvol(sb + S_ZERO + z);
    return z;
}
__device__ __forceinline__ void warm_mma(uint32_t& a, uint32_t& b) {
    asm volatile("mma.sync.aligned.m16n8k8.row.col.f16.f16.f16.f16 {%0,%1}, {%0,%1}, {%0}, {%0,%1};" : "+r"(a), "+r"(b) :: "memory");
}
#define KWNS2 20
#define KWNS 200
template <int STRIDE>
__device__ __forceinline__ float gather8(const char* p, uint32_t par) {
    uint32_t v[8];
    int guard = 0;
    do {
#pragma unroll
        for (int s = 0; s < 8; s++) v[s] = ldp32(p + s * STRIDE);
    } while ((chk8(v, par) & 1) && ++guard < SPIN_LIMIT);
    return sum8(v);
}
template <class F>
__device__ __forceinline__ void gather16(const char* p, uint32_t par, int k, F use) {
    uint32_t v[8], u[8];
    int guard = 0;
    bool again;
    do {
#pragma unroll
        for (int s = 0; s < 8; s++) v[s] = ldp32(p + s * 512);
#pragma unroll
        for (int s = 0; s < 8; s++) u[s] = ldp32(p + HALF + s * 512);
        const uint32_t stale = use(sum8(v) + sum8(u), ((v[0] ^ par) & 1) * 8);
        again = __any_sync(~0u, (or3(chk8(v, par), chk8(u, par), stale) & 1) != 0);
    } while (again & (++guard < SPIN_LIMIT));
    SWEEPS(k, guard - 1);
}

struct Params {
    const __nv_bfloat16 *x, *k, *v, *wr;
    __nv_bfloat16* out;
};
struct Maps { CUtensorMap k, v, vu, wq, wo, wg, wu, wd; };

constexpr int KV_BATCH_KEYS = 32 * 4096;

__device__ __forceinline__ void tma2d(uint32_t dst, const CUtensorMap* m, int c0, int c1, uint32_t bar, uint32_t bytes, uint64_t pol) {
    asm volatile("{\n .reg .pred p;\n elect.sync _|p, 0xffffffff;\n"
                 " @p mbarrier.arrive.expect_tx.shared::cta.b64 _, [%2], %6;\n"
                 " @p cp.async.bulk.tensor.2d.shared::cluster.global.mbarrier::complete_tx::bytes.L2::cache_hint [%0], [%1, {%3, %4}], [%2], %5;\n}"
                 :: "r"(dst), "l"(m), "r"(bar), "r"(c0), "r"(c1), "l"(pol), "r"(bytes) : "memory");
}
__device__ __forceinline__ void scrap_copy(uint32_t dst, const char* src, uint32_t bar) {
    asm volatile("{\n .reg .pred p;\n elect.sync _|p, 0xffffffff;\n"
                 " @p mbarrier.arrive.expect_tx.shared::cta.b64 _, [%2], 12288;\n"
                 " @p cp.async.bulk.shared::cluster.global.mbarrier::complete_tx::bytes [%0], [%1], 4096, [%2];\n"
                 " @p cp.async.bulk.shared::cluster.global.mbarrier::complete_tx::bytes [%0], [%1+4096], 4096, [%2];\n"
                 " @p cp.async.bulk.shared::cluster.global.mbarrier::complete_tx::bytes [%0], [%1+8192], 4096, [%2];\n}"
                 :: "r"(dst), "l"(src), "r"(bar) : "memory");
}
__device__ __forceinline__ void prefetch_l2(const void* p, uint32_t bytes) {
    asm volatile("{\n .reg .pred p;\n elect.sync _|p, 0xffffffff;\n @p cp.async.bulk.prefetch.L2.global [%0], %1;\n}" :: "l"(p), "r"(bytes) : "memory");
}
__device__ __forceinline__ uint64_t pol_first() { uint64_t p; asm("createpolicy.fractional.L2::evict_first.b64 %0, 1.0;" : "=l"(p)); return p; }
__device__ __forceinline__ uint64_t pol_normal() { uint64_t p; asm("createpolicy.fractional.L2::evict_normal.b64 %0, 1.0;" : "=l"(p)); return p; }
__device__ __forceinline__ bool utest(uint32_t bar, uint32_t parity) { return __all_sync(~0u, mbar_test(bar, parity)); }
__device__ __forceinline__ void uwait(uint32_t bar, uint32_t parity) {
    int n = 0;
    while (!__all_sync(~0u, mbar_try(bar, parity)) && ++n < SPIN_LIMIT) {}
}
template <int A, int B, int CNT> __device__ __forceinline__ void init_bars(uint32_t sb) {
#pragma unroll 1
    for (int k = A; k < B; k++)
        asm volatile("{\n .reg .pred p;\n elect.sync _|p, 0xffffffff;\n @p mbarrier.init.shared::cta.b64 [%0], %1;\n}" :: "r"(sb + S_BAR + 8 * k), "n"(CNT) : "memory");
}
__device__ __forceinline__ int first_key() { return (blockIdx.x >> 2) * 4096 + 3072 + (blockIdx.x & 3) * 256; }
__device__ __forceinline__ void load_tile(const CUtensorMap* m, uint32_t dst, uint32_t bar, uint32_t bytes, int key, uint64_t pol) { tma2d(dst, m, 0, 3 * key, bar, bytes, pol); }
__device__ __forceinline__ const char* unit_ptr(const Params& P, int n) {
    return (const char*)((n & 16) ? P.v : P.k) + (size_t)(first_key() + (n >> 5) * KV_BATCH_KEYS + (n & 15) * 16) * 384;
}
#define LSTAMP(k) do {} while (0)

__device__ __forceinline__ uint32_t k_place(uint32_t b, uint32_t s) { return s + 3 + 5 * (b & 1); }
__device__ __forceinline__ uint32_t v_place(uint32_t b, uint32_t s) { return s < 3 ? s : s + 8 - 8 * (b & 1); }
__device__ __forceinline__ void k_load(const Maps& M, uint32_t dst, uint32_t bar, int key8, uint64_t pol) {
    asm volatile("{\n .reg .pred p;\n elect.sync _|p, 0xffffffff;\n"
                 " @p mbarrier.arrive.expect_tx.shared::cta.b64 _, [%2], 6144;\n"
                 " @p cp.async.bulk.tensor.4d.shared::cluster.global.mbarrier::complete_tx::bytes.L2::cache_hint [%0], [%1, {0, 0, 0, %3}], [%2], %4;\n}"
                 :: "r"(dst), "l"(&M.k), "r"(bar), "r"(key8), "l"(pol) : "memory");
}
__device__ __forceinline__ int unit_key8(uint32_t n) { return first_key() / 8 + (n >> 4) * (KV_BATCH_KEYS / 8) + 2 * (n & 15); }
__device__ __forceinline__ void ring_load(const Maps& M, uint32_t sb, uint32_t b, uint32_t u, uint32_t pos) {
    if (u < 16) k_load(M, sb + pos * UNIT, sb + S_RING + 8 * pos, unit_key8(16 * b + u), pol_normal());
    else load_tile(&M.vu, sb + pos * UNIT, sb + S_FV + 4 * (pos & 6), UNIT, first_key() + b * KV_BATCH_KEYS + 16 * pos, pol_first());
}
__device__ __forceinline__ uint32_t token(bool p, uint32_t a, uint32_t n) {
    uint32_t v;
    asm volatile("{\n .reg .pred p;\n setp.ne.u32 p, %2, 0;\n mov.u32 %0, 0;\n @p atom.shared.exch.b32 %0, [%1], %3;\n}" : "=r"(v) : "r"(a), "r"((uint32_t)p), "r"(n) : "memory");
    return v;
}
__device__ __forceinline__ void place_load(const Maps& M, uint32_t sb, uint32_t n) {
    k_load(M, sb + k_place(n >> 4, 0) * SLOT + (n & 15) * UNIT, sb + S_FK + 4 * (n & 14), unit_key8(n), pol_first());
}
__device__ __forceinline__ void v_load(const Maps& M, uint32_t sb, uint32_t b, uint32_t s) {
    load_tile(&M.v, sb + v_place(b, s) * SLOT, sb + S_FV + 8 * s, SLOT, first_key() + b * KV_BATCH_KEYS + 32 * s, pol_first());
}
__device__ __forceinline__ bool due(uint32_t t) { return __all_sync(~0u, (int)(gtime32() * 16 - t) >= 0); }
__device__ __forceinline__ bool reached(uint32_t a, int v) { return __all_sync(~0u, ldsvol(a) >= v); }

__device__ __forceinline__ void stream_warp(const Params& P, const Maps& M, uint32_t sb, uint32_t lane) {
    const uint64_t pol = pol_first();
    const int bid = blockIdx.x, g = bid >> 3, i = bid & 7;
    const uint32_t wf = sb + S_WFULL;
    if (PF0 > 0 && !PFTOP) prefetch_l2(unit_ptr(P, 0), PF0 * UNIT);
    uint32_t tn = __shfl_sync(~0u, gtime32(), 0) * 16 - T_LEAD;
    auto pace = [&](uint32_t dt) {
        int k = 0;
        uint32_t now;
        do now = __shfl_sync(~0u, gtime32(), 0) * 16; while ((int)(now - tn) < 0 && ++k < SPIN_LIMIT);
        if ((int)(now - tn) > SLACK0) tn = now - SLACK0;
        tn += dt;
    };
#pragma unroll
    for (int k = 0; k < 10; k++) {
        if (k < 2) {
            if (k == 0) init_bars<26, 27, 1>(sb); else init_bars<27, 37, 1>(sb);
            asm volatile("fence.mbarrier_init.release.cluster;" ::: "memory");
            if (k == 1) { asm volatile("bar.arrive 2, %0;" :: "n"(NTHR) : "memory"); asm volatile("bar.sync 3, 128;" ::: "memory"); }
        }
        if (k >= WIN_W) uwait(wf + 8 * (k - WIN_W), 0);
        pace(TAUW * 5 / 2);
        if (k < 4) tma2d(sb + ST_WQ + 15360 * k, &M.wq, 384 * g + 192 * (k >> 1), 80 * i + 40 * (k & 1), wf + 8 * k, 15360, pol);
        else if (k < 6) tma2d(sb + ST_WG + 15360 * (k - 4), k == 4 ? &M.wg : &M.wu, 96 * g, 80 * i, wf + 8 * k, 15360, pol);
        else tma2d(sb + ST_WO + 15360 * (k - 6), &M.wo, 80 * i, 384 * g + 96 * (k - 6), wf + 8 * k, 15360, pol);
    }
#pragma unroll 1
    for (int n = 0; n < 16; n++) {
        if (n == 0 || n == 5 || n == 11) uwait(sb + S_RELW + (n == 0 ? 0 : n == 5 ? 8 : 16), 0);
        uwait(n < WIN_S ? wf + 8 * (10 - WIN_S + n) : sb + S_FV + 8 * ((n - WIN_S) ^ 8), 0);
        pace(max(min(2 * n + 2 - PF0, 2), 0) * TAU0);
        if (n < 8) { place_load(M, sb, 2 * n); place_load(M, sb, 2 * n + 1); }
        else if (n < 11) { ring_load(M, sb, 0, 2 * n, 2 * n - 16); ring_load(M, sb, 0, 2 * n + 1, 2 * n - 15); }
        else v_load(M, sb, 0, n - 8);
        if (n == 7) { pace(TAUW * 5 / 2); tma2d(sb + S_WD, &M.wd, 80 * i, 96 * g, wf + 80, 15360, pol); }
    }
    int nd = 0;
    uint32_t q[4];
#pragma unroll
    for (int r = 0; r < 4; r++) q[r] = sb + S_FV + 8 * (7 - r);
    tn -= TSH;
    uint32_t td = tn;
    uint32_t pos = 2;
#pragma unroll 1
    for (int m = 16; m < 64; m++) {
        const int b = m >> 4, j = m & 15;
        const char* src = unit_ptr(P, 2 * m);
        const uint32_t tok = sb + S_TOK + (j < 3 ? 4 * pos : j < 11 ? 24 + 4 * pos : 16 + 4 * j) + 4 * lane;
        static_assert(WIN_U <= 12, "a ring position has at most one token of the timetable");
        int k = 0;
        while (true) {
            const uint2 c = lds64(sb + S_KF);
            if (__all_sync(~0u, mbar_test(q[WIN_S - 1] & ~1u, q[WIN_S - 1] & 1) & (min((int)c.x + 1, (int)c.y) >= 16 * b + min(2 * j + 2 - WIN_U, 16))) || ++k >= SPIN_LIMIT) break;
        }
        uint32_t now;
        while (true) {
            now = __shfl_sync(~0u, gtime32(), 0) * 16;
            if ((int)(now - td) >= 0 || ++k >= SPIN_LIMIT) break;
            if (PSLEEP > 0 && (int)(td - now) > 16 * PSLEEP * 2) __nanosleep(PSLEEP);
        }
        const uint32_t mine = __ballot_sync(~0u, token(lane < (j < 11 ? 2 : 1), tok, 2 * m + lane) == 2 * m + lane);
        q[3] = q[2]; q[2] = q[1]; q[1] = q[0]; q[0] = sb + S_QRDY;
        if (j < 11) {
            if (mine & 1) ring_load(M, sb, b, 2 * j, pos); else prefetch_l2(src, UNIT);
            if (mine & 2) ring_load(M, sb, b, 2 * j + 1, pos + 1); else prefetch_l2(src + UNIT, UNIT);
            if (j >= 8) q[0] = (sb + S_FV + 8 * (j - 8)) | (b & 1);
        } else if (mine) { v_load(M, sb, b, j - 8); q[0] = (sb + S_FV + 8 * (j - 8)) | (b & 1); }
        else if (j - 8 >= VPF) prefetch_l2(src, SLOT);
        else {
            scrap_copy(sb + S_DUMMY, src, sb + S_DBAR + 8 * (nd & 3));
            q[0] = (sb + S_DBAR + 8 * (nd & 3)) | ((nd >> 2) & 1);
            nd++;
        }
        pos = j == 15 ? 2 : pos == 4 ? 0 : pos + 2;
        if ((int)(now - tn) > SLACK) tn = now - SLACK;
        tn += 2 * TAU;
        td = (int)(tn - now) > 2 * TMIN ? tn : now + 2 * TMIN;
        if (m >= 48 + JFREE) td = now + TFREE;
    }
#pragma unroll 1
    for (int m = max(nd - 4, 0); m < nd; m++) uwait(sb + S_DBAR + 8 * (m & 3), (m >> 2) & 1);
}

__host__ __device__ constexpr uint64_t bit_list(uint32_t m) { uint64_t r = 0; int n = 0; for (int k = 0; k < 12; k++) if ((m >> k) & 1) r |= (uint64_t)k << (4 * n++); return r; }
__device__ __forceinline__ float scaled(float s) { return bfr(bfr(s) * 0.07216878364870322f); }
__device__ __forceinline__ void probs(float s, uint32_t ps, uint32_t src, uint32_t ln) {
    const uint32_t q8 = ln >> 2, t4 = ln & 3;
    int key = __float_as_int(s);
    key ^= (key >> 31) & 0x7fffffff;
    key = __reduce_max_sync(~0u, key);
    key ^= (key >> 31) & 0x7fffffff;
    const float ml = __int_as_float(key) * LOG2E;
    sts16(ps + 64 * src + (q8 >> 1) * 16 + t4 * 4 + (q8 & 1) * 2, pack2(ex2(fmaf(s, LOG2E, -ml)), 0.f));
    stsf(ps + PS_MAX + 4 * src, ml);
}
template <int H> __device__ __forceinline__ uint32_t b_pos(uint32_t e) { const uint32_t h = e >= H, k = e - H * h; return h * 192 + (k & 6) * 24 + (k >> 3) * 4 + (k & 1) * 2; }
__device__ __forceinline__ uint32_t a_pos(uint32_t e) { const uint32_t h = e >= 40, k = e - 40 * h; return (k & 6) * 24 + (k >> 3) * 8 + h * 4 + (k & 1) * 2; }
__device__ __forceinline__ uint32_t q_pos(uint32_t d) { const uint32_t s = 3 * ((d >> 4) & 3) + (d >> 6); return s * 32 + (d & 6) * 4 + ((d >> 3) & 1) * 4 + (d & 1) * 2; }
__device__ __forceinline__ uint32_t k_off(uint32_t ln) { return (ln & 8) * 384 + (ln & 7) * 128 + (((ln & 7) ^ (ln >> 4)) << 4); }

#define HSTAMP(k) do {} while (0)
__device__ __forceinline__ char* xwindow() { return reinterpret_cast<char*>((reinterpret_cast<uintptr_t>(g_x) + (2u << 20) - 1) & ~(uintptr_t)((2u << 20) - 1)); }

struct XPtr {
    uint32_t lo, hi;
    __device__ __forceinline__ explicit XPtr(char* p) : lo((uint32_t)(uintptr_t)p), hi((uint32_t)((uintptr_t)p >> 32)) {}
    __device__ __forceinline__ XPtr(uint32_t l, uint32_t h) : lo(l), hi(h) {}
    __device__ __forceinline__ XPtr operator+(uint32_t o) const { return XPtr(lo + o, hi); }
    __device__ __forceinline__ operator char*() const { uint64_t p; asm("mov.b64 %0, {%1, %2};" : "=l"(p) : "r"(lo), "r"(hi)); return (char*)p; }
};
__device__ __forceinline__ void keep(XPtr& v) { keep(v.lo); }

__device__ __forceinline__ void side_warp(uint32_t sb) {
    const uint32_t bid = blockIdx.x, g = bid >> 3, i = bid & 7, P = pairG(0, 0, i);
    char* p = xwindow() + P * 8192 + (g >> 3) * HALF + (g & 7) * 512 + 448;
    uint32_t best[2] = {~0u, ~0u};
    asm volatile("st.relaxed.gpu.global.b32 [%0], 1;" :: "l"(p) : "memory");
    asm volatile("st.relaxed.gpu.global.b32 [%0], 1;" :: "l"(p + COPY) : "memory");
#pragma unroll 1
    for (int r = 0; r < 64; r++) {
        if (r >= 4 && !(r & 1) && min(best[0], best[1]) < 380 && max(best[0], best[1]) > min(best[0], best[1]) + 80) break;
        uint32_t c0, c1, v;
        asm volatile("mov.u32 %0, %clock;" : "=r"(c0) :: "memory");
        asm volatile("atom.relaxed.gpu.global.exch.b32 %0, [%1], 0;" : "=r"(v) : "l"(p + (r & 1) * COPY) : "memory");
        asm volatile("{\n .reg .pred q;\n setp.eq.u32 q, %1, 0x13579bdf;\n mov.u32 %0, 0;\n @!q mov.u32 %0, %clock;\n}" : "=r"(c1) : "r"(v) : "memory");
        if (r & 1) best[1] = min(best[1], c1 - c0); else best[0] = min(best[0], c1 - c0);
    }
    stsvol(sb + S_SIDE, 1 + ((best[1] < best[0]) ^ (__popc(P & PMASK) & 1)));
}

template <int N>
__device__ __forceinline__ void hop_a(const char* src, uint32_t par, uint32_t dst, bool st, int k) {
    uint2 v[N][4];
    float e[4], rl;
    int guard = 0;
    bool again;
    do {
#pragma unroll
        for (int s = 0; s < 4 * N; s++) v[s / 4][s % 4] = ldp64(src + (s / 4) * 256 + (s % 4) * 1024);
        again = __any_sync(~0u, ((chk4(v[0], par) | chk4(v[N - 1], par)) & 1) != 0);
        const int M = max(max((int)v[0][0].x, (int)v[0][1].x), max((int)v[0][2].x, (int)v[0][3].x)) - 254;
#pragma unroll
        for (int s = 0; s < 4; s++) e[s] = __int_as_float(max((int)v[0][s].x - M, 0) << 22);
        rl = rcp(fmaf(e[0], asf(v[0][0].y), e[1] * asf(v[0][1].y)) + fmaf(e[2], asf(v[0][2].y), e[3] * asf(v[0][3].y)));
#pragma unroll
        for (int s = 0; s < 4; s++) e[s] = __shfl_sync(~0u, e[s], 24);
        keep(rl);
    } while (again & (++guard < SPIN_LIMIT));
    rl = __shfl_sync(~0u, rl, 24);
#pragma unroll
    for (int n = 0; n < N; n++) {
        const float o0 = fmaf(e[0], asf(v[n][0].x), e[1] * asf(v[n][1].x)) + fmaf(e[2], asf(v[n][2].x), e[3] * asf(v[n][3].x));
        const float o1 = fmaf(e[0], asf(v[n][0].y), e[1] * asf(v[n][1].y)) + fmaf(e[2], asf(v[n][2].y), e[3] * asf(v[n][3].y));
        sts32_if(st, dst + 192 * n, pack2(o0 * rl, o1 * rl));
    }
    SWEEPS(k, guard - 1);
    __syncwarp();
}

__device__ __forceinline__ void score_warp(const Maps& M, uint32_t sb, uint32_t h, uint32_t ln) {
    const uint32_t lane0 = ln;
    uwait(sb + S_QRDY, 0);
    const uint32_t q8 = ln >> 2;
    const uint32_t k0 = k_off(ln);
    uint32_t pos = h + 6, bar = sb + S_FK, par = 0, phases = 0;
    uint2 q = lds64(sb + S_QS + 8 * ln), qh = lds64(sb + S_QS + 8 * ln + 256);
    auto first_round = [&](uint32_t b, uint32_t ln) {
        uwait(sb + S_RELR, b & 1);
        const uint32_t u = h + 2 * ln, p = u < 4 ? u + 2 : u - 4;
        uint32_t todo = __ballot_sync(~0u, token(ln < 3, sb + S_TOK + 4 * p, 32 * b + 32 + u) == 32 * b + 32 + u);
#pragma unroll 1
        for (uint32_t r = h; todo; todo >>= 1, r += 2) if (todo & 1) ring_load(M, sb, b + 1, r, r < 4 ? r + 2 : r - 4);
    };
#pragma unroll 1
    for (uint32_t n = h; n < 64; n += 2) {
        HSTAMP(0);
        const uint32_t ua = sb + pos * UNIT;
        if (!__all_sync(~0u, mbar_try(bar, par))) uwait(bar, par);
        HSTAMP(1);
        float acc[2][4] = {};
        uint32_t mine = 0;
        const uint32_t id = n + (n & 48) + 6;
#pragma unroll
        for (int s = 0; s < 12; s++) {
            uint32_t kf[4];
            ldsm4(kf, (k0 ^ (32 * (s / 3))) + (ua + 1024 * (s % 3)));
            if (s == 11) {
                __syncwarp();
                mine = token(ln == 0 && n >= 16, sb + S_TOK + 24 + 4 * pos, id);
                stsvol(sb + S_KF + 4 * h, n + 1);
            }
            const bool m = q8 == (s & 7);
            mmaA(acc[s & 1], kf, m ? (s < 8 ? q.x : qh.x) : 0u, m ? (s < 8 ? q.y : qh.y) : 0u);
        }
        const uint32_t pos0 = pos;
        const bool last = (n & 14) == 14;
        pos = last ? h + 2 : n >= 16 && pos >= 4 ? h : pos + 2;
        bar = n >= 14 ? sb + S_RING + 8 * pos : bar + 8;
        par = n >= 14 ? (phases >> pos) & 1 : 0;
        phases ^= n >= 14 ? 1u << pos : 0;
        const float w0 = (acc[0][0] + acc[0][1]) + (acc[1][0] + acc[1][1]), w1 = (acc[0][2] + acc[0][3]) + (acc[1][2] + acc[1][3]);
        HSTAMP(2);
        if (__any_sync(~0u, mine == id)) ring_load(M, sb, n >> 4, (n & 15) + 6, pos0);
        HSTAMP(3);
        float s = ((ln & 1) ? w1 : w0) + __shfl_xor_sync(~0u, (ln & 1) ? w0 : w1, 1);
        s += __shfl_xor_sync(~0u, s, 2);
        sts_hi16(sb + S_SC + (((n & 12) >> 1) + h) * 64 + (n & 2) * 2 + (ln & 29) * 2, scaled(s));
        if (last) {
            __syncwarp();
            arrive_if(ln == 0, sb + S_SCO);
            const uint32_t b = n >> 4, ln = lane0 + lag<1>(sb);
            if (b > 0) {
                uwait(sb + S_RELK, (b - 1) & 1);
                if (h == 0) LSTAMP(64 + 2 * b);
                const uint32_t sl = 3 + h + 2 * ln, idv = 32 * b + 16 + 2 * sl;
                uint32_t todo = __ballot_sync(~0u, token(sl < 8, sb + S_TOK + 48 + 4 * sl, idv) == idv);
#pragma unroll 1
                for (uint32_t r = 3 + h; todo; todo >>= 1, r += 2) if (todo & 1) v_load(M, sb, b, r);
                const uint32_t g = blockIdx.x >> 3, pr = pairL(RA, 1, g), side = ldsvol(sb + S_SIDE);
                const char* src = xwindow() + pr * 8192 + ((side ^ 1 ^ __popc(pr & PMASK)) & 1) * COPY + h * HALF + 8 * min(ln, 24u);
                uwait(sb + S_RELV, (b - 1) & 1);
                __nanosleep(HOP1_NS);
#pragma unroll 1
                for (uint32_t r = 0; r < 4; r += 2) {
                    hop_a<2>(src + 256 * r, b & 1, sb + S_OS + 192 * (4 * h + r) + 96 + 4 * ln, ln < 24, 25);
                    if (r == RELR_AT && b < 3) first_round(b, ln);
                }
                arrive_if(ln == 0, sb + S_OS1);
            } else first_round(0, ln);
            q = lds64(sb + S_QS + 24 * ((n + 2) & 48) + 8 * ln); qh = lds64(sb + S_QS + 24 * ((n + 2) & 48) + 8 * ln + 256);
        }
    }
}

__global__ void __launch_bounds__(NTHR, 1)
fused_kernel(const Params P, const __grid_constant__ Maps M) {
    extern __shared__ __align__(1024) unsigned char smem[];
    const uint32_t sb = smem_u32(smem);
    const int tid = threadIdx.x, bid = blockIdx.x;
    if (PFTOP && tid == 0) {
        if (PFTOP == 2) asm volatile("prefetch.tensormap [%0];" :: "l"(&M.wq) : "memory");
        asm volatile("cp.async.bulk.prefetch.L2.global [%0], %1;" :: "l"(unit_ptr(P, 0)), "r"(PF0 * UNIT) : "memory");
    }
    const int w = __shfl_sync(~0u, tid >> 5, 0), lane = tid & 31;

    if (w >= 8) {
        asm volatile("setmaxnreg.dec.sync.aligned.u32 " REG_LO ";");
        if (w == 8) {
            stream_warp(P, M, sb, lane);
        } else {
            if (PFMAP && w == 11 && lane < 8) asm volatile("prefetch.tensormap [%0];" :: "l"(&M.k + lane) : "memory");
            if (w == 9) { init_bars<0, 3, 2>(sb); init_bars<3, 8, 1>(sb); init_bars<16, 22, 1>(sb); }
            else if (w == 10) { init_bars<8, 16, 2>(sb); init_bars<22, 26, 1>(sb); }
            else { init_bars<37, 38, 1>(sb); init_bars<38, 40, 8>(sb); init_bars<40, 41, 1>(sb); init_bars<41, 44, 8>(sb); init_bars<44, 46, 2>(sb); stsvol(sb + S_ZERO + 4 * lane, 0); if (lane < 16) stsvol(sb + S_LN + 4 * lane, 0); }
            asm volatile("fence.mbarrier_init.release.cluster;" ::: "memory");
            asm volatile("bar.arrive 3, 128;" ::: "memory");
            asm volatile("bar.sync 2, %0;" :: "n"(NTHR) : "memory");
            if (w < 11) score_warp(M, sb, w - 9, lane);
            else {
                if (lane == 0) side_warp(sb);
                __syncwarp();
                uint32_t a = 0, b = 0;
                int k = 0;
                while (ldsvol(sb + S_GATE) == 0 && ++k < SPIN_LIMIT) { warm_mma(a, b); __nanosleep(KWNS); }
                uint4* d = reinterpret_cast<uint4*>(reinterpret_cast<char*>(g_s) + XS + bid * 7680) + lane;
                const uint4 z = make_uint4(0, 0, 0, 0);
#pragma unroll 1
                for (int u = 0; u < 15; u++) d[32 * u] = z;
                d = reinterpret_cast<uint4*>(reinterpret_cast<char*>(g_s) + XS2 + bid * 768) + lane;
                d[0] = z;
                if (lane < 16) d[32] = z;
                const uint32_t side = (ldsvol(sb + S_SIDE) & 1) ^ 1, g = bid >> 3, i = bid & 7;
                const XPtr gx(xwindow());
                auto nearp = [&](uint32_t pr) { return gx.lo + pr * 8192 + ((side ^ __popc(pr & PMASK)) & 1) * COPY; };
                const uint32_t own = (i >> 2) * HALF + (i & 3) * 1024 + (lane & 7) * 128;
                const uint32_t pAC = nearp(pairL(lane >> 4, (lane >> 3) & 1, g)) + own, pE = nearp(pairL(RE, (lane >> 3) & 1, g)) + own;
                const uint32_t pG = nearp(pairG((lane >> 2) & 1, (lane >> 3) & 1, i)) + min(lane & 3, 2) * 128;
                uint32_t tr = 0, tk = 0, ph = 0, src = g + (lane >> 4), seen = 0, n = 16, cs = 0;
                bool go = false, first = true;
                while (n < 64 && ++k < SPIN_LIMIT) {
                    const uint32_t now = __shfl_sync(~0u, gtime32(), 0) * 16;
                    if (!go && utest((n & 15) < KRE_EARLY ? sb + S_RELK : sb + S_RELV, ((n >> 4) & 1) ^ 1)) { go = true; if ((int)(now - tk) > 0 || !(n & 15)) tk = now; }
                    if (go && (int)(now - tk) >= 0) {
                        place_load(M, sb, (n & 16) ? n : (n & 48) | ((n + 10) & 15));
                        tk += n >= 48 ? KRE_TAU3 : (n & 15) < KRE_N1 ? KRE_TAU1 : KRE_TAU;
                        n++;
                        go = (n & 15) != 0 && (n & 15) != KRE_EARLY;
                        if (!(n & 15)) LSTAMP(63 + (n >> 3));
                    } else if (first || (int)(now - tr) >= 0) {
                        first = false;
                        tr = now + RFR_TAU;
                        b |= seen & a;
                        warm_mma(a, b);
                        if (RFR_ON) seen = ldp32(XPtr(ph == 0 ? pAC : ph == 1 && lane < 16 ? pE : pG + (src & 8) * (HALF / 8) + (src & 7) * 512, gx.hi));
                        if (RFR_XS && (++cs & (RFR_XS - 1)) < 2) {
                            const uint32_t l = lane + 32 * (cs & 1);
                            *reinterpret_cast<volatile uint32_t*>(reinterpret_cast<char*>(g_s) + (l < 60 ? XS + bid * 7680 + 128 * l : XS2 + bid * 768 + 128 * (l - 60))) = 0;
                        }
                        src += ph == 0 ? 0 : ph == 1 ? 2 : 1;
                        ph = ph == 2 ? 0 : ph + 1;
                    } else __nanosleep(KWNS2);
                }
                while (ldsvol(sb + S_GATE) < 6 && ++k < SPIN_LIMIT) { warm_mma(a, b); __nanosleep(KWNS); }
                if (a | b) stsvol(sb + S_GATE, 6);
            }
        }
        return;
    }
    asm volatile("setmaxnreg.inc.sync.aligned.u32 " REG_HI ";");

    const int g = bid >> 3, i = bid & 7;
    const int g8 = lane >> 2, t = lane & 3;
    char* const gs = reinterpret_cast<char*>(g_s);
    const XPtr gx(xwindow());

    auto zero_words = [&] {
        const uint4 z = make_uint4(0, 0, 0, 0);
        const uint32_t c = (tid >> 6) & 1, cp = (tid >> 7) * COPY, k = (tid & 63) * 16;
        *reinterpret_cast<uint4*>((char*)(gx + pairL(RA, c, g) * 8192 + (i >> 2) * HALF + (i & 3) * 1024 + cp + k)) = z;
        *reinterpret_cast<uint4*>((char*)(gx + pairL(RC, c, g) * 8192 + (i >> 2) * HALF + (i & 3) * 1024 + cp + k)) = z;
        *reinterpret_cast<uint4*>((char*)(gx + pairL(RE, c, g) * 8192 + (i >> 2) * HALF + (i & 3) * 1024 + cp + k)) = z;
        if ((tid & 31) < 24) *reinterpret_cast<uint4*>((char*)(gx + pairG((tid >> 5) & 1, c, i) * 8192 + (g >> 3) * HALF + (g & 7) * 512 + cp + (tid & 31) * 16)) = z;
    };
    if (ZPOS == 0) zero_words();
    W80 Wq[6], Wgu[3];
    uint32_t Wo[5][3][4];
    if (w < 4) {
        const uint32_t* xp = reinterpret_cast<const uint32_t*>(P.x + 640 * w);
        float sum = 0.f, sq = 0.f;
#pragma unroll
        for (int u = 0; u < 10; u++) { uint32_t v = xp[lane + 32 * u]; float a = bf_lo(v), b = bf_hi(v); sum += a + b; sq += a * a + b * b; }
#pragma unroll
        for (int o = 16; o > 0; o >>= 1) { sum += __shfl_xor_sync(~0u, sum, o); sq += __shfl_xor_sync(~0u, sq, o); }
        float mean, den; ln_stats(sum, sq, mean, den);
        if (lane < 20) {
            const uint2 v = reinterpret_cast<const uint2*>(P.x + 640 * w + 80 * i)[lane];
            sts64(sb + S_X0 + 160 * w + 8 * lane, v.x, v.y);
            sts32(sb + S_L0 + 384 * w + b_pos<40>(4 * lane), pack2(__fdiv_rn(bfr(bf_lo(v.x) - mean), den), __fdiv_rn(bfr(bf_hi(v.x) - mean), den)));
            sts32(sb + S_L0 + 384 * w + b_pos<40>(4 * lane + 2), pack2(__fdiv_rn(bfr(bf_lo(v.y) - mean), den), __fdiv_rn(bfr(bf_hi(v.y) - mean), den)));
        }
    } else if (w == 4) {
        const uint32_t* xp = reinterpret_cast<const uint32_t*>(P.wr);
        float sum = 0.f;
#pragma unroll
        for (int u = 0; u < 10; u++) { uint32_t v = xp[lane + 32 * u]; sum += bf_lo(v) + bf_hi(v); }
#pragma unroll
        for (int o = 16; o > 0; o >>= 1) sum += __shfl_xor_sync(~0u, sum, o);
        if (lane == 0) stsf(sb + S_SWR, sum);
        if (lane < 20) {
            const uint2 v = reinterpret_cast<const uint2*>(P.wr + 80 * i)[lane];
            sts32(sb + S_XA + 576 + a_pos(4 * lane), v.x); sts32(sb + S_XA + 576 + a_pos(4 * lane + 2), v.y);
            sts32(sb + S_XA + a_pos(4 * lane), ONES); sts32(sb + S_XA + a_pos(4 * lane + 2), ONES);
        }
    }
    asm volatile("bar.sync 2, %0;" :: "n"(NTHR) : "memory");
    auto frag = [](uint32_t (&a)[4], uint32_t p, int pitch) {
        const uint32_t r0 = lds32(p), r1 = lds32(p + pitch), r2 = lds32(p + 2 * pitch), r3 = lds32(p + 3 * pitch);
        a[0] = __byte_perm(r0, r1, 0x5410); a[1] = __byte_perm(r0, r1, 0x7632);
        a[2] = __byte_perm(r2, r3, 0x5410); a[3] = __byte_perm(r2, r3, 0x7632);
    };
    mbar_wait(sb + S_WFULL + 16 * (w >> 2), 0);
    mbar_wait(sb + S_WFULL + 16 * (w >> 2) + 8, 0);
    {
        const uint32_t p = sb + ST_WQ + (w >> 2) * 30720 + (2 * t) * 384 + (48 * (w & 3) + 2 * g8) * 2;
#pragma unroll
        for (int r = 0; r < 10; r++)
#pragma unroll
            for (int m = 0; m < 3; m++) {
                const uint32_t q = p + ((r & 1) * 40 + (r >> 1) * 8) * 384 + 32 * m, r0 = lds32(q), r1 = lds32(q + 384);
                (r < 8 ? Wq[2 * m].a[(r >> 2) & 1][r & 3] : Wq[2 * m].c[r & 1]) = __byte_perm(r0, r1, 0x5410);
                (r < 8 ? Wq[2 * m + 1].a[(r >> 2) & 1][r & 3] : Wq[2 * m + 1].c[r & 1]) = __byte_perm(r0, r1, 0x7632);
            }
    }
    __syncwarp();
    if (lane == 0) mbar_arrive(sb + S_RELW);
    TSTAMP(1);
    {
        char* d = gs + XS + bid * 7680 + (w >> 2) * 3840 + (48 * (w & 3) + 2 * g8) * 4;
        float acc[6][4] = {};
        mul80(acc, Wq, lds128(sb + S_L0 + 48 * lane), lds32(sb + S_L0 + 48 * lane + 16));
#pragma unroll
        for (int m = 0; m < 6; m += 2) stp64(d + t * 768 + 32 * m, acc[m][0] + acc[m][3], acc[m + 1][0] + acc[m + 1][3], 1);
        float sum[6][4] = {};
        mul80(sum, Wq, make_uint4(ONES, ONES, ONES, ONES), ONES);
        if (t == 0)
#pragma unroll
            for (int m = 0; m < 6; m += 2) stp64(d + 4 * 768 + 32 * m, sum[m][0] + sum[m][3], sum[m + 1][0] + sum[m + 1][3], 1);
    }
    mbar_wait(sb + S_WFULL + 32, 0);
    mbar_wait(sb + S_WFULL + 40, 0);
    const uint32_t oct = 3 * (w >> 1) + (w & 1), oct2 = 3 * (w >> 1) + 2;
    {
        const uint32_t p = sb + ST_WG + ((lane & 7) + 40 * ((lane >> 3) & 1) + 8 * (lane >> 4)) * 192;
#pragma unroll
        for (int T = 0; T < 3; T++) {
            const uint32_t q = p + (T < 2 ? T * 15360 + 16 * oct : (w & 1) * 15360 + 16 * oct2);
            ldsm4t(Wgu[T].a[0], q); ldsm4t(Wgu[T].a[1], q + 16 * 192); ldsm2t(Wgu[T].c, q + 32 * 192);
        }
        float sum[3][4] = {};
        mul80(sum, Wgu, make_uint4(ONES, ONES, ONES, ONES), ONES);
        if (t < 3) stp32(gs + XS2 + bid * 768 + (t < 2 ? 64 * oct + 4 * t : 64 * oct2 + 4 * (w & 1)) + 8 * g8,
                         sel4(t, sum[0][0] + sum[0][3], sum[1][0] + sum[1][3], sum[2][0] + sum[2][3], 0.f), 1);
    }
    __syncwarp();
    if (lane == 0) mbar_arrive(sb + S_RELW + 8);
    const char* srcS = gs + XS + g * 8 * 7680 + (i >> 2) * 3840 + min(tid, 191) * 4;
    uint32_t vs[5][8];
#pragma unroll
    for (int b = 0; b < 5; b++)
#pragma unroll
        for (int s = 0; s < 8; s++) vs[b][s] = LOOK1 ? ldp32(srcS + b * 768 + s * 7680) : 0;
    uint32_t cs2[8];
#pragma unroll
    for (int s = 0; s < 8; s++) cs2[s] = LOOK2 ? ldp32(gs + XS2 + (g * 8 + s) * 768 + min(tid, 191) * 4) : 0;
    __syncwarp();
    mbar_wait(sb + S_WFULL + 48 + 8 * (w >> 1), 0);
    {
        const uint32_t po = sb + ST_WO + (48 * w + 12 * t) * 160 + 4 * g8;
#pragma unroll
        for (int s = 0; s < 3; s++)
#pragma unroll
            for (int m = 0; m < 5; m++) frag(Wo[m][s], po + 4 * s * 160 + 32 * m, 160);
    }
    __syncwarp();
    if (lane == 0) mbar_arrive(sb + S_RELW + 16);
    if (ZPOS == 1) zero_words();
    if (tid < 192) {
        int guard = 0;
        while (((or3(chk8(vs[0], 1), chk8(vs[1], 1), chk8(vs[2], 1)) | chk8(vs[3], 1) | chk8(vs[4], 1)) & 1) && ++guard < SPIN_LIMIT) {
#pragma unroll
            for (int b = 0; b < 5; b++)
#pragma unroll
                for (int s = 0; s < 8; s++) vs[b][s] = ldp32(srcS + b * 768 + s * 7680);
        }
        const uint32_t qpos = sb + S_QS + q_pos(tid);
#pragma unroll
        for (int b = 0; b < 4; b++) {
            sts_hi16(qpos + 384 * b, bfr(sum8(vs[b])));
        }
        stsf(sb + S_CSQ + 4 * tid, sum8(vs[4]));
    }
    if (tid < 192) stsf(sb + S_CSGU + 4 * tid, (chk8(cs2, 1) & 1) ? gather8<768>(gs + XS2 + g * 8 * 768 + tid * 4, 1) : sum8(cs2));
    __syncwarp();
    bar_main();
    arrive_if(tid == 0, sb + S_QRDY);
    if (ZPOS == 2) zero_words();
    TSTAMP(2);

    uint32_t side;
    { int k = 0; while ((side = ldsvol(sb + S_SIDE)) == 0 && ++k < SPIN_LIMIT) {} }
    const uint32_t td = __shfl_sync(~0u, tid, lane);
    const uint32_t wp = __shfl_sync(~0u, tid >> 5, 0);
    const uint32_t cc = wp >= 3;
    auto uni = [](uint32_t v) { return __shfl_sync(~0u, v, 0); };
    auto pin = [&](uint32_t v) { return __shfl_sync(~0u, v, td); };
    auto nearp = [&](uint32_t P) { return gx.lo + P * 8192 + ((side ^ 1 ^ __popc(P & PMASK)) & 1) * COPY; };
    constexpr uint32_t COL = 32 * 8192;
    const uint32_t ownL = gx.lo + (i >> 2) * HALF + (i & 3) * 1024, ownG = gx.lo + (g >> 3) * HALF + (g & 7) * 512;
    const uint32_t uPubA = uni(ownL + pairL(RA, 0, g) * 8192 + (wp >> 1) * 256 + (wp & 1) * 96), uPolA = uni(nearp(pairL(RA, 0, g)) + (wp >> 2) * HALF + (wp & 3) * 256);
    const uint32_t uPubB = uni(ownG + pairG(0, cc, i) * 8192), uPolB = uni(nearp(pairG(0, cc, i)));
    const uint32_t uPubC = uni(ownL + pairL(RC, 0, g) * 8192), uPolC = uni(nearp(pairL(RC, wp < 6 ? cc : 0, g)));
    const uint32_t uPubD = uni(ownG + pairG(1, 0, i) * 8192 + (wp < 7 ? 32 * wp : 256)), uPolD = uni(nearp(pairG(1, cc, i)));
    const uint32_t uPubE = uni(ownL + pairL(RE, 0, g) * 8192), uPolE = uni(nearp(pairL(RE, i >> 2, g)));
    const uint32_t uOS = uni(sb + S_OS + 192 * wp);
    auto xp = [&](uint32_t lo) { return (char*)XPtr(lo, gx.hi); };
#define IDS() __syncwarp(); const uint32_t z0_ = lag<1>(sb), z_ = td + z0_; const uint32_t ln = z_ & 31, q8 = ln >> 2, t4 = z_ & 3, n96 = z_ - 96 * cc, n80 = min(n96, 79u); (void)q8; (void)t4; (void)n80; (void)ln

    auto vaddr = [&](uint32_t (&voff)[3]) {
        const uint32_t ln = td & 31;
        const uint32_t key3 = 3 * ((ln & 7) + 2 * (ln & 8) + ((ln >> 1) & 8));
#pragma unroll
        for (int T = 0; T < 3; T++) {
            const uint32_t u = 3 * wp + T, r = key3 + (u >> 3);
            voff[T] = r * 128 + (((u ^ r) & 7) << 4);
        }
    };
    auto values = [&](uint32_t (&vf)[8][3][4], float (&acc)[3][4], auto order, auto step, uint32_t ps, uint32_t col, uint32_t par) {
        const uint32_t ln = td & 31, q8 = ln >> 2, t4 = td & 3;
        const uint4 p = lds128(ps + 16 * ln);
        float f0 = 0.f, f1 = 0.f, r3 = 0.f;
#pragma unroll
        for (int k = 0; k < 12; k++) acc[k / 4][k % 4] = 0.f;
        int M = 0;
#pragma unroll
        for (int k = 0; k < 8; k++) {
            step(k);
            const int s = (order.value >> (4 * k)) & 7;
            const bool m = (q8 >> 1) == (s >> 1);
            const uint32_t b0 = m ? ((s & 1) ? p.z : p.x) : 0u, b1 = m ? ((s & 1) ? p.w : p.y) : 0u;
#pragma unroll
            for (int T = 0; T < 3; T++) mmaA(acc[T], vf[s][T], b0, b1);
            if (k == FSTEP) {
                const uint2 mp = lds64(ps + PS_MAX + 8 * t4);
                M = __reduce_max_sync(~0u, __float2int_ru(fmaxf(asf(mp.x), asf(mp.y))));
                f0 = ex2(asf(mp.x) - (float)M); f1 = ex2(asf(mp.y) - (float)M);
                float l[4] = {};
                mma16816(l, ONES, ONES, ONES, ONES, p.x, p.y); mma16816(l, ONES, ONES, ONES, ONES, p.z, p.w);
                r3 = fmaf(f0, l[0], f1 * l[1]);
            }
        }
        CSTAMP(25);
        char* pubA = xp(uPubA + col * COL + 32 * t4 + 4 * q8);
        const float r0 = fmaf(f0, acc[0][0], f1 * acc[0][3]), r1 = fmaf(f0, acc[1][0], f1 * acc[1][3]), r2 = fmaf(f0, acc[2][0], f1 * acc[2][3]);
        const bool hi = t4 & 2, od = t4 & 1;
        const float u0 = (hi ? r2 : r0) + __shfl_xor_sync(~0u, hi ? r0 : r2, 2), u1 = (hi ? r3 : r1) + __shfl_xor_sync(~0u, hi ? r1 : r3, 2);
        const float o = (od ? u1 : u0) + __shfl_xor_sync(~0u, od ? u0 : u1, 1);
        stp32_if(t4 < 3 || ((wp & 1) && q8 < 2), pubA, ln == 3 ? __int_as_float(2 * M) : o, par);
    };

    uint32_t left[36] = {};
#pragma unroll 1
    for (int ch = 0; ch < 5; ch++) {
        const uint32_t par0 = (ch + 1) & 1, par1 = ch & 1;
        uint32_t voff[3], vf[8][3][4];
        float acc_[3][4];
        if (ch < 4) {
            vaddr(voff);
            mbar_wait(sb + S_SCO, par1);
            if (ch == 0) mbar_wait(sb + S_WFULL + 80, 0);
            TST(0);
            auto ldw = [&](int s) {
                mbar_wait(sb + S_FV + 8 * s, par1);
#pragma unroll
                for (int T = 0; T < 3; T++) ldsm4t(vf[s][T], voff[T] + (sb + v_place(ch, s) * SLOT));
            };
            probs(bf_lo(lds16(sb + S_SC + 2 * td)), sb + S_PS, wp, td & 31);
            ldw(0); ldw(1); ldw(2);
            bar_main();
            arrive_if(td == 0, sb + S_RELR);
            values(vf, acc_, std::integral_constant<uint32_t, 0x76543210>(), [&](int s) {
                if (s >= 3) ldw(s);
            }, sb + S_PS, 0, par0);
            TST(1);
            CSTAMP(5);
            if (ch > 0) mbar_wait(sb + S_OS1, par0);
        } else {
#pragma unroll
            for (int s = 0; s < 36; s++) vf[s / 12][(s / 4) % 3][s & 3] = left[s];
        }
        const bool has0 = ch < 4, has1 = ch > 0;
        const bool actc = wp < 6 && (cc ? has1 : has0);
        const uint32_t parc = cc ? par1 : par0;
        const uint32_t pub0 = has0 ? par0 : 0;
        uint32_t rr, pubB;
        {
            IDS();
            const uint32_t c = ch == 4;
            const uint32_t osa = pin(uOS + 96 * c + 4 * ln), oa = pin(uOS + 48 * (q8 & 2) + 24 * t4), ra = pin(sb + S_RED + 640 * wp + 320 * (t4 & 1) + 8 * q8);
            rr = pin(sb + S_RED + 320 * cc + 4 * n80); pubB = pin(uPubB + 4 * n80);
            hop_a<1>(xp(uPolA + c * COL + 8 * min(ln, 24u) + lag<DELAY_L>(sb, z0_)), pub0, osa, ln < 24, 5 * ch);
            TST(2);
            CSTAMP(6);
            float acc[5][4] = {};
            const uint2 b0 = lds64(oa), b1 = lds64(oa + 8), b2 = lds64(oa + 16);
#pragma unroll
            for (int m = 0; m < 5; m++) mmaA(acc[m], Wo[m][0], b0.x, b0.y);
#pragma unroll
            for (int m = 0; m < 5; m++) mmaA(acc[m], Wo[m][1], b1.x, b1.y);
#pragma unroll
            for (int m = 0; m < 5; m++) mmaA(acc[m], Wo[m][2], b2.x, b2.y);
#pragma unroll
            for (int m = 0; m < 5; m++) { stsf(ra + 64 * m, acc[m][0]); stsf(ra + 64 * m + 4, acc[m][2]); }
        }
        CSTAMP(7);
        uint32_t xr, fl, pubC, pubC2;
        auto prepC = [&](uint32_t ln) {
            const uint32_t q8 = ln >> 2, t4 = ln & 3;
            xr = pin(sb + S_XB + 48 * (ln & 15));
            pubC = pin(uPubC + (t4 & 1) * COL + 192 * (wp >> 1) + 64 * (wp & 1) + 8 * q8);
            pubC2 = pin(uPubC + (t4 & 1) * COL + ((t4 & 2) ? 192 * (wp >> 1) + 128 + 4 * (wp & 1) + 8 * q8 : 768 + 2 * ((q8 + 1) & 6)));
            fl = pin(((t4 & 1) ? par1 : pub0) | (t4 >= 2 || (wp == 7 && q8 < 4 && q8 != 2 - t4) ? 2 : 0));
        };
        auto stats = [&](uint32_t xa, const uint4& b, uint32_t b4) {
            float a0[4] = {}, a1[4] = {}, a2[4] = {};
            const uint4 p0 = lds128(xa), p1 = lds128(xa + 16);
            const uint2 p2 = lds64(xa + 32);
            mmaV(a0, p0, b.x, b.y); mmaV(a1, p1, b.z, b.w); mma8(a2, p2.x, p2.y, b4);
            return ((a0[0] + a0[3]) + (a1[0] + a1[3])) + (a2[0] + a2[3]);
        };
        auto give_ln = [&](uint32_t src0, uint32_t par, uint32_t dst, uint32_t ln, float& mean, float& den, auto also) {
            const char* src = xp(src0 + 768 + (ln & 1) * HALF);
            float sx, sq;
            int guard = 0;
            bool again;
            do {
                uint2 st[4];
#pragma unroll
                for (int s = 0; s < 4; s++) st[s] = ldp64(src + s * 1024);
                again = __any_sync(~0u, ((chk4(st, par) | also()) & 1) != 0);
                sx = (asf(st[0].x) + asf(st[1].x)) + (asf(st[2].x) + asf(st[3].x)); sq = (asf(st[0].y) + asf(st[1].y)) + (asf(st[2].y) + asf(st[3].y));
                sx += __shfl_xor_sync(~0u, sx, 1); sq += __shfl_xor_sync(~0u, sq, 1);
            } while (again & (++guard < SPIN_LIMIT));
            ln_stats(sx, sq, mean, den);
            stsvol64(dst, __byte_perm(__float_as_uint(den), __float_as_uint(mean), 0x7632), (__float_as_uint(rcp(den)) & ~7u) | (ch + 1));
        };
        auto take_ln = [&](uint2& c, uint32_t a) { int k = 0; do c = ldsvol64(a); while (__any_sync(~0u, (c.y & 7) != ch + 1) & (++k < SPIN_LIMIT)); };
        {
            auto gate_up = [&](auto with_stats) {
                bar_main();
                TST(3);
                CSTAMP(11);
                const uint4 b = lds128(xr);
                uint32_t b4 = lds32(xr + 16);
                float acc[3][4] = {};
                if (with_stats.value) {
                    stp32_if(fl > 1 && !(td & 2), xp(pubC2), stats(xr + (S_XA - S_XB), b, b4), fl & 1);
                    __syncwarp();
                    b4 = lds32(xr + 16);
                }
                mul80(acc, Wgu, b, b4);
                stp64_if(!(td & 2), xp(pubC), tagw(acc[0][0] + acc[0][3], fl & 1), tagw(acc[1][0] + acc[1][3], fl & 1));
                stp32_if(td & 2, xp(pubC2), acc[2][0] + acc[2][3], fl & 1);
            };
            if (wp == 7) {
                bar_main();
                IDS();
                prepC(ln);
                sts32(sb + S_ZERO + 4, or3(pubC, pubC2, fl));
                gate_up(std::true_type());
            } else {
                if (actc) {
                    bar_main();
                    CSTAMP(8);
                    uint32_t r[8];
#pragma unroll
                    for (int s = 0; s < 8; s++) r[s] = lds32(rr + 640 * s);
                    stp32_if(true, xp(pubB), sum8(r), parc);
                    CSTAMP(9);
                    IDS();
                    prepC(ln);
                    const uint32_t n4 = 4 * n80;
                    const uint32_t xas = pin(sb + S_XA + 192 + 192 * cc + a_pos(n80)), xbs = pin(sb + S_XB + 384 * cc + b_pos<40>(n80));
                    const float x0 = cc ? ldsf(sb + S_XCAR + n4) : bf_lo(lds16(sb + S_X0 + 160 * (ch & 3) + n4 / 2));
                    gather16(xp(uPolB + n4 + lag<DELAY_G>(sb, z0_)), parc, 5 * ch + 1, [&](float y, uint32_t) {
                        const uint32_t x = pack2(x0 + bfr(y), 0.f);
                        sts16(xbs, x);
                        sts16(xas, x);
                        return 0u;
                    });
                    CSTAMP(10);
                } else {
                    bar_main();
                    IDS();
                    prepC(ln);
                }
                gate_up(std::false_type());
            }
        }
        CSTAMP(12);
        float mean = 0.f, den = 1.f;
        {
            IDS();
            const uint32_t wh = pin((((ln & 7) + 48 * ((ln >> 3) & 1) + 8 * (ln >> 4)) * 160 + (wp < 7 ? 16 * wp : 128)) | ((384 * cc + b_pos<48>(n96)) << 16));
            const uint32_t pubD = pin(uPubD + (t4 & 1) * COL + 16 * (t4 & 2) + 4 * q8 + (fl & 1)), ha = xr + (S_HS - S_XB);
            auto down = [&](const uint32_t (&W)[3][4], const uint4& h0, const uint2& h1) {
                float a0[4] = {}, a1[4] = {}, a2[4] = {};
                mmaA(a0, W[0], h0.x, h0.y); mmaA(a1, W[1], h0.z, h0.w); mmaA(a2, W[2], h1.x, h1.y);
                return ((a0[0] + a0[3]) + (a1[0] + a1[3])) + (a2[0] + a2[3]);
            };
            if (wp < 6) {
                uint32_t Wd[3][4];
                auto ldd = [&](uint32_t z) {
#pragma unroll
                    for (int s = 0; s < 3; s++) ldsm4t(Wd[s], ((wh ^ z) & 0xffff) + (sb + S_WD + s * 2560));
                };
                ldd(0);
                if (actc) {
                    const char* srcv = xp(uPolC + lag<DELAY_C>(sb, z0_) + 8 * n96);
                    const uint2 cs = lds64(sb + S_CSGU + 8 * n96);
                    float gt, up;
                    int guard = 0;
                    while (true) {
                        uint2 v[8];
#pragma unroll
                        for (int s = 0; s < 8; s++) v[s] = ldp64(srcv + (s >> 2) * HALF + (s & 3) * 1024);
                        uint2 c = ldsvol64(sb + S_LN + 8 * cc + ((v[0].x ^ parc) & 1) * 32);
                        const bool stale = __any_sync(~0u, ((chk8(v, parc) | chk8y(v, parc)) & 1) != 0), late = __any_sync(~0u, (c.y & 7) != ch + 1);
                        const float pg = sum8x(v), pu = sum8y(v);
                        auto norm = [&] {
                            mean = bf_hi(c.x); den = bf_lo(c.x);
                            gt = bfr(fmaf(-mean, asf(cs.x), pg) * asf(c.y)); up = fmaf(-mean, asf(cs.y), pu) * asf(c.y);
                            keep(gt); keep(up);
                        };
                        norm();
                        if (!((stale | late) & (++guard < SPIN_LIMIT))) break;
                        if (!stale) { take_ln(c, sb + S_LN + 8 * cc); norm(); break; }
                    }
                    CSTAMP(13);
                    SWEEPS(5 * ch + 2, guard - 1);
                    const uint32_t h = pack2(bfr(gt * sigmoidf_(gt)) * bfr(up), 0.f);
                    sts16((wh >> 16) + (sb + S_HS), h);
                    CSTAMP(14);
                    if (ch == 3) CSTAMP(0);
                }
                bar_main();
                TST(4);
                CSTAMP(15);
                const uint4 h0 = lds128(ha);
                const uint2 h1 = lds64(ha + 16);
                stp32_if(!(td & 2), xp(pubD & ~1u), down(Wd, h0, h1), pubD & 1);
            } else {
                uint32_t v = 0;
                const uint32_t col = wp == 7 || !has0;
                const bool serve = wp == 6 || (has0 && has1);
                if (serve) {
                    const uint32_t par = col ? par1 : par0;
                    const char* src = xp(uPolC + col * COL + 776 + (td & 4) * (HALF / 4) + (td & 3) * 1024);
                    give_ln(uPolC + col * COL, par, sb + S_LN + 8 * col, td, mean, den, [&] { v = ldp32(src); return v ^ par; });
                }
                stsvol(sb + S_GATE, ch + 1);
                uint32_t Wd[2][3][4];
#pragma unroll
                for (int s = 0; s < 6; s++) ldsm4t(Wd[s / 3][s % 3], (wh & 0xffff) + (sb + S_WD + (s / 3) * 16 + (s % 3) * 2560));
                bar_main();
                const uint4 h0 = lds128(ha);
                const uint2 h1 = lds64(ha + 16);
                const float d0 = down(Wd[0], h0, h1), d1 = down(Wd[1], h0, h1);
                stp32_if(true, xp(pubD & ~1u), (td & 2) ? d1 : d0, pubD & 1);
                if (serve) {
                    float xw = asf(v);
                    xw += __shfl_xor_sync(~0u, xw, 1); xw += __shfl_xor_sync(~0u, xw, 2); xw += __shfl_xor_sync(~0u, xw, 4);
                    const float r = bfr(fmaf(-mean, ldsf(sb + S_SWR), xw) * rcp(den));
                    sts32(sb + S_STAT + 4 * col, __float_as_uint(bfr(sigmoidf_(r))) | (ch + 1));
                }
            }
        }
        CSTAMP(16);
        {
            IDS();
            const uint32_t pubE = pin(uPubE + (t4 < 3 ? (wp >> 2) * COL + 192 * (wp & 3) + 64 * t4 + 8 * q8 : (q8 >> 2) * COL + 768 + 4 * (q8 & 1)));
            xr = pin(sb + S_XB + 48 * (ln & 7));
            uint32_t x2 = 0;
            auto hop_d = [&](auto col) {
                const uint32_t xbs = pin(sb + S_XB + 384 * col.value + b_pos<40>(n80)), xas = col.value ? 0 : pin(sb + S_XA + 192 + a_pos(n80));
                const float x1 = bf_lo(lds16(xbs));
                const float lnx = __uint_as_float(pin(__float_as_uint(bfr(__fdiv_rn(bfr(x1 - mean), den)))));
                gather16(xp(uPolD + 4 * n80 + lag<DELAY_D>(sb, z0_)), col.value ? par1 : par0, 5 * ch + 3, [&](float y, uint32_t z) {
                    const uint32_t gate = ldsvol(sb + S_STAT + 4 * col.value + z);
                    x2 = pack2(x1 + bfr(lnx + bfr(bfr(y) * bf_hi(gate))), 0.f);
                    if (col.value) keep(x2); else { sts16(xbs, x2); sts16(xas, x2); }
                    return (uint32_t)((gate & 7) != ch + 1);
                });
                CSTAMP(17);
            };
            auto qproj = [&](auto with_stats) {
                bar_main();
                TST(5);
                CSTAMP(19);
                const uint32_t t4 = td & 3;
                const uint4 b = lds128(xr);
                uint32_t b4 = lds32(xr + 16);
                float acc[6][4] = {};
                if (with_stats.value) {
                    stp32_if((td & 11) == 3, xp(pubE), stats(xr + (S_XA - S_XB), b, b4), par0);
                    __syncwarp();
                    b4 = lds32(xr + 16);
                }
                mul80(acc, Wq, b, b4);
                const float v0 = sel4(t4, acc[0][0] + acc[0][3], acc[2][0] + acc[2][3], acc[4][0] + acc[4][3], acc[4][0] + acc[4][3]);
                const float v1 = sel4(t4, acc[1][0] + acc[1][3], acc[3][0] + acc[3][3], acc[5][0] + acc[5][3], acc[5][0] + acc[5][3]);
                stp64_if(t4 < 3, xp(pubE), tagw(v0, par0), tagw(v1, par0));
            };
            if (wp == 7) {
                if (!has0) break;
                qproj(std::true_type());
            } else {
                if (actc && !cc) hop_d(std::integral_constant<int, 0>());
                else {
                    if (actc && g == 0) {
                        const uint32_t po = pin(1280 * (ch - 1) + 160 * i + 2 * n80);
                        hop_d(std::integral_constant<int, 1>());
                        *reinterpret_cast<unsigned short*>(reinterpret_cast<char*>(P.out) + po) = (unsigned short)x2;
                    }
                    if (!has0) break;
                }
                qproj(std::false_type());
                sts32_if(td < 80, sb + S_XCAR + 4 * td, x2 << 16);
            }
        }
        CSTAMP(20);
        if (wp == 6) give_ln(uPolE, par0, sb + S_LN + 16, td, mean, den, [] { return 0u; });
        auto pass2 = [&](auto d0, auto d1, auto d2) {
            constexpr int D0 = d0.value, D1 = d1.value, D = D0 + D1 + d2.value;
            IDS();
            const uint32_t ua = sb + k_place(ch, wp & 6) * SLOT + (wp & 1) * UNIT, k0 = k_off(ln);
            uint32_t kf[12][2][4];
            auto ldk = [&](int s) { const uint32_t a = (k0 ^ (32 * (s / 3))) + (ua + 1024 * (s % 3)); ldsm4(kf[s][0], a); ldsm4(kf[s][1], a + SLOT); };
            auto ldv1 = [&](int k) { ldsm4t(vf[k / 3][k % 3], voff[k % 3] + (sb + v_place(ch, k / 3) * SLOT)); };
            auto ldv = [&](int s) { ldv1(3 * s); ldv1(3 * s + 1); ldv1(3 * s + 2); };
            constexpr uint32_t LATE = LAST_LATE;
            constexpr uint64_t EARLY_LIST = bit_list(~LATE), LATE_LIST = bit_list(LATE);
            auto early = [&](int k) {
                if (D1 == 0) ldk(k);
                else if (k < 3) { ldv1(9 + 2 * k); ldv1(10 + 2 * k); }
                else ldk((EARLY_LIST >> (4 * (k - 3))) & 15);
            };
            uint32_t v[8] = {}, qsa = 0;
            const char* srcv = xp(uPolE + lag<(D1 > 0 ? DELAY_E3 : DELAY_E)>(sb, z0_) + 4 * td);
            auto look = [&] {
#pragma unroll
                for (int s = 0; s < 8; s++) v[s] = ldp32(srcv + (s >> 2) * HALF + (s & 3) * 1024);
            };
            if (LOOK_FIRST && wp < 6) { look(); qsa = pin(sb + S_QS + 384 * ch + q_pos(z_)); }
            if (D1 > 0) vaddr(voff);
            if (!(mbar_try(sb + S_FK + 8 * (wp & 6), par1) & mbar_try(sb + S_FK + 8 * (wp | 1), par1))) { mbar_wait(sb + S_FK + 8 * (wp & 6), par1); mbar_wait(sb + S_FK + 8 * (wp | 1), par1); }
#pragma unroll
            for (int s = 0; s < D0; s++) early(s);
            if (!LOOK_FIRST && wp < 6) { look(); qsa = pin(sb + S_QS + 384 * ch + q_pos(z_)); }
#pragma unroll
            for (int s = D0; s < D0 + D1; s++) early(s);
            if (wp < 6) {
                const float cs = ldsf(sb + S_CSQ + 4 * td);
                int guard = 0;
                while (true) {
                    uint2 c = ldsvol64(sb + S_LN + 16 + ((v[0] ^ par0) & 1) * 32);
                    const bool stale = __any_sync(~0u, (chk8(v, par0) & 1) != 0), late = __any_sync(~0u, (c.y & 7) != ch + 1);
                    const float qs = sum8(v);
                    auto norm = [&] {
                        const uint32_t q = pack2(fmaf(-bf_hi(c.x), cs, qs) * asf(c.y), 0.f);
                        sts16(qsa, q);
                    };
                    norm();
                    if (!((stale | late) & (++guard < SPIN_LIMIT))) break;
                    if (!stale) { take_ln(c, sb + S_LN + 16); norm(); break; }
                    look();
                }
                SWEEPS(5 * ch + 4, guard - 1);
                CSTAMP(22);
            }
#pragma unroll
            for (int s = D0 + D1; s < D; s++) early(s);
            CSTAMP(21);
            bar_main();
            TST(6);
            CSTAMP(1);
            uint2 q = lds64(sb + S_QS + 384 * ch + 8 * ln);
            float acc[2][4] = {};
            constexpr int V0 = 13 - D, NV = D1 > 0 ? 2 : (2 * (D - 1)) / 3;
            static_assert(D1 == 0 || LAST0 == 0 || D - 3 + __builtin_popcount(LATE) == 12, "plan");
#pragma unroll
            for (int s = 0; s < 12; s++) {
                const bool m = q8 == (s & 7);
                const uint32_t b0 = m ? q.x : 0u, b1 = m ? q.y : 0u;
                if (s == 7) q = lds64(sb + S_QS + 384 * ch + 8 * ln + 256);
                mmaA(acc[0], kf[s][0], b0, b1);
                mmaA(acc[1], kf[s][1], b0, b1);
                if (D1 > 0) {
                    if (s >= 1 && s <= __builtin_popcount(LATE)) ldk((LATE_LIST >> (4 * (s - 1))) & 15);
                } else {
                    if (s >= 1 && s + D - 1 < 12) ldk(s + D - 1);
                    if (s >= 1 && s + D - 1 == 11) { __syncwarp(); arrive_if(ln == 0, sb + S_RELK); }
                    if (s == V0) vaddr(voff);
                    if (s >= V0 && 2 * (s - V0) < 3 * NV) ldv1(9 + 2 * (s - V0));
                    if (s >= V0 && 2 * (s - V0) + 1 < 3 * NV) ldv1(10 + 2 * (s - V0));
                }
            }
            CSTAMP(24);
            {
                const float v0 = acc[0][0] + acc[0][1], v1 = acc[0][2] + acc[0][3], v2 = acc[1][0] + acc[1][1], v3 = acc[1][2] + acc[1][3];
                const bool hi = t4 & 2, od = t4 & 1;
                const float u0 = (hi ? v2 : v0) + __shfl_xor_sync(~0u, hi ? v0 : v2, 2), u1 = (hi ? v3 : v1) + __shfl_xor_sync(~0u, hi ? v1 : v3, 2);
                const float s = (od ? u1 : u0) + __shfl_xor_sync(~0u, od ? u0 : u1, 1);
                CSTAMP(2);
                probs(scaled(s), sb + S_PS + PS_PASS, wp, ln);
                CSTAMP(3);
            }
            bar_main();
            TST(10);
            CSTAMP(4);
            if (D1 > 0) values(vf, acc_, std::integral_constant<uint32_t, ORDER_L>(), [&](int s) { if (s < 3) ldv(s + 5); }, sb + S_PS + PS_PASS, 1, par0);
            else values(vf, acc_, std::integral_constant<uint32_t, (NV > 1 ? ORDER_R : 0x76543210)>(),
                        [&](int s) { if (s >= (NV > 1 ? 2 : 1) && s + NV + (NV > 1 ? 1 : 2) < 8) ldv(s + NV + (NV > 1 ? 1 : 2)); }, sb + S_PS + PS_PASS, 1, par0);
            arrive_if(ln == 0, sb + S_RELV);
        };
        if (LAST0 > 0 && ch == 3) {
            pass2(std::integral_constant<int, LAST0>(), std::integral_constant<int, LAST1>(), std::integral_constant<int, LAST2>());
#pragma unroll
            for (int m = 0; m < 48; m++) Wq[m / 8].a[(m / 4) % 2][m % 4] = vf[3 + m / 12][(m / 4) % 3][m % 4];
#pragma unroll
            for (int m = 0; m < 12; m++) Wq[m / 2].c[m % 2] = vf[7][m / 4][m % 4];
#pragma unroll
            for (int m = 0; m < 36; m++) left[m] = m < 12 ? __float_as_uint(acc_[m / 4][m % 4]) : vf[m / 12][(m / 4) % 3][m % 4];
        } else {
            pass2(std::integral_constant<int, KPRE>(), std::integral_constant<int, 0>(), std::integral_constant<int, KPRE2>());
#pragma unroll
            for (int m = 0; m < 36; m++) left[m] = m < 12 ? __float_as_uint(acc_[m / 4][m % 4]) : vf[4 + m / 12][(m / 4) % 3][m % 4];
        }
        TST(11);
        CSTAMP(23);
    }
    sts32_if(td == 255, sb + S_GATE, 6);
    TSTAMP(3);
}

typedef CUresult (*EncodeFn)(CUtensorMap*, CUtensorMapDataType, cuuint32_t, void*, const cuuint64_t*, const cuuint64_t*, const cuuint32_t*,
                             const cuuint32_t*, CUtensorMapInterleave, CUtensorMapSwizzle, CUtensorMapL2promotion, CUtensorMapFloatOOBfill);

void make_map(EncodeFn enc, CUtensorMap* m, const void* base, uint64_t cols, uint64_t rows, uint32_t box_cols, uint32_t box_rows, bool swizzle) {
    cuuint64_t dims[2] = {cols, rows};
    cuuint64_t strides[1] = {cols * 2};
    cuuint32_t box[2] = {box_cols, box_rows};
    cuuint32_t es[2] = {1, 1};
    enc(m, CU_TENSOR_MAP_DATA_TYPE_BFLOAT16, 2, const_cast<void*>(base), dims, strides, box, es, CU_TENSOR_MAP_INTERLEAVE_NONE,
        swizzle ? CU_TENSOR_MAP_SWIZZLE_128B : CU_TENSOR_MAP_SWIZZLE_NONE, swizzle ? CU_TENSOR_MAP_L2_PROMOTION_NONE : WPROMO, CU_TENSOR_MAP_FLOAT_OOB_FILL_NONE);
}

}

extern "C" void kernel_launch(void* const* d_in, const int* in_sizes, int n_in, void* d_out, int out_size) {
    (void)in_sizes; (void)n_in; (void)out_size;
    static EncodeFn enc = nullptr;
    if (!enc) {
        void* f = nullptr;
        cudaDriverEntryPointQueryResult q;
        cudaGetDriverEntryPoint("cuTensorMapEncodeTiled", &f, cudaEnableDefault, &q);
        enc = (EncodeFn)f;
        cudaFuncSetAttribute(fused_kernel, cudaFuncAttributeMaxDynamicSharedMemorySize, SMEM_BYTES);
    }
    Params P;
    P.x = (const __nv_bfloat16*)d_in[0]; P.k = (const __nv_bfloat16*)d_in[1]; P.v = (const __nv_bfloat16*)d_in[2];
    P.wr = (const __nv_bfloat16*)d_in[6];
    P.out = (__nv_bfloat16*)d_out;
    Maps M;
    {
        cuuint64_t dims[4] = {64, 8, 3, (cuuint64_t)KV_BATCH_KEYS / 2}, strides[3] = {384, 128, 3072};
        cuuint32_t box[4] = {64, 8, 3, 2}, es[4] = {1, 1, 1, 1};
        enc(&M.k, CU_TENSOR_MAP_DATA_TYPE_BFLOAT16, 4, d_in[1], dims, strides, box, es, CU_TENSOR_MAP_INTERLEAVE_NONE, CU_TENSOR_MAP_SWIZZLE_128B,
            CU_TENSOR_MAP_L2_PROMOTION_NONE, CU_TENSOR_MAP_FLOAT_OOB_FILL_NONE);
    }
    make_map(enc, &M.v, P.v, 64, (uint64_t)12 * KV_BATCH_KEYS, 64, 96, true);
    make_map(enc, &M.vu, P.v, 64, (uint64_t)12 * KV_BATCH_KEYS, 64, 48, true);
    make_map(enc, &M.wq, d_in[3], 6144, 640, 192, 40, false);
    make_map(enc, &M.wo, d_in[4], 640, 6144, 80, 96, false);
    make_map(enc, &M.wg, d_in[7], 1536, 640, 96, 80, false);
    make_map(enc, &M.wu, d_in[8], 1536, 640, 96, 80, false);
    make_map(enc, &M.wd, d_in[9], 640, 1536, 80, 96, false);
    fused_kernel<<<NCTA, NTHR, SMEM_BYTES, cudaStreamPerThread>>>(P, M);
}
```

```cpp
#include <cuda_runtime.h>
#include <cuda.h>
#include <cuda_bf16.h>
#include <stdint.h>
#include <type_traits>

namespace {

constexpr int NCTA = 128;
constexpr int NTHR = 384;
constexpr int UNIT = 6144;
constexpr int SLOT = 12288;
#define TAU 3970
#define TAUW 3820
#define TAU0 3820
#define PF0 2
#define PFMAP 1
#define ZPOS 1
#define LOOK1 0
#define LOOK2 0
#define SLACK 4000
#define SLACK0 2000
#define TSH 0
#define HOP1_NS 200
#define RELR_AT 0
#define PSLEEP 0
#define KRE_EARLY 6
#define PFTOP 2
#define RFR_XS 2
#define TMIN 2400
#define T_LEAD 0
#define WIN_W 3
#define WIN_S 4
#define WIN_U 10
#define RFR_ON 1
#define KRE_N1 0
#define KRE_TAU1 2500
#define RFR_TAU 25600
#define VPF 4
#define KRE_GATE 0
#define KRE_GATE3 KRE_GATE
#define JFREE 16
#define TFREE 0
#define KRE_TAU 2600
#define KRE_TAU3 KRE_TAU
#define HDEPTH 3
#define LAST0 4
#define ORDER_L 0x76543210
#define ORDER_R 0x76543210
#define LOOK_FIRST 0
#define LAST_LATE 0xaa8
#define LAST1 4
#define LAST2 2
#define FSTEP 4
#define SPEC 1
#define PV1PIPE 0
#define HOPA0 6
#define HOPA1 6
#define WPROMO CU_TENSOR_MAP_L2_PROMOTION_NONE
#define KPRE 1
#define KPRE2 3
#define DELAY_G 2
#define DELAY_L 2
#define DELAY_E3 0
#define DELAY_C 3
#define DELAY_D 0
#define DELAY_E 1
#define REG_LO "40"
#define REG_HI "232"
#define SPIN_LOG 17
constexpr int SPIN_LIMIT = 1 << SPIN_LOG;

__host__ __device__ constexpr uint32_t pairL(uint32_t region, uint32_t c, uint32_t g) { return (g & 1) | ((g >> 1) << 2) | (c << 5) | (region << 6); }
__host__ __device__ constexpr uint32_t pairG(uint32_t d, uint32_t c, uint32_t i) { return (i & 1) | ((i >> 1) << 2) | (d << 4) | (c << 5) | (3u << 6); }
constexpr uint32_t RA = 0, RC = 1, RE = 2, HALF = 16384, COPY = 4096, PMASK = 0x59;
constexpr uint32_t XS = 0;
constexpr uint32_t XS2 = XS + 128 * 7680;
constexpr uint32_t XSEND = XS2 + 128 * 768;
__device__ uint4 g_s[XSEND / 16];
__device__ uint4 g_x[(4u << 20) / 16];
#define SWEEPS(k, n) do {} while (0)

constexpr uint32_t S_WD = 16 * SLOT;
constexpr uint32_t S_DUMMY = S_WD + 15360;
constexpr uint32_t S_BAR = S_DUMMY + 4096;
constexpr uint32_t S_FV = S_BAR, S_FK = S_FV + 64, S_RING = S_FK + 64, S_DBAR = S_RING + 48, S_WFULL = S_DBAR + 32, S_QRDY = S_WFULL + 88;
constexpr uint32_t S_RELK = S_QRDY + 8, S_RELV = S_RELK + 8, S_RELR = S_RELV + 8, S_RELW = S_RELR + 8, S_SCO = S_RELW + 24;
constexpr uint32_t S_OS1 = S_SCO + 8;
constexpr uint32_t S_ZERO = S_OS1 + 8;
constexpr uint32_t S_KF = S_ZERO + 8;
constexpr uint32_t S_TOK = S_KF + 8;
constexpr uint32_t S_SIDE = S_TOK + 80, S_GATE = S_SIDE + 4;
constexpr uint32_t S_STAT = S_GATE + 12, S_SWR = S_STAT + 16;
constexpr uint32_t S_LN = S_STAT + 32;
constexpr uint32_t S_XCAR = S_LN + 64;
constexpr uint32_t S_CSQ = S_XCAR + 320;
constexpr uint32_t S_CSGU = S_CSQ + 768;
constexpr uint32_t S_RED = S_CSGU + 768;
constexpr uint32_t S_L0 = S_RED;
constexpr uint32_t S_OS = S_RED + 5120;
constexpr uint32_t S_PS = S_OS + 1536;
constexpr uint32_t PS_MAX = 512, PS_PASS = 544;
constexpr uint32_t S_QS = S_PS + 2 * PS_PASS;
constexpr uint32_t S_XB = S_QS + 1536;
constexpr uint32_t S_XA = S_XB + 768;
constexpr uint32_t S_HS = S_XA + 768;
constexpr uint32_t S_X0 = S_HS + 768;
constexpr uint32_t S_SC = S_X0 + 640;
constexpr uint32_t S_TM = S_SC + 512;
constexpr int SMEM_BYTES = S_TM + 256;
static_assert(SMEM_BYTES <= 232448 && S_STAT % 16 == 0 && S_RED % 16 == 0 && S_XB % 16 == 0 && S_HS % 16 == 0 && S_PS % 16 == 0 && S_QS % 16 == 0, "smem");
static_assert(S_SCO == S_BAR + 44 * 8 && S_RELK == S_BAR + 38 * 8, "barriers");
constexpr uint32_t ST_WQ = 3 * SLOT, ST_WG = 8 * SLOT, ST_WO = 11 * SLOT;

__device__ __forceinline__ uint32_t smem_u32(const void* p) { return (uint32_t)__cvta_generic_to_shared(p); }
__device__ __forceinline__ void mbar_init(uint32_t bar, uint32_t cnt) { asm volatile("mbarrier.init.shared::cta.b64 [%0], %1;" :: "r"(bar), "r"(cnt) : "memory"); }
__device__ __forceinline__ void mbar_expect(uint32_t bar, uint32_t bytes) { asm volatile("mbarrier.arrive.expect_tx.shared::cta.b64 _, [%0], %1;" :: "r"(bar), "r"(bytes) : "memory"); }
__device__ __forceinline__ void mbar_arrive(uint32_t bar) { asm volatile("mbarrier.arrive.shared::cta.b64 _, [%0];" :: "r"(bar) : "memory"); }
__device__ __forceinline__ bool mbar_try(uint32_t bar, uint32_t parity) {
    uint32_t ok;
    asm volatile("{\n .reg .pred p;\n mbarrier.try_wait.parity.shared::cta.b64 p, [%1], %2;\n selp.u32 %0, 1, 0, p;\n}" : "=r"(ok) : "r"(bar), "r"(parity) : "memory");
    return ok != 0;
}
__device__ __forceinline__ bool mbar_test(uint32_t bar, uint32_t parity) {
    uint32_t ok;
    asm volatile("{\n .reg .pred p;\n mbarrier.test_wait.parity.shared::cta.b64 p, [%1], %2;\n selp.u32 %0, 1, 0, p;\n}" : "=r"(ok) : "r"(bar), "r"(parity) : "memory");
    return ok != 0;
}
__device__ __forceinline__ void mbar_wait(uint32_t bar, uint32_t parity) {
    int n = 0;
    while (!mbar_try(bar, parity) && ++n < SPIN_LIMIT) {}
}
__device__ __forceinline__ unsigned long long gtime() { unsigned long long t; asm volatile("mov.u64 %0, %globaltimer;" : "=l"(t)); return t; }
__device__ __forceinline__ uint32_t gtime32() { uint32_t t; asm volatile("mov.u32 %0, %globaltimer_lo;" : "=r"(t)); return t; }
__device__ __forceinline__ void bar_main() { asm volatile("bar.sync 1, 256;" ::: "memory"); }

__device__ __forceinline__ void mma16816(float (&c)[4], uint32_t a0, uint32_t a1, uint32_t a2, uint32_t a3, uint32_t b0, uint32_t b1) {
    asm("mma.sync.aligned.m16n8k16.row.col.f32.bf16.bf16.f32 {%0,%1,%2,%3}, {%4,%5,%6,%7}, {%8,%9}, {%0,%1,%2,%3};"
        : "+f"(c[0]), "+f"(c[1]), "+f"(c[2]), "+f"(c[3]) : "r"(a0), "r"(a1), "r"(a2), "r"(a3), "r"(b0), "r"(b1));
}
__device__ __forceinline__ void mmaA(float (&c)[4], const uint32_t (&a)[4], uint32_t b0, uint32_t b1) { mma16816(c, a[0], a[1], a[2], a[3], b0, b1); }
__device__ __forceinline__ void mmaAv(float (&c)[4], const uint32_t (&a)[4], uint32_t b0, uint32_t b1) {
    asm volatile("mma.sync.aligned.m16n8k16.row.col.f32.bf16.bf16.f32 {%0,%1,%2,%3}, {%4,%5,%6,%7}, {%8,%9}, {%0,%1,%2,%3};"
        : "+f"(c[0]), "+f"(c[1]), "+f"(c[2]), "+f"(c[3]) : "r"(a[0]), "r"(a[1]), "r"(a[2]), "r"(a[3]), "r"(b0), "r"(b1) : "memory");
}
__device__ __forceinline__ void mma8(float (&c)[4], uint32_t a0, uint32_t a1, uint32_t b0) {
    asm("mma.sync.aligned.m16n8k8.row.col.f32.bf16.bf16.f32 {%0,%1,%2,%3}, {%4,%5}, {%6}, {%0,%1,%2,%3};"
        : "+f"(c[0]), "+f"(c[1]), "+f"(c[2]), "+f"(c[3]) : "r"(a0), "r"(a1), "r"(b0));
}
struct W80 { uint32_t a[2][4], c[2]; };
template <int N> __device__ __forceinline__ void mul80(float (&acc)[N][4], const W80 (&W)[N], const uint4& b, uint32_t b4) {
#pragma unroll
    for (int m = 0; m < N; m++) mmaA(acc[m], W[m].a[0], b.x, b.y);
#pragma unroll
    for (int m = 0; m < N; m++) mmaA(acc[m], W[m].a[1], b.z, b.w);
#pragma unroll
    for (int m = 0; m < N; m++) mma8(acc[m], W[m].c[0], W[m].c[1], b4);
}
__device__ __forceinline__ void ldsm2t(uint32_t (&r)[2], uint32_t addr) {
    asm volatile("ldmatrix.sync.aligned.m8n8.x2.trans.shared.b16 {%0,%1}, [%2];" : "=r"(r[0]), "=r"(r[1]) : "r"(addr) : "memory");
}
__device__ __forceinline__ void mmaV(float (&c)[4], const uint4& a, uint32_t b0, uint32_t b1) { mma16816(c, a.x, a.y, a.z, a.w, b0, b1); }
__device__ __forceinline__ void ldsm4(uint32_t (&r)[4], uint32_t addr) {
    asm volatile("ldmatrix.sync.aligned.m8n8.x4.shared.b16 {%0,%1,%2,%3}, [%4];" : "=r"(r[0]), "=r"(r[1]), "=r"(r[2]), "=r"(r[3]) : "r"(addr) : "memory");
}
__device__ __forceinline__ void ldsm4t(uint32_t (&r)[4], uint32_t addr) {
    asm volatile("ldmatrix.sync.aligned.m8n8.x4.trans.shared.b16 {%0,%1,%2,%3}, [%4];" : "=r"(r[0]), "=r"(r[1]), "=r"(r[2]), "=r"(r[3]) : "r"(addr) : "memory");
}
__device__ __forceinline__ uint32_t lds16(uint32_t a) { uint16_t v; asm volatile("ld.shared.u16 %0, [%1];" : "=h"(v) : "r"(a) : "memory"); return v; }
__device__ __forceinline__ uint32_t lds32(uint32_t a) { uint32_t v; asm volatile("ld.shared.u32 %0, [%1];" : "=r"(v) : "r"(a) : "memory"); return v; }
__device__ __forceinline__ float ldsf(uint32_t a) { return __uint_as_float(lds32(a)); }
__device__ __forceinline__ uint2 lds64(uint32_t a) { uint2 v; asm volatile("ld.shared.v2.u32 {%0,%1}, [%2];" : "=r"(v.x), "=r"(v.y) : "r"(a) : "memory"); return v; }
__device__ __forceinline__ uint4 lds128(uint32_t a) { uint4 v; asm volatile("ld.shared.v4.u32 {%0,%1,%2,%3}, [%4];" : "=r"(v.x), "=r"(v.y), "=r"(v.z), "=r"(v.w) : "r"(a) : "memory"); return v; }
__device__ __forceinline__ int ldsvol(uint32_t a) { int v; asm volatile("ld.volatile.shared.u32 %0, [%1];" : "=r"(v) : "r"(a) : "memory"); return v; }
__device__ __forceinline__ uint2 ldsvol64(uint32_t a) { uint2 v; asm volatile("{\n .reg .b64 d;\n ld.volatile.shared.b64 d, [%2];\n mov.b64 {%0,%1}, d;\n}" : "=r"(v.x), "=r"(v.y) : "r"(a) : "memory"); return v; }
__device__ __forceinline__ void stsvol64(uint32_t a, uint32_t x, uint32_t y) { asm volatile("{\n .reg .b64 d;\n mov.b64 d, {%1,%2};\n st.volatile.shared.b64 [%0], d;\n}" :: "r"(a), "r"(x), "r"(y) : "memory"); }
__device__ __forceinline__ void stsvol(uint32_t a, int v) { asm volatile("st.volatile.shared.u32 [%0], %1;" :: "r"(a), "r"(v) : "memory"); }
__device__ __forceinline__ void sts_hi16(uint32_t a, float v) { asm volatile("{\n .reg .b16 lo, hi;\n mov.b32 {lo, hi}, %1;\n st.shared.u16 [%0], hi;\n}" :: "r"(a), "r"(__float_as_uint(v)) : "memory"); }
__device__ __forceinline__ void sts16(uint32_t a, uint32_t v) { asm volatile("st.shared.u16 [%0], %1;" :: "r"(a), "r"(v) : "memory"); }
__device__ __forceinline__ void sts32(uint32_t a, uint32_t v) { asm volatile("st.shared.u32 [%0], %1;" :: "r"(a), "r"(v) : "memory"); }
__device__ __forceinline__ void stsf(uint32_t a, float v) { sts32(a, __float_as_uint(v)); }
__device__ __forceinline__ void sts64(uint32_t a, uint32_t x, uint32_t y) { asm volatile("st.shared.v2.u32 [%0], {%1,%2};" :: "r"(a), "r"(x), "r"(y) : "memory"); }

__device__ __forceinline__ void sts_hi16_if(bool p, uint32_t a, float v) {
    asm volatile("{\n .reg .pred p;\n .reg .b16 lo, hi;\n setp.ne.u32 p, %2, 0;\n mov.b32 {lo, hi}, %1;\n @p st.shared.u16 [%0], hi;\n}" :: "r"(a), "r"(__float_as_uint(v)), "r"((uint32_t)p) : "memory");
}
__device__ __forceinline__ void sts32_if(bool p, uint32_t a, uint32_t v) {
    asm volatile("{\n .reg .pred p;\n setp.ne.u32 p, %2, 0;\n @p st.shared.u32 [%0], %1;\n}" :: "r"(a), "r"(v), "r"((uint32_t)p) : "memory");
}
__device__ __forceinline__ void sts64_if(bool p, uint32_t a, float x, float y) {
    asm volatile("{\n .reg .pred p;\n setp.ne.u32 p, %3, 0;\n @p st.shared.v2.f32 [%0], {%1,%2};\n}" :: "r"(a), "f"(x), "f"(y), "r"((uint32_t)p) : "memory");
}
__device__ __forceinline__ void arrive_if(bool p, uint32_t bar) {
    asm volatile("{\n .reg .pred p;\n setp.ne.u32 p, %1, 0;\n @p mbarrier.arrive.shared::cta.b64 _, [%0];\n}" :: "r"(bar), "r"((uint32_t)p) : "memory");
}
__device__ __forceinline__ void opaque(uint32_t& v) { asm volatile("" : "+r"(v)); }
__device__ __forceinline__ void keep(uint32_t& v) { asm volatile("" : "+r"(v)); }
__device__ __forceinline__ void keep(float& v) { asm volatile("" : "+f"(v)); }
template <class T> __device__ __forceinline__ void keep(T*& v) { asm volatile("" : "+l"(v)); }

__device__ __forceinline__ uint32_t ldp32(const char* p) { uint32_t v; asm volatile("ld.relaxed.gpu.global.u32 %0, [%1];" : "=r"(v) : "l"(p) : "memory"); return v; }
__device__ __forceinline__ uint2 ldp64(const char* p) {
    uint2 v; asm volatile("{\n .reg .b64 d;\n ld.relaxed.gpu.global.b64 d, [%2];\n mov.b64 {%0,%1}, d;\n}" : "=r"(v.x), "=r"(v.y) : "l"(p) : "memory"); return v;
}
__device__ __forceinline__ uint32_t tagw(float f, uint32_t par) { return (__float_as_uint(f) & ~1u) | par; }
__device__ __forceinline__ void stp32(char* p, float a, uint32_t par) { asm volatile("st.relaxed.gpu.global.u32 [%0], %1;" :: "l"(p), "r"(tagw(a, par)) : "memory"); }
__device__ __forceinline__ void stp64(char* p, float a, float b, uint32_t par) {
    asm volatile("{\n .reg .b64 d;\n mov.b64 d, {%1,%2};\n st.relaxed.gpu.global.b64 [%0], d;\n}" :: "l"(p), "r"(tagw(a, par)), "r"(tagw(b, par)) : "memory");
}
__device__ __forceinline__ void stp32_if(bool p, char* d, float a, uint32_t par) {
    asm volatile("{\n .reg .pred p;\n setp.ne.u32 p, %2, 0;\n @p st.relaxed.gpu.global.u32 [%0], %1;\n @p st.relaxed.gpu.global.u32 [%0+4096], %1;\n}" :: "l"(d), "r"(tagw(a, par)), "r"((uint32_t)p) : "memory");
}
__device__ __forceinline__ void stp64_if(bool p, char* d, uint32_t lo, uint32_t hi) {
    asm volatile("{\n .reg .pred p;\n .reg .b64 d;\n setp.ne.u32 p, %3, 0;\n mov.b64 d, {%1,%2};\n @p st.relaxed.gpu.global.b64 [%0], d;\n @p st.relaxed.gpu.global.b64 [%0+4096], d;\n}" :: "l"(d), "r"(lo), "r"(hi), "r"((uint32_t)p) : "memory");
}
__device__ __forceinline__ uint32_t chk2(uint32_t a, uint32_t b, uint32_t par) { uint32_t r; asm("lop3.b32 %0, %1, %2, %3, 0x7E;" : "=r"(r) : "r"(a), "r"(b), "r"(par)); return r; }
__device__ __forceinline__ uint32_t or3(uint32_t a, uint32_t b, uint32_t c) { uint32_t r; asm("lop3.b32 %0, %1, %2, %3, 0xFE;" : "=r"(r) : "r"(a), "r"(b), "r"(c)); return r; }
__device__ __forceinline__ uint32_t chk8(const uint32_t (&v)[8], uint32_t par) { return or3(chk2(v[0], v[1], par), chk2(v[2], v[3], par), or3(chk2(v[4], v[5], par), chk2(v[6], v[7], par), 0)); }
__device__ __forceinline__ uint32_t chk8(const uint2 (&v)[8], uint32_t par) { return or3(chk2(v[0].x, v[1].x, par), chk2(v[2].x, v[3].x, par), or3(chk2(v[4].x, v[5].x, par), chk2(v[6].x, v[7].x, par), 0)); }
__device__ __forceinline__ uint32_t chk8y(const uint2 (&v)[8], uint32_t par) { return or3(chk2(v[0].y, v[1].y, par), chk2(v[2].y, v[3].y, par), or3(chk2(v[4].y, v[5].y, par), chk2(v[6].y, v[7].y, par), 0)); }
__device__ __forceinline__ uint32_t chk4(const uint2 (&v)[4], uint32_t par) { return or3(chk2(v[0].x, v[0].y, par), chk2(v[1].x, v[1].y, par), or3(chk2(v[2].x, v[2].y, par), chk2(v[3].x, v[3].y, par), 0)); }
__device__ __forceinline__ float asf(uint32_t v) { return __uint_as_float(v); }
__device__ __forceinline__ float sum8(const uint32_t (&v)[8]) { return ((asf(v[0]) + asf(v[1])) + (asf(v[2]) + asf(v[3]))) + ((asf(v[4]) + asf(v[5])) + (asf(v[6]) + asf(v[7]))); }
__device__ __forceinline__ float sum8x(const uint2 (&v)[8]) { return ((asf(v[0].x) + asf(v[1].x)) + (asf(v[2].x) + asf(v[3].x))) + ((asf(v[4].x) + asf(v[5].x)) + (asf(v[6].x) + asf(v[7].x))); }
__device__ __forceinline__ float sum8y(const uint2 (&v)[8]) { return ((asf(v[0].y) + asf(v[1].y)) + (asf(v[2].y) + asf(v[3].y))) + ((asf(v[4].y) + asf(v[5].y)) + (asf(v[6].y) + asf(v[7].y))); }

__device__ __forceinline__ uint32_t pack2(float lo, float hi) { uint32_t r; asm("cvt.rn.bf16x2.f32 %0, %1, %2;" : "=r"(r) : "f"(hi), "f"(lo)); return r; }
__device__ __forceinline__ float bfr(float x) { return __uint_as_float(pack2(0.0f, x)); }
__device__ __forceinline__ float ex2(float x) { float r; asm("ex2.approx.ftz.f32 %0, %1;" : "=f"(r) : "f"(x)); return r; }
__device__ __forceinline__ float rcp(float x) { float r; asm("rcp.approx.ftz.f32 %0, %1;" : "=f"(r) : "f"(x)); return r; }
__device__ __forceinline__ float sqrt_(float x) { float r; asm("sqrt.approx.ftz.f32 %0, %1;" : "=f"(r) : "f"(x)); return r; }
__device__ __forceinline__ float bf_lo(uint32_t v) { return __uint_as_float(v << 16); }
__device__ __forceinline__ float bf_hi(uint32_t v) { return __uint_as_float(v & 0xffff0000u); }
__device__ __forceinline__ float sel4(int k, float a, float b, float c, float d) { return (k & 2) ? ((k & 1) ? d : c) : ((k & 1) ? b : a); }
constexpr float LOG2E = 1.4426950408889634f;
constexpr uint32_t ONES = 0x3f803f80u;

__device__ __forceinline__ void ln_stats(float sum, float sq, float& mean, float& den) {
    const float m = sum * (1.0f / 640.0f);
    const float var = fmaxf(fmaf(sq, 1.0f / 640.0f, -m * m), 0.0f);
    mean = bfr(m);
    den = bfr(sqrt_(bfr(bfr(var) + 1e-5f)));
}
__device__ __forceinline__ float sigmoidf_(float x) { return rcp(1.0f + ex2(-x * LOG2E)); }

#define TSTAMP(k) do {} while (0)
#define TST(k) do {} while (0)

#define CSTAMP(k) do {} while (0)
template <int N> __device__ __forceinline__ uint32_t lag(uint32_t sb, uint32_t z = 0) {
#pragma unroll
    for (int k = 0; k < N; k++) z = ldsvol(sb + S_ZERO + z);
    return z;
}
__device__ __forceinline__ void warm_mma(uint32_t& a, uint32_t& b) {
    asm volatile("mma.sync.aligned.m16n8k8.row.col.f16.f16.f16.f16 {%0,%1}, {%0,%1}, {%0}, {%0,%1};" : "+r"(a), "+r"(b) :: "memory");
}
#define KWNS2 20
#define KWNS 200
template <int STRIDE>
__device__ __forceinline__ float gather8(const char* p, uint32_t par) {
    uint32_t v[8];
    int guard = 0;
    do {
#pragma unroll
        for (int s = 0; s < 8; s++) v[s] = ldp32(p + s * STRIDE);
    } while ((chk8(v, par) & 1) && ++guard < SPIN_LIMIT);
    return sum8(v);
}
template <class F>
__device__ __forceinline__ void gather16(const char* p, uint32_t par, int k, F use) {
    uint32_t v[8], u[8];
    int guard = 0;
    bool again;
    do {
#pragma unroll
        for (int s = 0; s < 8; s++) v[s] = ldp32(p + s * 512);
#pragma unroll
        for (int s = 0; s < 8; s++) u[s] = ldp32(p + HALF + s * 512);
        const uint32_t stale = use(sum8(v) + sum8(u), ((v[0] ^ par) & 1) * 8);
        again = __any_sync(~0u, (or3(chk8(v, par), chk8(u, par), stale) & 1) != 0);
    } while (again & (++guard < SPIN_LIMIT));
    SWEEPS(k, guard - 1);
}

struct Params {
    const __nv_bfloat16 *x, *k, *v, *wr;
    __nv_bfloat16* out;
};
struct Maps { CUtensorMap k, v, vu, wq, wo, wg, wu, wd; };

constexpr int KV_BATCH_KEYS = 32 * 4096;

__device__ __forceinline__ void tma2d(uint32_t dst, const CUtensorMap* m, int c0, int c1, uint32_t bar, uint32_t bytes, uint64_t pol) {
    asm volatile("{\n .reg .pred p;\n elect.sync _|p, 0xffffffff;\n"
                 " @p mbarrier.arrive.expect_tx.shared::cta.b64 _, [%2], %6;\n"
                 " @p cp.async.bulk.tensor.2d.shared::cluster.global.mbarrier::complete_tx::bytes.L2::cache_hint [%0], [%1, {%3, %4}], [%2], %5;\n}"
                 :: "r"(dst), "l"(m), "r"(bar), "r"(c0), "r"(c1), "l"(pol), "r"(bytes) : "memory");
}
__device__ __forceinline__ void scrap_copy(uint32_t dst, const char* src, uint32_t bar) {
    asm volatile("{\n .reg .pred p;\n elect.sync _|p, 0xffffffff;\n"
                 " @p mbarrier.arrive.expect_tx.shared::cta.b64 _, [%2], 12288;\n"
                 " @p cp.async.bulk.shared::cluster.global.mbarrier::complete_tx::bytes [%0], [%1], 4096, [%2];\n"
                 " @p cp.async.bulk.shared::cluster.global.mbarrier::complete_tx::bytes [%0], [%1+4096], 4096, [%2];\n"
                 " @p cp.async.bulk.shared::cluster.global.mbarrier::complete_tx::bytes [%0], [%1+8192], 4096, [%2];\n}"
                 :: "r"(dst), "l"(src), "r"(bar) : "memory");
}
__device__ __forceinline__ void prefetch_l2(const void* p, uint32_t bytes) {
    asm volatile("{\n .reg .pred p;\n elect.sync _|p, 0xffffffff;\n @p cp.async.bulk.prefetch.L2.global [%0], %1;\n}" :: "l"(p), "r"(bytes) : "memory");
}
__device__ __forceinline__ uint64_t pol_first() { uint64_t p; asm("createpolicy.fractional.L2::evict_first.b64 %0, 1.0;" : "=l"(p)); return p; }
__device__ __forceinline__ uint64_t pol_normal() { uint64_t p; asm("createpolicy.fractional.L2::evict_normal.b64 %0, 1.0;" : "=l"(p)); return p; }
__device__ __forceinline__ bool utest(uint32_t bar, uint32_t parity) { return __all_sync(~0u, mbar_test(bar, parity)); }
__device__ __forceinline__ void uwait(uint32_t bar, uint32_t parity) {
    int n = 0;
    while (!__all_sync(~0u, mbar_try(bar, parity)) && ++n < SPIN_LIMIT) {}
}
template <int A, int B, int CNT> __device__ __forceinline__ void init_bars(uint32_t sb) {
#pragma unroll 1
    for (int k = A; k < B; k++)
        asm volatile("{\n .reg .pred p;\n elect.sync _|p, 0xffffffff;\n @p mbarrier.init.shared::cta.b64 [%0], %1;\n}" :: "r"(sb + S_BAR + 8 * k), "n"(CNT) : "memory");
}
__device__ __forceinline__ int first_key() { return (blockIdx.x >> 2) * 4096 + 3072 + (blockIdx.x & 3) * 256; }
__device__ __forceinline__ void load_tile(const CUtensorMap* m, uint32_t dst, uint32_t bar, uint32_t bytes, int key, uint64_t pol) { tma2d(dst, m, 0, 3 * key, bar, bytes, pol); }
__device__ __forceinline__ const char* unit_ptr(const Params& P, int n) {
    return (const char*)((n & 16) ? P.v : P.k) + (size_t)(first_key() + (n >> 5) * KV_BATCH_KEYS + (n & 15) * 16) * 384;
}
#define LSTAMP(k) do {} while (0)

__device__ __forceinline__ uint32_t k_place(uint32_t b, uint32_t s) { return s + 3 + 5 * (b & 1); }
__device__ __forceinline__ uint32_t v_place(uint32_t b, uint32_t s) { return s < 3 ? s : s + 8 - 8 * (b & 1); }
__device__ __forceinline__ void k_load(const Maps& M, uint32_t dst, uint32_t bar, int key8, uint64_t pol) {
    asm volatile("{\n .reg .pred p;\n elect.sync _|p, 0xffffffff;\n"
                 " @p mbarrier.arrive.expect_tx.shared::cta.b64 _, [%2], 6144;\n"
                 " @p cp.async.bulk.tensor.4d.shared::cluster.global.mbarrier::complete_tx::bytes.L2::cache_hint [%0], [%1, {0, 0, 0, %3}], [%2], %4;\n}"
                 :: "r"(dst), "l"(&M.k), "r"(bar), "r"(key8), "l"(pol) : "memory");
}
__device__ __forceinline__ int unit_key8(uint32_t n) { return first_key() / 8 + (n >> 4) * (KV_BATCH_KEYS / 8) + 2 * (n & 15); }
__device__ __forceinline__ void ring_load(const Maps& M, uint32_t sb, uint32_t b, uint32_t u, uint32_t pos) {
    if (u < 16) k_load(M, sb + pos * UNIT, sb + S_RING + 8 * pos, unit_key8(16 * b + u), pol_normal());
    else load_tile(&M.vu, sb + pos * UNIT, sb + S_FV + 4 * (pos & 6), UNIT, first_key() + b * KV_BATCH_KEYS + 16 * pos, pol_first());
}
__device__ __forceinline__ uint32_t token(bool p, uint32_t a, uint32_t n) {
    uint32_t v;
    asm volatile("{\n .reg .pred p;\n setp.ne.u32 p, %2, 0;\n mov.u32 %0, 0;\n @p atom.shared.exch.b32 %0, [%1], %3;\n}" : "=r"(v) : "r"(a), "r"((uint32_t)p), "r"(n) : "memory");
    return v;
}
__device__ __forceinline__ void place_load(const Maps& M, uint32_t sb, uint32_t n) {
    k_load(M, sb + k_place(n >> 4, 0) * SLOT + (n & 15) * UNIT, sb + S_FK + 4 * (n & 14), unit_key8(n), pol_first());
}
__device__ __forceinline__ void v_load(const Maps& M, uint32_t sb, uint32_t b, uint32_t s) {
    load_tile(&M.v, sb + v_place(b, s) * SLOT, sb + S_FV + 8 * s, SLOT, first_key() + b * KV_BATCH_KEYS + 32 * s, pol_first());
}
__device__ __forceinline__ bool due(uint32_t t) { return __all_sync(~0u, (int)(gtime32() * 16 - t) >= 0); }
__device__ __forceinline__ bool reached(uint32_t a, int v) { return __all_sync(~0u, ldsvol(a) >= v); }

__device__ __forceinline__ void stream_warp(const Params& P, const Maps& M, uint32_t sb, uint32_t lane) {
    const uint64_t pol = pol_first();
    const int bid = blockIdx.x, g = bid >> 3, i = bid & 7;
    const uint32_t wf = sb + S_WFULL;
    if (PF0 > 0 && !PFTOP) prefetch_l2(unit_ptr(P, 0), PF0 * UNIT);
    uint32_t tn = __shfl_sync(~0u, gtime32(), 0) * 16 - T_LEAD;
    auto pace = [&](uint32_t dt) {
        int k = 0;
        uint32_t now;
        do now = __shfl_sync(~0u, gtime32(), 0) * 16; while ((int)(now - tn) < 0 && ++k < SPIN_LIMIT);
        if ((int)(now - tn) > SLACK0) tn = now - SLACK0;
        tn += dt;
    };
#pragma unroll
    for (int k = 0; k < 10; k++) {
        if (k < 2) {
            if (k == 0) init_bars<26, 27, 1>(sb); else init_bars<27, 37, 1>(sb);
            asm volatile("fence.mbarrier_init.release.cluster;" ::: "memory");
            if (k == 1) { asm volatile("bar.arrive 2, %0;" :: "n"(NTHR) : "memory"); asm volatile("bar.sync 3, 128;" ::: "memory"); }
        }
        if (k >= WIN_W) uwait(wf + 8 * (k - WIN_W), 0);
        pace(TAUW * 5 / 2);
        if (k < 4) tma2d(sb + ST_WQ + 15360 * k, &M.wq, 384 * g + 192 * (k >> 1), 80 * i + 40 * (k & 1), wf + 8 * k, 15360, pol);
        else if (k < 6) tma2d(sb + ST_WG + 15360 * (k - 4), k == 4 ? &M.wg : &M.wu, 96 * g, 80 * i, wf + 8 * k, 15360, pol);
        else tma2d(sb + ST_WO + 15360 * (k - 6), &M.wo, 80 * i, 384 * g + 96 * (k - 6), wf + 8 * k, 15360, pol);
    }
#pragma unroll 1
    for (int n = 0; n < 16; n++) {
        if (n == 0 || n == 5 || n == 11) uwait(sb + S_RELW + (n == 0 ? 0 : n == 5 ? 8 : 16), 0);
        uwait(n < WIN_S ? wf + 8 * (10 - WIN_S + n) : sb + S_FV + 8 * ((n - WIN_S) ^ 8), 0);
        pace(max(min(2 * n + 2 - PF0, 2), 0) * TAU0);
        if (n < 8) { place_load(M, sb, 2 * n); place_load(M, sb, 2 * n + 1); }
        else if (n < 11) { ring_load(M, sb, 0, 2 * n, 2 * n - 16); ring_load(M, sb, 0, 2 * n + 1, 2 * n - 15); }
        else v_load(M, sb, 0, n - 8);
        if (n == 7) { pace(TAUW * 5 / 2); tma2d(sb + S_WD, &M.wd, 80 * i, 96 * g, wf + 80, 15360, pol); }
    }
    int nd = 0;
    uint32_t q[4];
#pragma unroll
    for (int r = 0; r < 4; r++) q[r] = sb + S_FV + 8 * (7 - r);
    tn -= TSH;
    uint32_t td = tn;
    uint32_t pos = 2;
#pragma unroll 1
    for (int m = 16; m < 64; m++) {
        const int b = m >> 4, j = m & 15;
        const char* src = unit_ptr(P, 2 * m);
        const uint32_t tok = sb + S_TOK + (j < 3 ? 4 * pos : j < 11 ? 24 + 4 * pos : 16 + 4 * j) + 4 * lane;
        static_assert(WIN_U <= 12, "a ring position has at most one token of the timetable");
        int k = 0;
        while (true) {
            const uint2 c = lds64(sb + S_KF);
            if (__all_sync(~0u, mbar_test(q[WIN_S - 1] & ~1u, q[WIN_S - 1] & 1) & (min((int)c.x + 1, (int)c.y) >= 16 * b + min(2 * j + 2 - WIN_U, 16))) || ++k >= SPIN_LIMIT) break;
        }
        uint32_t now;
        while (true) {
            now = __shfl_sync(~0u, gtime32(), 0) * 16;
            if ((int)(now - td) >= 0 || ++k >= SPIN_LIMIT) break;
            if (PSLEEP > 0 && (int)(td - now) > 16 * PSLEEP * 2) __nanosleep(PSLEEP);
        }
        const uint32_t mine = __ballot_sync(~0u, token(lane < (j < 11 ? 2 : 1), tok, 2 * m + lane) == 2 * m + lane);
        q[3] = q[2]; q[2] = q[1]; q[1] = q[0]; q[0] = sb + S_QRDY;
        if (j < 11) {
            if (mine & 1) ring_load(M, sb, b, 2 * j, pos); else prefetch_l2(src, UNIT);
            if (mine & 2) ring_load(M, sb, b, 2 * j + 1, pos + 1); else prefetch_l2(src + UNIT, UNIT);
            if (j >= 8) q[0] = (sb + S_FV + 8 * (j - 8)) | (b & 1);
        } else if (mine) { v_load(M, sb, b, j - 8); q[0] = (sb + S_FV + 8 * (j - 8)) | (b & 1); }
        else if (j - 8 >= VPF) prefetch_l2(src, SLOT);
        else {
            scrap_copy(sb + S_DUMMY, src, sb + S_DBAR + 8 * (nd & 3));
            q[0] = (sb + S_DBAR + 8 * (nd & 3)) | ((nd >> 2) & 1);
            nd++;
        }
        pos = j == 15 ? 2 : pos == 4 ? 0 : pos + 2;
        if ((int)(now - tn) > SLACK) tn = now - SLACK;
        tn += 2 * TAU;
        td = (int)(tn - now) > 2 * TMIN ? tn : now + 2 * TMIN;
        if (m >= 48 + JFREE) td = now + TFREE;
    }
#pragma unroll 1
    for (int m = max(nd - 4, 0); m < nd; m++) uwait(sb + S_DBAR + 8 * (m & 3), (m >> 2) & 1);
}

__host__ __device__ constexpr uint64_t bit_list(uint32_t m) { uint64_t r = 0; int n = 0; for (int k = 0; k < 12; k++) if ((m >> k) & 1) r |= (uint64_t)k << (4 * n++); return r; }
__device__ __forceinline__ float scaled(float s) { return bfr(bfr(s) * 0.07216878364870322f); }
__device__ __forceinline__ void probs(float s, uint32_t ps, uint32_t src, uint32_t ln) {
    const uint32_t q8 = ln >> 2, t4 = ln & 3;
    int key = __float_as_int(s);
    key ^= (key >> 31) & 0x7fffffff;
    key = __reduce_max_sync(~0u, key);
    key ^= (key >> 31) & 0x7fffffff;
    const float ml = __int_as_float(key) * LOG2E;
    sts16(ps + 64 * src + (q8 >> 1) * 16 + t4 * 4 + (q8 & 1) * 2, pack2(ex2(fmaf(s, LOG2E, -ml)), 0.f));
    stsf(ps + PS_MAX + 4 * src, ml);
}
template <int H> __device__ __forceinline__ uint32_t b_pos(uint32_t e) { const uint32_t h = e >= H, k = e - H * h; return h * 192 + (k & 6) * 24 + (k >> 3) * 4 + (k & 1) * 2; }
__device__ __forceinline__ uint32_t a_pos(uint32_t e) { const uint32_t h = e >= 40, k = e - 40 * h; return (k & 6) * 24 + (k >> 3) * 8 + h * 4 + (k & 1) * 2; }
__device__ __forceinline__ uint32_t q_pos(uint32_t d) { const uint32_t s = 3 * ((d >> 4) & 3) + (d >> 6); return s * 32 + (d & 6) * 4 + ((d >> 3) & 1) * 4 + (d & 1) * 2; }
__device__ __forceinline__ uint32_t k_off(uint32_t ln) { return (ln & 8) * 384 + (ln & 7) * 128 + (((ln & 7) ^ (ln >> 4)) << 4); }

#define HSTAMP(k) do {} while (0)
__device__ __forceinline__ char* xwindow() { return reinterpret_cast<char*>((reinterpret_cast<uintptr_t>(g_x) + (2u << 20) - 1) & ~(uintptr_t)((2u << 20) - 1)); }

struct XPtr {
    uint32_t lo, hi;
    __device__ __forceinline__ explicit XPtr(char* p) : lo((uint32_t)(uintptr_t)p), hi((uint32_t)((uintptr_t)p >> 32)) {}
    __device__ __forceinline__ XPtr(uint32_t l, uint32_t h) : lo(l), hi(h) {}
    __device__ __forceinline__ XPtr operator+(uint32_t o) const { return XPtr(lo + o, hi); }
    __device__ __forceinline__ operator char*() const { uint64_t p; asm("mov.b64 %0, {%1, %2};" : "=l"(p) : "r"(lo), "r"(hi)); return (char*)p; }
};
__device__ __forceinline__ void keep(XPtr& v) { keep(v.lo); }

__device__ __forceinline__ void side_warp(uint32_t sb) {
    const uint32_t bid = blockIdx.x, g = bid >> 3, i = bid & 7, P = pairG(0, 0, i);
    char* p = xwindow() + P * 8192 + (g >> 3) * HALF + (g & 7) * 512 + 448;
    uint32_t best[2] = {~0u, ~0u};
    asm volatile("st.relaxed.gpu.global.b32 [%0], 1;" :: "l"(p) : "memory");
    asm volatile("st.relaxed.gpu.global.b32 [%0], 1;" :: "l"(p + COPY) : "memory");
#pragma unroll 1
    for (int r = 0; r < 64; r++) {
        if (r >= 4 && !(r & 1) && min(best[0], best[1]) < 380 && max(best[0], best[1]) > min(best[0], best[1]) + 80) break;
        uint32_t c0, c1, v;
        asm volatile("mov.u32 %0, %clock;" : "=r"(c0) :: "memory");
        asm volatile("atom.relaxed.gpu.global.exch.b32 %0, [%1], 0;" : "=r"(v) : "l"(p + (r & 1) * COPY) : "memory");
        asm volatile("{\n .reg .pred q;\n setp.eq.u32 q, %1, 0x13579bdf;\n mov.u32 %0, 0;\n @!q mov.u32 %0, %clock;\n}" : "=r"(c1) : "r"(v) : "memory");
        if (r & 1) best[1] = min(best[1], c1 - c0); else best[0] = min(best[0], c1 - c0);
    }
    stsvol(sb + S_SIDE, 1 + ((best[1] < best[0]) ^ (__popc(P & PMASK) & 1)));
}

template <int N>
__device__ __forceinline__ void hop_a(const char* src, uint32_t par, uint32_t dst, bool st, int k) {
    uint2 v[N][4];
    float e[4], rl;
    int guard = 0;
    bool again;
    do {
#pragma unroll
        for (int s = 0; s < 4 * N; s++) v[s / 4][s % 4] = ldp64(src + (s / 4) * 256 + (s % 4) * 1024);
        again = __any_sync(~0u, ((chk4(v[0], par) | chk4(v[N - 1], par)) & 1) != 0);
        const int M = max(max((int)v[0][0].x, (int)v[0][1].x), max((int)v[0][2].x, (int)v[0][3].x)) - 254;
#pragma unroll
        for (int s = 0; s < 4; s++) e[s] = __int_as_float(max((int)v[0][s].x - M, 0) << 22);
        rl = rcp(fmaf(e[0], asf(v[0][0].y), e[1] * asf(v[0][1].y)) + fmaf(e[2], asf(v[0][2].y), e[3] * asf(v[0][3].y)));
#pragma unroll
        for (int s = 0; s < 4; s++) e[s] = __shfl_sync(~0u, e[s], 24);
        keep(rl);
    } while (again & (++guard < SPIN_LIMIT));
    rl = __shfl_sync(~0u, rl, 24);
#pragma unroll
    for (int n = 0; n < N; n++) {
        const float o0 = fmaf(e[0], asf(v[n][0].x), e[1] * asf(v[n][1].x)) + fmaf(e[2], asf(v[n][2].x), e[3] * asf(v[n][3].x));
        const float o1 = fmaf(e[0], asf(v[n][0].y), e[1] * asf(v[n][1].y)) + fmaf(e[2], asf(v[n][2].y), e[3] * asf(v[n][3].y));
        sts32_if(st, dst + 192 * n, pack2(o0 * rl, o1 * rl));
    }
    SWEEPS(k, guard - 1);
    __syncwarp();
}

__device__ __forceinline__ void score_warp(const Maps& M, uint32_t sb, uint32_t h, uint32_t ln) {
    const uint32_t lane0 = ln;
    uwait(sb + S_QRDY, 0);
    const uint32_t q8 = ln >> 2;
    const uint32_t k0 = k_off(ln);
    uint32_t pos = h + 6, bar = sb + S_FK, par = 0, phases = 0;
    uint2 q = lds64(sb + S_QS + 8 * ln), qh = lds64(sb + S_QS + 8 * ln + 256);
    auto first_round = [&](uint32_t b, uint32_t ln) {
        uwait(sb + S_RELR, b & 1);
        const uint32_t u = h + 2 * ln, p = u < 4 ? u + 2 : u - 4;
        uint32_t todo = __ballot_sync(~0u, token(ln < 3, sb + S_TOK + 4 * p, 32 * b + 32 + u) == 32 * b + 32 + u);
#pragma unroll 1
        for (uint32_t r = h; todo; todo >>= 1, r += 2) if (todo & 1) ring_load(M, sb, b + 1, r, r < 4 ? r + 2 : r - 4);
    };
#pragma unroll 1
    for (uint32_t n = h; n < 64; n += 2) {
        HSTAMP(0);
        const uint32_t ua = sb + pos * UNIT;
        if (!__all_sync(~0u, mbar_try(bar, par))) uwait(bar, par);
        HSTAMP(1);
        float acc[2][4] = {};
        uint32_t mine = 0;
        const uint32_t id = n + (n & 48) + 6;
#pragma unroll
        for (int s = 0; s < 12; s++) {
            uint32_t kf[4];
            ldsm4(kf, (k0 ^ (32 * (s / 3))) + (ua + 1024 * (s % 3)));
            if (s == 11) {
                __syncwarp();
                mine = token(ln == 0 && n >= 16, sb + S_TOK + 24 + 4 * pos, id);
                stsvol(sb + S_KF + 4 * h, n + 1);
            }
            const bool m = q8 == (s & 7);
            mmaA(acc[s & 1], kf, m ? (s < 8 ? q.x : qh.x) : 0u, m ? (s < 8 ? q.y : qh.y) : 0u);
        }
        const uint32_t pos0 = pos;
        const bool last = (n & 14) == 14;
        pos = last ? h + 2 : n >= 16 && pos >= 4 ? h : pos + 2;
        bar = n >= 14 ? sb + S_RING + 8 * pos : bar + 8;
        par = n >= 14 ? (phases >> pos) & 1 : 0;
        phases ^= n >= 14 ? 1u << pos : 0;
        const float w0 = (acc[0][0] + acc[0][1]) + (acc[1][0] + acc[1][1]), w1 = (acc[0][2] + acc[0][3]) + (acc[1][2] + acc[1][3]);
        HSTAMP(2);
        if (__any_sync(~0u, mine == id)) ring_load(M, sb, n >> 4, (n & 15) + 6, pos0);
        HSTAMP(3);
        float s = ((ln & 1) ? w1 : w0) + __shfl_xor_sync(~0u, (ln & 1) ? w0 : w1, 1);
        s += __shfl_xor_sync(~0u, s, 2);
        sts_hi16(sb + S_SC + (((n & 12) >> 1) + h) * 64 + (n & 2) * 2 + (ln & 29) * 2, scaled(s));
        if (last) {
            __syncwarp();
            arrive_if(ln == 0, sb + S_SCO);
            const uint32_t b = n >> 4, ln = lane0 + lag<1>(sb);
            if (b > 0) {
                uwait(sb + S_RELK, (b - 1) & 1);
                if (h == 0) LSTAMP(64 + 2 * b);
                const uint32_t sl = 3 + h + 2 * ln, idv = 32 * b + 16 + 2 * sl;
                uint32_t todo = __ballot_sync(~0u, token(sl < 8, sb + S_TOK + 48 + 4 * sl, idv) == idv);
#pragma unroll 1
                for (uint32_t r = 3 + h; todo; todo >>= 1, r += 2) if (todo & 1) v_load(M, sb, b, r);
                const uint32_t g = blockIdx.x >> 3, pr = pairL(RA, 1, g), side = ldsvol(sb + S_SIDE);
                const char* src = xwindow() + pr * 8192 + ((side ^ 1 ^ __popc(pr & PMASK)) & 1) * COPY + h * HALF + 8 * min(ln, 24u);
                uwait(sb + S_RELV, (b - 1) & 1);
                __nanosleep(HOP1_NS);
#pragma unroll 1
                for (uint32_t r = 0; r < 4; r += 2) {
                    hop_a<2>(src + 256 * r, b & 1, sb + S_OS + 192 * (4 * h + r) + 96 + 4 * ln, ln < 24, 25);
                    if (r == RELR_AT && b < 3) first_round(b, ln);
                }
                arrive_if(ln == 0, sb + S_OS1);
            } else first_round(0, ln);
            q = lds64(sb + S_QS + 24 * ((n + 2) & 48) + 8 * ln); qh = lds64(sb + S_QS + 24 * ((n + 2) & 48) + 8 * ln + 256);
        }
    }
}

__global__ void __launch_bounds__(NTHR, 1)
fused_kernel(const Params P, const __grid_constant__ Maps M) {
    extern __shared__ __align__(1024) unsigned char smem[];
    const uint32_t sb = smem_u32(smem);
    const int tid = threadIdx.x, bid = blockIdx.x;
    if (PFTOP && tid == 0) {
        if (PFTOP == 2) asm volatile("prefetch.tensormap [%0];" :: "l"(&M.wq) : "memory");
        asm volatile("cp.async.bulk.prefetch.L2.global [%0], %1;" :: "l"(unit_ptr(P, 0)), "r"(PF0 * UNIT) : "memory");
    }
    const int w = __shfl_sync(~0u, tid >> 5, 0), lane = tid & 31;

    if (w >= 8) {
        asm volatile("setmaxnreg.dec.sync.aligned.u32 " REG_LO ";");
        if (w == 8) {
            stream_warp(P, M, sb, lane);
        } else {
            if (PFMAP && w == 11 && lane < 8) asm volatile("prefetch.tensormap [%0];" :: "l"(&M.k + lane) : "memory");
            if (w == 9) { init_bars<0, 3, 2>(sb); init_bars<3, 8, 1>(sb); init_bars<16, 22, 1>(sb); }
            else if (w == 10) { init_bars<8, 16, 2>(sb); init_bars<22, 26, 1>(sb); }
            else { init_bars<37, 38, 1>(sb); init_bars<38, 40, 8>(sb); init_bars<40, 41, 1>(sb); init_bars<41, 44, 8>(sb); init_bars<44, 46, 2>(sb); stsvol(sb + S_ZERO + 4 * lane, 0); if (lane < 16) stsvol(sb + S_LN + 4 * lane, 0); }
            asm volatile("fence.mbarrier_init.release.cluster;" ::: "memory");
            asm volatile("bar.arrive 3, 128;" ::: "memory");
            asm volatile("bar.sync 2, %0;" :: "n"(NTHR) : "memory");
            if (w < 11) score_warp(M, sb, w - 9, lane);
            else {
                if (lane == 0) side_warp(sb);
                __syncwarp();
                uint32_t a = 0, b = 0;
                int k = 0;
                while (ldsvol(sb + S_GATE) == 0 && ++k < SPIN_LIMIT) { warm_mma(a, b); __nanosleep(KWNS); }
                uint4* d = reinterpret_cast<uint4*>(reinterpret_cast<char*>(g_s) + XS + bid * 7680) + lane;
                const uint4 z = make_uint4(0, 0, 0, 0);
#pragma unroll 1
                for (int u = 0; u < 15; u++) d[32 * u] = z;
                d = reinterpret_cast<uint4*>(reinterpret_cast<char*>(g_s) + XS2 + bid * 768) + lane;
                d[0] = z;
                if (lane < 16) d[32] = z;
                const uint32_t side = (ldsvol(sb + S_SIDE) & 1) ^ 1, g = bid >> 3, i = bid & 7;
                const XPtr gx(xwindow());
                auto nearp = [&](uint32_t pr) { return gx.lo + pr * 8192 + ((side ^ __popc(pr & PMASK)) & 1) * COPY; };
                const uint32_t own = (i >> 2) * HALF + (i & 3) * 1024 + (lane & 7) * 128;
                const uint32_t pAC = nearp(pairL(lane >> 4, (lane >> 3) & 1, g)) + own, pE = nearp(pairL(RE, (lane >> 3) & 1, g)) + own;
                const uint32_t pG = nearp(pairG((lane >> 2) & 1, (lane >> 3) & 1, i)) + min(lane & 3, 2) * 128;
                uint32_t tr = 0, tk = 0, ph = 0, src = g + (lane >> 4), seen = 0, n = 16, cs = 0;
                bool go = false, first = true;
                while (n < 64 && ++k < SPIN_LIMIT) {
                    const uint32_t now = __shfl_sync(~0u, gtime32(), 0) * 16;
                    if (!go && utest((n & 15) < KRE_EARLY ? sb + S_RELK : sb + S_RELV, ((n >> 4) & 1) ^ 1)) { go = true; if ((int)(now - tk) > 0 || !(n & 15)) tk = now; }
                    if (go && (int)(now - tk) >= 0) {
                        place_load(M, sb, (n & 16) ? n : (n & 48) | ((n + 10) & 15));
                        tk += n >= 48 ? KRE_TAU3 : (n & 15) < KRE_N1 ? KRE_TAU1 : KRE_TAU;
                        n++;
                        go = (n & 15) != 0 && (n & 15) != KRE_EARLY;
                        if (!(n & 15)) LSTAMP(63 + (n >> 3));
                    } else if (first || (int)(now - tr) >= 0) {
                        first = false;
                        tr = now + RFR_TAU;
                        b |= seen & a;
                        warm_mma(a, b);
                        if (RFR_ON) seen = ldp32(XPtr(ph == 0 ? pAC : ph == 1 && lane < 16 ? pE : pG + (src & 8) * (HALF / 8) + (src & 7) * 512, gx.hi));
                        if (RFR_XS && (++cs & (RFR_XS - 1)) < 2) {
                            const uint32_t l = lane + 32 * (cs & 1);
                            *reinterpret_cast<volatile uint32_t*>(reinterpret_cast<char*>(g_s) + (l < 60 ? XS + bid * 7680 + 128 * l : XS2 + bid * 768 + 128 * (l - 60))) = 0;
                        }
                        src += ph == 0 ? 0 : ph == 1 ? 2 : 1;
                        ph = ph == 2 ? 0 : ph + 1;
                    } else __nanosleep(KWNS2);
                }
                while (ldsvol(sb + S_GATE) < 6 && ++k < SPIN_LIMIT) { warm_mma(a, b); __nanosleep(KWNS); }
                if (a | b) stsvol(sb + S_GATE, 6);
            }
        }
        return;
    }
    asm volatile("setmaxnreg.inc.sync.aligned.u32 " REG_HI ";");

    const int g = bid >> 3, i = bid & 7;
    const int g8 = lane >> 2, t = lane & 3;
    char* const gs = reinterpret_cast<char*>(g_s);
    const XPtr gx(xwindow());

    auto zero_words = [&] {
        const uint4 z = make_uint4(0, 0, 0, 0);
        const uint32_t c = (tid >> 6) & 1, cp = (tid >> 7) * COPY, k = (tid & 63) * 16;
        *reinterpret_cast<uint4*>((char*)(gx + pairL(RA, c, g) * 8192 + (i >> 2) * HALF + (i & 3) * 1024 + cp + k)) = z;
        *reinterpret_cast<uint4*>((char*)(gx + pairL(RC, c, g) * 8192 + (i >> 2) * HALF + (i & 3) * 1024 + cp + k)) = z;
        *reinterpret_cast<uint4*>((char*)(gx + pairL(RE, c, g) * 8192 + (i >> 2) * HALF + (i & 3) * 1024 + cp + k)) = z;
        if ((tid & 31) < 24) *reinterpret_cast<uint4*>((char*)(gx + pairG((tid >> 5) & 1, c, i) * 8192 + (g >> 3) * HALF + (g & 7) * 512 + cp + (tid & 31) * 16)) = z;
    };
    if (ZPOS == 0) zero_words();
    W80 Wq[6], Wgu[3];
    uint32_t Wo[5][3][4];
    if (w < 4) {
        const uint32_t* xp = reinterpret_cast<const uint32_t*>(P.x + 640 * w);
        float sum = 0.f, sq = 0.f;
#pragma unroll
        for (int u = 0; u < 10; u++) { uint32_t v = xp[lane + 32 * u]; float a = bf_lo(v), b = bf_hi(v); sum += a + b; sq += a * a + b * b; }
#pragma unroll
        for (int o = 16; o > 0; o >>= 1) { sum += __shfl_xor_sync(~0u, sum, o); sq += __shfl_xor_sync(~0u, sq, o); }
        float mean, den; ln_stats(sum, sq, mean, den);
        if (lane < 20) {
            const uint2 v = reinterpret_cast<const uint2*>(P.x + 640 * w + 80 * i)[lane];
            sts64(sb + S_X0 + 160 * w + 8 * lane, v.x, v.y);
            sts32(sb + S_L0 + 384 * w + b_pos<40>(4 * lane), pack2(__fdiv_rn(bfr(bf_lo(v.x) - mean), den), __fdiv_rn(bfr(bf_hi(v.x) - mean), den)));
            sts32(sb + S_L0 + 384 * w + b_pos<40>(4 * lane + 2), pack2(__fdiv_rn(bfr(bf_lo(v.y) - mean), den), __fdiv_rn(bfr(bf_hi(v.y) - mean), den)));
        }
    } else if (w == 4) {
        const uint32_t* xp = reinterpret_cast<const uint32_t*>(P.wr);
        float sum = 0.f;
#pragma unroll
        for (int u = 0; u < 10; u++) { uint32_t v = xp[lane + 32 * u]; sum += bf_lo(v) + bf_hi(v); }
#pragma unroll
        for (int o = 16; o > 0; o >>= 1) sum += __shfl_xor_sync(~0u, sum, o);
        if (lane == 0) stsf(sb + S_SWR, sum);
        if (lane < 20) {
            const uint2 v = reinterpret_cast<const uint2*>(P.wr + 80 * i)[lane];
            sts32(sb + S_XA + 576 + a_pos(4 * lane), v.x); sts32(sb + S_XA + 576 + a_pos(4 * lane + 2), v.y);
            sts32(sb + S_XA + a_pos(4 * lane), ONES); sts32(sb + S_XA + a_pos(4 * lane + 2), ONES);
        }
    }
    asm volatile("bar.sync 2, %0;" :: "n"(NTHR) : "memory");
    auto frag = [](uint32_t (&a)[4], uint32_t p, int pitch) {
        const uint32_t r0 = lds32(p), r1 = lds32(p + pitch), r2 = lds32(p + 2 * pitch), r3 = lds32(p + 3 * pitch);
        a[0] = __byte_perm(r0, r1, 0x5410); a[1] = __byte_perm(r0, r1, 0x7632);
        a[2] = __byte_perm(r2, r3, 0x5410); a[3] = __byte_perm(r2, r3, 0x7632);
    };
    mbar_wait(sb + S_WFULL + 16 * (w >> 2), 0);
    mbar_wait(sb + S_WFULL + 16 * (w >> 2) + 8, 0);
    {
        const uint32_t p = sb + ST_WQ + (w >> 2) * 30720 + (2 * t) * 384 + (48 * (w & 3) + 2 * g8) * 2;
#pragma unroll
        for (int r = 0; r < 10; r++)
#pragma unroll
            for (int m = 0; m < 3; m++) {
                const uint32_t q = p + ((r & 1) * 40 + (r >> 1) * 8) * 384 + 32 * m, r0 = lds32(q), r1 = lds32(q + 384);
                (r < 8 ? Wq[2 * m].a[(r >> 2) & 1][r & 3] : Wq[2 * m].c[r & 1]) = __byte_perm(r0, r1, 0x5410);
                (r < 8 ? Wq[2 * m + 1].a[(r >> 2) & 1][r & 3] : Wq[2 * m + 1].c[r & 1]) = __byte_perm(r0, r1, 0x7632);
            }
    }
    __syncwarp();
    if (lane == 0) mbar_arrive(sb + S_RELW);
    TSTAMP(1);
    {
        char* d = gs + XS + bid * 7680 + (w >> 2) * 3840 + (48 * (w & 3) + 2 * g8) * 4;
        float acc[6][4] = {};
        mul80(acc, Wq, lds128(sb + S_L0 + 48 * lane), lds32(sb + S_L0 + 48 * lane + 16));
#pragma unroll
        for (int m = 0; m < 6; m += 2) stp64(d + t * 768 + 32 * m, acc[m][0] + acc[m][3], acc[m + 1][0] + acc[m + 1][3], 1);
        float sum[6][4] = {};
        mul80(sum, Wq, make_uint4(ONES, ONES, ONES, ONES), ONES);
        if (t == 0)
#pragma unroll
            for (int m = 0; m < 6; m += 2) stp64(d + 4 * 768 + 32 * m, sum[m][0] + sum[m][3], sum[m + 1][0] + sum[m + 1][3], 1);
    }
    mbar_wait(sb + S_WFULL + 32, 0);
    mbar_wait(sb + S_WFULL + 40, 0);
    const uint32_t oct = 3 * (w >> 1) + (w & 1), oct2 = 3 * (w >> 1) + 2;
    {
        const uint32_t p = sb + ST_WG + ((lane & 7) + 40 * ((lane >> 3) & 1) + 8 * (lane >> 4)) * 192;
#pragma unroll
        for (int T = 0; T < 3; T++) {
            const uint32_t q = p + (T < 2 ? T * 15360 + 16 * oct : (w & 1) * 15360 + 16 * oct2);
            ldsm4t(Wgu[T].a[0], q); ldsm4t(Wgu[T].a[1], q + 16 * 192); ldsm2t(Wgu[T].c, q + 32 * 192);
        }
        float sum[3][4] = {};
        mul80(sum, Wgu, make_uint4(ONES, ONES, ONES, ONES), ONES);
        if (t < 3) stp32(gs + XS2 + bid * 768 + (t < 2 ? 64 * oct + 4 * t : 64 * oct2 + 4 * (w & 1)) + 8 * g8,
                         sel4(t, sum[0][0] + sum[0][3], sum[1][0] + sum[1][3], sum[2][0] + sum[2][3], 0.f), 1);
    }
    __syncwarp();
    if (lane == 0) mbar_arrive(sb + S_RELW + 8);
    const char* srcS = gs + XS + g * 8 * 7680 + (i >> 2) * 3840 + min(tid, 191) * 4;
    uint32_t vs[5][8];
#pragma unroll
    for (int b = 0; b < 5; b++)
#pragma unroll
        for (int s = 0; s < 8; s++) vs[b][s] = LOOK1 ? ldp32(srcS + b * 768 + s * 7680) : 0;
    uint32_t cs2[8];
#pragma unroll
    for (int s = 0; s < 8; s++) cs2[s] = LOOK2 ? ldp32(gs + XS2 + (g * 8 + s) * 768 + min(tid, 191) * 4) : 0;
    __syncwarp();
    mbar_wait(sb + S_WFULL + 48 + 8 * (w >> 1), 0);
    {
        const uint32_t po = sb + ST_WO + (48 * w + 12 * t) * 160 + 4 * g8;
#pragma unroll
        for (int s = 0; s < 3; s++)
#pragma unroll
            for (int m = 0; m < 5; m++) frag(Wo[m][s], po + 4 * s * 160 + 32 * m, 160);
    }
    __syncwarp();
    if (lane == 0) mbar_arrive(sb + S_RELW + 16);
    if (ZPOS == 1) zero_words();
    if (tid < 192) {
        int guard = 0;
        while (((or3(chk8(vs[0], 1), chk8(vs[1], 1), chk8(vs[2], 1)) | chk8(vs[3], 1) | chk8(vs[4], 1)) & 1) && ++guard < SPIN_LIMIT) {
#pragma unroll
            for (int b = 0; b < 5; b++)
#pragma unroll
                for (int s = 0; s < 8; s++) vs[b][s] = ldp32(srcS + b * 768 + s * 7680);
        }
        const uint32_t qpos = sb + S_QS + q_pos(tid);
#pragma unroll
        for (int b = 0; b < 4; b++) {
            sts_hi16(qpos + 384 * b, bfr(sum8(vs[b])));
        }
        stsf(sb + S_CSQ + 4 * tid, sum8(vs[4]));
    }
    if (tid < 192) stsf(sb + S_CSGU + 4 * tid, (chk8(cs2, 1) & 1) ? gather8<768>(gs + XS2 + g * 8 * 768 + tid * 4, 1) : sum8(cs2));
    __syncwarp();
    bar_main();
    arrive_if(tid == 0, sb + S_QRDY);
    if (ZPOS == 2) zero_words();
    TSTAMP(2);

    uint32_t side;
    { int k = 0; while ((side = ldsvol(sb + S_SIDE)) == 0 && ++k < SPIN_LIMIT) {} }
    const uint32_t td = __shfl_sync(~0u, tid, lane);
    const uint32_t wp = __shfl_sync(~0u, tid >> 5, 0);
    const uint32_t cc = wp >= 3;
    auto uni = [](uint32_t v) { return __shfl_sync(~0u, v, 0); };
    auto pin = [&](uint32_t v) { return __shfl_sync(~0u, v, td); };
    auto nearp = [&](uint32_t P) { return gx.lo + P * 8192 + ((side ^ 1 ^ __popc(P & PMASK)) & 1) * COPY; };
    constexpr uint32_t COL = 32 * 8192;
    const uint32_t ownL = gx.lo + (i >> 2) * HALF + (i & 3) * 1024, ownG = gx.lo + (g >> 3) * HALF + (g & 7) * 512;
    const uint32_t uPubA = uni(ownL + pairL(RA, 0, g) * 8192 + (wp >> 1) * 256 + (wp & 1) * 96), uPolA = uni(nearp(pairL(RA, 0, g)) + (wp >> 2) * HALF + (wp & 3) * 256);
    const uint32_t uPubB = uni(ownG + pairG(0, cc, i) * 8192), uPolB = uni(nearp(pairG(0, cc, i)));
    const uint32_t uPubC = uni(ownL + pairL(RC, 0, g) * 8192), uPolC = uni(nearp(pairL(RC, wp < 6 ? cc : 0, g)));
    const uint32_t uPubD = uni(ownG + pairG(1, 0, i) * 8192 + (wp < 7 ? 32 * wp : 256)), uPolD = uni(nearp(pairG(1, cc, i)));
    const uint32_t uPubE = uni(ownL + pairL(RE, 0, g) * 8192), uPolE = uni(nearp(pairL(RE, i >> 2, g)));
    const uint32_t uOS = uni(sb + S_OS + 192 * wp);
    auto xp = [&](uint32_t lo) { return (char*)XPtr(lo, gx.hi); };
#define IDS() __syncwarp(); const uint32_t z0_ = lag<1>(sb), z_ = td + z0_; const uint32_t ln = z_ & 31, q8 = ln >> 2, t4 = z_ & 3, n96 = z_ - 96 * cc, n80 = min(n96, 79u); (void)q8; (void)t4; (void)n80; (void)ln

    auto vaddr = [&](uint32_t (&voff)[3]) {
        const uint32_t ln = td & 31;
        const uint32_t key3 = 3 * ((ln & 7) + 2 * (ln & 8) + ((ln >> 1) & 8));
#pragma unroll
        for (int T = 0; T < 3; T++) {
            const uint32_t u = 3 * wp + T, r = key3 + (u >> 3);
            voff[T] = r * 128 + (((u ^ r) & 7) << 4);
        }
    };
    auto values = [&](uint32_t (&vf)[8][3][4], float (&acc)[3][4], auto order, auto step, uint32_t ps, uint32_t col, uint32_t par) {
        const uint32_t ln = td & 31, q8 = ln >> 2, t4 = td & 3;
        const uint4 p = lds128(ps + 16 * ln);
        float f0 = 0.f, f1 = 0.f, r3 = 0.f;
#pragma unroll
        for (int k = 0; k < 12; k++) acc[k / 4][k % 4] = 0.f;
        int M = 0;
#pragma unroll
        for (int k = 0; k < 8; k++) {
            step(k);
            const int s = (order.value >> (4 * k)) & 7;
            const bool m = (q8 >> 1) == (s >> 1);
            const uint32_t b0 = m ? ((s & 1) ? p.z : p.x) : 0u, b1 = m ? ((s & 1) ? p.w : p.y) : 0u;
#pragma unroll
            for (int T = 0; T < 3; T++) mmaA(acc[T], vf[s][T], b0, b1);
            if (k == FSTEP) {
                const uint2 mp = lds64(ps + PS_MAX + 8 * t4);
                M = __reduce_max_sync(~0u, __float2int_ru(fmaxf(asf(mp.x), asf(mp.y))));
                f0 = ex2(asf(mp.x) - (float)M); f1 = ex2(asf(mp.y) - (float)M);
                float l[4] = {};
                mma16816(l, ONES, ONES, ONES, ONES, p.x, p.y); mma16816(l, ONES, ONES, ONES, ONES, p.z, p.w);
                r3 = fmaf(f0, l[0], f1 * l[1]);
            }
        }
        CSTAMP(25);
        char* pubA = xp(uPubA + col * COL + 32 * t4 + 4 * q8);
        const float r0 = fmaf(f0, acc[0][0], f1 * acc[0][3]), r1 = fmaf(f0, acc[1][0], f1 * acc[1][3]), r2 = fmaf(f0, acc[2][0], f1 * acc[2][3]);
        const bool hi = t4 & 2, od = t4 & 1;
        const float u0 = (hi ? r2 : r0) + __shfl_xor_sync(~0u, hi ? r0 : r2, 2), u1 = (hi ? r3 : r1) + __shfl_xor_sync(~0u, hi ? r1 : r3, 2);
        const float o = (od ? u1 : u0) + __shfl_xor_sync(~0u, od ? u0 : u1, 1);
        stp32_if(t4 < 3 || ((wp & 1) && q8 < 2), pubA, ln == 3 ? __int_as_float(2 * M) : o, par);
    };

    uint32_t left[36] = {};
#pragma unroll 1
    for (int ch = 0; ch < 5; ch++) {
        const uint32_t par0 = (ch + 1) & 1, par1 = ch & 1;
        uint32_t voff[3], vf[8][3][4];
        float acc_[3][4];
        if (ch < 4) {
            vaddr(voff);
            mbar_wait(sb + S_SCO, par1);
            if (ch == 0) mbar_wait(sb + S_WFULL + 80, 0);
            TST(0);
            auto ldw = [&](int s) {
                mbar_wait(sb + S_FV + 8 * s, par1);
#pragma unroll
                for (int T = 0; T < 3; T++) ldsm4t(vf[s][T], voff[T] + (sb + v_place(ch, s) * SLOT));
            };
            probs(bf_lo(lds16(sb + S_SC + 2 * td)), sb + S_PS, wp, td & 31);
            ldw(0); ldw(1); ldw(2);
            bar_main();
            arrive_if(td == 0, sb + S_RELR);
            values(vf, acc_, std::integral_constant<uint32_t, 0x76543210>(), [&](int s) {
                if (s >= 3) ldw(s);
            }, sb + S_PS, 0, par0);
            TST(1);
            CSTAMP(5);
            if (ch > 0) mbar_wait(sb + S_OS1, par0);
        } else {
#pragma unroll
            for (int s = 0; s < 36; s++) vf[s / 12][(s / 4) % 3][s & 3] = left[s];
        }
        const bool has0 = ch < 4, has1 = ch > 0;
        const bool actc = wp < 6 && (cc ? has1 : has0);
        const uint32_t parc = cc ? par1 : par0;
        const uint32_t pub0 = has0 ? par0 : 0;
        uint32_t rr, pubB;
        {
            IDS();
            const uint32_t c = ch == 4;
            const uint32_t osa = pin(uOS + 96 * c + 4 * ln), oa = pin(uOS + 48 * (q8 & 2) + 24 * t4), ra = pin(sb + S_RED + 640 * wp + 320 * (t4 & 1) + 8 * q8);
            rr = pin(sb + S_RED + 320 * cc + 4 * n80); pubB = pin(uPubB + 4 * n80);
            hop_a<1>(xp(uPolA + c * COL + 8 * min(ln, 24u) + lag<DELAY_L>(sb, z0_)), pub0, osa, ln < 24, 5 * ch);
            TST(2);
            CSTAMP(6);
            float acc[5][4] = {};
            const uint2 b0 = lds64(oa), b1 = lds64(oa + 8), b2 = lds64(oa + 16);
#pragma unroll
            for (int m = 0; m < 5; m++) mmaA(acc[m], Wo[m][0], b0.x, b0.y);
#pragma unroll
            for (int m = 0; m < 5; m++) mmaA(acc[m], Wo[m][1], b1.x, b1.y);
#pragma unroll
            for (int m = 0; m < 5; m++) mmaA(acc[m], Wo[m][2], b2.x, b2.y);
#pragma unroll
            for (int m = 0; m < 5; m++) { stsf(ra + 64 * m, acc[m][0]); stsf(ra + 64 * m + 4, acc[m][2]); }
        }
        CSTAMP(7);
        uint32_t xr, fl, pubC, pubC2;
        auto prepC = [&](uint32_t ln) {
            const uint32_t q8 = ln >> 2, t4 = ln & 3;
            xr = pin(sb + S_XB + 48 * (ln & 15));
            pubC = pin(uPubC + (t4 & 1) * COL + 192 * (wp >> 1) + 64 * (wp & 1) + 8 * q8);
            pubC2 = pin(uPubC + (t4 & 1) * COL + ((t4 & 2) ? 192 * (wp >> 1) + 128 + 4 * (wp & 1) + 8 * q8 : 768 + 2 * ((q8 + 1) & 6)));
            fl = pin(((t4 & 1) ? par1 : pub0) | (t4 >= 2 || (wp == 7 && q8 < 4 && q8 != 2 - t4) ? 2 : 0));
        };
        auto stats = [&](uint32_t xa, const uint4& b, uint32_t b4) {
            float a0[4] = {}, a1[4] = {}, a2[4] = {};
            const uint4 p0 = lds128(xa), p1 = lds128(xa + 16);
            const uint2 p2 = lds64(xa + 32);
            mmaV(a0, p0, b.x, b.y); mmaV(a1, p1, b.z, b.w); mma8(a2, p2.x, p2.y, b4);
            return ((a0[0] + a0[3]) + (a1[0] + a1[3])) + (a2[0] + a2[3]);
        };
        auto give_ln = [&](uint32_t src0, uint32_t par, uint32_t dst, uint32_t ln, float& mean, float& den, auto also) {
            const char* src = xp(src0 + 768 + (ln & 1) * HALF);
            float sx, sq;
            int guard = 0;
            bool again;
            do {
                uint2 st[4];
#pragma unroll
                for (int s = 0; s < 4; s++) st[s] = ldp64(src + s * 1024);
                again = __any_sync(~0u, ((chk4(st, par) | also()) & 1) != 0);
                sx = (asf(st[0].x) + asf(st[1].x)) + (asf(st[2].x) + asf(st[3].x)); sq = (asf(st[0].y) + asf(st[1].y)) + (asf(st[2].y) + asf(st[3].y));
                sx += __shfl_xor_sync(~0u, sx, 1); sq += __shfl_xor_sync(~0u, sq, 1);
            } while (again & (++guard < SPIN_LIMIT));
            ln_stats(sx, sq, mean, den);
            stsvol64(dst, __byte_perm(__float_as_uint(den), __float_as_uint(mean), 0x7632), (__float_as_uint(rcp(den)) & ~7u) | (ch + 1));
        };
        auto take_ln = [&](uint2& c, uint32_t a) { int k = 0; do c = ldsvol64(a); while (__any_sync(~0u, (c.y & 7) != ch + 1) & (++k < SPIN_LIMIT)); };
        {
            auto gate_up = [&](auto with_stats) {
                bar_main();
                TST(3);
                CSTAMP(11);
                const uint4 b = lds128(xr);
                uint32_t b4 = lds32(xr + 16);
                float acc[3][4] = {};
                if (with_stats.value) {
                    stp32_if(fl > 1 && !(td & 2), xp(pubC2), stats(xr + (S_XA - S_XB), b, b4), fl & 1);
                    __syncwarp();
                    b4 = lds32(xr + 16);
                }
                mul80(acc, Wgu, b, b4);
                stp64_if(!(td & 2), xp(pubC), tagw(acc[0][0] + acc[0][3], fl & 1), tagw(acc[1][0] + acc[1][3], fl & 1));
                stp32_if(td & 2, xp(pubC2), acc[2][0] + acc[2][3], fl & 1);
            };
            if (wp == 7) {
                bar_main();
                IDS();
                prepC(ln);
                sts32(sb + S_ZERO + 4, or3(pubC, pubC2, fl));
                gate_up(std::true_type());
            } else {
                if (actc) {
                    bar_main();
                    CSTAMP(8);
                    uint32_t r[8];
#pragma unroll
                    for (int s = 0; s < 8; s++) r[s] = lds32(rr + 640 * s);
                    stp32_if(true, xp(pubB), sum8(r), parc);
                    CSTAMP(9);
                    IDS();
                    prepC(ln);
                    const uint32_t n4 = 4 * n80;
                    const uint32_t xas = pin(sb + S_XA + 192 + 192 * cc + a_pos(n80)), xbs = pin(sb + S_XB + 384 * cc + b_pos<40>(n80));
                    const float x0 = cc ? ldsf(sb + S_XCAR + n4) : bf_lo(lds16(sb + S_X0 + 160 * (ch & 3) + n4 / 2));
                    gather16(xp(uPolB + n4 + lag<DELAY_G>(sb, z0_)), parc, 5 * ch + 1, [&](float y, uint32_t) {
                        const uint32_t x = pack2(x0 + bfr(y), 0.f);
                        sts16(xbs, x);
                        sts16(xas, x);
                        return 0u;
                    });
                    CSTAMP(10);
                } else {
                    bar_main();
                    IDS();
                    prepC(ln);
                }
                gate_up(std::false_type());
            }
        }
        CSTAMP(12);
        float mean = 0.f, den = 1.f;
        {
            IDS();
            const uint32_t wh = pin((((ln & 7) + 48 * ((ln >> 3) & 1) + 8 * (ln >> 4)) * 160 + (wp < 7 ? 16 * wp : 128)) | ((384 * cc + b_pos<48>(n96)) << 16));
            const uint32_t pubD = pin(uPubD + (t4 & 1) * COL + 16 * (t4 & 2) + 4 * q8 + (fl & 1)), ha = xr + (S_HS - S_XB);
            auto down = [&](const uint32_t (&W)[3][4], const uint4& h0, const uint2& h1) {
                float a0[4] = {}, a1[4] = {}, a2[4] = {};
                mmaA(a0, W[0], h0.x, h0.y); mmaA(a1, W[1], h0.z, h0.w); mmaA(a2, W[2], h1.x, h1.y);
                return ((a0[0] + a0[3]) + (a1[0] + a1[3])) + (a2[0] + a2[3]);
            };
            if (wp < 6) {
                uint32_t Wd[3][4];
                auto ldd = [&](uint32_t z) {
#pragma unroll
                    for (int s = 0; s < 3; s++) ldsm4t(Wd[s], ((wh ^ z) & 0xffff) + (sb + S_WD + s * 2560));
                };
                ldd(0);
                if (actc) {
                    const char* srcv = xp(uPolC + lag<DELAY_C>(sb, z0_) + 8 * n96);
                    const uint2 cs = lds64(sb + S_CSGU + 8 * n96);
                    float gt, up;
                    int guard = 0;
                    while (true) {
                        uint2 v[8];
#pragma unroll
                        for (int s = 0; s < 8; s++) v[s] = ldp64(srcv + (s >> 2) * HALF + (s & 3) * 1024);
                        uint2 c = ldsvol64(sb + S_LN + 8 * cc + ((v[0].x ^ parc) & 1) * 32);
                        const bool stale = __any_sync(~0u, ((chk8(v, parc) | chk8y(v, parc)) & 1) != 0), late = __any_sync(~0u, (c.y & 7) != ch + 1);
                        const float pg = sum8x(v), pu = sum8y(v);
                        auto norm = [&] {
                            mean = bf_hi(c.x); den = bf_lo(c.x);
                            gt = bfr(fmaf(-mean, asf(cs.x), pg) * asf(c.y)); up = fmaf(-mean, asf(cs.y), pu) * asf(c.y);
                            keep(gt); keep(up);
                        };
                        norm();
                        if (!((stale | late) & (++guard < SPIN_LIMIT))) break;
                        if (!stale) { take_ln(c, sb + S_LN + 8 * cc); norm(); break; }
                    }
                    CSTAMP(13);
                    SWEEPS(5 * ch + 2, guard - 1);
                    const uint32_t h = pack2(bfr(gt * sigmoidf_(gt)) * bfr(up), 0.f);
                    sts16((wh >> 16) + (sb + S_HS), h);
                    CSTAMP(14);
                    if (ch == 3) CSTAMP(0);
                }
                bar_main();
                TST(4);
                CSTAMP(15);
                const uint4 h0 = lds128(ha);
                const uint2 h1 = lds64(ha + 16);
                stp32_if(!(td & 2), xp(pubD & ~1u), down(Wd, h0, h1), pubD & 1);
            } else {
                uint32_t v = 0;
                const uint32_t col = wp == 7 || !has0;
                const bool serve = wp == 6 || (has0 && has1);
                if (serve) {
                    const uint32_t par = col ? par1 : par0;
                    const char* src = xp(uPolC + col * COL + 776 + (td & 4) * (HALF / 4) + (td & 3) * 1024);
                    give_ln(uPolC + col * COL, par, sb + S_LN + 8 * col, td, mean, den, [&] { v = ldp32(src); return v ^ par; });
                }
                stsvol(sb + S_GATE, ch + 1);
                uint32_t Wd[2][3][4];
#pragma unroll
                for (int s = 0; s < 6; s++) ldsm4t(Wd[s / 3][s % 3], (wh & 0xffff) + (sb + S_WD + (s / 3) * 16 + (s % 3) * 2560));
                bar_main();
                const uint4 h0 = lds128(ha);
                const uint2 h1 = lds64(ha + 16);
                const float d0 = down(Wd[0], h0, h1), d1 = down(Wd[1], h0, h1);
                stp32_if(true, xp(pubD & ~1u), (td & 2) ? d1 : d0, pubD & 1);
                if (serve) {
                    float xw = asf(v);
                    xw += __shfl_xor_sync(~0u, xw, 1); xw += __shfl_xor_sync(~0u, xw, 2); xw += __shfl_xor_sync(~0u, xw, 4);
                    const float r = bfr(fmaf(-mean, ldsf(sb + S_SWR), xw) * rcp(den));
                    sts32(sb + S_STAT + 4 * col, __float_as_uint(bfr(sigmoidf_(r))) | (ch + 1));
                }
            }
        }
        CSTAMP(16);
        {
            IDS();
            const uint32_t pubE = pin(uPubE + (t4 < 3 ? (wp >> 2) * COL + 192 * (wp & 3) + 64 * t4 + 8 * q8 : (q8 >> 2) * COL + 768 + 4 * (q8 & 1)));
            xr = pin(sb + S_XB + 48 * (ln & 7));
            uint32_t x2 = 0;
            auto hop_d = [&](auto col) {
                const uint32_t xbs = pin(sb + S_XB + 384 * col.value + b_pos<40>(n80)), xas = col.value ? 0 : pin(sb + S_XA + 192 + a_pos(n80));
                const float x1 = bf_lo(lds16(xbs));
                const float lnx = __uint_as_float(pin(__float_as_uint(bfr(__fdiv_rn(bfr(x1 - mean), den)))));
                gather16(xp(uPolD + 4 * n80 + lag<DELAY_D>(sb, z0_)), col.value ? par1 : par0, 5 * ch + 3, [&](float y, uint32_t z) {
                    const uint32_t gate = ldsvol(sb + S_STAT + 4 * col.value + z);
                    x2 = pack2(x1 + bfr(lnx + bfr(bfr(y) * bf_hi(gate))), 0.f);
                    if (col.value) keep(x2); else { sts16(xbs, x2); sts16(xas, x2); }
                    return (uint32_t)((gate & 7) != ch + 1);
                });
                CSTAMP(17);
            };
            auto qproj = [&](auto with_stats) {
                bar_main();
                TST(5);
                CSTAMP(19);
                const uint32_t t4 = td & 3;
                const uint4 b = lds128(xr);
                uint32_t b4 = lds32(xr + 16);
                float acc[6][4] = {};
                if (with_stats.value) {
                    stp32_if((td & 11) == 3, xp(pubE), stats(xr + (S_XA - S_XB), b, b4), par0);
                    __syncwarp();
                    b4 = lds32(xr + 16);
                }
                mul80(acc, Wq, b, b4);
                const float v0 = sel4(t4, acc[0][0] + acc[0][3], acc[2][0] + acc[2][3], acc[4][0] + acc[4][3], acc[4][0] + acc[4][3]);
                const float v1 = sel4(t4, acc[1][0] + acc[1][3], acc[3][0] + acc[3][3], acc[5][0] + acc[5][3], acc[5][0] + acc[5][3]);
                stp64_if(t4 < 3, xp(pubE), tagw(v0, par0), tagw(v1, par0));
            };
            if (wp == 7) {
                if (!has0) break;
                qproj(std::true_type());
            } else {
                if (actc && !cc) hop_d(std::integral_constant<int, 0>());
                else {
                    if (actc && g == 0) {
                        const uint32_t po = pin(1280 * (ch - 1) + 160 * i + 2 * n80);
                        hop_d(std::integral_constant<int, 1>());
                        *reinterpret_cast<unsigned short*>(reinterpret_cast<char*>(P.out) + po) = (unsigned short)x2;
                    }
                    if (!has0) break;
                }
                qproj(std::false_type());
                sts32_if(td < 80, sb + S_XCAR + 4 * td, x2 << 16);
            }
        }
        CSTAMP(20);
        if (wp == 6) give_ln(uPolE, par0, sb + S_LN + 16, td, mean, den, [] { return 0u; });
        auto pass2 = [&](auto d0, auto d1, auto d2) {
            constexpr int D0 = d0.value, D1 = d1.value, D = D0 + D1 + d2.value;
            IDS();
            const uint32_t ua = sb + k_place(ch, wp & 6) * SLOT + (wp & 1) * UNIT, k0 = k_off(ln);
            uint32_t kf[12][2][4];
            auto ldk = [&](int s) { const uint32_t a = (k0 ^ (32 * (s / 3))) + (ua + 1024 * (s % 3)); ldsm4(kf[s][0], a); ldsm4(kf[s][1], a + SLOT); };
            auto ldv1 = [&](int k) { ldsm4t(vf[k / 3][k % 3], voff[k % 3] + (sb + v_place(ch, k / 3) * SLOT)); };
            auto ldv = [&](int s) { ldv1(3 * s); ldv1(3 * s + 1); ldv1(3 * s + 2); };
            constexpr uint32_t LATE = LAST_LATE;
            constexpr uint64_t EARLY_LIST = bit_list(~LATE), LATE_LIST = bit_list(LATE);
            auto early = [&](int k) {
                if (D1 == 0) ldk(k);
                else if (k < 3) { ldv1(9 + 2 * k); ldv1(10 + 2 * k); }
                else ldk((EARLY_LIST >> (4 * (k - 3))) & 15);
            };
            uint32_t v[8] = {}, qsa = 0;
            const char* srcv = xp(uPolE + lag<(D1 > 0 ? DELAY_E3 : DELAY_E)>(sb, z0_) + 4 * td);
            auto look = [&] {
#pragma unroll
                for (int s = 0; s < 8; s++) v[s] = ldp32(srcv + (s >> 2) * HALF + (s & 3) * 1024);
            };
            if (LOOK_FIRST && wp < 6) { look(); qsa = pin(sb + S_QS + 384 * ch + q_pos(z_)); }
            if (D1 > 0) vaddr(voff);
            if (!(mbar_try(sb + S_FK + 8 * (wp & 6), par1) & mbar_try(sb + S_FK + 8 * (wp | 1), par1))) { mbar_wait(sb + S_FK + 8 * (wp & 6), par1); mbar_wait(sb + S_FK + 8 * (wp | 1), par1); }
#pragma unroll
            for (int s = 0; s < D0; s++) early(s);
            if (!LOOK_FIRST && wp < 6) { look(); qsa = pin(sb + S_QS + 384 * ch + q_pos(z_)); }
#pragma unroll
            for (int s = D0; s < D0 + D1; s++) early(s);
            if (wp < 6) {
                const float cs = ldsf(sb + S_CSQ + 4 * td);
                int guard = 0;
                while (true) {
                    uint2 c = ldsvol64(sb + S_LN + 16 + ((v[0] ^ par0) & 1) * 32);
                    const bool stale = __any_sync(~0u, (chk8(v, par0) & 1) != 0), late = __any_sync(~0u, (c.y & 7) != ch + 1);
                    const float qs = sum8(v);
                    auto norm = [&] {
                        const uint32_t q = pack2(fmaf(-bf_hi(c.x), cs, qs) * asf(c.y), 0.f);
                        sts16(qsa, q);
                    };
                    norm();
                    if (!((stale | late) & (++guard < SPIN_LIMIT))) break;
                    if (!stale) { take_ln(c, sb + S_LN + 16); norm(); break; }
                    look();
                }
                SWEEPS(5 * ch + 4, guard - 1);
                CSTAMP(22);
            }
#pragma unroll
            for (int s = D0 + D1; s < D; s++) early(s);
            CSTAMP(21);
            bar_main();
            TST(6);
            CSTAMP(1);
            uint2 q = lds64(sb + S_QS + 384 * ch + 8 * ln);
            float acc[2][4] = {};
            constexpr int V0 = 13 - D, NV = D1 > 0 ? 2 : (2 * (D - 1)) / 3;
            static_assert(D1 == 0 || LAST0 == 0 || D - 3 + __builtin_popcount(LATE) == 12, "plan");
#pragma unroll
            for (int s = 0; s < 12; s++) {
                const bool m = q8 == (s & 7);
                const uint32_t b0 = m ? q.x : 0u, b1 = m ? q.y : 0u;
                if (s == 7) q = lds64(sb + S_QS + 384 * ch + 8 * ln + 256);
                mmaA(acc[0], kf[s][0], b0, b1);
                mmaA(acc[1], kf[s][1], b0, b1);
                if (D1 > 0) {
                    if (s >= 1 && s <= __builtin_popcount(LATE)) ldk((LATE_LIST >> (4 * (s - 1))) & 15);
                } else {
                    if (s >= 1 && s + D - 1 < 12) ldk(s + D - 1);
                    if (s >= 1 && s + D - 1 == 11) { __syncwarp(); arrive_if(ln == 0, sb + S_RELK); }
                    if (s == V0) vaddr(voff);
                    if (s >= V0 && 2 * (s - V0) < 3 * NV) ldv1(9 + 2 * (s - V0));
                    if (s >= V0 && 2 * (s - V0) + 1 < 3 * NV) ldv1(10 + 2 * (s - V0));
                }
            }
            CSTAMP(24);
            {
                const float v0 = acc[0][0] + acc[0][1], v1 = acc[0][2] + acc[0][3], v2 = acc[1][0] + acc[1][1], v3 = acc[1][2] + acc[1][3];
                const bool hi = t4 & 2, od = t4 & 1;
                const float u0 = (hi ? v2 : v0) + __shfl_xor_sync(~0u, hi ? v0 : v2, 2), u1 = (hi ? v3 : v1) + __shfl_xor_sync(~0u, hi ? v1 : v3, 2);
                const float s = (od ? u1 : u0) + __shfl_xor_sync(~0u, od ? u0 : u1, 1);
                CSTAMP(2);
                probs(scaled(s), sb + S_PS + PS_PASS, wp, ln);
                CSTAMP(3);
            }
            bar_main();
            TST(10);
            CSTAMP(4);
            if (D1 > 0) values(vf, acc_, std::integral_constant<uint32_t, ORDER_L>(), [&](int s) { if (s < 3) ldv(s + 5); }, sb + S_PS + PS_PASS, 1, par0);
            else values(vf, acc_, std::integral_constant<uint32_t, (NV > 1 ? ORDER_R : 0x76543210)>(),
                        [&](int s) { if (s >= (NV > 1 ? 2 : 1) && s + NV + (NV > 1 ? 1 : 2) < 8) ldv(s + NV + (NV > 1 ? 1 : 2)); }, sb + S_PS + PS_PASS, 1, par0);
            arrive_if(ln == 0, sb + S_RELV);
        };
        if (LAST0 > 0 && ch == 3) {
            pass2(std::integral_constant<int, LAST0>(), std::integral_constant<int, LAST1>(), std::integral_constant<int, LAST2>());
#pragma unroll
            for (int m = 0; m < 48; m++) Wq[m / 8].a[(m / 4) % 2][m % 4] = vf[3 + m / 12][(m / 4) % 3][m % 4];
#pragma unroll
            for (int m = 0; m < 12; m++) Wq[m / 2].c[m % 2] = vf[7][m / 4][m % 4];
#pragma unroll
            for (int m = 0; m < 36; m++) left[m] = m < 12 ? __float_as_uint(acc_[m / 4][m % 4]) : vf[m / 12][(m / 4) % 3][m % 4];
        } else {
            pass2(std::integral_constant<int, KPRE>(), std::integral_constant<int, 0>(), std::integral_constant<int, KPRE2>());
#pragma unroll
            for (int m = 0; m < 36; m++) left[m] = m < 12 ? __float_as_uint(acc_[m / 4][m % 4]) : vf[4 + m / 12][(m / 4) % 3][m % 4];
        }
        TST(11);
        CSTAMP(23);
    }
    sts32_if(td == 255, sb + S_GATE, 6);
    TSTAMP(3);
}

typedef CUresult (*EncodeFn)(CUtensorMap*, CUtensorMapDataType, cuuint32_t, void*, const cuuint64_t*, const cuuint64_t*, const cuuint32_t*,
                             const cuuint32_t*, CUtensorMapInterleave, CUtensorMapSwizzle, CUtensorMapL2promotion, CUtensorMapFloatOOBfill);

void make_map(EncodeFn enc, CUtensorMap* m, const void* base, uint64_t cols, uint64_t rows, uint32_t box_cols, uint32_t box_rows, bool swizzle) {
    cuuint64_t dims[2] = {cols, rows};
    cuuint64_t strides[1] = {cols * 2};
    cuuint32_t box[2] = {box_cols, box_rows};
    cuuint32_t es[2] = {1, 1};
    enc(m, CU_TENSOR_MAP_DATA_TYPE_BFLOAT16, 2, const_cast<void*>(base), dims, strides, box, es, CU_TENSOR_MAP_INTERLEAVE_NONE,
        swizzle ? CU_TENSOR_MAP_SWIZZLE_128B : CU_TENSOR_MAP_SWIZZLE_NONE, swizzle ? CU_TENSOR_MAP_L2_PROMOTION_NONE : WPROMO, CU_TENSOR_MAP_FLOAT_OOB_FILL_NONE);
}

}

extern "C" void kernel_launch(void* const* d_in, const int* in_sizes, int n_in, void* d_out, int out_size) {
    (void)in_sizes; (void)n_in; (void)out_size;
    static EncodeFn enc = nullptr;
    if (!enc) {
        void* f = nullptr;
        cudaDriverEntryPointQueryResult q;
        cudaGetDriverEntryPoint("cuTensorMapEncodeTiled", &f, cudaEnableDefault, &q);
        enc = (EncodeFn)f;
        cudaFuncSetAttribute(fused_kernel, cudaFuncAttributeMaxDynamicSharedMemorySize, SMEM_BYTES);
    }
    Params P;
    P.x = (const __nv_bfloat16*)d_in[0]; P.k = (const __nv_bfloat16*)d_in[1]; P.v = (const __nv_bfloat16*)d_in[2];
    P.wr = (const __nv_bfloat16*)d_in[6];
    P.out = (__nv_bfloat16*)d_out;
    Maps M;
    {
        cuuint64_t dims[4] = {64, 8, 3, (cuuint64_t)KV_BATCH_KEYS / 2}, strides[3] = {384, 128, 3072};
        cuuint32_t box[4] = {64, 8, 3, 2}, es[4] = {1, 1, 1, 1};
        enc(&M.k, CU_TENSOR_MAP_DATA_TYPE_BFLOAT16, 4, d_in[1], dims, strides, box, es, CU_TENSOR_MAP_INTERLEAVE_NONE, CU_TENSOR_MAP_SWIZZLE_128B,
            CU_TENSOR_MAP_L2_PROMOTION_NONE, CU_TENSOR_MAP_FLOAT_OOB_FILL_NONE);
    }
    make_map(enc, &M.v, P.v, 64, (uint64_t)12 * KV_BATCH_KEYS, 64, 96, true);
    make_map(enc, &M.vu, P.v, 64, (uint64_t)12 * KV_BATCH_KEYS, 64, 48, true);
    make_map(enc, &M.wq, d_in[3], 6144, 640, 192, 40, false);
    make_map(enc, &M.wo, d_in[4], 640, 6144, 80, 96, false);
    make_map(enc, &M.wg, d_in[7], 1536, 640, 96, 80, false);
    make_map(enc, &M.wu, d_in[8], 1536, 640, 96, 80, false);
    make_map(enc, &M.wd, d_in[9], 640, 1536, 80, 96, false);
    fused_kernel<<<NCTA, NTHR, SMEM_BYTES, cudaStreamPerThread>>>(P, M);
}
```

```cpp
#include <cuda_runtime.h>
#include <cuda.h>
#include <cuda_bf16.h>
#include <stdint.h>
#include <type_traits>

namespace {

constexpr int NCTA = 128;
constexpr int NTHR = 384;
constexpr int UNIT = 6144;
constexpr int SLOT = 12288;
#define TAU 3970
#define TAUW 3820
#define TAU0 3820
#define TMIN 2400
#define SLACK 4000
#define SLACK0 2000
#define PF0 2
#define WIN_W 3
#define WIN_S 4
#define WIN_U 10
#define VPF 4
#define KRE_TAU 2600
#define RFR_TAU 25600
#define HOP1_NS 200
#define KPRE 1
#define KPRE2 3
#define LAST0 4
#define LAST1 4
#define LAST2 2
#define LAST_LATE 0xaa8
#define FSTEP 4
#define DELAY_L 2
#define DELAY_G 2
#define DELAY_C 3
#define DELAY_D 0
#define DELAY_E 1
#define REG_LO "40"
#define REG_HI "232"
#define SPIN_LOG 17
constexpr int SPIN_LIMIT = 1 << SPIN_LOG;

__host__ __device__ constexpr uint32_t pairL(uint32_t region, uint32_t c, uint32_t g) { return (g & 1) | ((g >> 1) << 2) | (c << 5) | (region << 6); }
__host__ __device__ constexpr uint32_t pairG(uint32_t d, uint32_t c, uint32_t i) { return (i & 1) | ((i >> 1) << 2) | (d << 4) | (c << 5) | (3u << 6); }
constexpr uint32_t RA = 0, RC = 1, RE = 2, HALF = 16384, COPY = 4096, PMASK = 0x59;
constexpr uint32_t XS = 0;
constexpr uint32_t XS2 = XS + 128 * 7680;
constexpr uint32_t XSEND = XS2 + 128 * 768;
__device__ uint4 g_s[XSEND / 16];
__device__ uint4 g_x[(4u << 20) / 16];
#define SWEEPS(k, n) do {} while (0)

constexpr uint32_t S_WD = 16 * SLOT;
constexpr uint32_t S_DUMMY = S_WD + 15360;
constexpr uint32_t S_BAR = S_DUMMY + 4096;
constexpr uint32_t S_FV = S_BAR, S_FK = S_FV + 64, S_RING = S_FK + 64, S_DBAR = S_RING + 48, S_WFULL = S_DBAR + 32, S_QRDY = S_WFULL + 88;
constexpr uint32_t S_RELK = S_QRDY + 8, S_RELV = S_RELK + 8, S_RELR = S_RELV + 8, S_RELW = S_RELR + 8, S_SCO = S_RELW + 24;
constexpr uint32_t S_OS1 = S_SCO + 8;
constexpr uint32_t S_ZERO = S_OS1 + 8;
constexpr uint32_t S_KF = S_ZERO + 8;
constexpr uint32_t S_TOK = S_KF + 8;
constexpr uint32_t S_SIDE = S_TOK + 80, S_GATE = S_SIDE + 4;
constexpr uint32_t S_STAT = S_GATE + 12, S_SWR = S_STAT + 16;
constexpr uint32_t S_LN = S_STAT + 32;
constexpr uint32_t S_XCAR = S_LN + 64;
constexpr uint32_t S_CSQ = S_XCAR + 320;
constexpr uint32_t S_CSGU = S_CSQ + 768;
constexpr uint32_t S_RED = S_CSGU + 768;
constexpr uint32_t S_L0 = S_RED;
constexpr uint32_t S_OS = S_RED + 5120;
constexpr uint32_t S_PS = S_OS + 1536;
constexpr uint32_t PS_MAX = 512, PS_PASS = 544;
constexpr uint32_t S_QS = S_PS + 2 * PS_PASS;
constexpr uint32_t S_XB = S_QS + 1536;
constexpr uint32_t S_XA = S_XB + 768;
constexpr uint32_t S_HS = S_XA + 768;
constexpr uint32_t S_X0 = S_HS + 768;
constexpr uint32_t S_SC = S_X0 + 640;
constexpr uint32_t S_TM = S_SC + 512;
constexpr int SMEM_BYTES = S_TM + 256;
static_assert(SMEM_BYTES <= 232448 && S_STAT % 16 == 0 && S_RED % 16 == 0 && S_XB % 16 == 0 && S_HS % 16 == 0 && S_PS % 16 == 0 && S_QS % 16 == 0, "smem");
static_assert(S_SCO == S_BAR + 44 * 8 && S_RELK == S_BAR + 38 * 8, "barriers");
constexpr uint32_t ST_WQ = 3 * SLOT, ST_WG = 8 * SLOT, ST_WO = 11 * SLOT;

__device__ __forceinline__ uint32_t smem_u32(const void* p) { return (uint32_t)__cvta_generic_to_shared(p); }
__device__ __forceinline__ void mbar_arrive(uint32_t bar) { asm volatile("mbarrier.arrive.shared::cta.b64 _, [%0];" :: "r"(bar) : "memory"); }
__device__ __forceinline__ bool mbar_try(uint32_t bar, uint32_t parity) {
    uint32_t ok;
    asm volatile("{\n .reg .pred p;\n mbarrier.try_wait.parity.shared::cta.b64 p, [%1], %2;\n selp.u32 %0, 1, 0, p;\n}" : "=r"(ok) : "r"(bar), "r"(parity) : "memory");
    return ok != 0;
}
__device__ __forceinline__ bool mbar_test(uint32_t bar, uint32_t parity) {
    uint32_t ok;
    asm volatile("{\n .reg .pred p;\n mbarrier.test_wait.parity.shared::cta.b64 p, [%1], %2;\n selp.u32 %0, 1, 0, p;\n}" : "=r"(ok) : "r"(bar), "r"(parity) : "memory");
    return ok != 0;
}
__device__ __forceinline__ void mbar_wait(uint32_t bar, uint32_t parity) {
    int n = 0;
    while (!mbar_try(bar, parity) && ++n < SPIN_LIMIT) {}
}
__device__ __forceinline__ uint32_t gtime32() { uint32_t t; asm volatile("mov.u32 %0, %globaltimer_lo;" : "=r"(t)); return t; }
__device__ __forceinline__ void bar_main() { asm volatile("bar.sync 1, 256;" ::: "memory"); }

__device__ __forceinline__ void mma16816(float (&c)[4], uint32_t a0, uint32_t a1, uint32_t a2, uint32_t a3, uint32_t b0, uint32_t b1) {
    asm("mma.sync.aligned.m16n8k16.row.col.f32.bf16.bf16.f32 {%0,%1,%2,%3}, {%4,%5,%6,%7}, {%8,%9}, {%0,%1,%2,%3};"
        : "+f"(c[0]), "+f"(c[1]), "+f"(c[2]), "+f"(c[3]) : "r"(a0), "r"(a1), "r"(a2), "r"(a3), "r"(b0), "r"(b1));
}
__device__ __forceinline__ void mmaA(float (&c)[4], const uint32_t (&a)[4], uint32_t b0, uint32_t b1) { mma16816(c, a[0], a[1], a[2], a[3], b0, b1); }
__device__ __forceinline__ void mma8(float (&c)[4], uint32_t a0, uint32_t a1, uint32_t b0) {
    asm("mma.sync.aligned.m16n8k8.row.col.f32.bf16.bf16.f32 {%0,%1,%2,%3}, {%4,%5}, {%6}, {%0,%1,%2,%3};"
        : "+f"(c[0]), "+f"(c[1]), "+f"(c[2]), "+f"(c[3]) : "r"(a0), "r"(a1), "r"(b0));
}
struct W80 { uint32_t a[2][4], c[2]; };
template <int N> __device__ __forceinline__ void mul80(float (&acc)[N][4], const W80 (&W)[N], const uint4& b, uint32_t b4) {
#pragma unroll
    for (int m = 0; m < N; m++) mmaA(acc[m], W[m].a[0], b.x, b.y);
#pragma unroll
    for (int m = 0; m < N; m++) mmaA(acc[m], W[m].a[1], b.z, b.w);
#pragma unroll
    for (int m = 0; m < N; m++) mma8(acc[m], W[m].c[0], W[m].c[1], b4);
}
__device__ __forceinline__ void ldsm2t(uint32_t (&r)[2], uint32_t addr) {
    asm volatile("ldmatrix.sync.aligned.m8n8.x2.trans.shared.b16 {%0,%1}, [%2];" : "=r"(r[0]), "=r"(r[1]) : "r"(addr) : "memory");
}
__device__ __forceinline__ void mmaV(float (&c)[4], const uint4& a, uint32_t b0, uint32_t b1) { mma16816(c, a.x, a.y, a.z, a.w, b0, b1); }
__device__ __forceinline__ void ldsm4(uint32_t (&r)[4], uint32_t addr) {
    asm volatile("ldmatrix.sync.aligned.m8n8.x4.shared.b16 {%0,%1,%2,%3}, [%4];" : "=r"(r[0]), "=r"(r[1]), "=r"(r[2]), "=r"(r[3]) : "r"(addr) : "memory");
}
__device__ __forceinline__ void ldsm4t(uint32_t (&r)[4], uint32_t addr) {
    asm volatile("ldmatrix.sync.aligned.m8n8.x4.trans.shared.b16 {%0,%1,%2,%3}, [%4];" : "=r"(r[0]), "=r"(r[1]), "=r"(r[2]), "=r"(r[3]) : "r"(addr) : "memory");
}
__device__ __forceinline__ uint32_t lds16(uint32_t a) { uint16_t v; asm volatile("ld.shared.u16 %0, [%1];" : "=h"(v) : "r"(a) : "memory"); return v; }
__device__ __forceinline__ uint32_t lds32(uint32_t a) { uint32_t v; asm volatile("ld.shared.u32 %0, [%1];" : "=r"(v) : "r"(a) : "memory"); return v; }
__device__ __forceinline__ float ldsf(uint32_t a) { return __uint_as_float(lds32(a)); }
__device__ __forceinline__ uint2 lds64(uint32_t a) { uint2 v; asm volatile("ld.shared.v2.u32 {%0,%1}, [%2];" : "=r"(v.x), "=r"(v.y) : "r"(a) : "memory"); return v; }
__device__ __forceinline__ uint4 lds128(uint32_t a) { uint4 v; asm volatile("ld.shared.v4.u32 {%0,%1,%2,%3}, [%4];" : "=r"(v.x), "=r"(v.y), "=r"(v.z), "=r"(v.w) : "r"(a) : "memory"); return v; }
__device__ __forceinline__ int ldsvol(uint32_t a) { int v; asm volatile("ld.volatile.shared.u32 %0, [%1];" : "=r"(v) : "r"(a) : "memory"); return v; }
__device__ __forceinline__ uint2 ldsvol64(uint32_t a) { uint2 v; asm volatile("{\n .reg .b64 d;\n ld.volatile.shared.b64 d, [%2];\n mov.b64 {%0,%1}, d;\n}" : "=r"(v.x), "=r"(v.y) : "r"(a) : "memory"); return v; }
__device__ __forceinline__ void stsvol64(uint32_t a, uint32_t x, uint32_t y) { asm volatile("{\n .reg .b64 d;\n mov.b64 d, {%1,%2};\n st.volatile.shared.b64 [%0], d;\n}" :: "r"(a), "r"(x), "r"(y) : "memory"); }
__device__ __forceinline__ void stsvol(uint32_t a, int v) { asm volatile("st.volatile.shared.u32 [%0], %1;" :: "r"(a), "r"(v) : "memory"); }
__device__ __forceinline__ void sts_hi16(uint32_t a, float v) { asm volatile("{\n .reg .b16 lo, hi;\n mov.b32 {lo, hi}, %1;\n st.shared.u16 [%0], hi;\n}" :: "r"(a), "r"(__float_as_uint(v)) : "memory"); }
__device__ __forceinline__ void sts16(uint32_t a, uint32_t v) { asm volatile("st.shared.u16 [%0], %1;" :: "r"(a), "r"(v) : "memory"); }
__device__ __forceinline__ void sts32(uint32_t a, uint32_t v) { asm volatile("st.shared.u32 [%0], %1;" :: "r"(a), "r"(v) : "memory"); }
__device__ __forceinline__ void stsf(uint32_t a, float v) { sts32(a, __float_as_uint(v)); }
__device__ __forceinline__ void sts64(uint32_t a, uint32_t x, uint32_t y) { asm volatile("st.shared.v2.u32 [%0], {%1,%2};" :: "r"(a), "r"(x), "r"(y) : "memory"); }

__device__ __forceinline__ void sts32_if(bool p, uint32_t a, uint32_t v) {
    asm volatile("{\n .reg .pred p;\n setp.ne.u32 p, %2, 0;\n @p st.shared.u32 [%0], %1;\n}" :: "r"(a), "r"(v), "r"((uint32_t)p) : "memory");
}
__device__ __forceinline__ void arrive_if(bool p, uint32_t bar) {
    asm volatile("{\n .reg .pred p;\n setp.ne.u32 p, %1, 0;\n @p mbarrier.arrive.shared::cta.b64 _, [%0];\n}" :: "r"(bar), "r"((uint32_t)p) : "memory");
}
__device__ __forceinline__ void keep(uint32_t& v) { asm volatile("" : "+r"(v)); }
__device__ __forceinline__ void keep(float& v) { asm volatile("" : "+f"(v)); }

__device__ __forceinline__ uint32_t ldp32(const char* p) { uint32_t v; asm volatile("ld.relaxed.gpu.global.u32 %0, [%1];" : "=r"(v) : "l"(p) : "memory"); return v; }
__device__ __forceinline__ uint2 ldp64(const char* p) {
    uint2 v; asm volatile("{\n .reg .b64 d;\n ld.relaxed.gpu.global.b64 d, [%2];\n mov.b64 {%0,%1}, d;\n}" : "=r"(v.x), "=r"(v.y) : "l"(p) : "memory"); return v;
}
__device__ __forceinline__ uint32_t tagw(float f, uint32_t par) { return (__float_as_uint(f) & ~1u) | par; }
__device__ __forceinline__ void stp32(char* p, float a, uint32_t par) { asm volatile("st.relaxed.gpu.global.u32 [%0], %1;" :: "l"(p), "r"(tagw(a, par)) : "memory"); }
__device__ __forceinline__ void stp64(char* p, float a, float b, uint32_t par) {
    asm volatile("{\n .reg .b64 d;\n mov.b64 d, {%1,%2};\n st.relaxed.gpu.global.b64 [%0], d;\n}" :: "l"(p), "r"(tagw(a, par)), "r"(tagw(b, par)) : "memory");
}
__device__ __forceinline__ void stp32_if(bool p, char* d, float a, uint32_t par) {
    asm volatile("{\n .reg .pred p;\n setp.ne.u32 p, %2, 0;\n @p st.relaxed.gpu.global.u32 [%0], %1;\n @p st.relaxed.gpu.global.u32 [%0+4096], %1;\n}" :: "l"(d), "r"(tagw(a, par)), "r"((uint32_t)p) : "memory");
}
__device__ __forceinline__ void stp64_if(bool p, char* d, uint32_t lo, uint32_t hi) {
    asm volatile("{\n .reg .pred p;\n .reg .b64 d;\n setp.ne.u32 p, %3, 0;\n mov.b64 d, {%1,%2};\n @p st.relaxed.gpu.global.b64 [%0], d;\n @p st.relaxed.gpu.global.b64 [%0+4096], d;\n}" :: "l"(d), "r"(lo), "r"(hi), "r"((uint32_t)p) : "memory");
}
__device__ __forceinline__ uint32_t chk2(uint32_t a, uint32_t b, uint32_t par) { uint32_t r; asm("lop3.b32 %0, %1, %2, %3, 0x7E;" : "=r"(r) : "r"(a), "r"(b), "r"(par)); return r; }
__device__ __forceinline__ uint32_t or3(uint32_t a, uint32_t b, uint32_t c) { uint32_t r; asm("lop3.b32 %0, %1, %2, %3, 0xFE;" : "=r"(r) : "r"(a), "r"(b), "r"(c)); return r; }
__device__ __forceinline__ uint32_t chk8(const uint32_t (&v)[8], uint32_t par) { return or3(chk2(v[0], v[1], par), chk2(v[2], v[3], par), or3(chk2(v[4], v[5], par), chk2(v[6], v[7], par), 0)); }
__device__ __forceinline__ uint32_t chk8(const uint2 (&v)[8], uint32_t par) { return or3(chk2(v[0].x, v[1].x, par), chk2(v[2].x, v[3].x, par), or3(chk2(v[4].x, v[5].x, par), chk2(v[6].x, v[7].x, par), 0)); }
__device__ __forceinline__ uint32_t chk8y(const uint2 (&v)[8], uint32_t par) { return or3(chk2(v[0].y, v[1].y, par), chk2(v[2].y, v[3].y, par), or3(chk2(v[4].y, v[5].y, par), chk2(v[6].y, v[7].y, par), 0)); }
__device__ __forceinline__ uint32_t chk4(const uint2 (&v)[4], uint32_t par) { return or3(chk2(v[0].x, v[0].y, par), chk2(v[1].x, v[1].y, par), or3(chk2(v[2].x, v[2].y, par), chk2(v[3].x, v[3].y, par), 0)); }
__device__ __forceinline__ float asf(uint32_t v) { return __uint_as_float(v); }
__device__ __forceinline__ float sum8(const uint32_t (&v)[8]) { return ((asf(v[0]) + asf(v[1])) + (asf(v[2]) + asf(v[3]))) + ((asf(v[4]) + asf(v[5])) + (asf(v[6]) + asf(v[7]))); }
__device__ __forceinline__ float sum8x(const uint2 (&v)[8]) { return ((asf(v[0].x) + asf(v[1].x)) + (asf(v[2].x) + asf(v[3].x))) + ((asf(v[4].x) + asf(v[5].x)) + (asf(v[6].x) + asf(v[7].x))); }
__device__ __forceinline__ float sum8y(const uint2 (&v)[8]) { return ((asf(v[0].y) + asf(v[1].y)) + (asf(v[2].y) + asf(v[3].y))) + ((asf(v[4].y) + asf(v[5].y)) + (asf(v[6].y) + asf(v[7].y))); }

__device__ __forceinline__ uint32_t pack2(float lo, float hi) { uint32_t r; asm("cvt.rn.bf16x2.f32 %0, %1, %2;" : "=r"(r) : "f"(hi), "f"(lo)); return r; }
__device__ __forceinline__ float bfr(float x) { return __uint_as_float(pack2(0.0f, x)); }
__device__ __forceinline__ float ex2(float x) { float r; asm("ex2.approx.ftz.f32 %0, %1;" : "=f"(r) : "f"(x)); return r; }
__device__ __forceinline__ float rcp(float x) { float r; asm("rcp.approx.ftz.f32 %0, %1;" : "=f"(r) : "f"(x)); return r; }
__device__ __forceinline__ float sqrt_(float x) { float r; asm("sqrt.approx.ftz.f32 %0, %1;" : "=f"(r) : "f"(x)); return r; }
__device__ __forceinline__ float bf_lo(uint32_t v) { return __uint_as_float(v << 16); }
__device__ __forceinline__ float bf_hi(uint32_t v) { return __uint_as_float(v & 0xffff0000u); }
__device__ __forceinline__ float sel4(int k, float a, float b, float c, float d) { return (k & 2) ? ((k & 1) ? d : c) : ((k & 1) ? b : a); }
constexpr float LOG2E = 1.4426950408889634f;
constexpr uint32_t ONES = 0x3f803f80u;

__device__ __forceinline__ void ln_stats(float sum, float sq, float& mean, float& den) {
    const float m = sum * (1.0f / 640.0f);
    const float var = fmaxf(fmaf(sq, 1.0f / 640.0f, -m * m), 0.0f);
    mean = bfr(m);
    den = bfr(sqrt_(bfr(bfr(var) + 1e-5f)));
}
__device__ __forceinline__ float sigmoidf_(float x) { return rcp(1.0f + ex2(-x * LOG2E)); }

#define TSTAMP(k) do {} while (0)
#define TST(k) do {} while (0)

#define CSTAMP(k) do {} while (0)
template <int N> __device__ __forceinline__ uint32_t lag(uint32_t sb, uint32_t z = 0) {
#pragma unroll
    for (int k = 0; k < N; k++) z = ldsvol(sb + S_ZERO + z);
    return z;
}
__device__ __forceinline__ void warm_mma(uint32_t& a, uint32_t& b) {
    asm volatile("mma.sync.aligned.m16n8k8.row.col.f16.f16.f16.f16 {%0,%1}, {%0,%1}, {%0}, {%0,%1};" : "+r"(a), "+r"(b) :: "memory");
}
#define KWNS2 20
#define KWNS 200
template <int STRIDE>
__device__ __forceinline__ float gather8(const char* p, uint32_t par) {
    uint32_t v[8];
    int guard = 0;
    do {
#pragma unroll
        for (int s = 0; s < 8; s++) v[s] = ldp32(p + s * STRIDE);
    } while ((chk8(v, par) & 1) && ++guard < SPIN_LIMIT);
    return sum8(v);
}
template <class F>
__device__ __forceinline__ void gather16(const char* p, uint32_t par, int k, F use) {
    uint32_t v[8], u[8];
    int guard = 0;
    bool again;
    do {
#pragma unroll
        for (int s = 0; s < 8; s++) v[s] = ldp32(p + s * 512);
#pragma unroll
        for (int s = 0; s < 8; s++) u[s] = ldp32(p + HALF + s * 512);
        const uint32_t stale = use(sum8(v) + sum8(u), ((v[0] ^ par) & 1) * 8);
        again = __any_sync(~0u, (or3(chk8(v, par), chk8(u, par), stale) & 1) != 0);
    } while (again & (++guard < SPIN_LIMIT));
    SWEEPS(k, guard - 1);
}

struct Params {
    const __nv_bfloat16 *x, *k, *v, *wr;
    __nv_bfloat16* out;
};
struct Maps { CUtensorMap k, v, vu, wq, wo, wg, wu, wd; };

constexpr int KV_BATCH_KEYS = 32 * 4096;

__device__ __forceinline__ void tma2d(uint32_t dst, const CUtensorMap* m, int c0, int c1, uint32_t bar, uint32_t bytes, uint64_t pol) {
    asm volatile("{\n .reg .pred p;\n elect.sync _|p, 0xffffffff;\n"
                 " @p mbarrier.arrive.expect_tx.shared::cta.b64 _, [%2], %6;\n"
                 " @p cp.async.bulk.tensor.2d.shared::cluster.global.mbarrier::complete_tx::bytes.L2::cache_hint [%0], [%1, {%3, %4}], [%2], %5;\n}"
                 :: "r"(dst), "l"(m), "r"(bar), "r"(c0), "r"(c1), "l"(pol), "r"(bytes) : "memory");
}
__device__ __forceinline__ void scrap_copy(uint32_t dst, const char* src, uint32_t bar) {
    asm volatile("{\n .reg .pred p;\n elect.sync _|p, 0xffffffff;\n"
                 " @p mbarrier.arrive.expect_tx.shared::cta.b64 _, [%2], 12288;\n"
                 " @p cp.async.bulk.shared::cluster.global.mbarrier::complete_tx::bytes [%0], [%1], 4096, [%2];\n"
                 " @p cp.async.bulk.shared::cluster.global.mbarrier::complete_tx::bytes [%0], [%1+4096], 4096, [%2];\n"
                 " @p cp.async.bulk.shared::cluster.global.mbarrier::complete_tx::bytes [%0], [%1+8192], 4096, [%2];\n}"
                 :: "r"(dst), "l"(src), "r"(bar) : "memory");
}
__device__ __forceinline__ void prefetch_l2(const void* p, uint32_t bytes) {
    asm volatile("{\n .reg .pred p;\n elect.sync _|p, 0xffffffff;\n @p cp.async.bulk.prefetch.L2.global [%0], %1;\n}" :: "l"(p), "r"(bytes) : "memory");
}
__device__ __forceinline__ uint64_t pol_first() { uint64_t p; asm("createpolicy.fractional.L2::evict_first.b64 %0, 1.0;" : "=l"(p)); return p; }
__device__ __forceinline__ uint64_t pol_normal() { uint64_t p; asm("createpolicy.fractional.L2::evict_normal.b64 %0, 1.0;" : "=l"(p)); return p; }
__device__ __forceinline__ bool utest(uint32_t bar, uint32_t parity) { return __all_sync(~0u, mbar_test(bar, parity)); }
__device__ __forceinline__ void uwait(uint32_t bar, uint32_t parity) {
    int n = 0;
    while (!__all_sync(~0u, mbar_try(bar, parity)) && ++n < SPIN_LIMIT) {}
}
template <int A, int B, int CNT> __device__ __forceinline__ void init_bars(uint32_t sb) {
#pragma unroll 1
    for (int k = A; k < B; k++)
        asm volatile("{\n .reg .pred p;\n elect.sync _|p, 0xffffffff;\n @p mbarrier.init.shared::cta.b64 [%0], %1;\n}" :: "r"(sb + S_BAR + 8 * k), "n"(CNT) : "memory");
}
__device__ __forceinline__ int first_key() { return (blockIdx.x >> 2) * 4096 + 3072 + (blockIdx.x & 3) * 256; }
__device__ __forceinline__ void load_tile(const CUtensorMap* m, uint32_t dst, uint32_t bar, uint32_t bytes, int key, uint64_t pol) { tma2d(dst, m, 0, 3 * key, bar, bytes, pol); }
__device__ __forceinline__ const char* unit_ptr(const Params& P, int n) {
    return (const char*)((n & 16) ? P.v : P.k) + (size_t)(first_key() + (n >> 5) * KV_BATCH_KEYS + (n & 15) * 16) * 384;
}
#define LSTAMP(k) do {} while (0)

__device__ __forceinline__ uint32_t k_place(uint32_t b, uint32_t s) { return s + 3 + 5 * (b & 1); }
__device__ __forceinline__ uint32_t v_place(uint32_t b, uint32_t s) { return s < 3 ? s : s + 8 - 8 * (b & 1); }
__device__ __forceinline__ void k_load(const Maps& M, uint32_t dst, uint32_t bar, int key8, uint64_t pol) {
    asm volatile("{\n .reg .pred p;\n elect.sync _|p, 0xffffffff;\n"
                 " @p mbarrier.arrive.expect_tx.shared::cta.b64 _, [%2], 6144;\n"
                 " @p cp.async.bulk.tensor.4d.shared::cluster.global.mbarrier::complete_tx::bytes.L2::cache_hint [%0], [%1, {0, 0, 0, %3}], [%2], %4;\n}"
                 :: "r"(dst), "l"(&M.k), "r"(bar), "r"(key8), "l"(pol) : "memory");
}
__device__ __forceinline__ int unit_key8(uint32_t n) { return first_key() / 8 + (n >> 4) * (KV_BATCH_KEYS / 8) + 2 * (n & 15); }
__device__ __forceinline__ void ring_load(const Maps& M, uint32_t sb, uint32_t b, uint32_t u, uint32_t pos) {
    if (u < 16) k_load(M, sb + pos * UNIT, sb + S_RING + 8 * pos, unit_key8(16 * b + u), pol_normal());
    else load_tile(&M.vu, sb + pos * UNIT, sb + S_FV + 4 * (pos & 6), UNIT, first_key() + b * KV_BATCH_KEYS + 16 * pos, pol_first());
}
__device__ __forceinline__ uint32_t token(bool p, uint32_t a, uint32_t n) {
    uint32_t v;
    asm volatile("{\n .reg .pred p;\n setp.ne.u32 p, %2, 0;\n mov.u32 %0, 0;\n @p atom.shared.exch.b32 %0, [%1], %3;\n}" : "=r"(v) : "r"(a), "r"((uint32_t)p), "r"(n) : "memory");
    return v;
}
__device__ __forceinline__ void place_load(const Maps& M, uint32_t sb, uint32_t n) {
    k_load(M, sb + k_place(n >> 4, 0) * SLOT + (n & 15) * UNIT, sb + S_FK + 4 * (n & 14), unit_key8(n), pol_first());
}
__device__ __forceinline__ void v_load(const Maps& M, uint32_t sb, uint32_t b, uint32_t s) {
    load_tile(&M.v, sb + v_place(b, s) * SLOT, sb + S_FV + 8 * s, SLOT, first_key() + b * KV_BATCH_KEYS + 32 * s, pol_first());
}

__device__ __forceinline__ void stream_warp(const Params& P, const Maps& M, uint32_t sb, uint32_t lane) {
    const uint64_t pol = pol_first();
    const int bid = blockIdx.x, g = bid >> 3, i = bid & 7;
    const uint32_t wf = sb + S_WFULL;
    uint32_t tn = __shfl_sync(~0u, gtime32(), 0) * 16;
    auto pace = [&](uint32_t dt) {
        int k = 0;
        uint32_t now;
        do now = __shfl_sync(~0u, gtime32(), 0) * 16; while ((int)(now - tn) < 0 && ++k < SPIN_LIMIT);
        if ((int)(now - tn) > SLACK0) tn = now - SLACK0;
        tn += dt;
    };
#pragma unroll
    for (int k = 0; k < 10; k++) {
        if (k < 2) {
            if (k == 0) init_bars<26, 27, 1>(sb); else init_bars<27, 37, 1>(sb);
            asm volatile("fence.mbarrier_init.release.cluster;" ::: "memory");
            if (k == 1) { asm volatile("bar.arrive 2, %0;" :: "n"(NTHR) : "memory"); asm volatile("bar.sync 3, 128;" ::: "memory"); }
        }
        if (k >= WIN_W) uwait(wf + 8 * (k - WIN_W), 0);
        pace(TAUW * 5 / 2);
        if (k < 4) tma2d(sb + ST_WQ + 15360 * k, &M.wq, 384 * g + 192 * (k >> 1), 80 * i + 40 * (k & 1), wf + 8 * k, 15360, pol);
        else if (k < 6) tma2d(sb + ST_WG + 15360 * (k - 4), k == 4 ? &M.wg : &M.wu, 96 * g, 80 * i, wf + 8 * k, 15360, pol);
        else tma2d(sb + ST_WO + 15360 * (k - 6), &M.wo, 80 * i, 384 * g + 96 * (k - 6), wf + 8 * k, 15360, pol);
    }
#pragma unroll 1
    for (int n = 0; n < 16; n++) {
        if (n == 0 || n == 5 || n == 11) uwait(sb + S_RELW + (n == 0 ? 0 : n == 5 ? 8 : 16), 0);
        uwait(n < WIN_S ? wf + 8 * (10 - WIN_S + n) : sb + S_FV + 8 * ((n - WIN_S) ^ 8), 0);
        pace(max(min(2 * n + 2 - PF0, 2), 0) * TAU0);
        if (n < 8) { place_load(M, sb, 2 * n); place_load(M, sb, 2 * n + 1); }
        else if (n < 11) { ring_load(M, sb, 0, 2 * n, 2 * n - 16); ring_load(M, sb, 0, 2 * n + 1, 2 * n - 15); }
        else v_load(M, sb, 0, n - 8);
        if (n == 7) { pace(TAUW * 5 / 2); tma2d(sb + S_WD, &M.wd, 80 * i, 96 * g, wf + 80, 15360, pol); }
    }
    int nd = 0;
    uint32_t q[4];
#pragma unroll
    for (int r = 0; r < 4; r++) q[r] = sb + S_FV + 8 * (7 - r);
    uint32_t td = tn;
    uint32_t pos = 2;
#pragma unroll 1
    for (int m = 16; m < 64; m++) {
        const int b = m >> 4, j = m & 15;
        const char* src = unit_ptr(P, 2 * m);
        const uint32_t tok = sb + S_TOK + (j < 3 ? 4 * pos : j < 11 ? 24 + 4 * pos : 16 + 4 * j) + 4 * lane;
        static_assert(WIN_U <= 12, "a ring position has at most one token of the timetable");
        int k = 0;
        while (true) {
            const uint2 c = lds64(sb + S_KF);
            if (__all_sync(~0u, mbar_test(q[WIN_S - 1] & ~1u, q[WIN_S - 1] & 1) & (min((int)c.x + 1, (int)c.y) >= 16 * b + min(2 * j + 2 - WIN_U, 16))) || ++k >= SPIN_LIMIT) break;
        }
        uint32_t now;
        while (true) {
            now = __shfl_sync(~0u, gtime32(), 0) * 16;
            if ((int)(now - td) >= 0 || ++k >= SPIN_LIMIT) break;
        }
        const uint32_t mine = __ballot_sync(~0u, token(lane < (j < 11 ? 2 : 1), tok, 2 * m + lane) == 2 * m + lane);
        q[3] = q[2]; q[2] = q[1]; q[1] = q[0]; q[0] = sb + S_QRDY;
        if (j < 11) {
            if (mine & 1) ring_load(M, sb, b, 2 * j, pos); else prefetch_l2(src, UNIT);
            if (mine & 2) ring_load(M, sb, b, 2 * j + 1, pos + 1); else prefetch_l2(src + UNIT, UNIT);
            if (j >= 8) q[0] = (sb + S_FV + 8 * (j - 8)) | (b & 1);
        } else if (mine) { v_load(M, sb, b, j - 8); q[0] = (sb + S_FV + 8 * (j - 8)) | (b & 1); }
        else if (j - 8 >= VPF) prefetch_l2(src, SLOT);
        else {
            scrap_copy(sb + S_DUMMY, src, sb + S_DBAR + 8 * (nd & 3));
            q[0] = (sb + S_DBAR + 8 * (nd & 3)) | ((nd >> 2) & 1);
            nd++;
        }
        pos = j == 15 ? 2 : pos == 4 ? 0 : pos + 2;
        if ((int)(now - tn) > SLACK) tn = now - SLACK;
        tn += 2 * TAU;
        td = (int)(tn - now) > 2 * TMIN ? tn : now + 2 * TMIN;
    }
#pragma unroll 1
    for (int m = max(nd - 4, 0); m < nd; m++) uwait(sb + S_DBAR + 8 * (m & 3), (m >> 2) & 1);
}

__host__ __device__ constexpr uint64_t bit_list(uint32_t m) { uint64_t r = 0; int n = 0; for (int k = 0; k < 12; k++) if ((m >> k) & 1) r |= (uint64_t)k << (4 * n++); return r; }
__device__ __forceinline__ float scaled(float s) { return bfr(bfr(s) * 0.07216878364870322f); }
__device__ __forceinline__ void probs(float s, uint32_t ps, uint32_t src, uint32_t ln) {
    const uint32_t q8 = ln >> 2, t4 = ln & 3;
    int key = __float_as_int(s);
    key ^= (key >> 31) & 0x7fffffff;
    key = __reduce_max_sync(~0u, key);
    key ^= (key >> 31) & 0x7fffffff;
    const float ml = __int_as_float(key) * LOG2E;
    sts16(ps + 64 * src + (q8 >> 1) * 16 + t4 * 4 + (q8 & 1) * 2, pack2(ex2(fmaf(s, LOG2E, -ml)), 0.f));
    stsf(ps + PS_MAX + 4 * src, ml);
}
template <int H> __device__ __forceinline__ uint32_t b_pos(uint32_t e) { const uint32_t h = e >= H, k = e - H * h; return h * 192 + (k & 6) * 24 + (k >> 3) * 4 + (k & 1) * 2; }
__device__ __forceinline__ uint32_t a_pos(uint32_t e) { const uint32_t h = e >= 40, k = e - 40 * h; return (k & 6) * 24 + (k >> 3) * 8 + h * 4 + (k & 1) * 2; }
__device__ __forceinline__ uint32_t q_pos(uint32_t d) { const uint32_t s = 3 * ((d >> 4) & 3) + (d >> 6); return s * 32 + (d & 6) * 4 + ((d >> 3) & 1) * 4 + (d & 1) * 2; }
__device__ __forceinline__ uint32_t k_off(uint32_t ln) { return (ln & 8) * 384 + (ln & 7) * 128 + (((ln & 7) ^ (ln >> 4)) << 4); }

#define HSTAMP(k) do {} while (0)
__device__ __forceinline__ char* xwindow() { return reinterpret_cast<char*>((reinterpret_cast<uintptr_t>(g_x) + (2u << 20) - 1) & ~(uintptr_t)((2u << 20) - 1)); }

struct XPtr {
    uint32_t lo, hi;
    __device__ __forceinline__ explicit XPtr(char* p) : lo((uint32_t)(uintptr_t)p), hi((uint32_t)((uintptr_t)p >> 32)) {}
    __device__ __forceinline__ XPtr(uint32_t l, uint32_t h) : lo(l), hi(h) {}
    __device__ __forceinline__ XPtr operator+(uint32_t o) const { return XPtr(lo + o, hi); }
    __device__ __forceinline__ operator char*() const { uint64_t p; asm("mov.b64 %0, {%1, %2};" : "=l"(p) : "r"(lo), "r"(hi)); return (char*)p; }
};

__device__ __forceinline__ void side_warp(uint32_t sb) {
    const uint32_t bid = blockIdx.x, g = bid >> 3, i = bid & 7, P = pairG(0, 0, i);
    char* p = xwindow() + P * 8192 + (g >> 3) * HALF + (g & 7) * 512 + 448;
    uint32_t best[2] = {~0u, ~0u};
    asm volatile("st.relaxed.gpu.global.b32 [%0], 1;" :: "l"(p) : "memory");
    asm volatile("st.relaxed.gpu.global.b32 [%0], 1;" :: "l"(p + COPY) : "memory");
#pragma unroll 1
    for (int r = 0; r < 64; r++) {
        if (r >= 4 && !(r & 1) && min(best[0], best[1]) < 380 && max(best[0], best[1]) > min(best[0], best[1]) + 80) break;
        uint32_t c0, c1, v;
        asm volatile("mov.u32 %0, %clock;" : "=r"(c0) :: "memory");
        asm volatile("atom.relaxed.gpu.global.exch.b32 %0, [%1], 0;" : "=r"(v) : "l"(p + (r & 1) * COPY) : "memory");
        asm volatile("{\n .reg .pred q;\n setp.eq.u32 q, %1, 0x13579bdf;\n mov.u32 %0, 0;\n @!q mov.u32 %0, %clock;\n}" : "=r"(c1) : "r"(v) : "memory");
        if (r & 1) best[1] = min(best[1], c1 - c0); else best[0] = min(best[0], c1 - c0);
    }
    stsvol(sb + S_SIDE, 1 + ((best[1] < best[0]) ^ (__popc(P & PMASK) & 1)));
}

template <int N>
__device__ __forceinline__ void hop_a(const char* src, uint32_t par, uint32_t dst, bool st, int k) {
    uint2 v[N][4];
    float e[4], rl;
    int guard = 0;
    bool again;
    do {
#pragma unroll
        for (int s = 0; s < 4 * N; s++) v[s / 4][s % 4] = ldp64(src + (s / 4) * 256 + (s % 4) * 1024);
        again = __any_sync(~0u, ((chk4(v[0], par) | chk4(v[N - 1], par)) & 1) != 0);
        const int M = max(max((int)v[0][0].x, (int)v[0][1].x), max((int)v[0][2].x, (int)v[0][3].x)) - 254;
#pragma unroll
        for (int s = 0; s < 4; s++) e[s] = __int_as_float(max((int)v[0][s].x - M, 0) << 22);
        rl = rcp(fmaf(e[0], asf(v[0][0].y), e[1] * asf(v[0][1].y)) + fmaf(e[2], asf(v[0][2].y), e[3] * asf(v[0][3].y)));
#pragma unroll
        for (int s = 0; s < 4; s++) e[s] = __shfl_sync(~0u, e[s], 24);
        keep(rl);
    } while (again & (++guard < SPIN_LIMIT));
    rl = __shfl_sync(~0u, rl, 24);
#pragma unroll
    for (int n = 0; n < N; n++) {
        const float o0 = fmaf(e[0], asf(v[n][0].x), e[1] * asf(v[n][1].x)) + fmaf(e[2], asf(v[n][2].x), e[3] * asf(v[n][3].x));
        const float o1 = fmaf(e[0], asf(v[n][0].y), e[1] * asf(v[n][1].y)) + fmaf(e[2], asf(v[n][2].y), e[3] * asf(v[n][3].y));
        sts32_if(st, dst + 192 * n, pack2(o0 * rl, o1 * rl));
    }
    SWEEPS(k, guard - 1);
    __syncwarp();
}

__device__ __forceinline__ void score_warp(const Maps& M, uint32_t sb, uint32_t h, uint32_t ln) {
    const uint32_t lane0 = ln;
    uwait(sb + S_QRDY, 0);
    const uint32_t q8 = ln >> 2;
    const uint32_t k0 = k_off(ln);
    uint32_t pos = h + 6, bar = sb + S_FK, par = 0, phases = 0;
    uint2 q = lds64(sb + S_QS + 8 * ln), qh = lds64(sb + S_QS + 8 * ln + 256);
    auto first_round = [&](uint32_t b, uint32_t ln) {
        uwait(sb + S_RELR, b & 1);
        const uint32_t u = h + 2 * ln, p = u < 4 ? u + 2 : u - 4;
        uint32_t todo = __ballot_sync(~0u, token(ln < 3, sb + S_TOK + 4 * p, 32 * b + 32 + u) == 32 * b + 32 + u);
#pragma unroll 1
        for (uint32_t r = h; todo; todo >>= 1, r += 2) if (todo & 1) ring_load(M, sb, b + 1, r, r < 4 ? r + 2 : r - 4);
    };
#pragma unroll 1
    for (uint32_t n = h; n < 64; n += 2) {
        HSTAMP(0);
        const uint32_t ua = sb + pos * UNIT;
        if (!__all_sync(~0u, mbar_try(bar, par))) uwait(bar, par);
        HSTAMP(1);
        float acc[2][4] = {};
        uint32_t mine = 0;
        const uint32_t id = n + (n & 48) + 6;
#pragma unroll
        for (int s = 0; s < 12; s++) {
            uint32_t kf[4];
            ldsm4(kf, (k0 ^ (32 * (s / 3))) + (ua + 1024 * (s % 3)));
            if (s == 11) {
                __syncwarp();
                mine = token(ln == 0 && n >= 16, sb + S_TOK + 24 + 4 * pos, id);
                stsvol(sb + S_KF + 4 * h, n + 1);
            }
            const bool m = q8 == (s & 7);
            mmaA(acc[s & 1], kf, m ? (s < 8 ? q.x : qh.x) : 0u, m ? (s < 8 ? q.y : qh.y) : 0u);
        }
        const uint32_t pos0 = pos;
        const bool last = (n & 14) == 14;
        pos = last ? h + 2 : n >= 16 && pos >= 4 ? h : pos + 2;
        bar = n >= 14 ? sb + S_RING + 8 * pos : bar + 8;
        par = n >= 14 ? (phases >> pos) & 1 : 0;
        phases ^= n >= 14 ? 1u << pos : 0;
        const float w0 = (acc[0][0] + acc[0][1]) + (acc[1][0] + acc[1][1]), w1 = (acc[0][2] + acc[0][3]) + (acc[1][2] + acc[1][3]);
        HSTAMP(2);
        if (__any_sync(~0u, mine == id)) ring_load(M, sb, n >> 4, (n & 15) + 6, pos0);
        HSTAMP(3);
        float s = ((ln & 1) ? w1 : w0) + __shfl_xor_sync(~0u, (ln & 1) ? w0 : w1, 1);
        s += __shfl_xor_sync(~0u, s, 2);
        sts_hi16(sb + S_SC + (((n & 12) >> 1) + h) * 64 + (n & 2) * 2 + (ln & 29) * 2, scaled(s));
        if (last) {
            __syncwarp();
            arrive_if(ln == 0, sb + S_SCO);
            const uint32_t b = n >> 4, ln = lane0 + lag<1>(sb);
            if (b > 0) {
                uwait(sb + S_RELK, (b - 1) & 1);
                if (h == 0) LSTAMP(64 + 2 * b);
                const uint32_t sl = 3 + h + 2 * ln, idv = 32 * b + 16 + 2 * sl;
                uint32_t todo = __ballot_sync(~0u, token(sl < 8, sb + S_TOK + 48 + 4 * sl, idv) == idv);
#pragma unroll 1
                for (uint32_t r = 3 + h; todo; todo >>= 1, r += 2) if (todo & 1) v_load(M, sb, b, r);
                const uint32_t g = blockIdx.x >> 3, pr = pairL(RA, 1, g), side = ldsvol(sb + S_SIDE);
                const char* src = xwindow() + pr * 8192 + ((side ^ 1 ^ __popc(pr & PMASK)) & 1) * COPY + h * HALF + 8 * min(ln, 24u);
                uwait(sb + S_RELV, (b - 1) & 1);
                __nanosleep(HOP1_NS);
#pragma unroll 1
                for (uint32_t r = 0; r < 4; r += 2) {
                    hop_a<2>(src + 256 * r, b & 1, sb + S_OS + 192 * (4 * h + r) + 96 + 4 * ln, ln < 24, 25);
                    if (r == 0 && b < 3) first_round(b, ln);
                }
                arrive_if(ln == 0, sb + S_OS1);
            } else first_round(0, ln);
            q = lds64(sb + S_QS + 24 * ((n + 2) & 48) + 8 * ln); qh = lds64(sb + S_QS + 24 * ((n + 2) & 48) + 8 * ln + 256);
        }
    }
}

__global__ void __launch_bounds__(NTHR, 1)
fused_kernel(const Params P, const __grid_constant__ Maps M) {
    extern __shared__ __align__(1024) unsigned char smem[];
    const uint32_t sb = smem_u32(smem);
    const int tid = threadIdx.x, bid = blockIdx.x;
    if (tid == 0) {
        asm volatile("prefetch.tensormap [%0];" :: "l"(&M.wq) : "memory");
        asm volatile("cp.async.bulk.prefetch.L2.global [%0], %1;" :: "l"(unit_ptr(P, 0)), "r"(PF0 * UNIT) : "memory");
    }
    const int w = __shfl_sync(~0u, tid >> 5, 0), lane = tid & 31;

    if (w >= 8) {
        asm volatile("setmaxnreg.dec.sync.aligned.u32 " REG_LO ";");
        if (w == 8) {
            stream_warp(P, M, sb, lane);
        } else {
            if (w == 11 && lane < 8) asm volatile("prefetch.tensormap [%0];" :: "l"(&M.k + lane) : "memory");
            if (w == 9) { init_bars<0, 3, 2>(sb); init_bars<3, 8, 1>(sb); init_bars<16, 22, 1>(sb); }
            else if (w == 10) { init_bars<8, 16, 2>(sb); init_bars<22, 26, 1>(sb); }
            else { init_bars<37, 38, 1>(sb); init_bars<38, 40, 8>(sb); init_bars<40, 41, 1>(sb); init_bars<41, 44, 8>(sb); init_bars<44, 46, 2>(sb); stsvol(sb + S_ZERO + 4 * lane, 0); if (lane < 16) stsvol(sb + S_LN + 4 * lane, 0); }
            asm volatile("fence.mbarrier_init.release.cluster;" ::: "memory");
            asm volatile("bar.arrive 3, 128;" ::: "memory");
            asm volatile("bar.sync 2, %0;" :: "n"(NTHR) : "memory");
            if (w < 11) score_warp(M, sb, w - 9, lane);
            else {
                if (lane == 0) side_warp(sb);
                __syncwarp();
                uint32_t a = 0, b = 0;
                int k = 0;
                while (ldsvol(sb + S_GATE) == 0 && ++k < SPIN_LIMIT) { warm_mma(a, b); __nanosleep(KWNS); }
                uint4* d = reinterpret_cast<uint4*>(reinterpret_cast<char*>(g_s) + XS + bid * 7680) + lane;
                const uint4 z = make_uint4(0, 0, 0, 0);
#pragma unroll 1
                for (int u = 0; u < 15; u++) d[32 * u] = z;
                d = reinterpret_cast<uint4*>(reinterpret_cast<char*>(g_s) + XS2 + bid * 768) + lane;
                d[0] = z;
                if (lane < 16) d[32] = z;
                const uint32_t side = (ldsvol(sb + S_SIDE) & 1) ^ 1, g = bid >> 3, i = bid & 7;
                const XPtr gx(xwindow());
                auto nearp = [&](uint32_t pr) { return gx.lo + pr * 8192 + ((side ^ __popc(pr & PMASK)) & 1) * COPY; };
                const uint32_t own = (i >> 2) * HALF + (i & 3) * 1024 + (lane & 7) * 128;
                const uint32_t pAC = nearp(pairL(lane >> 4, (lane >> 3) & 1, g)) + own, pE = nearp(pairL(RE, (lane >> 3) & 1, g)) + own;
                const uint32_t pG = nearp(pairG((lane >> 2) & 1, (lane >> 3) & 1, i)) + min(lane & 3, 2) * 128;
                uint32_t tr = 0, tk = 0, ph = 0, src = g + (lane >> 4), seen = 0, n = 16, cs = 0;
                bool go = false, first = true;
                while (n < 64 && ++k < SPIN_LIMIT) {
                    const uint32_t now = __shfl_sync(~0u, gtime32(), 0) * 16;
                    if (!go && utest((n & 15) < 6 ? sb + S_RELK : sb + S_RELV, ((n >> 4) & 1) ^ 1)) { go = true; if ((int)(now - tk) > 0 || !(n & 15)) tk = now; }
                    if (go && (int)(now - tk) >= 0) {
                        place_load(M, sb, (n & 16) ? n : (n & 48) | ((n + 10) & 15));
                        tk += KRE_TAU;
                        n++;
                        go = (n & 15) != 0 && (n & 15) != 6;
                        if (!(n & 15)) LSTAMP(63 + (n >> 3));
                    } else if (first || (int)(now - tr) >= 0) {
                        first = false;
                        tr = now + RFR_TAU;
                        b |= seen & a;
                        warm_mma(a, b);
                        seen = ldp32(XPtr(ph == 0 ? pAC : ph == 1 && lane < 16 ? pE : pG + (src & 8) * (HALF / 8) + (src & 7) * 512, gx.hi));
                        const uint32_t l = lane + 32 * (++cs & 1);
                        *reinterpret_cast<volatile uint32_t*>(reinterpret_cast<char*>(g_s) + (l < 60 ? XS + bid * 7680 + 128 * l : XS2 + bid * 768 + 128 * (l - 60))) = 0;
                        src += ph == 0 ? 0 : ph == 1 ? 2 : 1;
                        ph = ph == 2 ? 0 : ph + 1;
                    } else __nanosleep(KWNS2);
                }
                while (ldsvol(sb + S_GATE) < 6 && ++k < SPIN_LIMIT) { warm_mma(a, b); __nanosleep(KWNS); }
                if (a | b) stsvol(sb + S_GATE, 6);
            }
        }
        return;
    }
    asm volatile("setmaxnreg.inc.sync.aligned.u32 " REG_HI ";");

    const int g = bid >> 3, i = bid & 7;
    const int g8 = lane >> 2, t = lane & 3;
    char* const gs = reinterpret_cast<char*>(g_s);
    const XPtr gx(xwindow());

    auto zero_words = [&] {
        const uint4 z = make_uint4(0, 0, 0, 0);
        const uint32_t c = (tid >> 6) & 1, cp = (tid >> 7) * COPY, k = (tid & 63) * 16;
        *reinterpret_cast<uint4*>((char*)(gx + pairL(RA, c, g) * 8192 + (i >> 2) * HALF + (i & 3) * 1024 + cp + k)) = z;
        *reinterpret_cast<uint4*>((char*)(gx + pairL(RC, c, g) * 8192 + (i >> 2) * HALF + (i & 3) * 1024 + cp + k)) = z;
        *reinterpret_cast<uint4*>((char*)(gx + pairL(RE, c, g) * 8192 + (i >> 2) * HALF + (i & 3) * 1024 + cp + k)) = z;
        if ((tid & 31) < 24) *reinterpret_cast<uint4*>((char*)(gx + pairG((tid >> 5) & 1, c, i) * 8192 + (g >> 3) * HALF + (g & 7) * 512 + cp + (tid & 31) * 16)) = z;
    };
    W80 Wq[6], Wgu[3];
    uint32_t Wo[5][3][4];
    if (w < 4) {
        const uint32_t* xp = reinterpret_cast<const uint32_t*>(P.x + 640 * w);
        float sum = 0.f, sq = 0.f;
#pragma unroll
        for (int u = 0; u < 10; u++) { uint32_t v = xp[lane + 32 * u]; float a = bf_lo(v), b = bf_hi(v); sum += a + b; sq += a * a + b * b; }
#pragma unroll
        for (int o = 16; o > 0; o >>= 1) { sum += __shfl_xor_sync(~0u, sum, o); sq += __shfl_xor_sync(~0u, sq, o); }
        float mean, den; ln_stats(sum, sq, mean, den);
        if (lane < 20) {
            const uint2 v = reinterpret_cast<const uint2*>(P.x + 640 * w + 80 * i)[lane];
            sts64(sb + S_X0 + 160 * w + 8 * lane, v.x, v.y);
            sts32(sb + S_L0 + 384 * w + b_pos<40>(4 * lane), pack2(__fdiv_rn(bfr(bf_lo(v.x) - mean), den), __fdiv_rn(bfr(bf_hi(v.x) - mean), den)));
            sts32(sb + S_L0 + 384 * w + b_pos<40>(4 * lane + 2), pack2(__fdiv_rn(bfr(bf_lo(v.y) - mean), den), __fdiv_rn(bfr(bf_hi(v.y) - mean), den)));
        }
    } else if (w == 4) {
        const uint32_t* xp = reinterpret_cast<const uint32_t*>(P.wr);
        float sum = 0.f;
#pragma unroll
        for (int u = 0; u < 10; u++) { uint32_t v = xp[lane + 32 * u]; sum += bf_lo(v) + bf_hi(v); }
#pragma unroll
        for (int o = 16; o > 0; o >>= 1) sum += __shfl_xor_sync(~0u, sum, o);
        if (lane == 0) stsf(sb + S_SWR, sum);
        if (lane < 20) {
            const uint2 v = reinterpret_cast<const uint2*>(P.wr + 80 * i)[lane];
            sts32(sb + S_XA + 576 + a_pos(4 * lane), v.x); sts32(sb + S_XA + 576 + a_pos(4 * lane + 2), v.y);
            sts32(sb + S_XA + a_pos(4 * lane), ONES); sts32(sb + S_XA + a_pos(4 * lane + 2), ONES);
        }
    }
    asm volatile("bar.sync 2, %0;" :: "n"(NTHR) : "memory");
    auto frag = [](uint32_t (&a)[4], uint32_t p, int pitch) {
        const uint32_t r0 = lds32(p), r1 = lds32(p + pitch), r2 = lds32(p + 2 * pitch), r3 = lds32(p + 3 * pitch);
        a[0] = __byte_perm(r0, r1, 0x5410); a[1] = __byte_perm(r0, r1, 0x7632);
        a[2] = __byte_perm(r2, r3, 0x5410); a[3] = __byte_perm(r2, r3, 0x7632);
    };
    mbar_wait(sb + S_WFULL + 16 * (w >> 2), 0);
    mbar_wait(sb + S_WFULL + 16 * (w >> 2) + 8, 0);
    {
        const uint32_t p = sb + ST_WQ + (w >> 2) * 30720 + (2 * t) * 384 + (48 * (w & 3) + 2 * g8) * 2;
#pragma unroll
        for (int r = 0; r < 10; r++)
#pragma unroll
            for (int m = 0; m < 3; m++) {
                const uint32_t q = p + ((r & 1) * 40 + (r >> 1) * 8) * 384 + 32 * m, r0 = lds32(q), r1 = lds32(q + 384);
                (r < 8 ? Wq[2 * m].a[(r >> 2) & 1][r & 3] : Wq[2 * m].c[r & 1]) = __byte_perm(r0, r1, 0x5410);
                (r < 8 ? Wq[2 * m + 1].a[(r >> 2) & 1][r & 3] : Wq[2 * m + 1].c[r & 1]) = __byte_perm(r0, r1, 0x7632);
            }
    }
    __syncwarp();
    if (lane == 0) mbar_arrive(sb + S_RELW);
    TSTAMP(1);
    {
        char* d = gs + XS + bid * 7680 + (w >> 2) * 3840 + (48 * (w & 3) + 2 * g8) * 4;
        float acc[6][4] = {};
        mul80(acc, Wq, lds128(sb + S_L0 + 48 * lane), lds32(sb + S_L0 + 48 * lane + 16));
#pragma unroll
        for (int m = 0; m < 6; m += 2) stp64(d + t * 768 + 32 * m, acc[m][0] + acc[m][3], acc[m + 1][0] + acc[m + 1][3], 1);
        float sum[6][4] = {};
        mul80(sum, Wq, make_uint4(ONES, ONES, ONES, ONES), ONES);
        if (t == 0)
#pragma unroll
            for (int m = 0; m < 6; m += 2) stp64(d + 4 * 768 + 32 * m, sum[m][0] + sum[m][3], sum[m + 1][0] + sum[m + 1][3], 1);
    }
    mbar_wait(sb + S_WFULL + 32, 0);
    mbar_wait(sb + S_WFULL + 40, 0);
    const uint32_t oct = 3 * (w >> 1) + (w & 1), oct2 = 3 * (w >> 1) + 2;
    {
        const uint32_t p = sb + ST_WG + ((lane & 7) + 40 * ((lane >> 3) & 1) + 8 * (lane >> 4)) * 192;
#pragma unroll
        for (int T = 0; T < 3; T++) {
            const uint32_t q = p + (T < 2 ? T * 15360 + 16 * oct : (w & 1) * 15360 + 16 * oct2);
            ldsm4t(Wgu[T].a[0], q); ldsm4t(Wgu[T].a[1], q + 16 * 192); ldsm2t(Wgu[T].c, q + 32 * 192);
        }
        float sum[3][4] = {};
        mul80(sum, Wgu, make_uint4(ONES, ONES, ONES, ONES), ONES);
        if (t < 3) stp32(gs + XS2 + bid * 768 + (t < 2 ? 64 * oct + 4 * t : 64 * oct2 + 4 * (w & 1)) + 8 * g8,
                         sel4(t, sum[0][0] + sum[0][3], sum[1][0] + sum[1][3], sum[2][0] + sum[2][3], 0.f), 1);
    }
    __syncwarp();
    if (lane == 0) mbar_arrive(sb + S_RELW + 8);
    mbar_wait(sb + S_WFULL + 48 + 8 * (w >> 1), 0);
    {
        const uint32_t po = sb + ST_WO + (48 * w + 12 * t) * 160 + 4 * g8;
#pragma unroll
        for (int s = 0; s < 3; s++)
#pragma unroll
            for (int m = 0; m < 5; m++) frag(Wo[m][s], po + 4 * s * 160 + 32 * m, 160);
    }
    __syncwarp();
    if (lane == 0) mbar_arrive(sb + S_RELW + 16);
    zero_words();
    if (tid < 192) {
        const char* srcS = gs + XS + g * 8 * 7680 + (i >> 2) * 3840 + tid * 4;
        uint32_t vs[5][8];
        int guard = 0;
        do {
#pragma unroll
            for (int b = 0; b < 5; b++)
#pragma unroll
                for (int s = 0; s < 8; s++) vs[b][s] = ldp32(srcS + b * 768 + s * 7680);
        } while (((or3(chk8(vs[0], 1), chk8(vs[1], 1), chk8(vs[2], 1)) | chk8(vs[3], 1) | chk8(vs[4], 1)) & 1) && ++guard < SPIN_LIMIT);
        const uint32_t qpos = sb + S_QS + q_pos(tid);
#pragma unroll
        for (int b = 0; b < 4; b++) {
            sts_hi16(qpos + 384 * b, bfr(sum8(vs[b])));
        }
        stsf(sb + S_CSQ + 4 * tid, sum8(vs[4]));
    }
    if (tid < 192) stsf(sb + S_CSGU + 4 * tid, gather8<768>(gs + XS2 + g * 8 * 768 + tid * 4, 1));
    __syncwarp();
    bar_main();
    arrive_if(tid == 0, sb + S_QRDY);
    TSTAMP(2);

    uint32_t side;
    { int k = 0; while ((side = ldsvol(sb + S_SIDE)) == 0 && ++k < SPIN_LIMIT) {} }
    const uint32_t td = __shfl_sync(~0u, tid, lane);
    const uint32_t wp = __shfl_sync(~0u, tid >> 5, 0);
    const uint32_t cc = wp >= 3;
    auto uni = [](uint32_t v) { return __shfl_sync(~0u, v, 0); };
    auto pin = [&](uint32_t v) { return __shfl_sync(~0u, v, td); };
    auto nearp = [&](uint32_t P) { return gx.lo + P * 8192 + ((side ^ 1 ^ __popc(P & PMASK)) & 1) * COPY; };
    constexpr uint32_t COL = 32 * 8192;
    const uint32_t ownL = gx.lo + (i >> 2) * HALF + (i & 3) * 1024, ownG = gx.lo + (g >> 3) * HALF + (g & 7) * 512;
    const uint32_t uPubA = uni(ownL + pairL(RA, 0, g) * 8192 + (wp >> 1) * 256 + (wp & 1) * 96), uPolA = uni(nearp(pairL(RA, 0, g)) + (wp >> 2) * HALF + (wp & 3) * 256);
    const uint32_t uPubB = uni(ownG + pairG(0, cc, i) * 8192), uPolB = uni(nearp(pairG(0, cc, i)));
    const uint32_t uPubC = uni(ownL + pairL(RC, 0, g) * 8192), uPolC = uni(nearp(pairL(RC, wp < 6 ? cc : 0, g)));
    const uint32_t uPubD = uni(ownG + pairG(1, 0, i) * 8192 + (wp < 7 ? 32 * wp : 256)), uPolD = uni(nearp(pairG(1, cc, i)));
    const uint32_t uPubE = uni(ownL + pairL(RE, 0, g) * 8192), uPolE = uni(nearp(pairL(RE, i >> 2, g)));
    const uint32_t uOS = uni(sb + S_OS + 192 * wp);
    auto xp = [&](uint32_t lo) { return (char*)XPtr(lo, gx.hi); };
#define IDS() __syncwarp(); const uint32_t z0_ = lag<1>(sb), z_ = td + z0_; const uint32_t ln = z_ & 31, q8 = ln >> 2, t4 = z_ & 3, n96 = z_ - 96 * cc, n80 = min(n96, 79u); (void)q8; (void)t4; (void)n80; (void)ln

    auto vaddr = [&](uint32_t (&voff)[3]) {
        const uint32_t ln = td & 31;
        const uint32_t key3 = 3 * ((ln & 7) + 2 * (ln & 8) + ((ln >> 1) & 8));
#pragma unroll
        for (int T = 0; T < 3; T++) {
            const uint32_t u = 3 * wp + T, r = key3 + (u >> 3);
            voff[T] = r * 128 + (((u ^ r) & 7) << 4);
        }
    };
    auto values = [&](uint32_t (&vf)[8][3][4], float (&acc)[3][4], auto step, uint32_t ps, uint32_t col, uint32_t par) {
        const uint32_t ln = td & 31, q8 = ln >> 2, t4 = td & 3;
        const uint4 p = lds128(ps + 16 * ln);
        float f0 = 0.f, f1 = 0.f, r3 = 0.f;
#pragma unroll
        for (int k = 0; k < 12; k++) acc[k / 4][k % 4] = 0.f;
        int M = 0;
#pragma unroll
        for (int s = 0; s < 8; s++) {
            step(s);
            const bool m = (q8 >> 1) == (s >> 1);
            const uint32_t b0 = m ? ((s & 1) ? p.z : p.x) : 0u, b1 = m ? ((s & 1) ? p.w : p.y) : 0u;
#pragma unroll
            for (int T = 0; T < 3; T++) mmaA(acc[T], vf[s][T], b0, b1);
            if (s == FSTEP) {
                const uint2 mp = lds64(ps + PS_MAX + 8 * t4);
                M = __reduce_max_sync(~0u, __float2int_ru(fmaxf(asf(mp.x), asf(mp.y))));
                f0 = ex2(asf(mp.x) - (float)M); f1 = ex2(asf(mp.y) - (float)M);
                float l[4] = {};
                mma16816(l, ONES, ONES, ONES, ONES, p.x, p.y); mma16816(l, ONES, ONES, ONES, ONES, p.z, p.w);
                r3 = fmaf(f0, l[0], f1 * l[1]);
            }
        }
        CSTAMP(25);
        char* pubA = xp(uPubA + col * COL + 32 * t4 + 4 * q8);
        const float r0 = fmaf(f0, acc[0][0], f1 * acc[0][3]), r1 = fmaf(f0, acc[1][0], f1 * acc[1][3]), r2 = fmaf(f0, acc[2][0], f1 * acc[2][3]);
        const bool hi = t4 & 2, od = t4 & 1;
        const float u0 = (hi ? r2 : r0) + __shfl_xor_sync(~0u, hi ? r0 : r2, 2), u1 = (hi ? r3 : r1) + __shfl_xor_sync(~0u, hi ? r1 : r3, 2);
        const float o = (od ? u1 : u0) + __shfl_xor_sync(~0u, od ? u0 : u1, 1);
        stp32_if(t4 < 3 || ((wp & 1) && q8 < 2), pubA, ln == 3 ? __int_as_float(2 * M) : o, par);
    };

    uint32_t left[36] = {};
#pragma unroll 1
    for (int ch = 0; ch < 5; ch++) {
        const uint32_t par0 = (ch + 1) & 1, par1 = ch & 1;
        uint32_t voff[3], vf[8][3][4];
        float acc_[3][4];
        if (ch < 4) {
            vaddr(voff);
            mbar_wait(sb + S_SCO, par1);
            if (ch == 0) mbar_wait(sb + S_WFULL + 80, 0);
            TST(0);
            auto ldw = [&](int s) {
                mbar_wait(sb + S_FV + 8 * s, par1);
#pragma unroll
                for (int T = 0; T < 3; T++) ldsm4t(vf[s][T], voff[T] + (sb + v_place(ch, s) * SLOT));
            };
            probs(bf_lo(lds16(sb + S_SC + 2 * td)), sb + S_PS, wp, td & 31);
            ldw(0); ldw(1); ldw(2);
            bar_main();
            arrive_if(td == 0, sb + S_RELR);
            values(vf, acc_, [&](int s) {
                if (s >= 3) ldw(s);
            }, sb + S_PS, 0, par0);
            TST(1);
            CSTAMP(5);
            if (ch > 0) mbar_wait(sb + S_OS1, par0);
        } else {
#pragma unroll
            for (int s = 0; s < 36; s++) vf[s / 12][(s / 4) % 3][s & 3] = left[s];
        }
        const bool has0 = ch < 4, has1 = ch > 0;
        const bool actc = wp < 6 && (cc ? has1 : has0);
        const uint32_t parc = cc ? par1 : par0;
        const uint32_t pub0 = has0 ? par0 : 0;
        uint32_t rr, pubB;
        {
            IDS();
            const uint32_t c = ch == 4;
            const uint32_t osa = pin(uOS + 96 * c + 4 * ln), oa = pin(uOS + 48 * (q8 & 2) + 24 * t4), ra = pin(sb + S_RED + 640 * wp + 320 * (t4 & 1) + 8 * q8);
            rr = pin(sb + S_RED + 320 * cc + 4 * n80); pubB = pin(uPubB + 4 * n80);
            hop_a<1>(xp(uPolA + c * COL + 8 * min(ln, 24u) + lag<DELAY_L>(sb, z0_)), pub0, osa, ln < 24, 5 * ch);
            TST(2);
            CSTAMP(6);
            float acc[5][4] = {};
            const uint2 b0 = lds64(oa), b1 = lds64(oa + 8), b2 = lds64(oa + 16);
#pragma unroll
            for (int m = 0; m < 5; m++) mmaA(acc[m], Wo[m][0], b0.x, b0.y);
#pragma unroll
            for (int m = 0; m < 5; m++) mmaA(acc[m], Wo[m][1], b1.x, b1.y);
#pragma unroll
            for (int m = 0; m < 5; m++) mmaA(acc[m], Wo[m][2], b2.x, b2.y);
#pragma unroll
            for (int m = 0; m < 5; m++) { stsf(ra + 64 * m, acc[m][0]); stsf(ra + 64 * m + 4, acc[m][2]); }
        }
        CSTAMP(7);
        uint32_t xr, fl, pubC, pubC2;
        auto prepC = [&](uint32_t ln) {
            const uint32_t q8 = ln >> 2, t4 = ln & 3;
            xr = pin(sb + S_XB + 48 * (ln & 15));
            pubC = pin(uPubC + (t4 & 1) * COL + 192 * (wp >> 1) + 64 * (wp & 1) + 8 * q8);
            pubC2 = pin(uPubC + (t4 & 1) * COL + ((t4 & 2) ? 192 * (wp >> 1) + 128 + 4 * (wp & 1) + 8 * q8 : 768 + 2 * ((q8 + 1) & 6)));
            fl = pin(((t4 & 1) ? par1 : pub0) | (t4 >= 2 || (wp == 7 && q8 < 4 && q8 != 2 - t4) ? 2 : 0));
        };
        auto stats = [&](uint32_t xa, const uint4& b, uint32_t b4) {
            float a0[4] = {}, a1[4] = {}, a2[4] = {};
            const uint4 p0 = lds128(xa), p1 = lds128(xa + 16);
            const uint2 p2 = lds64(xa + 32);
            mmaV(a0, p0, b.x, b.y); mmaV(a1, p1, b.z, b.w); mma8(a2, p2.x, p2.y, b4);
            return ((a0[0] + a0[3]) + (a1[0] + a1[3])) + (a2[0] + a2[3]);
        };
        auto give_ln = [&](uint32_t src0, uint32_t par, uint32_t dst, uint32_t ln, float& mean, float& den, auto also) {
            const char* src = xp(src0 + 768 + (ln & 1) * HALF);
            float sx, sq;
            int guard = 0;
            bool again;
            do {
                uint2 st[4];
#pragma unroll
                for (int s = 0; s < 4; s++) st[s] = ldp64(src + s * 1024);
                again = __any_sync(~0u, ((chk4(st, par) | also()) & 1) != 0);
                sx = (asf(st[0].x) + asf(st[1].x)) + (asf(st[2].x) + asf(st[3].x)); sq = (asf(st[0].y) + asf(st[1].y)) + (asf(st[2].y) + asf(st[3].y));
                sx += __shfl_xor_sync(~0u, sx, 1); sq += __shfl_xor_sync(~0u, sq, 1);
            } while (again & (++guard < SPIN_LIMIT));
            ln_stats(sx, sq, mean, den);
            stsvol64(dst, __byte_perm(__float_as_uint(den), __float_as_uint(mean), 0x7632), (__float_as_uint(rcp(den)) & ~7u) | (ch + 1));
        };
        auto take_ln = [&](uint2& c, uint32_t a) { int k = 0; do c = ldsvol64(a); while (__any_sync(~0u, (c.y & 7) != ch + 1) & (++k < SPIN_LIMIT)); };
        {
            auto gate_up = [&](auto with_stats) {
                bar_main();
                TST(3);
                CSTAMP(11);
                const uint4 b = lds128(xr);
                uint32_t b4 = lds32(xr + 16);
                float acc[3][4] = {};
                if (with_stats.value) {
                    stp32_if(fl > 1 && !(td & 2), xp(pubC2), stats(xr + (S_XA - S_XB), b, b4), fl & 1);
                    __syncwarp();
                    b4 = lds32(xr + 16);
                }
                mul80(acc, Wgu, b, b4);
                stp64_if(!(td & 2), xp(pubC), tagw(acc[0][0] + acc[0][3], fl & 1), tagw(acc[1][0] + acc[1][3], fl & 1));
                stp32_if(td & 2, xp(pubC2), acc[2][0] + acc[2][3], fl & 1);
            };
            if (wp == 7) {
                bar_main();
                IDS();
                prepC(ln);
                sts32(sb + S_ZERO + 4, or3(pubC, pubC2, fl));
                gate_up(std::true_type());
            } else {
                if (actc) {
                    bar_main();
                    CSTAMP(8);
                    uint32_t r[8];
#pragma unroll
                    for (int s = 0; s < 8; s++) r[s] = lds32(rr + 640 * s);
                    stp32_if(true, xp(pubB), sum8(r), parc);
                    CSTAMP(9);
                    IDS();
                    prepC(ln);
                    const uint32_t n4 = 4 * n80;
                    const uint32_t xas = pin(sb + S_XA + 192 + 192 * cc + a_pos(n80)), xbs = pin(sb + S_XB + 384 * cc + b_pos<40>(n80));
                    const float x0 = cc ? ldsf(sb + S_XCAR + n4) : bf_lo(lds16(sb + S_X0 + 160 * (ch & 3) + n4 / 2));
                    gather16(xp(uPolB + n4 + lag<DELAY_G>(sb, z0_)), parc, 5 * ch + 1, [&](float y, uint32_t) {
                        const uint32_t x = pack2(x0 + bfr(y), 0.f);
                        sts16(xbs, x);
                        sts16(xas, x);
                        return 0u;
                    });
                    CSTAMP(10);
                } else {
                    bar_main();
                    IDS();
                    prepC(ln);
                }
                gate_up(std::false_type());
            }
        }
        CSTAMP(12);
        float mean = 0.f, den = 1.f;
        {
            IDS();
            const uint32_t wh = pin((((ln & 7) + 48 * ((ln >> 3) & 1) + 8 * (ln >> 4)) * 160 + (wp < 7 ? 16 * wp : 128)) | ((384 * cc + b_pos<48>(n96)) << 16));
            const uint32_t pubD = pin(uPubD + (t4 & 1) * COL + 16 * (t4 & 2) + 4 * q8 + (fl & 1)), ha = xr + (S_HS - S_XB);
            auto down = [&](const uint32_t (&W)[3][4], const uint4& h0, const uint2& h1) {
                float a0[4] = {}, a1[4] = {}, a2[4] = {};
                mmaA(a0, W[0], h0.x, h0.y); mmaA(a1, W[1], h0.z, h0.w); mmaA(a2, W[2], h1.x, h1.y);
                return ((a0[0] + a0[3]) + (a1[0] + a1[3])) + (a2[0] + a2[3]);
            };
            if (wp < 6) {
                uint32_t Wd[3][4];
                auto ldd = [&](uint32_t z) {
#pragma unroll
                    for (int s = 0; s < 3; s++) ldsm4t(Wd[s], ((wh ^ z) & 0xffff) + (sb + S_WD + s * 2560));
                };
                ldd(0);
                if (actc) {
                    const char* srcv = xp(uPolC + lag<DELAY_C>(sb, z0_) + 8 * n96);
                    const uint2 cs = lds64(sb + S_CSGU + 8 * n96);
                    float gt, up;
                    int guard = 0;
                    while (true) {
                        uint2 v[8];
#pragma unroll
                        for (int s = 0; s < 8; s++) v[s] = ldp64(srcv + (s >> 2) * HALF + (s & 3) * 1024);
                        uint2 c = ldsvol64(sb + S_LN + 8 * cc + ((v[0].x ^ parc) & 1) * 32);
                        const bool stale = __any_sync(~0u, ((chk8(v, parc) | chk8y(v, parc)) & 1) != 0), late = __any_sync(~0u, (c.y & 7) != ch + 1);
                        const float pg = sum8x(v), pu = sum8y(v);
                        auto norm = [&] {
                            mean = bf_hi(c.x); den = bf_lo(c.x);
                            gt = bfr(fmaf(-mean, asf(cs.x), pg) * asf(c.y)); up = fmaf(-mean, asf(cs.y), pu) * asf(c.y);
                            keep(gt); keep(up);
                        };
                        norm();
                        if (!((stale | late) & (++guard < SPIN_LIMIT))) break;
                        if (!stale) { take_ln(c, sb + S_LN + 8 * cc); norm(); break; }
                    }
                    CSTAMP(13);
                    SWEEPS(5 * ch + 2, guard - 1);
                    const uint32_t h = pack2(bfr(gt * sigmoidf_(gt)) * bfr(up), 0.f);
                    sts16((wh >> 16) + (sb + S_HS), h);
                    CSTAMP(14);
                    if (ch == 3) CSTAMP(0);
                }
                bar_main();
                TST(4);
                CSTAMP(15);
                const uint4 h0 = lds128(ha);
                const uint2 h1 = lds64(ha + 16);
                stp32_if(!(td & 2), xp(pubD & ~1u), down(Wd, h0, h1), pubD & 1);
            } else {
                uint32_t v = 0;
                const uint32_t col = wp == 7 || !has0;
                const bool serve = wp == 6 || (has0 && has1);
                if (serve) {
                    const uint32_t par = col ? par1 : par0;
                    const char* src = xp(uPolC + col * COL + 776 + (td & 4) * (HALF / 4) + (td & 3) * 1024);
                    give_ln(uPolC + col * COL, par, sb + S_LN + 8 * col, td, mean, den, [&] { v = ldp32(src); return v ^ par; });
                }
                stsvol(sb + S_GATE, ch + 1);
                uint32_t Wd[2][3][4];
#pragma unroll
                for (int s = 0; s < 6; s++) ldsm4t(Wd[s / 3][s % 3], (wh & 0xffff) + (sb + S_WD + (s / 3) * 16 + (s % 3) * 2560));
                bar_main();
                const uint4 h0 = lds128(ha);
                const uint2 h1 = lds64(ha + 16);
                const float d0 = down(Wd[0], h0, h1), d1 = down(Wd[1], h0, h1);
                stp32_if(true, xp(pubD & ~1u), (td & 2) ? d1 : d0, pubD & 1);
                if (serve) {
                    float xw = asf(v);
                    xw += __shfl_xor_sync(~0u, xw, 1); xw += __shfl_xor_sync(~0u, xw, 2); xw += __shfl_xor_sync(~0u, xw, 4);
                    const float r = bfr(fmaf(-mean, ldsf(sb + S_SWR), xw) * rcp(den));
                    sts32(sb + S_STAT + 4 * col, __float_as_uint(bfr(sigmoidf_(r))) | (ch + 1));
                }
            }
        }
        CSTAMP(16);
        {
            IDS();
            const uint32_t pubE = pin(uPubE + (t4 < 3 ? (wp >> 2) * COL + 192 * (wp & 3) + 64 * t4 + 8 * q8 : (q8 >> 2) * COL + 768 + 4 * (q8 & 1)));
            xr = pin(sb + S_XB + 48 * (ln & 7));
            uint32_t x2 = 0;
            auto hop_d = [&](auto col) {
                const uint32_t xbs = pin(sb + S_XB + 384 * col.value + b_pos<40>(n80)), xas = col.value ? 0 : pin(sb + S_XA + 192 + a_pos(n80));
                const float x1 = bf_lo(lds16(xbs));
                const float lnx = __uint_as_float(pin(__float_as_uint(bfr(__fdiv_rn(bfr(x1 - mean), den)))));
                gather16(xp(uPolD + 4 * n80 + lag<DELAY_D>(sb, z0_)), col.value ? par1 : par0, 5 * ch + 3, [&](float y, uint32_t z) {
                    const uint32_t gate = ldsvol(sb + S_STAT + 4 * col.value + z);
                    x2 = pack2(x1 + bfr(lnx + bfr(bfr(y) * bf_hi(gate))), 0.f);
                    if (col.value) keep(x2); else { sts16(xbs, x2); sts16(xas, x2); }
                    return (uint32_t)((gate & 7) != ch + 1);
                });
                CSTAMP(17);
            };
            auto qproj = [&](auto with_stats) {
                bar_main();
                TST(5);
                CSTAMP(19);
                const uint32_t t4 = td & 3;
                const uint4 b = lds128(xr);
                uint32_t b4 = lds32(xr + 16);
                float acc[6][4] = {};
                if (with_stats.value) {
                    stp32_if((td & 11) == 3, xp(pubE), stats(xr + (S_XA - S_XB), b, b4), par0);
                    __syncwarp();
                    b4 = lds32(xr + 16);
                }
                mul80(acc, Wq, b, b4);
                const float v0 = sel4(t4, acc[0][0] + acc[0][3], acc[2][0] + acc[2][3], acc[4][0] + acc[4][3], acc[4][0] + acc[4][3]);
                const float v1 = sel4(t4, acc[1][0] + acc[1][3], acc[3][0] + acc[3][3], acc[5][0] + acc[5][3], acc[5][0] + acc[5][3]);
                stp64_if(t4 < 3, xp(pubE), tagw(v0, par0), tagw(v1, par0));
            };
            if (wp == 7) {
                if (!has0) break;
                qproj(std::true_type());
            } else {
                if (actc && !cc) hop_d(std::integral_constant<int, 0>());
                else {
                    if (actc && g == 0) {
                        const uint32_t po = pin(1280 * (ch - 1) + 160 * i + 2 * n80);
                        hop_d(std::integral_constant<int, 1>());
                        *reinterpret_cast<unsigned short*>(reinterpret_cast<char*>(P.out) + po) = (unsigned short)x2;
                    }
                    if (!has0) break;
                }
                qproj(std::false_type());
                sts32_if(td < 80, sb + S_XCAR + 4 * td, x2 << 16);
            }
        }
        CSTAMP(20);
        if (wp == 6) give_ln(uPolE, par0, sb + S_LN + 16, td, mean, den, [] { return 0u; });
        auto pass2 = [&](auto d0, auto d1, auto d2) {
            constexpr int D0 = d0.value, D1 = d1.value, D = D0 + D1 + d2.value;
            IDS();
            const uint32_t ua = sb + k_place(ch, wp & 6) * SLOT + (wp & 1) * UNIT, k0 = k_off(ln);
            uint32_t kf[12][2][4];
            auto ldk = [&](int s) { const uint32_t a = (k0 ^ (32 * (s / 3))) + (ua + 1024 * (s % 3)); ldsm4(kf[s][0], a); ldsm4(kf[s][1], a + SLOT); };
            auto ldv1 = [&](int k) { ldsm4t(vf[k / 3][k % 3], voff[k % 3] + (sb + v_place(ch, k / 3) * SLOT)); };
            auto ldv = [&](int s) { ldv1(3 * s); ldv1(3 * s + 1); ldv1(3 * s + 2); };
            constexpr uint32_t LATE = LAST_LATE;
            constexpr uint64_t EARLY_LIST = bit_list(~LATE), LATE_LIST = bit_list(LATE);
            auto early = [&](int k) {
                if (D1 == 0) ldk(k);
                else if (k < 3) { ldv1(9 + 2 * k); ldv1(10 + 2 * k); }
                else ldk((EARLY_LIST >> (4 * (k - 3))) & 15);
            };
            uint32_t v[8] = {}, qsa = 0;
            const char* srcv = xp(uPolE + lag<(D1 > 0 ? 0 : DELAY_E)>(sb, z0_) + 4 * td);
            auto look = [&] {
#pragma unroll
                for (int s = 0; s < 8; s++) v[s] = ldp32(srcv + (s >> 2) * HALF + (s & 3) * 1024);
            };
            if (D1 > 0) vaddr(voff);
            if (!(mbar_try(sb + S_FK + 8 * (wp & 6), par1) & mbar_try(sb + S_FK + 8 * (wp | 1), par1))) { mbar_wait(sb + S_FK + 8 * (wp & 6), par1); mbar_wait(sb + S_FK + 8 * (wp | 1), par1); }
#pragma unroll
            for (int s = 0; s < D0; s++) early(s);
            if (wp < 6) { look(); qsa = pin(sb + S_QS + 384 * ch + q_pos(z_)); }
#pragma unroll
            for (int s = D0; s < D0 + D1; s++) early(s);
            if (wp < 6) {
                const float cs = ldsf(sb + S_CSQ + 4 * td);
                int guard = 0;
                while (true) {
                    uint2 c = ldsvol64(sb + S_LN + 16 + ((v[0] ^ par0) & 1) * 32);
                    const bool stale = __any_sync(~0u, (chk8(v, par0) & 1) != 0), late = __any_sync(~0u, (c.y & 7) != ch + 1);
                    const float qs = sum8(v);
                    auto norm = [&] {
                        const uint32_t q = pack2(fmaf(-bf_hi(c.x), cs, qs) * asf(c.y), 0.f);
                        sts16(qsa, q);
                    };
                    norm();
                    if (!((stale | late) & (++guard < SPIN_LIMIT))) break;
                    if (!stale) { take_ln(c, sb + S_LN + 16); norm(); break; }
                    look();
                }
                SWEEPS(5 * ch + 4, guard - 1);
                CSTAMP(22);
            }
#pragma unroll
            for (int s = D0 + D1; s < D; s++) early(s);
            CSTAMP(21);
            bar_main();
            TST(6);
            CSTAMP(1);
            uint2 q = lds64(sb + S_QS + 384 * ch + 8 * ln);
            float acc[2][4] = {};
            constexpr int V0 = 13 - D, NV = D1 > 0 ? 2 : (2 * (D - 1)) / 3;
            static_assert(D1 == 0 || D - 3 + __builtin_popcount(LATE) == 12, "plan");
#pragma unroll
            for (int s = 0; s < 12; s++) {
                const bool m = q8 == (s & 7);
                const uint32_t b0 = m ? q.x : 0u, b1 = m ? q.y : 0u;
                if (s == 7) q = lds64(sb + S_QS + 384 * ch + 8 * ln + 256);
                mmaA(acc[0], kf[s][0], b0, b1);
                mmaA(acc[1], kf[s][1], b0, b1);
                if (D1 > 0) {
                    if (s >= 1 && s <= __builtin_popcount(LATE)) ldk((LATE_LIST >> (4 * (s - 1))) & 15);
                } else {
                    if (s >= 1 && s + D - 1 < 12) ldk(s + D - 1);
                    if (s >= 1 && s + D - 1 == 11) { __syncwarp(); arrive_if(ln == 0, sb + S_RELK); }
                    if (s == V0) vaddr(voff);
                    if (s >= V0 && 2 * (s - V0) < 3 * NV) ldv1(9 + 2 * (s - V0));
                    if (s >= V0 && 2 * (s - V0) + 1 < 3 * NV) ldv1(10 + 2 * (s - V0));
                }
            }
            CSTAMP(24);
            {
                const float v0 = acc[0][0] + acc[0][1], v1 = acc[0][2] + acc[0][3], v2 = acc[1][0] + acc[1][1], v3 = acc[1][2] + acc[1][3];
                const bool hi = t4 & 2, od = t4 & 1;
                const float u0 = (hi ? v2 : v0) + __shfl_xor_sync(~0u, hi ? v0 : v2, 2), u1 = (hi ? v3 : v1) + __shfl_xor_sync(~0u, hi ? v1 : v3, 2);
                const float s = (od ? u1 : u0) + __shfl_xor_sync(~0u, od ? u0 : u1, 1);
                CSTAMP(2);
                probs(scaled(s), sb + S_PS + PS_PASS, wp, ln);
                CSTAMP(3);
            }
            bar_main();
            TST(10);
            CSTAMP(4);
            if (D1 > 0) values(vf, acc_, [&](int s) { if (s < 3) ldv(s + 5); }, sb + S_PS + PS_PASS, 1, par0);
            else values(vf, acc_, [&](int s) { if (s >= (NV > 1 ? 2 : 1) && s + NV + (NV > 1 ? 1 : 2) < 8) ldv(s + NV + (NV > 1 ? 1 : 2)); }, sb + S_PS + PS_PASS, 1, par0);
            arrive_if(ln == 0, sb + S_RELV);
        };
        if (ch == 3) {
            pass2(std::integral_constant<int, LAST0>(), std::integral_constant<int, LAST1>(), std::integral_constant<int, LAST2>());
#pragma unroll
            for (int m = 0; m < 48; m++) Wq[m / 8].a[(m / 4) % 2][m % 4] = vf[3 + m / 12][(m / 4) % 3][m % 4];
#pragma unroll
            for (int m = 0; m < 12; m++) Wq[m / 2].c[m % 2] = vf[7][m / 4][m % 4];
#pragma unroll
            for (int m = 0; m < 36; m++) left[m] = m < 12 ? __float_as_uint(acc_[m / 4][m % 4]) : vf[m / 12][(m / 4) % 3][m % 4];
        } else {
            pass2(std::integral_constant<int, KPRE>(), std::integral_constant<int, 0>(), std::integral_constant<int, KPRE2>());
#pragma unroll
            for (int m = 0; m < 36; m++) left[m] = m < 12 ? __float_as_uint(acc_[m / 4][m % 4]) : vf[4 + m / 12][(m / 4) % 3][m % 4];
        }
        TST(11);
        CSTAMP(23);
    }
    sts32_if(td == 255, sb + S_GATE, 6);
    TSTAMP(3);
}

typedef CUresult (*EncodeFn)(CUtensorMap*, CUtensorMapDataType, cuuint32_t, void*, const cuuint64_t*, const cuuint64_t*, const cuuint32_t*,
                             const cuuint32_t*, CUtensorMapInterleave, CUtensorMapSwizzle, CUtensorMapL2promotion, CUtensorMapFloatOOBfill);

void make_map(EncodeFn enc, CUtensorMap* m, const void* base, uint64_t cols, uint64_t rows, uint32_t box_cols, uint32_t box_rows, bool swizzle) {
    cuuint64_t dims[2] = {cols, rows};
    cuuint64_t strides[1] = {cols * 2};
    cuuint32_t box[2] = {box_cols, box_rows};
    cuuint32_t es[2] = {1, 1};
    enc(m, CU_TENSOR_MAP_DATA_TYPE_BFLOAT16, 2, const_cast<void*>(base), dims, strides, box, es, CU_TENSOR_MAP_INTERLEAVE_NONE,
        swizzle ? CU_TENSOR_MAP_SWIZZLE_128B : CU_TENSOR_MAP_SWIZZLE_NONE, CU_TENSOR_MAP_L2_PROMOTION_NONE, CU_TENSOR_MAP_FLOAT_OOB_FILL_NONE);
}

}

extern "C" void kernel_launch(void* const* d_in, const int* in_sizes, int n_in, void* d_out, int out_size) {
    (void)in_sizes; (void)n_in; (void)out_size;
    static EncodeFn enc = nullptr;
    if (!enc) {
        void* f = nullptr;
        cudaDriverEntryPointQueryResult q;
        cudaGetDriverEntryPoint("cuTensorMapEncodeTiled", &f, cudaEnableDefault, &q);
        enc = (EncodeFn)f;
        cudaFuncSetAttribute(fused_kernel, cudaFuncAttributeMaxDynamicSharedMemorySize, SMEM_BYTES);
    }
    Params P;
    P.x = (const __nv_bfloat16*)d_in[0]; P.k = (const __nv_bfloat16*)d_in[1]; P.v = (const __nv_bfloat16*)d_in[2];
    P.wr = (const __nv_bfloat16*)d_in[6];
    P.out = (__nv_bfloat16*)d_out;
    Maps M;
    {
        cuuint64_t dims[4] = {64, 8, 3, (cuuint64_t)KV_BATCH_KEYS / 2}, strides[3] = {384, 128, 3072};
        cuuint32_t box[4] = {64, 8, 3, 2}, es[4] = {1, 1, 1, 1};
        enc(&M.k, CU_TENSOR_MAP_DATA_TYPE_BFLOAT16, 4, d_in[1], dims, strides, box, es, CU_TENSOR_MAP_INTERLEAVE_NONE, CU_TENSOR_MAP_SWIZZLE_128B,
            CU_TENSOR_MAP_L2_PROMOTION_NONE, CU_TENSOR_MAP_FLOAT_OOB_FILL_NONE);
    }
    make_map(enc, &M.v, P.v, 64, (uint64_t)12 * KV_BATCH_KEYS, 64, 96, true);
    make_map(enc, &M.vu, P.v, 64, (uint64_t)12 * KV_BATCH_KEYS, 64, 48, true);
    make_map(enc, &M.wq, d_in[3], 6144, 640, 192, 40, false);
    make_map(enc, &M.wo, d_in[4], 640, 6144, 80, 96, false);
    make_map(enc, &M.wg, d_in[7], 1536, 640, 96, 80, false);
    make_map(enc, &M.wu, d_in[8], 1536, 640, 96, 80, false);
    make_map(enc, &M.wd, d_in[9], 640, 1536, 80, 96, false);
    fused_kernel<<<NCTA, NTHR, SMEM_BYTES, cudaStreamPerThread>>>(P, M);
}
```

```cpp
#include <cuda_runtime.h>
#include <cuda.h>
#include <cuda_bf16.h>
#include <stdint.h>
#include <type_traits>

namespace {

constexpr int NCTA = 128;
constexpr int NTHR = 384;
constexpr int UNIT = 6144;
constexpr int SLOT = 12288;
#define TAU 3940
#define TAUW 3720
#define TAU0 3820
#define ILV 4
#define XB 600
#define TMIN 2400
#define SLACK 6000
#define SLACK0 1000
#define PF0 1
#define WIN_W 3
#define WIN_S 4
#define WIN_U 10
#define VPF 4
#define KRE_TAU 2600
#define RFR_TAU 25600
#define HOP1_NS 200
#define KPRE 1
#define KPRE2 3
#define LAST0 4
#define LAST1 4
#define LAST2 2
#define LAST_LATE 0xaa8
#define FSTEP 4
#define DELAY_L 2
#define DELAY_G 2
#define DELAY_C 3
#define DELAY_D 0
#define DELAY_E 1
#define REG_LO "40"
#define REG_HI "232"
#define SPIN_LOG 17
constexpr int SPIN_LIMIT = 1 << SPIN_LOG;

__host__ __device__ constexpr uint32_t pairL(uint32_t region, uint32_t c, uint32_t g) { return (g & 1) | ((g >> 1) << 2) | (c << 5) | (region << 6); }
__host__ __device__ constexpr uint32_t pairG(uint32_t d, uint32_t c, uint32_t i) { return (i & 1) | ((i >> 1) << 2) | (d << 4) | (c << 5) | (3u << 6); }
constexpr uint32_t RA = 0, RC = 1, RE = 2, HALF = 16384, COPY = 4096, PMASK = 0x59;
constexpr uint32_t XS = 0;
constexpr uint32_t XS2 = XS + 128 * 7680;
constexpr uint32_t XSEND = XS2 + 128 * 768;
__device__ uint4 g_s[XSEND / 16];
__device__ uint4 g_x[(4u << 20) / 16];
#define SWEEPS(k, n) do {} while (0)

constexpr uint32_t S_WD = 16 * SLOT;
constexpr uint32_t S_DUMMY = S_WD + 15360;
constexpr uint32_t S_BAR = S_DUMMY + 4096;
constexpr uint32_t S_FV = S_BAR, S_FK = S_FV + 64, S_RING = S_FK + 64, S_DBAR = S_RING + 48, S_WFULL = S_DBAR + 32, S_QRDY = S_WFULL + 88;
constexpr uint32_t S_RELK = S_QRDY + 8, S_RELV = S_RELK + 8, S_RELR = S_RELV + 8, S_RELW = S_RELR + 8, S_SCO = S_RELW + 24;
constexpr uint32_t S_OS1 = S_SCO + 8;
constexpr uint32_t S_ZERO = S_OS1 + 8;
constexpr uint32_t S_KF = S_ZERO + 8;
constexpr uint32_t S_TOK = S_KF + 8;
constexpr uint32_t S_SIDE = S_TOK + 80, S_GATE = S_SIDE + 4;
constexpr uint32_t S_STAT = S_GATE + 12, S_SWR = S_STAT + 16;
constexpr uint32_t S_LN = S_STAT + 32;
constexpr uint32_t S_XCAR = S_LN + 64;
constexpr uint32_t S_CSQ = S_XCAR + 320;
constexpr uint32_t S_CSGU = S_CSQ + 768;
constexpr uint32_t S_RED = S_CSGU + 768;
constexpr uint32_t S_L0 = S_RED;
constexpr uint32_t S_OS = S_RED + 5120;
constexpr uint32_t S_PS = S_OS + 1536;
constexpr uint32_t PS_MAX = 512, PS_PASS = 544;
constexpr uint32_t S_QS = S_PS + 2 * PS_PASS;
constexpr uint32_t S_XB = S_QS + 1536;
constexpr uint32_t S_XA = S_XB + 768;
constexpr uint32_t S_HS = S_XA + 768;
constexpr uint32_t S_X0 = S_HS + 768;
constexpr uint32_t S_SC = S_X0 + 640;
constexpr uint32_t S_TM = S_SC + 512;
constexpr int SMEM_BYTES = S_TM + 256;
static_assert(SMEM_BYTES <= 232448 && S_STAT % 16 == 0 && S_RED % 16 == 0 && S_XB % 16 == 0 && S_HS % 16 == 0 && S_PS % 16 == 0 && S_QS % 16 == 0, "smem");
static_assert(S_SCO == S_BAR + 44 * 8 && S_RELK == S_BAR + 38 * 8, "barriers");
constexpr uint32_t ST_WQ = 3 * SLOT, ST_WG = 8 * SLOT, ST_WO = 11 * SLOT;

__device__ __forceinline__ uint32_t smem_u32(const void* p) { return (uint32_t)__cvta_generic_to_shared(p); }
__device__ __forceinline__ void mbar_arrive(uint32_t bar) { asm volatile("mbarrier.arrive.shared::cta.b64 _, [%0];" :: "r"(bar) : "memory"); }
__device__ __forceinline__ bool mbar_try(uint32_t bar, uint32_t parity) {
    uint32_t ok;
    asm volatile("{\n .reg .pred p;\n mbarrier.try_wait.parity.shared::cta.b64 p, [%1], %2;\n selp.u32 %0, 1, 0, p;\n}" : "=r"(ok) : "r"(bar), "r"(parity) : "memory");
    return ok != 0;
}
__device__ __forceinline__ bool mbar_test(uint32_t bar, uint32_t parity) {
    uint32_t ok;
    asm volatile("{\n .reg .pred p;\n mbarrier.test_wait.parity.shared::cta.b64 p, [%1], %2;\n selp.u32 %0, 1, 0, p;\n}" : "=r"(ok) : "r"(bar), "r"(parity) : "memory");
    return ok != 0;
}
__device__ __forceinline__ void mbar_wait(uint32_t bar, uint32_t parity) {
    int n = 0;
    while (!mbar_try(bar, parity) && ++n < SPIN_LIMIT) {}
}
__device__ __forceinline__ uint32_t gtime32() { uint32_t t; asm volatile("mov.u32 %0, %globaltimer_lo;" : "=r"(t)); return t; }
__device__ __forceinline__ void bar_main() { asm volatile("bar.sync 1, 256;" ::: "memory"); }

__device__ __forceinline__ void mma16816(float (&c)[4], uint32_t a0, uint32_t a1, uint32_t a2, uint32_t a3, uint32_t b0, uint32_t b1) {
    asm("mma.sync.aligned.m16n8k16.row.col.f32.bf16.bf16.f32 {%0,%1,%2,%3}, {%4,%5,%6,%7}, {%8,%9}, {%0,%1,%2,%3};"
        : "+f"(c[0]), "+f"(c[1]), "+f"(c[2]), "+f"(c[3]) : "r"(a0), "r"(a1), "r"(a2), "r"(a3), "r"(b0), "r"(b1));
}
__device__ __forceinline__ void mmaA(float (&c)[4], const uint32_t (&a)[4], uint32_t b0, uint32_t b1) { mma16816(c, a[0], a[1], a[2], a[3], b0, b1); }
__device__ __forceinline__ void mma8(float (&c)[4], uint32_t a0, uint32_t a1, uint32_t b0) {
    asm("mma.sync.aligned.m16n8k8.row.col.f32.bf16.bf16.f32 {%0,%1,%2,%3}, {%4,%5}, {%6}, {%0,%1,%2,%3};"
        : "+f"(c[0]), "+f"(c[1]), "+f"(c[2]), "+f"(c[3]) : "r"(a0), "r"(a1), "r"(b0));
}
struct W80 { uint32_t a[2][4], c[2]; };
template <int N> __device__ __forceinline__ void mul80(float (&acc)[N][4], const W80 (&W)[N], const uint4& b, uint32_t b4) {
#pragma unroll
    for (int m = 0; m < N; m++) mmaA(acc[m], W[m].a[0], b.x, b.y);
#pragma unroll
    for (int m = 0; m < N; m++) mmaA(acc[m], W[m].a[1], b.z, b.w);
#pragma unroll
    for (int m = 0; m < N; m++) mma8(acc[m], W[m].c[0], W[m].c[1], b4);
}
__device__ __forceinline__ void ldsm2t(uint32_t (&r)[2], uint32_t addr) {
    asm volatile("ldmatrix.sync.aligned.m8n8.x2.trans.shared.b16 {%0,%1}, [%2];" : "=r"(r[0]), "=r"(r[1]) : "r"(addr) : "memory");
}
__device__ __forceinline__ void mmaV(float (&c)[4], const uint4& a, uint32_t b0, uint32_t b1) { mma16816(c, a.x, a.y, a.z, a.w, b0, b1); }
__device__ __forceinline__ void ldsm4(uint32_t (&r)[4], uint32_t addr) {
    asm volatile("ldmatrix.sync.aligned.m8n8.x4.shared.b16 {%0,%1,%2,%3}, [%4];" : "=r"(r[0]), "=r"(r[1]), "=r"(r[2]), "=r"(r[3]) : "r"(addr) : "memory");
}
__device__ __forceinline__ void ldsm4t(uint32_t (&r)[4], uint32_t addr) {
    asm volatile("ldmatrix.sync.aligned.m8n8.x4.trans.shared.b16 {%0,%1,%2,%3}, [%4];" : "=r"(r[0]), "=r"(r[1]), "=r"(r[2]), "=r"(r[3]) : "r"(addr) : "memory");
}
__device__ __forceinline__ uint32_t lds16(uint32_t a) { uint16_t v; asm volatile("ld.shared.u16 %0, [%1];" : "=h"(v) : "r"(a) : "memory"); return v; }
__device__ __forceinline__ uint32_t lds32(uint32_t a) { uint32_t v; asm volatile("ld.shared.u32 %0, [%1];" : "=r"(v) : "r"(a) : "memory"); return v; }
__device__ __forceinline__ float ldsf(uint32_t a) { return __uint_as_float(lds32(a)); }
__device__ __forceinline__ uint2 lds64(uint32_t a) { uint2 v; asm volatile("ld.shared.v2.u32 {%0,%1}, [%2];" : "=r"(v.x), "=r"(v.y) : "r"(a) : "memory"); return v; }
__device__ __forceinline__ uint4 lds128(uint32_t a) { uint4 v; asm volatile("ld.shared.v4.u32 {%0,%1,%2,%3}, [%4];" : "=r"(v.x), "=r"(v.y), "=r"(v.z), "=r"(v.w) : "r"(a) : "memory"); return v; }
__device__ __forceinline__ int ldsvol(uint32_t a) { int v; asm volatile("ld.volatile.shared.u32 %0, [%1];" : "=r"(v) : "r"(a) : "memory"); return v; }
__device__ __forceinline__ uint2 ldsvol64(uint32_t a) { uint2 v; asm volatile("{\n .reg .b64 d;\n ld.volatile.shared.b64 d, [%2];\n mov.b64 {%0,%1}, d;\n}" : "=r"(v.x), "=r"(v.y) : "r"(a) : "memory"); return v; }
__device__ __forceinline__ void stsvol64(uint32_t a, uint32_t x, uint32_t y) { asm volatile("{\n .reg .b64 d;\n mov.b64 d, {%1,%2};\n st.volatile.shared.b64 [%0], d;\n}" :: "r"(a), "r"(x), "r"(y) : "memory"); }
__device__ __forceinline__ void stsvol(uint32_t a, int v) { asm volatile("st.volatile.shared.u32 [%0], %1;" :: "r"(a), "r"(v) : "memory"); }
__device__ __forceinline__ void sts_hi16(uint32_t a, float v) { asm volatile("{\n .reg .b16 lo, hi;\n mov.b32 {lo, hi}, %1;\n st.shared.u16 [%0], hi;\n}" :: "r"(a), "r"(__float_as_uint(v)) : "memory"); }
__device__ __forceinline__ void sts16(uint32_t a, uint32_t v) { asm volatile("st.shared.u16 [%0], %1;" :: "r"(a), "r"(v) : "memory"); }
__device__ __forceinline__ void sts32(uint32_t a, uint32_t v) { asm volatile("st.shared.u32 [%0], %1;" :: "r"(a), "r"(v) : "memory"); }
__device__ __forceinline__ void stsf(uint32_t a, float v) { sts32(a, __float_as_uint(v)); }
__device__ __forceinline__ void sts64(uint32_t a, uint32_t x, uint32_t y) { asm volatile("st.shared.v2.u32 [%0], {%1,%2};" :: "r"(a), "r"(x), "r"(y) : "memory"); }

__device__ __forceinline__ void sts32_if(bool p, uint32_t a, uint32_t v) {
    asm volatile("{\n .reg .pred p;\n setp.ne.u32 p, %2, 0;\n @p st.shared.u32 [%0], %1;\n}" :: "r"(a), "r"(v), "r"((uint32_t)p) : "memory");
}
__device__ __forceinline__ void arrive_if(bool p, uint32_t bar) {
    asm volatile("{\n .reg .pred p;\n setp.ne.u32 p, %1, 0;\n @p mbarrier.arrive.shared::cta.b64 _, [%0];\n}" :: "r"(bar), "r"((uint32_t)p) : "memory");
}
__device__ __forceinline__ void keep(uint32_t& v) { asm volatile("" : "+r"(v)); }
__device__ __forceinline__ void keep(float& v) { asm volatile("" : "+f"(v)); }

__device__ __forceinline__ uint32_t ldp32(const char* p) { uint32_t v; asm volatile("ld.relaxed.gpu.global.u32 %0, [%1];" : "=r"(v) : "l"(p) : "memory"); return v; }
__device__ __forceinline__ uint2 ldp64(const char* p) {
    uint2 v; asm volatile("{\n .reg .b64 d;\n ld.relaxed.gpu.global.b64 d, [%2];\n mov.b64 {%0,%1}, d;\n}" : "=r"(v.x), "=r"(v.y) : "l"(p) : "memory"); return v;
}
__device__ __forceinline__ uint32_t tagw(float f, uint32_t par) { return (__float_as_uint(f) & ~1u) | par; }
__device__ __forceinline__ void stp32(char* p, float a, uint32_t par) { asm volatile("st.relaxed.gpu.global.u32 [%0], %1;" :: "l"(p), "r"(tagw(a, par)) : "memory"); }
__device__ __forceinline__ void stp64(char* p, float a, float b, uint32_t par) {
    asm volatile("{\n .reg .b64 d;\n mov.b64 d, {%1,%2};\n st.relaxed.gpu.global.b64 [%0], d;\n}" :: "l"(p), "r"(tagw(a, par)), "r"(tagw(b, par)) : "memory");
}
__device__ __forceinline__ void stp32_if(bool p, char* d, float a, uint32_t par) {
    asm volatile("{\n .reg .pred p;\n setp.ne.u32 p, %2, 0;\n @p st.relaxed.gpu.global.u32 [%0], %1;\n @p st.relaxed.gpu.global.u32 [%0+4096], %1;\n}" :: "l"(d), "r"(tagw(a, par)), "r"((uint32_t)p) : "memory");
}
__device__ __forceinline__ void stp64_if(bool p, char* d, uint32_t lo, uint32_t hi) {
    asm volatile("{\n .reg .pred p;\n .reg .b64 d;\n setp.ne.u32 p, %3, 0;\n mov.b64 d, {%1,%2};\n @p st.relaxed.gpu.global.b64 [%0], d;\n @p st.relaxed.gpu.global.b64 [%0+4096], d;\n}" :: "l"(d), "r"(lo), "r"(hi), "r"((uint32_t)p) : "memory");
}
__device__ __forceinline__ uint32_t chk2(uint32_t a, uint32_t b, uint32_t par) { uint32_t r; asm("lop3.b32 %0, %1, %2, %3, 0x7E;" : "=r"(r) : "r"(a), "r"(b), "r"(par)); return r; }
__device__ __forceinline__ uint32_t or3(uint32_t a, uint32_t b, uint32_t c) { uint32_t r; asm("lop3.b32 %0, %1, %2, %3, 0xFE;" : "=r"(r) : "r"(a), "r"(b), "r"(c)); return r; }
__device__ __forceinline__ uint32_t chk8(const uint32_t (&v)[8], uint32_t par) { return or3(chk2(v[0], v[1], par), chk2(v[2], v[3], par), or3(chk2(v[4], v[5], par), chk2(v[6], v[7], par), 0)); }
__device__ __forceinline__ uint32_t chk8(const uint2 (&v)[8], uint32_t par) { return or3(chk2(v[0].x, v[1].x, par), chk2(v[2].x, v[3].x, par), or3(chk2(v[4].x, v[5].x, par), chk2(v[6].x, v[7].x, par), 0)); }
__device__ __forceinline__ uint32_t chk8y(const uint2 (&v)[8], uint32_t par) { return or3(chk2(v[0].y, v[1].y, par), chk2(v[2].y, v[3].y, par), or3(chk2(v[4].y, v[5].y, par), chk2(v[6].y, v[7].y, par), 0)); }
__device__ __forceinline__ uint32_t chk4(const uint2 (&v)[4], uint32_t par) { return or3(chk2(v[0].x, v[0].y, par), chk2(v[1].x, v[1].y, par), or3(chk2(v[2].x, v[2].y, par), chk2(v[3].x, v[3].y, par), 0)); }
__device__ __forceinline__ float asf(uint32_t v) { return __uint_as_float(v); }
__device__ __forceinline__ float sum8(const uint32_t (&v)[8]) { return ((asf(v[0]) + asf(v[1])) + (asf(v[2]) + asf(v[3]))) + ((asf(v[4]) + asf(v[5])) + (asf(v[6]) + asf(v[7]))); }
__device__ __forceinline__ float sum8x(const uint2 (&v)[8]) { return ((asf(v[0].x) + asf(v[1].x)) + (asf(v[2].x) + asf(v[3].x))) + ((asf(v[4].x) + asf(v[5].x)) + (asf(v[6].x) + asf(v[7].x))); }
__device__ __forceinline__ float sum8y(const uint2 (&v)[8]) { return ((asf(v[0].y) + asf(v[1].y)) + (asf(v[2].y) + asf(v[3].y))) + ((asf(v[4].y) + asf(v[5].y)) + (asf(v[6].y) + asf(v[7].y))); }

__device__ __forceinline__ uint32_t pack2(float lo, float hi) { uint32_t r; asm("cvt.rn.bf16x2.f32 %0, %1, %2;" : "=r"(r) : "f"(hi), "f"(lo)); return r; }
__device__ __forceinline__ float bfr(float x) { return __uint_as_float(pack2(0.0f, x)); }
__device__ __forceinline__ float ex2(float x) { float r; asm("ex2.approx.ftz.f32 %0, %1;" : "=f"(r) : "f"(x)); return r; }
__device__ __forceinline__ float rcp(float x) { float r; asm("rcp.approx.ftz.f32 %0, %1;" : "=f"(r) : "f"(x)); return r; }
__device__ __forceinline__ float sqrt_(float x) { float r; asm("sqrt.approx.ftz.f32 %0, %1;" : "=f"(r) : "f"(x)); return r; }
__device__ __forceinline__ float bf_lo(uint32_t v) { return __uint_as_float(v << 16); }
__device__ __forceinline__ float bf_hi(uint32_t v) { return __uint_as_float(v & 0xffff0000u); }
__device__ __forceinline__ float sel4(int k, float a, float b, float c, float d) { return (k & 2) ? ((k & 1) ? d : c) : ((k & 1) ? b : a); }
constexpr float LOG2E = 1.4426950408889634f;
constexpr uint32_t ONES = 0x3f803f80u;

__device__ __forceinline__ void ln_stats(float sum, float sq, float& mean, float& den) {
    const float m = sum * (1.0f / 640.0f);
    const float var = fmaxf(fmaf(sq, 1.0f / 640.0f, -m * m), 0.0f);
    mean = bfr(m);
    den = bfr(sqrt_(bfr(bfr(var) + 1e-5f)));
}
__device__ __forceinline__ float sigmoidf_(float x) { return rcp(1.0f + ex2(-x * LOG2E)); }

#define TSTAMP(k) do {} while (0)
#define TST(k) do {} while (0)

#define CSTAMP(k) do {} while (0)
template <int N> __device__ __forceinline__ uint32_t lag(uint32_t sb, uint32_t z = 0) {
#pragma unroll
    for (int k = 0; k < N; k++) z = ldsvol(sb + S_ZERO + z);
    return z;
}
__device__ __forceinline__ void warm_mma(uint32_t& a, uint32_t& b) {
    asm volatile("mma.sync.aligned.m16n8k8.row.col.f16.f16.f16.f16 {%0,%1}, {%0,%1}, {%0}, {%0,%1};" : "+r"(a), "+r"(b) :: "memory");
}
#define KWNS2 20
#define KWNS 200
template <int STRIDE>
__device__ __forceinline__ float gather8(const char* p, uint32_t par) {
    uint32_t v[8];
    int guard = 0;
    do {
#pragma unroll
        for (int s = 0; s < 8; s++) v[s] = ldp32(p + s * STRIDE);
    } while ((chk8(v, par) & 1) && ++guard < SPIN_LIMIT);
    return sum8(v);
}
template <class F>
__device__ __forceinline__ void gather16(const char* p, uint32_t par, int k, F use) {
    uint32_t v[8], u[8];
    int guard = 0;
    bool again;
    do {
#pragma unroll
        for (int s = 0; s < 8; s++) v[s] = ldp32(p + s * 512);
#pragma unroll
        for (int s = 0; s < 8; s++) u[s] = ldp32(p + HALF + s * 512);
        const uint32_t stale = use(sum8(v) + sum8(u), ((v[0] ^ par) & 1) * 8);
        again = __any_sync(~0u, (or3(chk8(v, par), chk8(u, par), stale) & 1) != 0);
    } while (again & (++guard < SPIN_LIMIT));
    SWEEPS(k, guard - 1);
}

struct Params {
    const __nv_bfloat16 *x, *k, *v, *wr;
    __nv_bfloat16* out;
};
struct Maps { CUtensorMap k, v, vu, wq, wo, wg, wu, wd; };

constexpr int KV_BATCH_KEYS = 32 * 4096;

__device__ __forceinline__ void tma2d(uint32_t dst, const CUtensorMap* m, int c0, int c1, uint32_t bar, uint32_t bytes, uint64_t pol) {
    asm volatile("{\n .reg .pred p;\n elect.sync _|p, 0xffffffff;\n"
                 " @p mbarrier.arrive.expect_tx.shared::cta.b64 _, [%2], %6;\n"
                 " @p cp.async.bulk.tensor.2d.shared::cluster.global.mbarrier::complete_tx::bytes.L2::cache_hint [%0], [%1, {%3, %4}], [%2], %5;\n}"
                 :: "r"(dst), "l"(m), "r"(bar), "r"(c0), "r"(c1), "l"(pol), "r"(bytes) : "memory");
}
__device__ __forceinline__ void scrap_copy(uint32_t dst, const char* src, uint32_t bar) {
    asm volatile("{\n .reg .pred p;\n elect.sync _|p, 0xffffffff;\n"
                 " @p mbarrier.arrive.expect_tx.shared::cta.b64 _, [%2], 12288;\n"
                 " @p cp.async.bulk.shared::cluster.global.mbarrier::complete_tx::bytes [%0], [%1], 4096, [%2];\n"
                 " @p cp.async.bulk.shared::cluster.global.mbarrier::complete_tx::bytes [%0], [%1+4096], 4096, [%2];\n"
                 " @p cp.async.bulk.shared::cluster.global.mbarrier::complete_tx::bytes [%0], [%1+8192], 4096, [%2];\n}"
                 :: "r"(dst), "l"(src), "r"(bar) : "memory");
}
__device__ __forceinline__ void prefetch_l2(const void* p, uint32_t bytes) {
    asm volatile("{\n .reg .pred p;\n elect.sync _|p, 0xffffffff;\n @p cp.async.bulk.prefetch.L2.global [%0], %1;\n}" :: "l"(p), "r"(bytes) : "memory");
}
__device__ __forceinline__ uint64_t pol_first() { uint64_t p; asm("createpolicy.fractional.L2::evict_first.b64 %0, 1.0;" : "=l"(p)); return p; }
__device__ __forceinline__ uint64_t pol_normal() { uint64_t p; asm("createpolicy.fractional.L2::evict_normal.b64 %0, 1.0;" : "=l"(p)); return p; }
__device__ __forceinline__ bool utest(uint32_t bar, uint32_t parity) { return __all_sync(~0u, mbar_test(bar, parity)); }
__device__ __forceinline__ void uwait(uint32_t bar, uint32_t parity) {
    int n = 0;
    while (!__all_sync(~0u, mbar_try(bar, parity)) && ++n < SPIN_LIMIT) {}
}
template <int A, int B, int CNT> __device__ __forceinline__ void init_bars(uint32_t sb) {
#pragma unroll 1
    for (int k = A; k < B; k++)
        asm volatile("{\n .reg .pred p;\n elect.sync _|p, 0xffffffff;\n @p mbarrier.init.shared::cta.b64 [%0], %1;\n}" :: "r"(sb + S_BAR + 8 * k), "n"(CNT) : "memory");
}
__device__ __forceinline__ int unit_key(uint32_t b, uint32_t u) {
    return (blockIdx.x >> 2) * 4096 + 3072 + (blockIdx.x & 3) * (16 * ILV) + b * KV_BATCH_KEYS + (u & ~(ILV - 1u)) * 64 + (u & (ILV - 1)) * 16;
}
__device__ __forceinline__ void load_tile(const CUtensorMap* m, uint32_t dst, uint32_t bar, uint32_t bytes, int key, uint64_t pol) { tma2d(dst, m, 0, 3 * key, bar, bytes, pol); }
__device__ __forceinline__ const char* unit_ptr(const Params& P, int n) { return (const char*)((n & 16) ? P.v : P.k) + (size_t)unit_key(n >> 5, n & 15) * 384; }
#define LSTAMP(k) do {} while (0)

__device__ __forceinline__ uint32_t k_place(uint32_t b, uint32_t s) { return s + 3 + 5 * (b & 1); }
__device__ __forceinline__ uint32_t v_place(uint32_t b, uint32_t s) { return s < 3 ? s : s + 8 - 8 * (b & 1); }
__device__ __forceinline__ void k_load(const Maps& M, uint32_t dst, uint32_t bar, int key8, uint64_t pol) {
    asm volatile("{\n .reg .pred p;\n elect.sync _|p, 0xffffffff;\n"
                 " @p mbarrier.arrive.expect_tx.shared::cta.b64 _, [%2], 6144;\n"
                 " @p cp.async.bulk.tensor.4d.shared::cluster.global.mbarrier::complete_tx::bytes.L2::cache_hint [%0], [%1, {0, 0, 0, %3}], [%2], %4;\n}"
                 :: "r"(dst), "l"(&M.k), "r"(bar), "r"(key8), "l"(pol) : "memory");
}
__device__ __forceinline__ int unit_key8(uint32_t n) { return unit_key(n >> 4, n & 15) >> 3; }
__device__ __forceinline__ void ring_load(const Maps& M, uint32_t sb, uint32_t b, uint32_t u, uint32_t pos) {
    if (u < 16) k_load(M, sb + pos * UNIT, sb + S_RING + 8 * pos, unit_key8(16 * b + u), pol_normal());
    else load_tile(&M.vu, sb + pos * UNIT, sb + S_FV + 4 * (pos & 6), UNIT, unit_key(b, pos), pol_first());
}
__device__ __forceinline__ uint32_t token(bool p, uint32_t a, uint32_t n) {
    uint32_t v;
    asm volatile("{\n .reg .pred p;\n setp.ne.u32 p, %2, 0;\n mov.u32 %0, 0;\n @p atom.shared.exch.b32 %0, [%1], %3;\n}" : "=r"(v) : "r"(a), "r"((uint32_t)p), "r"(n) : "memory");
    return v;
}
__device__ __forceinline__ void place_load(const Maps& M, uint32_t sb, uint32_t n) {
    k_load(M, sb + k_place(n >> 4, 0) * SLOT + (n & 15) * UNIT, sb + S_FK + 4 * (n & 14), unit_key8(n), pol_first());
}
__device__ __forceinline__ void v_load(const Maps& M, uint32_t sb, uint32_t b, uint32_t s) {
    load_tile(&M.v, sb + v_place(b, s) * SLOT, sb + S_FV + 8 * s, SLOT, unit_key(b, 2 * s), pol_first());
}

__device__ __forceinline__ void stream_warp(const Params& P, const Maps& M, uint32_t sb, uint32_t lane) {
    const uint64_t pol = pol_first();
    const int bid = blockIdx.x, g = bid >> 3, i = bid & 7;
    const uint32_t wf = sb + S_WFULL;
    uint32_t tn = __shfl_sync(~0u, gtime32(), 0) * 16;
    auto pace = [&](uint32_t dt) {
        int k = 0;
        uint32_t now;
        do now = __shfl_sync(~0u, gtime32(), 0) * 16; while ((int)(now - tn) < 0 && ++k < SPIN_LIMIT);
        if ((int)(now - tn) > SLACK0) tn = now - SLACK0;
        tn += dt;
    };
#pragma unroll
    for (int k = 0; k < 10; k++) {
        if (k < 2) {
            if (k == 0) init_bars<26, 27, 1>(sb); else init_bars<27, 37, 1>(sb);
            asm volatile("fence.mbarrier_init.release.cluster;" ::: "memory");
            if (k == 1) { asm volatile("bar.arrive 2, %0;" :: "n"(NTHR) : "memory"); asm volatile("bar.sync 3, 128;" ::: "memory"); }
        }
        if (k >= WIN_W) uwait(wf + 8 * (k - WIN_W), 0);
        pace(TAUW * 5 / 2);
        if (k < 4) tma2d(sb + ST_WQ + 15360 * k, &M.wq, 384 * g + 192 * (k >> 1), 80 * i + 40 * (k & 1), wf + 8 * k, 15360, pol);
        else if (k < 6) tma2d(sb + ST_WG + 15360 * (k - 4), k == 4 ? &M.wg : &M.wu, 96 * g, 80 * i, wf + 8 * k, 15360, pol);
        else tma2d(sb + ST_WO + 15360 * (k - 6), &M.wo, 80 * i, 384 * g + 96 * (k - 6), wf + 8 * k, 15360, pol);
    }
#pragma unroll 1
    for (int n = 0; n < 16; n++) {
        if (n == 0 || n == 5 || n == 11) uwait(sb + S_RELW + (n == 0 ? 0 : n == 5 ? 8 : 16), 0);
        uwait(n < WIN_S ? wf + 8 * (10 - WIN_S + n) : sb + S_FV + 8 * ((n - WIN_S) ^ 8), 0);
        pace(max(min(2 * n + 2 - PF0, 2), 0) * TAU0);
        if (n >= WIN_S && !utest(sb + S_FV + 8 * ((n - WIN_S + 1) ^ 8), 0)) tn += XB;
        if (n < 8) { place_load(M, sb, 2 * n); place_load(M, sb, 2 * n + 1); }
        else if (n < 11) { ring_load(M, sb, 0, 2 * n, 2 * n - 16); ring_load(M, sb, 0, 2 * n + 1, 2 * n - 15); }
        else v_load(M, sb, 0, n - 8);
        if (n == 7) { pace(TAUW * 5 / 2); tma2d(sb + S_WD, &M.wd, 80 * i, 96 * g, wf + 80, 15360, pol); }
    }
    int nd = 0;
    uint32_t q[4];
#pragma unroll
    for (int r = 0; r < 4; r++) q[r] = sb + S_FV + 8 * (7 - r);
    uint32_t td = tn;
    uint32_t pos = 2;
#pragma unroll 1
    for (int m = 16; m < 64; m++) {
        const int b = m >> 4, j = m & 15;
        const char* src = unit_ptr(P, 2 * m);
        const uint32_t tok = sb + S_TOK + (j < 3 ? 4 * pos : j < 11 ? 24 + 4 * pos : 16 + 4 * j) + 4 * lane;
        static_assert(WIN_U <= 12, "a ring position has at most one token of the timetable");
        int k = 0;
        while (true) {
            const uint2 c = lds64(sb + S_KF);
            if (__all_sync(~0u, mbar_test(q[WIN_S - 1] & ~1u, q[WIN_S - 1] & 1) & (min((int)c.x + 1, (int)c.y) >= 16 * b + min(2 * j + 2 - WIN_U, 16))) || ++k >= SPIN_LIMIT) break;
        }
        uint32_t now;
        while (true) {
            now = __shfl_sync(~0u, gtime32(), 0) * 16;
            if ((int)(now - td) >= 0 || ++k >= SPIN_LIMIT) break;
        }
        const uint32_t mine = __ballot_sync(~0u, token(lane < (j < 11 ? 2 : 1), tok, 2 * m + lane) == 2 * m + lane);
        {
            const uint2 c = lds64(sb + S_KF);
            if (!__all_sync(~0u, mbar_test(q[WIN_S - 2] & ~1u, q[WIN_S - 2] & 1) & (min((int)c.x + 1, (int)c.y) >= 16 * b + min(2 * j + 4 - WIN_U, 16)))) tn += XB;
        }
        q[3] = q[2]; q[2] = q[1]; q[1] = q[0]; q[0] = sb + S_QRDY;
        if (j < 11) {
            if (mine & 1) ring_load(M, sb, b, 2 * j, pos); else prefetch_l2(src, UNIT);
            if (mine & 2) ring_load(M, sb, b, 2 * j + 1, pos + 1); else prefetch_l2(src + UNIT, UNIT);
            if (j >= 8) q[0] = (sb + S_FV + 8 * (j - 8)) | (b & 1);
        } else if (mine) { v_load(M, sb, b, j - 8); q[0] = (sb + S_FV + 8 * (j - 8)) | (b & 1); }
        else if (j - 8 >= VPF) prefetch_l2(src, SLOT);
        else {
            scrap_copy(sb + S_DUMMY, src, sb + S_DBAR + 8 * (nd & 3));
            q[0] = (sb + S_DBAR + 8 * (nd & 3)) | ((nd >> 2) & 1);
            nd++;
        }
        pos = j == 15 ? 2 : pos == 4 ? 0 : pos + 2;
        if ((int)(now - tn) > SLACK) tn = now - SLACK;
        tn += 2 * TAU;
        td = (int)(tn - now) > 2 * TMIN ? tn : now + 2 * TMIN;
    }
#pragma unroll 1
    for (int m = max(nd - 4, 0); m < nd; m++) uwait(sb + S_DBAR + 8 * (m & 3), (m >> 2) & 1);
}

__host__ __device__ constexpr uint64_t bit_list(uint32_t m) { uint64_t r = 0; int n = 0; for (int k = 0; k < 12; k++) if ((m >> k) & 1) r |= (uint64_t)k << (4 * n++); return r; }
__device__ __forceinline__ float scaled(float s) { return bfr(bfr(s) * 0.07216878364870322f); }
__device__ __forceinline__ void probs(float s, uint32_t ps, uint32_t src, uint32_t ln) {
    const uint32_t q8 = ln >> 2, t4 = ln & 3;
    int key = __float_as_int(s);
    key ^= (key >> 31) & 0x7fffffff;
    key = __reduce_max_sync(~0u, key);
    key ^= (key >> 31) & 0x7fffffff;
    const float ml = __int_as_float(key) * LOG2E;
    sts16(ps + 64 * src + (q8 >> 1) * 16 + t4 * 4 + (q8 & 1) * 2, pack2(ex2(fmaf(s, LOG2E, -ml)), 0.f));
    stsf(ps + PS_MAX + 4 * src, ml);
}
template <int H> __device__ __forceinline__ uint32_t b_pos(uint32_t e) { const uint32_t h = e >= H, k = e - H * h; return h * 192 + (k & 6) * 24 + (k >> 3) * 4 + (k & 1) * 2; }
__device__ __forceinline__ uint32_t a_pos(uint32_t e) { const uint32_t h = e >= 40, k = e - 40 * h; return (k & 6) * 24 + (k >> 3) * 8 + h * 4 + (k & 1) * 2; }
__device__ __forceinline__ uint32_t q_pos(uint32_t d) { const uint32_t s = 3 * ((d >> 4) & 3) + (d >> 6); return s * 32 + (d & 6) * 4 + ((d >> 3) & 1) * 4 + (d & 1) * 2; }
__device__ __forceinline__ uint32_t k_off(uint32_t ln) { return (ln & 8) * 384 + (ln & 7) * 128 + (((ln & 7) ^ (ln >> 4)) << 4); }

#define HSTAMP(k) do {} while (0)
__device__ __forceinline__ char* xwindow() { return reinterpret_cast<char*>((reinterpret_cast<uintptr_t>(g_x) + (2u << 20) - 1) & ~(uintptr_t)((2u << 20) - 1)); }

struct XPtr {
    uint32_t lo, hi;
    __device__ __forceinline__ explicit XPtr(char* p) : lo((uint32_t)(uintptr_t)p), hi((uint32_t)((uintptr_t)p >> 32)) {}
    __device__ __forceinline__ XPtr(uint32_t l, uint32_t h) : lo(l), hi(h) {}
    __device__ __forceinline__ XPtr operator+(uint32_t o) const { return XPtr(lo + o, hi); }
    __device__ __forceinline__ operator char*() const { uint64_t p; asm("mov.b64 %0, {%1, %2};" : "=l"(p) : "r"(lo), "r"(hi)); return (char*)p; }
};

__device__ __forceinline__ void side_warp(uint32_t sb) {
    const uint32_t bid = blockIdx.x, g = bid >> 3, i = bid & 7, P = pairG(0, 0, i);
    char* p = xwindow() + P * 8192 + (g >> 3) * HALF + (g & 7) * 512 + 448;
    uint32_t best[2] = {~0u, ~0u};
    asm volatile("st.relaxed.gpu.global.b32 [%0], 1;" :: "l"(p) : "memory");
    asm volatile("st.relaxed.gpu.global.b32 [%0], 1;" :: "l"(p + COPY) : "memory");
#pragma unroll 1
    for (int r = 0; r < 64; r++) {
        if (r >= 4 && !(r & 1) && min(best[0], best[1]) < 380 && max(best[0], best[1]) > min(best[0], best[1]) + 80) break;
        uint32_t c0, c1, v;
        asm volatile("mov.u32 %0, %clock;" : "=r"(c0) :: "memory");
        asm volatile("atom.relaxed.gpu.global.exch.b32 %0, [%1], 0;" : "=r"(v) : "l"(p + (r & 1) * COPY) : "memory");
        asm volatile("{\n .reg .pred q;\n setp.eq.u32 q, %1, 0x13579bdf;\n mov.u32 %0, 0;\n @!q mov.u32 %0, %clock;\n}" : "=r"(c1) : "r"(v) : "memory");
        if (r & 1) best[1] = min(best[1], c1 - c0); else best[0] = min(best[0], c1 - c0);
    }
    stsvol(sb + S_SIDE, 1 + ((best[1] < best[0]) ^ (__popc(P & PMASK) & 1)));
}

template <int N>
__device__ __forceinline__ void hop_a(const char* src, uint32_t par, uint32_t dst, bool st, int k) {
    uint2 v[N][4];
    float e[4], rl;
    int guard = 0;
    bool again;
    do {
#pragma unroll
        for (int s = 0; s < 4 * N; s++) v[s / 4][s % 4] = ldp64(src + (s / 4) * 256 + (s % 4) * 1024);
        again = __any_sync(~0u, ((chk4(v[0], par) | chk4(v[N - 1], par)) & 1) != 0);
        const int M = max(max((int)v[0][0].x, (int)v[0][1].x), max((int)v[0][2].x, (int)v[0][3].x)) - 254;
#pragma unroll
        for (int s = 0; s < 4; s++) e[s] = __int_as_float(max((int)v[0][s].x - M, 0) << 22);
        rl = rcp(fmaf(e[0], asf(v[0][0].y), e[1] * asf(v[0][1].y)) + fmaf(e[2], asf(v[0][2].y), e[3] * asf(v[0][3].y)));
#pragma unroll
        for (int s = 0; s < 4; s++) e[s] = __shfl_sync(~0u, e[s], 24);
        keep(rl);
    } while (again & (++guard < SPIN_LIMIT));
    rl = __shfl_sync(~0u, rl, 24);
#pragma unroll
    for (int n = 0; n < N; n++) {
        const float o0 = fmaf(e[0], asf(v[n][0].x), e[1] * asf(v[n][1].x)) + fmaf(e[2], asf(v[n][2].x), e[3] * asf(v[n][3].x));
        const float o1 = fmaf(e[0], asf(v[n][0].y), e[1] * asf(v[n][1].y)) + fmaf(e[2], asf(v[n][2].y), e[3] * asf(v[n][3].y));
        sts32_if(st, dst + 192 * n, pack2(o0 * rl, o1 * rl));
    }
    SWEEPS(k, guard - 1);
    __syncwarp();
}

__device__ __forceinline__ void score_warp(const Maps& M, uint32_t sb, uint32_t h, uint32_t ln) {
    const uint32_t lane0 = ln;
    uwait(sb + S_QRDY, 0);
    const uint32_t q8 = ln >> 2;
    const uint32_t k0 = k_off(ln);
    uint32_t pos = h + 6, bar = sb + S_FK, par = 0, phases = 0;
    uint2 q = lds64(sb + S_QS + 8 * ln), qh = lds64(sb + S_QS + 8 * ln + 256);
    auto first_round = [&](uint32_t b, uint32_t ln) {
        uwait(sb + S_RELR, b & 1);
        const uint32_t u = h + 2 * ln, p = u < 4 ? u + 2 : u - 4;
        uint32_t todo = __ballot_sync(~0u, token(ln < 3, sb + S_TOK + 4 * p, 32 * b + 32 + u) == 32 * b + 32 + u);
#pragma unroll 1
        for (uint32_t r = h; todo; todo >>= 1, r += 2) if (todo & 1) ring_load(M, sb, b + 1, r, r < 4 ? r + 2 : r - 4);
    };
#pragma unroll 1
    for (uint32_t n = h; n < 64; n += 2) {
        HSTAMP(0);
        const uint32_t ua = sb + pos * UNIT;
        if (!__all_sync(~0u, mbar_try(bar, par))) uwait(bar, par);
        HSTAMP(1);
        float acc[2][4] = {};
        uint32_t mine = 0;
        const uint32_t id = n + (n & 48) + 6;
#pragma unroll
        for (int s = 0; s < 12; s++) {
            uint32_t kf[4];
            ldsm4(kf, (k0 ^ (32 * (s / 3))) + (ua + 1024 * (s % 3)));
            if (s == 11) {
                __syncwarp();
                mine = token(ln == 0 && n >= 16, sb + S_TOK + 24 + 4 * pos, id);
                stsvol(sb + S_KF + 4 * h, n + 1);
            }
            const bool m = q8 == (s & 7);
            mmaA(acc[s & 1], kf, m ? (s < 8 ? q.x : qh.x) : 0u, m ? (s < 8 ? q.y : qh.y) : 0u);
        }
        const uint32_t pos0 = pos;
        const bool last = (n & 14) == 14;
        pos = last ? h + 2 : n >= 16 && pos >= 4 ? h : pos + 2;
        bar = n >= 14 ? sb + S_RING + 8 * pos : bar + 8;
        par = n >= 14 ? (phases >> pos) & 1 : 0;
        phases ^= n >= 14 ? 1u << pos : 0;
        const float w0 = (acc[0][0] + acc[0][1]) + (acc[1][0] + acc[1][1]), w1 = (acc[0][2] + acc[0][3]) + (acc[1][2] + acc[1][3]);
        HSTAMP(2);
        if (__any_sync(~0u, mine == id)) ring_load(M, sb, n >> 4, (n & 15) + 6, pos0);
        HSTAMP(3);
        float s = ((ln & 1) ? w1 : w0) + __shfl_xor_sync(~0u, (ln & 1) ? w0 : w1, 1);
        s += __shfl_xor_sync(~0u, s, 2);
        sts_hi16(sb + S_SC + (((n & 12) >> 1) + h) * 64 + (n & 2) * 2 + (ln & 29) * 2, scaled(s));
        if (last) {
            __syncwarp();
            arrive_if(ln == 0, sb + S_SCO);
            const uint32_t b = n >> 4, ln = lane0 + lag<1>(sb);
            if (b > 0) {
                uwait(sb + S_RELK, (b - 1) & 1);
                if (h == 0) LSTAMP(64 + 2 * b);
                const uint32_t sl = 3 + h + 2 * ln, idv = 32 * b + 16 + 2 * sl;
                uint32_t todo = __ballot_sync(~0u, token(sl < 8, sb + S_TOK + 48 + 4 * sl, idv) == idv);
#pragma unroll 1
                for (uint32_t r = 3 + h; todo; todo >>= 1, r += 2) if (todo & 1) v_load(M, sb, b, r);
                const uint32_t g = blockIdx.x >> 3, pr = pairL(RA, 1, g), side = ldsvol(sb + S_SIDE);
                const char* src = xwindow() + pr * 8192 + ((side ^ 1 ^ __popc(pr & PMASK)) & 1) * COPY + h * HALF + 8 * min(ln, 24u);
                uwait(sb + S_RELV, (b - 1) & 1);
                __nanosleep(HOP1_NS);
#pragma unroll 1
                for (uint32_t r = 0; r < 4; r += 2) {
                    hop_a<2>(src + 256 * r, b & 1, sb + S_OS + 192 * (4 * h + r) + 96 + 4 * ln, ln < 24, 25);
                    if (r == 0 && b < 3) first_round(b, ln);
                }
                arrive_if(ln == 0, sb + S_OS1);
            } else first_round(0, ln);
            q = lds64(sb + S_QS + 24 * ((n + 2) & 48) + 8 * ln); qh = lds64(sb + S_QS + 24 * ((n + 2) & 48) + 8 * ln + 256);
        }
    }
}

__global__ void __launch_bounds__(NTHR, 1)
fused_kernel(const Params P, const __grid_constant__ Maps M) {
    extern __shared__ __align__(1024) unsigned char smem[];
    const uint32_t sb = smem_u32(smem);
    const int tid = threadIdx.x, bid = blockIdx.x;
    if (tid == 0) {
        asm volatile("prefetch.tensormap [%0];" :: "l"(&M.wq) : "memory");
        asm volatile("cp.async.bulk.prefetch.L2.global [%0], %1;" :: "l"(unit_ptr(P, 0)), "r"(PF0 * UNIT) : "memory");
    }
    const int w = __shfl_sync(~0u, tid >> 5, 0), lane = tid & 31;

    if (w >= 8) {
        asm volatile("setmaxnreg.dec.sync.aligned.u32 " REG_LO ";");
        if (w == 8) {
            stream_warp(P, M, sb, lane);
        } else {
            if (w == 11 && lane < 8) asm volatile("prefetch.tensormap [%0];" :: "l"(&M.k + lane) : "memory");
            if (w == 9) { init_bars<0, 3, 2>(sb); init_bars<3, 8, 1>(sb); init_bars<16, 22, 1>(sb); }
            else if (w == 10) { init_bars<8, 16, 2>(sb); init_bars<22, 26, 1>(sb); }
            else { init_bars<37, 38, 1>(sb); init_bars<38, 40, 8>(sb); init_bars<40, 41, 1>(sb); init_bars<41, 44, 8>(sb); init_bars<44, 46, 2>(sb); stsvol(sb + S_ZERO + 4 * lane, 0); if (lane < 16) stsvol(sb + S_LN + 4 * lane, 0); }
            asm volatile("fence.mbarrier_init.release.cluster;" ::: "memory");
            asm volatile("bar.arrive 3, 128;" ::: "memory");
            asm volatile("bar.sync 2, %0;" :: "n"(NTHR) : "memory");
            if (w < 11) score_warp(M, sb, w - 9, lane);
            else {
                if (lane == 0) side_warp(sb);
                __syncwarp();
                uint32_t a = 0, b = 0;
                int k = 0;
                while (ldsvol(sb + S_GATE) == 0 && ++k < SPIN_LIMIT) { warm_mma(a, b); __nanosleep(KWNS); }
                uint4* d = reinterpret_cast<uint4*>(reinterpret_cast<char*>(g_s) + XS + bid * 7680) + lane;
                const uint4 z = make_uint4(0, 0, 0, 0);
#pragma unroll 1
                for (int u = 0; u < 15; u++) d[32 * u] = z;
                d = reinterpret_cast<uint4*>(reinterpret_cast<char*>(g_s) + XS2 + bid * 768) + lane;
                d[0] = z;
                if (lane < 16) d[32] = z;
                const uint32_t side = (ldsvol(sb + S_SIDE) & 1) ^ 1, g = bid >> 3, i = bid & 7;
                const XPtr gx(xwindow());
                auto nearp = [&](uint32_t pr) { return gx.lo + pr * 8192 + ((side ^ __popc(pr & PMASK)) & 1) * COPY; };
                const uint32_t own = (i >> 2) * HALF + (i & 3) * 1024 + (lane & 7) * 128;
                const uint32_t pAC = nearp(pairL(lane >> 4, (lane >> 3) & 1, g)) + own, pE = nearp(pairL(RE, (lane >> 3) & 1, g)) + own;
                const uint32_t pG = nearp(pairG((lane >> 2) & 1, (lane >> 3) & 1, i)) + min(lane & 3, 2) * 128;
                uint32_t tr = 0, tk = 0, ph = 0, src = g + (lane >> 4), seen = 0, n = 16, cs = 0;
                bool go = false, first = true;
                while (n < 64 && ++k < SPIN_LIMIT) {
                    const uint32_t now = __shfl_sync(~0u, gtime32(), 0) * 16;
                    if (!go && utest((n & 15) < 6 ? sb + S_RELK : sb + S_RELV, ((n >> 4) & 1) ^ 1)) { go = true; if ((int)(now - tk) > 0 || !(n & 15)) tk = now; }
                    if (go && (int)(now - tk) >= 0) {
                        place_load(M, sb, (n & 16) ? n : (n & 48) | ((n + 10) & 15));
                        tk += KRE_TAU;
                        n++;
                        go = (n & 15) != 0 && (n & 15) != 6;
                        if (!(n & 15)) LSTAMP(63 + (n >> 3));
                    } else if (first || (int)(now - tr) >= 0) {
                        first = false;
                        tr = now + RFR_TAU;
                        b |= seen & a;
                        warm_mma(a, b);
                        seen = ldp32(XPtr(ph == 0 ? pAC : ph == 1 && lane < 16 ? pE : pG + (src & 8) * (HALF / 8) + (src & 7) * 512, gx.hi));
                        const uint32_t l = lane + 32 * (++cs & 1);
                        *reinterpret_cast<volatile uint32_t*>(reinterpret_cast<char*>(g_s) + (l < 60 ? XS + bid * 7680 + 128 * l : XS2 + bid * 768 + 128 * (l - 60))) = 0;
                        src += ph == 0 ? 0 : ph == 1 ? 2 : 1;
                        ph = ph == 2 ? 0 : ph + 1;
                    } else __nanosleep(KWNS2);
                }
                while (ldsvol(sb + S_GATE) < 6 && ++k < SPIN_LIMIT) { warm_mma(a, b); __nanosleep(KWNS); }
                if (a | b) stsvol(sb + S_GATE, 6);
            }
        }
        return;
    }
    asm volatile("setmaxnreg.inc.sync.aligned.u32 " REG_HI ";");

    const int g = bid >> 3, i = bid & 7;
    const int g8 = lane >> 2, t = lane & 3;
    char* const gs = reinterpret_cast<char*>(g_s);
    const XPtr gx(xwindow());

    auto zero_words = [&] {
        const uint4 z = make_uint4(0, 0, 0, 0);
        const uint32_t c = (tid >> 6) & 1, cp = (tid >> 7) * COPY, k = (tid & 63) * 16;
        *reinterpret_cast<uint4*>((char*)(gx + pairL(RA, c, g) * 8192 + (i >> 2) * HALF + (i & 3) * 1024 + cp + k)) = z;
        *reinterpret_cast<uint4*>((char*)(gx + pairL(RC, c, g) * 8192 + (i >> 2) * HALF + (i & 3) * 1024 + cp + k)) = z;
        *reinterpret_cast<uint4*>((char*)(gx + pairL(RE, c, g) * 8192 + (i >> 2) * HALF + (i & 3) * 1024 + cp + k)) = z;
        if ((tid & 31) < 24) *reinterpret_cast<uint4*>((char*)(gx + pairG((tid >> 5) & 1, c, i) * 8192 + (g >> 3) * HALF + (g & 7) * 512 + cp + (tid & 31) * 16)) = z;
    };
    W80 Wq[6], Wgu[3];
    uint32_t Wo[5][3][4];
    if (w < 4) {
        const uint32_t* xp = reinterpret_cast<const uint32_t*>(P.x + 640 * w);
        float sum = 0.f, sq = 0.f;
#pragma unroll
        for (int u = 0; u < 10; u++) { uint32_t v = xp[lane + 32 * u]; float a = bf_lo(v), b = bf_hi(v); sum += a + b; sq += a * a + b * b; }
#pragma unroll
        for (int o = 16; o > 0; o >>= 1) { sum += __shfl_xor_sync(~0u, sum, o); sq += __shfl_xor_sync(~0u, sq, o); }
        float mean, den; ln_stats(sum, sq, mean, den);
        if (lane < 20) {
            const uint2 v = reinterpret_cast<const uint2*>(P.x + 640 * w + 80 * i)[lane];
            sts64(sb + S_X0 + 160 * w + 8 * lane, v.x, v.y);
            sts32(sb + S_L0 + 384 * w + b_pos<40>(4 * lane), pack2(__fdiv_rn(bfr(bf_lo(v.x) - mean), den), __fdiv_rn(bfr(bf_hi(v.x) - mean), den)));
            sts32(sb + S_L0 + 384 * w + b_pos<40>(4 * lane + 2), pack2(__fdiv_rn(bfr(bf_lo(v.y) - mean), den), __fdiv_rn(bfr(bf_hi(v.y) - mean), den)));
        }
    } else if (w == 4) {
        const uint32_t* xp = reinterpret_cast<const uint32_t*>(P.wr);
        float sum = 0.f;
#pragma unroll
        for (int u = 0; u < 10; u++) { uint32_t v = xp[lane + 32 * u]; sum += bf_lo(v) + bf_hi(v); }
#pragma unroll
        for (int o = 16; o > 0; o >>= 1) sum += __shfl_xor_sync(~0u, sum, o);
        if (lane == 0) stsf(sb + S_SWR, sum);
        if (lane < 20) {
            const uint2 v = reinterpret_cast<const uint2*>(P.wr + 80 * i)[lane];
            sts32(sb + S_XA + 576 + a_pos(4 * lane), v.x); sts32(sb + S_XA + 576 + a_pos(4 * lane + 2), v.y);
            sts32(sb + S_XA + a_pos(4 * lane), ONES); sts32(sb + S_XA + a_pos(4 * lane + 2), ONES);
        }
    }
    asm volatile("bar.sync 2, %0;" :: "n"(NTHR) : "memory");
    auto frag = [](uint32_t (&a)[4], uint32_t p, int pitch) {
        const uint32_t r0 = lds32(p), r1 = lds32(p + pitch), r2 = lds32(p + 2 * pitch), r3 = lds32(p + 3 * pitch);
        a[0] = __byte_perm(r0, r1, 0x5410); a[1] = __byte_perm(r0, r1, 0x7632);
        a[2] = __byte_perm(r2, r3, 0x5410); a[3] = __byte_perm(r2, r3, 0x7632);
    };
    mbar_wait(sb + S_WFULL + 16 * (w >> 2), 0);
    mbar_wait(sb + S_WFULL + 16 * (w >> 2) + 8, 0);
    {
        const uint32_t p = sb + ST_WQ + (w >> 2) * 30720 + (2 * t) * 384 + (48 * (w & 3) + 2 * g8) * 2;
#pragma unroll
        for (int r = 0; r < 10; r++)
#pragma unroll
            for (int m = 0; m < 3; m++) {
                const uint32_t q = p + ((r & 1) * 40 + (r >> 1) * 8) * 384 + 32 * m, r0 = lds32(q), r1 = lds32(q + 384);
                (r < 8 ? Wq[2 * m].a[(r >> 2) & 1][r & 3] : Wq[2 * m].c[r & 1]) = __byte_perm(r0, r1, 0x5410);
                (r < 8 ? Wq[2 * m + 1].a[(r >> 2) & 1][r & 3] : Wq[2 * m + 1].c[r & 1]) = __byte_perm(r0, r1, 0x7632);
            }
    }
    __syncwarp();
    if (lane == 0) mbar_arrive(sb + S_RELW);
    TSTAMP(1);
    {
        char* d = gs + XS + bid * 7680 + (w >> 2) * 3840 + (48 * (w & 3) + 2 * g8) * 4;
        float acc[6][4] = {};
        mul80(acc, Wq, lds128(sb + S_L0 + 48 * lane), lds32(sb + S_L0 + 48 * lane + 16));
#pragma unroll
        for (int m = 0; m < 6; m += 2) stp64(d + t * 768 + 32 * m, acc[m][0] + acc[m][3], acc[m + 1][0] + acc[m + 1][3], 1);
        float sum[6][4] = {};
        mul80(sum, Wq, make_uint4(ONES, ONES, ONES, ONES), ONES);
        if (t == 0)
#pragma unroll
            for (int m = 0; m < 6; m += 2) stp64(d + 4 * 768 + 32 * m, sum[m][0] + sum[m][3], sum[m + 1][0] + sum[m + 1][3], 1);
    }
    mbar_wait(sb + S_WFULL + 32, 0);
    mbar_wait(sb + S_WFULL + 40, 0);
    const uint32_t oct = 3 * (w >> 1) + (w & 1), oct2 = 3 * (w >> 1) + 2;
    {
        const uint32_t p = sb + ST_WG + ((lane & 7) + 40 * ((lane >> 3) & 1) + 8 * (lane >> 4)) * 192;
#pragma unroll
        for (int T = 0; T < 3; T++) {
            const uint32_t q = p + (T < 2 ? T * 15360 + 16 * oct : (w & 1) * 15360 + 16 * oct2);
            ldsm4t(Wgu[T].a[0], q); ldsm4t(Wgu[T].a[1], q + 16 * 192); ldsm2t(Wgu[T].c, q + 32 * 192);
        }
        float sum[3][4] = {};
        mul80(sum, Wgu, make_uint4(ONES, ONES, ONES, ONES), ONES);
        if (t < 3) stp32(gs + XS2 + bid * 768 + (t < 2 ? 64 * oct + 4 * t : 64 * oct2 + 4 * (w & 1)) + 8 * g8,
                         sel4(t, sum[0][0] + sum[0][3], sum[1][0] + sum[1][3], sum[2][0] + sum[2][3], 0.f), 1);
    }
    __syncwarp();
    if (lane == 0) mbar_arrive(sb + S_RELW + 8);
    mbar_wait(sb + S_WFULL + 48 + 8 * (w >> 1), 0);
    {
        const uint32_t po = sb + ST_WO + (48 * w + 12 * t) * 160 + 4 * g8;
#pragma unroll
        for (int s = 0; s < 3; s++)
#pragma unroll
            for (int m = 0; m < 5; m++) frag(Wo[m][s], po + 4 * s * 160 + 32 * m, 160);
    }
    __syncwarp();
    if (lane == 0) mbar_arrive(sb + S_RELW + 16);
    zero_words();
    if (tid < 192) {
        const char* srcS = gs + XS + g * 8 * 7680 + (i >> 2) * 3840 + tid * 4;
        uint32_t vs[5][8];
        int guard = 0;
        do {
#pragma unroll
            for (int b = 0; b < 5; b++)
#pragma unroll
                for (int s = 0; s < 8; s++) vs[b][s] = ldp32(srcS + b * 768 + s * 7680);
        } while (((or3(chk8(vs[0], 1), chk8(vs[1], 1), chk8(vs[2], 1)) | chk8(vs[3], 1) | chk8(vs[4], 1)) & 1) && ++guard < SPIN_LIMIT);
        const uint32_t qpos = sb + S_QS + q_pos(tid);
#pragma unroll
        for (int b = 0; b < 4; b++) {
            sts_hi16(qpos + 384 * b, bfr(sum8(vs[b])));
        }
        stsf(sb + S_CSQ + 4 * tid, sum8(vs[4]));
    }
    if (tid < 192) stsf(sb + S_CSGU + 4 * tid, gather8<768>(gs + XS2 + g * 8 * 768 + tid * 4, 1));
    __syncwarp();
    bar_main();
    arrive_if(tid == 0, sb + S_QRDY);
    TSTAMP(2);

    uint32_t side;
    { int k = 0; while ((side = ldsvol(sb + S_SIDE)) == 0 && ++k < SPIN_LIMIT) {} }
    const uint32_t td = __shfl_sync(~0u, tid, lane);
    const uint32_t wp = __shfl_sync(~0u, tid >> 5, 0);
    const uint32_t cc = wp >= 3;
    auto uni = [](uint32_t v) { return __shfl_sync(~0u, v, 0); };
    auto pin = [&](uint32_t v) { return __shfl_sync(~0u, v, td); };
    auto nearp = [&](uint32_t P) { return gx.lo + P * 8192 + ((side ^ 1 ^ __popc(P & PMASK)) & 1) * COPY; };
    constexpr uint32_t COL = 32 * 8192;
    const uint32_t ownL = gx.lo + (i >> 2) * HALF + (i & 3) * 1024, ownG = gx.lo + (g >> 3) * HALF + (g & 7) * 512;
    const uint32_t uPubA = uni(ownL + pairL(RA, 0, g) * 8192 + (wp >> 1) * 256 + (wp & 1) * 96), uPolA = uni(nearp(pairL(RA, 0, g)) + (wp >> 2) * HALF + (wp & 3) * 256);
    const uint32_t uPubB = uni(ownG + pairG(0, cc, i) * 8192), uPolB = uni(nearp(pairG(0, cc, i)));
    const uint32_t uPubC = uni(ownL + pairL(RC, 0, g) * 8192), uPolC = uni(nearp(pairL(RC, wp < 6 ? cc : 0, g)));
    const uint32_t uPubD = uni(ownG + pairG(1, 0, i) * 8192 + (wp < 7 ? 32 * wp : 256)), uPolD = uni(nearp(pairG(1, cc, i)));
    const uint32_t uPubE = uni(ownL + pairL(RE, 0, g) * 8192), uPolE = uni(nearp(pairL(RE, i >> 2, g)));
    const uint32_t uOS = uni(sb + S_OS + 192 * wp);
    auto xp = [&](uint32_t lo) { return (char*)XPtr(lo, gx.hi); };
#define IDS() __syncwarp(); const uint32_t z0_ = lag<1>(sb), z_ = td + z0_; const uint32_t ln = z_ & 31, q8 = ln >> 2, t4 = z_ & 3, n96 = z_ - 96 * cc, n80 = min(n96, 79u); (void)q8; (void)t4; (void)n80; (void)ln

    auto vaddr = [&](uint32_t (&voff)[3]) {
        const uint32_t ln = td & 31;
        const uint32_t key3 = 3 * ((ln & 7) + 2 * (ln & 8) + ((ln >> 1) & 8));
#pragma unroll
        for (int T = 0; T < 3; T++) {
            const uint32_t u = 3 * wp + T, r = key3 + (u >> 3);
            voff[T] = r * 128 + (((u ^ r) & 7) << 4);
        }
    };
    auto values = [&](uint32_t (&vf)[8][3][4], float (&acc)[3][4], auto step, uint32_t ps, uint32_t col, uint32_t par) {
        const uint32_t ln = td & 31, q8 = ln >> 2, t4 = td & 3;
        const uint4 p = lds128(ps + 16 * ln);
        float f0 = 0.f, f1 = 0.f, r3 = 0.f;
#pragma unroll
        for (int k = 0; k < 12; k++) acc[k / 4][k % 4] = 0.f;
        int M = 0;
#pragma unroll
        for (int s = 0; s < 8; s++) {
            step(s);
            const bool m = (q8 >> 1) == (s >> 1);
            const uint32_t b0 = m ? ((s & 1) ? p.z : p.x) : 0u, b1 = m ? ((s & 1) ? p.w : p.y) : 0u;
#pragma unroll
            for (int T = 0; T < 3; T++) mmaA(acc[T], vf[s][T], b0, b1);
            if (s == FSTEP) {
                const uint2 mp = lds64(ps + PS_MAX + 8 * t4);
                M = __reduce_max_sync(~0u, __float2int_ru(fmaxf(asf(mp.x), asf(mp.y))));
                f0 = ex2(asf(mp.x) - (float)M); f1 = ex2(asf(mp.y) - (float)M);
                float l[4] = {};
                mma16816(l, ONES, ONES, ONES, ONES, p.x, p.y); mma16816(l, ONES, ONES, ONES, ONES, p.z, p.w);
                r3 = fmaf(f0, l[0], f1 * l[1]);
            }
        }
        CSTAMP(25);
        char* pubA = xp(uPubA + col * COL + 32 * t4 + 4 * q8);
        const float r0 = fmaf(f0, acc[0][0], f1 * acc[0][3]), r1 = fmaf(f0, acc[1][0], f1 * acc[1][3]), r2 = fmaf(f0, acc[2][0], f1 * acc[2][3]);
        const bool hi = t4 & 2, od = t4 & 1;
        const float u0 = (hi ? r2 : r0) + __shfl_xor_sync(~0u, hi ? r0 : r2, 2), u1 = (hi ? r3 : r1) + __shfl_xor_sync(~0u, hi ? r1 : r3, 2);
        const float o = (od ? u1 : u0) + __shfl_xor_sync(~0u, od ? u0 : u1, 1);
        stp32_if(t4 < 3 || ((wp & 1) && q8 < 2), pubA, ln == 3 ? __int_as_float(2 * M) : o, par);
    };

    uint32_t left[36] = {};
#pragma unroll 1
    for (int ch = 0; ch < 5; ch++) {
        const uint32_t par0 = (ch + 1) & 1, par1 = ch & 1;
        uint32_t voff[3], vf[8][3][4];
        float acc_[3][4];
        if (ch < 4) {
            vaddr(voff);
            mbar_wait(sb + S_SCO, par1);
            if (ch == 0) mbar_wait(sb + S_WFULL + 80, 0);
            TST(0);
            auto ldw = [&](int s) {
                mbar_wait(sb + S_FV + 8 * s, par1);
#pragma unroll
                for (int T = 0; T < 3; T++) ldsm4t(vf[s][T], voff[T] + (sb + v_place(ch, s) * SLOT));
            };
            probs(bf_lo(lds16(sb + S_SC + 2 * td)), sb + S_PS, wp, td & 31);
            ldw(0); ldw(1); ldw(2);
            bar_main();
            arrive_if(td == 0, sb + S_RELR);
            values(vf, acc_, [&](int s) {
                if (s >= 3) ldw(s);
            }, sb + S_PS, 0, par0);
            TST(1);
            CSTAMP(5);
            if (ch > 0) mbar_wait(sb + S_OS1, par0);
        } else {
#pragma unroll
            for (int s = 0; s < 36; s++) vf[s / 12][(s / 4) % 3][s & 3] = left[s];
        }
        const bool has0 = ch < 4, has1 = ch > 0;
        const bool actc = wp < 6 && (cc ? has1 : has0);
        const uint32_t parc = cc ? par1 : par0;
        const uint32_t pub0 = has0 ? par0 : 0;
        uint32_t rr, pubB;
        {
            IDS();
            const uint32_t c = ch == 4;
            const uint32_t osa = pin(uOS + 96 * c + 4 * ln), oa = pin(uOS + 48 * (q8 & 2) + 24 * t4), ra = pin(sb + S_RED + 640 * wp + 320 * (t4 & 1) + 8 * q8);
            rr = pin(sb + S_RED + 320 * cc + 4 * n80); pubB = pin(uPubB + 4 * n80);
            hop_a<1>(xp(uPolA + c * COL + 8 * min(ln, 24u) + lag<DELAY_L>(sb, z0_)), pub0, osa, ln < 24, 5 * ch);
            TST(2);
            CSTAMP(6);
            float acc[5][4] = {};
            const uint2 b0 = lds64(oa), b1 = lds64(oa + 8), b2 = lds64(oa + 16);
#pragma unroll
            for (int m = 0; m < 5; m++) mmaA(acc[m], Wo[m][0], b0.x, b0.y);
#pragma unroll
            for (int m = 0; m < 5; m++) mmaA(acc[m], Wo[m][1], b1.x, b1.y);
#pragma unroll
            for (int m = 0; m < 5; m++) mmaA(acc[m], Wo[m][2], b2.x, b2.y);
#pragma unroll
            for (int m = 0; m < 5; m++) { stsf(ra + 64 * m, acc[m][0]); stsf(ra + 64 * m + 4, acc[m][2]); }
        }
        CSTAMP(7);
        uint32_t xr, fl, pubC, pubC2;
        auto prepC = [&](uint32_t ln) {
            const uint32_t q8 = ln >> 2, t4 = ln & 3;
            xr = pin(sb + S_XB + 48 * (ln & 15));
            pubC = pin(uPubC + (t4 & 1) * COL + 192 * (wp >> 1) + 64 * (wp & 1) + 8 * q8);
            pubC2 = pin(uPubC + (t4 & 1) * COL + ((t4 & 2) ? 192 * (wp >> 1) + 128 + 4 * (wp & 1) + 8 * q8 : 768 + 2 * ((q8 + 1) & 6)));
            fl = pin(((t4 & 1) ? par1 : pub0) | (t4 >= 2 || (wp == 7 && q8 < 4 && q8 != 2 - t4) ? 2 : 0));
        };
        auto stats = [&](uint32_t xa, const uint4& b, uint32_t b4) {
            float a0[4] = {}, a1[4] = {}, a2[4] = {};
            const uint4 p0 = lds128(xa), p1 = lds128(xa + 16);
            const uint2 p2 = lds64(xa + 32);
            mmaV(a0, p0, b.x, b.y); mmaV(a1, p1, b.z, b.w); mma8(a2, p2.x, p2.y, b4);
            return ((a0[0] + a0[3]) + (a1[0] + a1[3])) + (a2[0] + a2[3]);
        };
        auto give_ln = [&](uint32_t src0, uint32_t par, uint32_t dst, uint32_t ln, float& mean, float& den, auto also) {
            const char* src = xp(src0 + 768 + (ln & 1) * HALF);
            float sx, sq;
            int guard = 0;
            bool again;
            do {
                uint2 st[4];
#pragma unroll
                for (int s = 0; s < 4; s++) st[s] = ldp64(src + s * 1024);
                again = __any_sync(~0u, ((chk4(st, par) | also()) & 1) != 0);
                sx = (asf(st[0].x) + asf(st[1].x)) + (asf(st[2].x) + asf(st[3].x)); sq = (asf(st[0].y) + asf(st[1].y)) + (asf(st[2].y) + asf(st[3].y));
                sx += __shfl_xor_sync(~0u, sx, 1); sq += __shfl_xor_sync(~0u, sq, 1);
            } while (again & (++guard < SPIN_LIMIT));
            ln_stats(sx, sq, mean, den);
            stsvol64(dst, __byte_perm(__float_as_uint(den), __float_as_uint(mean), 0x7632), (__float_as_uint(rcp(den)) & ~7u) | (ch + 1));
        };
        auto take_ln = [&](uint2& c, uint32_t a) { int k = 0; do c = ldsvol64(a); while (__any_sync(~0u, (c.y & 7) != ch + 1) & (++k < SPIN_LIMIT)); };
        {
            auto gate_up = [&](auto with_stats) {
                bar_main();
                TST(3);
                CSTAMP(11);
                const uint4 b = lds128(xr);
                uint32_t b4 = lds32(xr + 16);
                float acc[3][4] = {};
                if (with_stats.value) {
                    stp32_if(fl > 1 && !(td & 2), xp(pubC2), stats(xr + (S_XA - S_XB), b, b4), fl & 1);
                    __syncwarp();
                    b4 = lds32(xr + 16);
                }
                mul80(acc, Wgu, b, b4);
                stp64_if(!(td & 2), xp(pubC), tagw(acc[0][0] + acc[0][3], fl & 1), tagw(acc[1][0] + acc[1][3], fl & 1));
                stp32_if(td & 2, xp(pubC2), acc[2][0] + acc[2][3], fl & 1);
            };
            if (wp == 7) {
                bar_main();
                IDS();
                prepC(ln);
                sts32(sb + S_ZERO + 4, or3(pubC, pubC2, fl));
                gate_up(std::true_type());
            } else {
                if (actc) {
                    bar_main();
                    CSTAMP(8);
                    uint32_t r[8];
#pragma unroll
                    for (int s = 0; s < 8; s++) r[s] = lds32(rr + 640 * s);
                    stp32_if(true, xp(pubB), sum8(r), parc);
                    CSTAMP(9);
                    IDS();
                    prepC(ln);
                    const uint32_t n4 = 4 * n80;
                    const uint32_t xas = pin(sb + S_XA + 192 + 192 * cc + a_pos(n80)), xbs = pin(sb + S_XB + 384 * cc + b_pos<40>(n80));
                    const float x0 = cc ? ldsf(sb + S_XCAR + n4) : bf_lo(lds16(sb + S_X0 + 160 * (ch & 3) + n4 / 2));
                    gather16(xp(uPolB + n4 + lag<DELAY_G>(sb, z0_)), parc, 5 * ch + 1, [&](float y, uint32_t) {
                        const uint32_t x = pack2(x0 + bfr(y), 0.f);
                        sts16(xbs, x);
                        sts16(xas, x);
                        return 0u;
                    });
                    CSTAMP(10);
                } else {
                    bar_main();
                    IDS();
                    prepC(ln);
                }
                gate_up(std::false_type());
            }
        }
        CSTAMP(12);
        float mean = 0.f, den = 1.f;
        {
            IDS();
            const uint32_t wh = pin((((ln & 7) + 48 * ((ln >> 3) & 1) + 8 * (ln >> 4)) * 160 + (wp < 7 ? 16 * wp : 128)) | ((384 * cc + b_pos<48>(n96)) << 16));
            const uint32_t pubD = pin(uPubD + (t4 & 1) * COL + 16 * (t4 & 2) + 4 * q8 + (fl & 1)), ha = xr + (S_HS - S_XB);
            auto down = [&](const uint32_t (&W)[3][4], const uint4& h0, const uint2& h1) {
                float a0[4] = {}, a1[4] = {}, a2[4] = {};
                mmaA(a0, W[0], h0.x, h0.y); mmaA(a1, W[1], h0.z, h0.w); mmaA(a2, W[2], h1.x, h1.y);
                return ((a0[0] + a0[3]) + (a1[0] + a1[3])) + (a2[0] + a2[3]);
            };
            if (wp < 6) {
                uint32_t Wd[3][4];
                auto ldd = [&](uint32_t z) {
#pragma unroll
                    for (int s = 0; s < 3; s++) ldsm4t(Wd[s], ((wh ^ z) & 0xffff) + (sb + S_WD + s * 2560));
                };
                ldd(0);
                if (actc) {
                    const char* srcv = xp(uPolC + lag<DELAY_C>(sb, z0_) + 8 * n96);
                    const uint2 cs = lds64(sb + S_CSGU + 8 * n96);
                    float gt, up;
                    int guard = 0;
                    while (true) {
                        uint2 v[8];
#pragma unroll
                        for (int s = 0; s < 8; s++) v[s] = ldp64(srcv + (s >> 2) * HALF + (s & 3) * 1024);
                        uint2 c = ldsvol64(sb + S_LN + 8 * cc + ((v[0].x ^ parc) & 1) * 32);
                        const bool stale = __any_sync(~0u, ((chk8(v, parc) | chk8y(v, parc)) & 1) != 0), late = __any_sync(~0u, (c.y & 7) != ch + 1);
                        const float pg = sum8x(v), pu = sum8y(v);
                        auto norm = [&] {
                            mean = bf_hi(c.x); den = bf_lo(c.x);
                            gt = bfr(fmaf(-mean, asf(cs.x), pg) * asf(c.y)); up = fmaf(-mean, asf(cs.y), pu) * asf(c.y);
                            keep(gt); keep(up);
                        };
                        norm();
                        if (!((stale | late) & (++guard < SPIN_LIMIT))) break;
                        if (!stale) { take_ln(c, sb + S_LN + 8 * cc); norm(); break; }
                    }
                    CSTAMP(13);
                    SWEEPS(5 * ch + 2, guard - 1);
                    const uint32_t h = pack2(bfr(gt * sigmoidf_(gt)) * bfr(up), 0.f);
                    sts16((wh >> 16) + (sb + S_HS), h);
                    CSTAMP(14);
                    if (ch == 3) CSTAMP(0);
                }
                bar_main();
                TST(4);
                CSTAMP(15);
                const uint4 h0 = lds128(ha);
                const uint2 h1 = lds64(ha + 16);
                stp32_if(!(td & 2), xp(pubD & ~1u), down(Wd, h0, h1), pubD & 1);
            } else {
                uint32_t v = 0;
                const uint32_t col = wp == 7 || !has0;
                const bool serve = wp == 6 || (has0 && has1);
                if (serve) {
                    const uint32_t par = col ? par1 : par0;
                    const char* src = xp(uPolC + col * COL + 776 + (td & 4) * (HALF / 4) + (td & 3) * 1024);
                    give_ln(uPolC + col * COL, par, sb + S_LN + 8 * col, td, mean, den, [&] { v = ldp32(src); return v ^ par; });
                }
                stsvol(sb + S_GATE, ch + 1);
                uint32_t Wd[2][3][4];
#pragma unroll
                for (int s = 0; s < 6; s++) ldsm4t(Wd[s / 3][s % 3], (wh & 0xffff) + (sb + S_WD + (s / 3) * 16 + (s % 3) * 2560));
                bar_main();
                const uint4 h0 = lds128(ha);
                const uint2 h1 = lds64(ha + 16);
                const float d0 = down(Wd[0], h0, h1), d1 = down(Wd[1], h0, h1);
                stp32_if(true, xp(pubD & ~1u), (td & 2) ? d1 : d0, pubD & 1);
                if (serve) {
                    float xw = asf(v);
                    xw += __shfl_xor_sync(~0u, xw, 1); xw += __shfl_xor_sync(~0u, xw, 2); xw += __shfl_xor_sync(~0u, xw, 4);
                    const float r = bfr(fmaf(-mean, ldsf(sb + S_SWR), xw) * rcp(den));
                    sts32(sb + S_STAT + 4 * col, __float_as_uint(bfr(sigmoidf_(r))) | (ch + 1));
                }
            }
        }
        CSTAMP(16);
        {
            IDS();
            const uint32_t pubE = pin(uPubE + (t4 < 3 ? (wp >> 2) * COL + 192 * (wp & 3) + 64 * t4 + 8 * q8 : (q8 >> 2) * COL + 768 + 4 * (q8 & 1)));
            xr = pin(sb + S_XB + 48 * (ln & 7));
            uint32_t x2 = 0;
            auto hop_d = [&](auto col) {
                const uint32_t xbs = pin(sb + S_XB + 384 * col.value + b_pos<40>(n80)), xas = col.value ? 0 : pin(sb + S_XA + 192 + a_pos(n80));
                const float x1 = bf_lo(lds16(xbs));
                const float lnx = __uint_as_float(pin(__float_as_uint(bfr(__fdiv_rn(bfr(x1 - mean), den)))));
                gather16(xp(uPolD + 4 * n80 + lag<DELAY_D>(sb, z0_)), col.value ? par1 : par0, 5 * ch + 3, [&](float y, uint32_t z) {
                    const uint32_t gate = ldsvol(sb + S_STAT + 4 * col.value + z);
                    x2 = pack2(x1 + bfr(lnx + bfr(bfr(y) * bf_hi(gate))), 0.f);
                    if (col.value) keep(x2); else { sts16(xbs, x2); sts16(xas, x2); }
                    return (uint32_t)((gate & 7) != ch + 1);
                });
                CSTAMP(17);
            };
            auto qproj = [&](auto with_stats) {
                bar_main();
                TST(5);
                CSTAMP(19);
                const uint32_t t4 = td & 3;
                const uint4 b = lds128(xr);
                uint32_t b4 = lds32(xr + 16);
                float acc[6][4] = {};
                if (with_stats.value) {
                    stp32_if((td & 11) == 3, xp(pubE), stats(xr + (S_XA - S_XB), b, b4), par0);
                    __syncwarp();
                    b4 = lds32(xr + 16);
                }
                mul80(acc, Wq, b, b4);
                const float v0 = sel4(t4, acc[0][0] + acc[0][3], acc[2][0] + acc[2][3], acc[4][0] + acc[4][3], acc[4][0] + acc[4][3]);
                const float v1 = sel4(t4, acc[1][0] + acc[1][3], acc[3][0] + acc[3][3], acc[5][0] + acc[5][3], acc[5][0] + acc[5][3]);
                stp64_if(t4 < 3, xp(pubE), tagw(v0, par0), tagw(v1, par0));
            };
            if (wp == 7) {
                if (!has0) break;
                qproj(std::true_type());
            } else {
                if (actc && !cc) hop_d(std::integral_constant<int, 0>());
                else {
                    if (actc && g == 0) {
                        const uint32_t po = pin(1280 * (ch - 1) + 160 * i + 2 * n80);
                        hop_d(std::integral_constant<int, 1>());
                        *reinterpret_cast<unsigned short*>(reinterpret_cast<char*>(P.out) + po) = (unsigned short)x2;
                    }
                    if (!has0) break;
                }
                qproj(std::false_type());
                sts32_if(td < 80, sb + S_XCAR + 4 * td, x2 << 16);
            }
        }
        CSTAMP(20);
        if (wp == 6) give_ln(uPolE, par0, sb + S_LN + 16, td, mean, den, [] { return 0u; });
        auto pass2 = [&](auto d0, auto d1, auto d2) {
            constexpr int D0 = d0.value, D1 = d1.value, D = D0 + D1 + d2.value;
            IDS();
            const uint32_t ua = sb + k_place(ch, wp & 6) * SLOT + (wp & 1) * UNIT, k0 = k_off(ln);
            uint32_t kf[12][2][4];
            auto ldk = [&](int s) { const uint32_t a = (k0 ^ (32 * (s / 3))) + (ua + 1024 * (s % 3)); ldsm4(kf[s][0], a); ldsm4(kf[s][1], a + SLOT); };
            auto ldv1 = [&](int k) { ldsm4t(vf[k / 3][k % 3], voff[k % 3] + (sb + v_place(ch, k / 3) * SLOT)); };
            auto ldv = [&](int s) { ldv1(3 * s); ldv1(3 * s + 1); ldv1(3 * s + 2); };
            constexpr uint32_t LATE = LAST_LATE;
            constexpr uint64_t EARLY_LIST = bit_list(~LATE), LATE_LIST = bit_list(LATE);
            auto early = [&](int k) {
                if (D1 == 0) ldk(k);
                else if (k < 3) { ldv1(9 + 2 * k); ldv1(10 + 2 * k); }
                else ldk((EARLY_LIST >> (4 * (k - 3))) & 15);
            };
            uint32_t v[8] = {}, qsa = 0;
            const char* srcv = xp(uPolE + lag<(D1 > 0 ? 0 : DELAY_E)>(sb, z0_) + 4 * td);
            auto look = [&] {
#pragma unroll
                for (int s = 0; s < 8; s++) v[s] = ldp32(srcv + (s >> 2) * HALF + (s & 3) * 1024);
            };
            if (D1 > 0) vaddr(voff);
            if (!(mbar_try(sb + S_FK + 8 * (wp & 6), par1) & mbar_try(sb + S_FK + 8 * (wp | 1), par1))) { mbar_wait(sb + S_FK + 8 * (wp & 6), par1); mbar_wait(sb + S_FK + 8 * (wp | 1), par1); }
#pragma unroll
            for (int s = 0; s < D0; s++) early(s);
            if (wp < 6) { look(); qsa = pin(sb + S_QS + 384 * ch + q_pos(z_)); }
#pragma unroll
            for (int s = D0; s < D0 + D1; s++) early(s);
            if (wp < 6) {
                const float cs = ldsf(sb + S_CSQ + 4 * td);
                int guard = 0;
                while (true) {
                    uint2 c = ldsvol64(sb + S_LN + 16 + ((v[0] ^ par0) & 1) * 32);
                    const bool stale = __any_sync(~0u, (chk8(v, par0) & 1) != 0), late = __any_sync(~0u, (c.y & 7) != ch + 1);
                    const float qs = sum8(v);
                    auto norm = [&] {
                        const uint32_t q = pack2(fmaf(-bf_hi(c.x), cs, qs) * asf(c.y), 0.f);
                        sts16(qsa, q);
                    };
                    norm();
                    if (!((stale | late) & (++guard < SPIN_LIMIT))) break;
                    if (!stale) { take_ln(c, sb + S_LN + 16); norm(); break; }
                    look();
                }
                SWEEPS(5 * ch + 4, guard - 1);
                CSTAMP(22);
            }
#pragma unroll
            for (int s = D0 + D1; s < D; s++) early(s);
            CSTAMP(21);
            bar_main();
            TST(6);
            CSTAMP(1);
            uint2 q = lds64(sb + S_QS + 384 * ch + 8 * ln);
            float acc[2][4] = {};
            constexpr int V0 = 13 - D, NV = D1 > 0 ? 2 : (2 * (D - 1)) / 3;
            static_assert(D1 == 0 || D - 3 + __builtin_popcount(LATE) == 12, "plan");
#pragma unroll
            for (int s = 0; s < 12; s++) {
                const bool m = q8 == (s & 7);
                const uint32_t b0 = m ? q.x : 0u, b1 = m ? q.y : 0u;
                if (s == 7) q = lds64(sb + S_QS + 384 * ch + 8 * ln + 256);
                mmaA(acc[0], kf[s][0], b0, b1);
                mmaA(acc[1], kf[s][1], b0, b1);
                if (D1 > 0) {
                    if (s >= 1 && s <= __builtin_popcount(LATE)) ldk((LATE_LIST >> (4 * (s - 1))) & 15);
                } else {
                    if (s >= 1 && s + D - 1 < 12) ldk(s + D - 1);
                    if (s >= 1 && s + D - 1 == 11) { __syncwarp(); arrive_if(ln == 0, sb + S_RELK); }
                    if (s == V0) vaddr(voff);
                    if (s >= V0 && 2 * (s - V0) < 3 * NV) ldv1(9 + 2 * (s - V0));
                    if (s >= V0 && 2 * (s - V0) + 1 < 3 * NV) ldv1(10 + 2 * (s - V0));
                }
            }
            CSTAMP(24);
            {
                const float v0 = acc[0][0] + acc[0][1], v1 = acc[0][2] + acc[0][3], v2 = acc[1][0] + acc[1][1], v3 = acc[1][2] + acc[1][3];
                const bool hi = t4 & 2, od = t4 & 1;
                const float u0 = (hi ? v2 : v0) + __shfl_xor_sync(~0u, hi ? v0 : v2, 2), u1 = (hi ? v3 : v1) + __shfl_xor_sync(~0u, hi ? v1 : v3, 2);
                const float s = (od ? u1 : u0) + __shfl_xor_sync(~0u, od ? u0 : u1, 1);
                CSTAMP(2);
                probs(scaled(s), sb + S_PS + PS_PASS, wp, ln);
                CSTAMP(3);
            }
            bar_main();
            TST(10);
            CSTAMP(4);
            if (D1 > 0) values(vf, acc_, [&](int s) { if (s < 3) ldv(s + 5); }, sb + S_PS + PS_PASS, 1, par0);
            else values(vf, acc_, [&](int s) { if (s >= (NV > 1 ? 2 : 1) && s + NV + (NV > 1 ? 1 : 2) < 8) ldv(s + NV + (NV > 1 ? 1 : 2)); }, sb + S_PS + PS_PASS, 1, par0);
            arrive_if(ln == 0, sb + S_RELV);
        };
        if (ch == 3) {
            pass2(std::integral_constant<int, LAST0>(), std::integral_constant<int, LAST1>(), std::integral_constant<int, LAST2>());
#pragma unroll
            for (int m = 0; m < 48; m++) Wq[m / 8].a[(m / 4) % 2][m % 4] = vf[3 + m / 12][(m / 4) % 3][m % 4];
#pragma unroll
            for (int m = 0; m < 12; m++) Wq[m / 2].c[m % 2] = vf[7][m / 4][m % 4];
#pragma unroll
            for (int m = 0; m < 36; m++) left[m] = m < 12 ? __float_as_uint(acc_[m / 4][m % 4]) : vf[m / 12][(m / 4) % 3][m % 4];
        } else {
            pass2(std::integral_constant<int, KPRE>(), std::integral_constant<int, 0>(), std::integral_constant<int, KPRE2>());
#pragma unroll
            for (int m = 0; m < 36; m++) left[m] = m < 12 ? __float_as_uint(acc_[m / 4][m % 4]) : vf[4 + m / 12][(m / 4) % 3][m % 4];
        }
        TST(11);
        CSTAMP(23);
    }
    sts32_if(td == 255, sb + S_GATE, 6);
    TSTAMP(3);
}

typedef CUresult (*EncodeFn)(CUtensorMap*, CUtensorMapDataType, cuuint32_t, void*, const cuuint64_t*, const cuuint64_t*, const cuuint32_t*,
                             const cuuint32_t*, CUtensorMapInterleave, CUtensorMapSwizzle, CUtensorMapL2promotion, CUtensorMapFloatOOBfill);

void make_map(EncodeFn enc, CUtensorMap* m, const void* base, uint64_t cols, uint64_t rows, uint32_t box_cols, uint32_t box_rows, bool swizzle) {
    cuuint64_t dims[2] = {cols, rows};
    cuuint64_t strides[1] = {cols * 2};
    cuuint32_t box[2] = {box_cols, box_rows};
    cuuint32_t es[2] = {1, 1};
    enc(m, CU_TENSOR_MAP_DATA_TYPE_BFLOAT16, 2, const_cast<void*>(base), dims, strides, box, es, CU_TENSOR_MAP_INTERLEAVE_NONE,
        swizzle ? CU_TENSOR_MAP_SWIZZLE_128B : CU_TENSOR_MAP_SWIZZLE_NONE, CU_TENSOR_MAP_L2_PROMOTION_NONE, CU_TENSOR_MAP_FLOAT_OOB_FILL_NONE);
}

}

extern "C" void kernel_launch(void* const* d_in, const int* in_sizes, int n_in, void* d_out, int out_size) {
    (void)in_sizes; (void)n_in; (void)out_size;
    static EncodeFn enc = nullptr;
    if (!enc) {
        void* f = nullptr;
        cudaDriverEntryPointQueryResult q;
        cudaGetDriverEntryPoint("cuTensorMapEncodeTiled", &f, cudaEnableDefault, &q);
        enc = (EncodeFn)f;
        cudaFuncSetAttribute(fused_kernel, cudaFuncAttributeMaxDynamicSharedMemorySize, SMEM_BYTES);
    }
    Params P;
    P.x = (const __nv_bfloat16*)d_in[0]; P.k = (const __nv_bfloat16*)d_in[1]; P.v = (const __nv_bfloat16*)d_in[2];
    P.wr = (const __nv_bfloat16*)d_in[6];
    P.out = (__nv_bfloat16*)d_out;
    Maps M;
    {
        cuuint64_t dims[4] = {64, 8, 3, (cuuint64_t)KV_BATCH_KEYS / 2}, strides[3] = {384, 128, 3072};
        cuuint32_t box[4] = {64, 8, 3, 2}, es[4] = {1, 1, 1, 1};
        enc(&M.k, CU_TENSOR_MAP_DATA_TYPE_BFLOAT16, 4, d_in[1], dims, strides, box, es, CU_TENSOR_MAP_INTERLEAVE_NONE, CU_TENSOR_MAP_SWIZZLE_128B,
            CU_TENSOR_MAP_L2_PROMOTION_NONE, CU_TENSOR_MAP_FLOAT_OOB_FILL_NONE);
    }
    make_map(enc, &M.v, P.v, 64, (uint64_t)12 * KV_BATCH_KEYS, 64, 96, true);
    make_map(enc, &M.vu, P.v, 64, (uint64_t)12 * KV_BATCH_KEYS, 64, 48, true);
    make_map(enc, &M.wq, d_in[3], 6144, 640, 192, 40, false);
    make_map(enc, &M.wo, d_in[4], 640, 6144, 80, 96, false);
    make_map(enc, &M.wg, d_in[7], 1536, 640, 96, 80, false);
    make_map(enc, &M.wu, d_in[8], 1536, 640, 96, 80, false);
    make_map(enc, &M.wd, d_in[9], 640, 1536, 80, 96, false);
    fused_kernel<<<NCTA, NTHR, SMEM_BYTES, cudaStreamPerThread>>>(P, M);
}
```

```cpp
#include <cuda_runtime.h>
#include <cuda.h>
#include <cuda_bf16.h>
#include <stdint.h>
#include <type_traits>

namespace {

constexpr int NCTA = 128;
constexpr int NTHR = 384;
constexpr int UNIT = 6144;
constexpr int SLOT = 12288;
#define TAU 3940
#define TAUW 3720
#define TAU0 3820
#define ILV 4
#define XB 600
#define TMIN 2400
#define SLACK 6000
#define SLACK0 1000
#define PF0 1
#define WIN_W 3
#define WIN_S 4
#define WIN_U 10
#define VPF 4
#define KRE_TAU 2600
#define RFR_TAU 25600
#define HOP1_NS 200
#define KPRE 2
#define KPRE2 2
#define LAST0 4
#define LAST1 4
#define LAST2 2
#define LAST_LATE 0xaa8
#define FSTEP 4
#define DELAY_L 2
#define DELAY_G 2
#define DELAY_C 3
#define DELAY_D 0
#define DELAY_E 1
#define REG_LO "40"
#define REG_HI "232"
#define SPIN_LOG 17
constexpr int SPIN_LIMIT = 1 << SPIN_LOG;

__host__ __device__ constexpr uint32_t pairL(uint32_t region, uint32_t c, uint32_t g) { return (g & 1) | ((g >> 1) << 2) | (c << 5) | (region << 6); }
__host__ __device__ constexpr uint32_t pairG(uint32_t d, uint32_t c, uint32_t i) { return (i & 1) | ((i >> 1) << 2) | (d << 4) | (c << 5) | (3u << 6); }
constexpr uint32_t RA = 0, RC = 1, RE = 2, HALF = 16384, COPY = 4096, PMASK = 0x59;
constexpr uint32_t XS = 0;
constexpr uint32_t XS2 = XS + 128 * 7680;
constexpr uint32_t XSEND = XS2 + 128 * 768;
__device__ uint4 g_s[XSEND / 16];
__device__ uint4 g_x[(4u << 20) / 16];
#define SWEEPS(k, n) do {} while (0)

constexpr uint32_t S_WD = 16 * SLOT;
constexpr uint32_t S_DUMMY = S_WD + 15360;
constexpr uint32_t S_BAR = S_DUMMY + 4096;
constexpr uint32_t S_FV = S_BAR, S_FK = S_FV + 64, S_RING = S_FK + 64, S_DBAR = S_RING + 48, S_WFULL = S_DBAR + 32, S_QRDY = S_WFULL + 88;
constexpr uint32_t S_RELK = S_QRDY + 8, S_RELV = S_RELK + 8, S_RELR = S_RELV + 8, S_RELW = S_RELR + 8, S_SCO = S_RELW + 24;
constexpr uint32_t S_OS1 = S_SCO + 8;
constexpr uint32_t S_ZERO = S_OS1 + 8;
constexpr uint32_t S_KF = S_ZERO + 8;
constexpr uint32_t S_TOK = S_KF + 8;
constexpr uint32_t S_SIDE = S_TOK + 80, S_GATE = S_SIDE + 4;
constexpr uint32_t S_STAT = S_GATE + 12, S_SWR = S_STAT + 16;
constexpr uint32_t S_LN = S_STAT + 32;
constexpr uint32_t S_XCAR = S_LN + 64;
constexpr uint32_t S_CSQ = S_XCAR + 320;
constexpr uint32_t S_CSGU = S_CSQ + 768;
constexpr uint32_t S_RED = S_CSGU + 768;
constexpr uint32_t S_L0 = S_RED;
constexpr uint32_t S_OS = S_RED + 5120;
constexpr uint32_t S_PS = S_OS + 1536;
constexpr uint32_t PS_MAX = 512, PS_PASS = 544;
constexpr uint32_t S_QS = S_PS + 2 * PS_PASS;
constexpr uint32_t S_XB = S_QS + 1536;
constexpr uint32_t S_XA = S_XB + 768;
constexpr uint32_t S_HS = S_XA + 768;
constexpr uint32_t S_X0 = S_HS + 768;
constexpr uint32_t S_SC = S_X0 + 640;
constexpr uint32_t S_TM = S_SC + 512;
constexpr int SMEM_BYTES = S_TM + 256;
static_assert(SMEM_BYTES <= 232448 && S_STAT % 16 == 0 && S_RED % 16 == 0 && S_XB % 16 == 0 && S_HS % 16 == 0 && S_PS % 16 == 0 && S_QS % 16 == 0, "smem");
static_assert(S_SCO == S_BAR + 44 * 8 && S_RELK == S_BAR + 38 * 8, "barriers");
constexpr uint32_t ST_WQ = 3 * SLOT, ST_WG = 8 * SLOT, ST_WO = 11 * SLOT;

__device__ __forceinline__ uint32_t smem_u32(const void* p) { return (uint32_t)__cvta_generic_to_shared(p); }
__device__ __forceinline__ void mbar_arrive(uint32_t bar) { asm volatile("mbarrier.arrive.shared::cta.b64 _, [%0];" :: "r"(bar) : "memory"); }
__device__ __forceinline__ bool mbar_try(uint32_t bar, uint32_t parity) {
    uint32_t ok;
    asm volatile("{\n .reg .pred p;\n mbarrier.try_wait.parity.shared::cta.b64 p, [%1], %2;\n selp.u32 %0, 1, 0, p;\n}" : "=r"(ok) : "r"(bar), "r"(parity) : "memory");
    return ok != 0;
}
__device__ __forceinline__ bool mbar_test(uint32_t bar, uint32_t parity) {
    uint32_t ok;
    asm volatile("{\n .reg .pred p;\n mbarrier.test_wait.parity.shared::cta.b64 p, [%1], %2;\n selp.u32 %0, 1, 0, p;\n}" : "=r"(ok) : "r"(bar), "r"(parity) : "memory");
    return ok != 0;
}
__device__ __forceinline__ void mbar_wait(uint32_t bar, uint32_t parity) {
    int n = 0;
    while (!mbar_try(bar, parity) && ++n < SPIN_LIMIT) {}
}
__device__ __forceinline__ uint32_t gtime32() { uint32_t t; asm volatile("mov.u32 %0, %globaltimer_lo;" : "=r"(t)); return t; }
__device__ __forceinline__ void bar_main() { asm volatile("bar.sync 1, 256;" ::: "memory"); }

__device__ __forceinline__ void mma16816(float (&c)[4], uint32_t a0, uint32_t a1, uint32_t a2, uint32_t a3, uint32_t b0, uint32_t b1) {
    asm("mma.sync.aligned.m16n8k16.row.col.f32.bf16.bf16.f32 {%0,%1,%2,%3}, {%4,%5,%6,%7}, {%8,%9}, {%0,%1,%2,%3};"
        : "+f"(c[0]), "+f"(c[1]), "+f"(c[2]), "+f"(c[3]) : "r"(a0), "r"(a1), "r"(a2), "r"(a3), "r"(b0), "r"(b1));
}
__device__ __forceinline__ void mmaA(float (&c)[4], const uint32_t (&a)[4], uint32_t b0, uint32_t b1) { mma16816(c, a[0], a[1], a[2], a[3], b0, b1); }
__device__ __forceinline__ void mma8(float (&c)[4], uint32_t a0, uint32_t a1, uint32_t b0) {
    asm("mma.sync.aligned.m16n8k8.row.col.f32.bf16.bf16.f32 {%0,%1,%2,%3}, {%4,%5}, {%6}, {%0,%1,%2,%3};"
        : "+f"(c[0]), "+f"(c[1]), "+f"(c[2]), "+f"(c[3]) : "r"(a0), "r"(a1), "r"(b0));
}
struct W80 { uint32_t a[2][4], c[2]; };
template <int N> __device__ __forceinline__ void mul80(float (&acc)[N][4], const W80 (&W)[N], const uint4& b, uint32_t b4) {
#pragma unroll
    for (int m = 0; m < N; m++) mmaA(acc[m], W[m].a[0], b.x, b.y);
#pragma unroll
    for (int m = 0; m < N; m++) mmaA(acc[m], W[m].a[1], b.z, b.w);
#pragma unroll
    for (int m = 0; m < N; m++) mma8(acc[m], W[m].c[0], W[m].c[1], b4);
}
__device__ __forceinline__ void ldsm2t(uint32_t (&r)[2], uint32_t addr) {
    asm volatile("ldmatrix.sync.aligned.m8n8.x2.trans.shared.b16 {%0,%1}, [%2];" : "=r"(r[0]), "=r"(r[1]) : "r"(addr) : "memory");
}
__device__ __forceinline__ void mmaV(float (&c)[4], const uint4& a, uint32_t b0, uint32_t b1) { mma16816(c, a.x, a.y, a.z, a.w, b0, b1); }
__device__ __forceinline__ void ldsm4(uint32_t (&r)[4], uint32_t addr) {
    asm volatile("ldmatrix.sync.aligned.m8n8.x4.shared.b16 {%0,%1,%2,%3}, [%4];" : "=r"(r[0]), "=r"(r[1]), "=r"(r[2]), "=r"(r[3]) : "r"(addr) : "memory");
}
__device__ __forceinline__ void ldsm4t(uint32_t (&r)[4], uint32_t addr) {
    asm volatile("ldmatrix.sync.aligned.m8n8.x4.trans.shared.b16 {%0,%1,%2,%3}, [%4];" : "=r"(r[0]), "=r"(r[1]), "=r"(r[2]), "=r"(r[3]) : "r"(addr) : "memory");
}
__device__ __forceinline__ uint32_t lds16(uint32_t a) { uint16_t v; asm volatile("ld.shared.u16 %0, [%1];" : "=h"(v) : "r"(a) : "memory"); return v; }
__device__ __forceinline__ uint32_t lds32(uint32_t a) { uint32_t v; asm volatile("ld.shared.u32 %0, [%1];" : "=r"(v) : "r"(a) : "memory"); return v; }
__device__ __forceinline__ float ldsf(uint32_t a) { return __uint_as_float(lds32(a)); }
__device__ __forceinline__ uint2 lds64(uint32_t a) { uint2 v; asm volatile("ld.shared.v2.u32 {%0,%1}, [%2];" : "=r"(v.x), "=r"(v.y) : "r"(a) : "memory"); return v; }
__device__ __forceinline__ uint4 lds128(uint32_t a) { uint4 v; asm volatile("ld.shared.v4.u32 {%0,%1,%2,%3}, [%4];" : "=r"(v.x), "=r"(v.y), "=r"(v.z), "=r"(v.w) : "r"(a) : "memory"); return v; }
__device__ __forceinline__ int ldsvol(uint32_t a) { int v; asm volatile("ld.volatile.shared.u32 %0, [%1];" : "=r"(v) : "r"(a) : "memory"); return v; }
__device__ __forceinline__ uint2 ldsvol64(uint32_t a) { uint2 v; asm volatile("{\n .reg .b64 d;\n ld.volatile.shared.b64 d, [%2];\n mov.b64 {%0,%1}, d;\n}" : "=r"(v.x), "=r"(v.y) : "r"(a) : "memory"); return v; }
__device__ __forceinline__ void stsvol64(uint32_t a, uint32_t x, uint32_t y) { asm volatile("{\n .reg .b64 d;\n mov.b64 d, {%1,%2};\n st.volatile.shared.b64 [%0], d;\n}" :: "r"(a), "r"(x), "r"(y) : "memory"); }
__device__ __forceinline__ void stsvol(uint32_t a, int v) { asm volatile("st.volatile.shared.u32 [%0], %1;" :: "r"(a), "r"(v) : "memory"); }
__device__ __forceinline__ void sts_hi16(uint32_t a, float v) { asm volatile("{\n .reg .b16 lo, hi;\n mov.b32 {lo, hi}, %1;\n st.shared.u16 [%0], hi;\n}" :: "r"(a), "r"(__float_as_uint(v)) : "memory"); }
__device__ __forceinline__ void sts16(uint32_t a, uint32_t v) { asm volatile("st.shared.u16 [%0], %1;" :: "r"(a), "r"(v) : "memory"); }
__device__ __forceinline__ void sts32(uint32_t a, uint32_t v) { asm volatile("st.shared.u32 [%0], %1;" :: "r"(a), "r"(v) : "memory"); }
__device__ __forceinline__ void stsf(uint32_t a, float v) { sts32(a, __float_as_uint(v)); }
__device__ __forceinline__ void sts64(uint32_t a, uint32_t x, uint32_t y) { asm volatile("st.shared.v2.u32 [%0], {%1,%2};" :: "r"(a), "r"(x), "r"(y) : "memory"); }

__device__ __forceinline__ void sts32_if(bool p, uint32_t a, uint32_t v) {
    asm volatile("{\n .reg .pred p;\n setp.ne.u32 p, %2, 0;\n @p st.shared.u32 [%0], %1;\n}" :: "r"(a), "r"(v), "r"((uint32_t)p) : "memory");
}
__device__ __forceinline__ void arrive_if(bool p, uint32_t bar) {
    asm volatile("{\n .reg .pred p;\n setp.ne.u32 p, %1, 0;\n @p mbarrier.arrive.shared::cta.b64 _, [%0];\n}" :: "r"(bar), "r"((uint32_t)p) : "memory");
}
__device__ __forceinline__ void keep(uint32_t& v) { asm volatile("" : "+r"(v)); }
__device__ __forceinline__ void keep(float& v) { asm volatile("" : "+f"(v)); }

__device__ __forceinline__ uint32_t ldp32(const char* p) { uint32_t v; asm volatile("ld.relaxed.gpu.global.u32 %0, [%1];" : "=r"(v) : "l"(p) : "memory"); return v; }
__device__ __forceinline__ uint2 ldp64(const char* p) {
    uint2 v; asm volatile("{\n .reg .b64 d;\n ld.relaxed.gpu.global.b64 d, [%2];\n mov.b64 {%0,%1}, d;\n}" : "=r"(v.x), "=r"(v.y) : "l"(p) : "memory"); return v;
}
__device__ __forceinline__ uint32_t tagw(float f, uint32_t par) { return (__float_as_uint(f) & ~1u) | par; }
__device__ __forceinline__ void stp32(char* p, float a, uint32_t par) { asm volatile("st.relaxed.gpu.global.u32 [%0], %1;" :: "l"(p), "r"(tagw(a, par)) : "memory"); }
__device__ __forceinline__ void stp64(char* p, float a, float b, uint32_t par) {
    asm volatile("{\n .reg .b64 d;\n mov.b64 d, {%1,%2};\n st.relaxed.gpu.global.b64 [%0], d;\n}" :: "l"(p), "r"(tagw(a, par)), "r"(tagw(b, par)) : "memory");
}
__device__ __forceinline__ void stp32_if(bool p, char* d, float a, uint32_t par) {
    asm volatile("{\n .reg .pred p;\n setp.ne.u32 p, %2, 0;\n @p st.relaxed.gpu.global.u32 [%0], %1;\n @p st.relaxed.gpu.global.u32 [%0+4096], %1;\n}" :: "l"(d), "r"(tagw(a, par)), "r"((uint32_t)p) : "memory");
}
__device__ __forceinline__ void stp64_if(bool p, char* d, uint32_t lo, uint32_t hi) {
    asm volatile("{\n .reg .pred p;\n .reg .b64 d;\n setp.ne.u32 p, %3, 0;\n mov.b64 d, {%1,%2};\n @p st.relaxed.gpu.global.b64 [%0], d;\n @p st.relaxed.gpu.global.b64 [%0+4096], d;\n}" :: "l"(d), "r"(lo), "r"(hi), "r"((uint32_t)p) : "memory");
}
__device__ __forceinline__ uint32_t chk2(uint32_t a, uint32_t b, uint32_t par) { uint32_t r; asm("lop3.b32 %0, %1, %2, %3, 0x7E;" : "=r"(r) : "r"(a), "r"(b), "r"(par)); return r; }
__device__ __forceinline__ uint32_t or3(uint32_t a, uint32_t b, uint32_t c) { uint32_t r; asm("lop3.b32 %0, %1, %2, %3, 0xFE;" : "=r"(r) : "r"(a), "r"(b), "r"(c)); return r; }
__device__ __forceinline__ uint32_t chk8(const uint32_t (&v)[8], uint32_t par) { return or3(chk2(v[0], v[1], par), chk2(v[2], v[3], par), or3(chk2(v[4], v[5], par), chk2(v[6], v[7], par), 0)); }
__device__ __forceinline__ uint32_t chk8(const uint2 (&v)[8], uint32_t par) { return or3(chk2(v[0].x, v[1].x, par), chk2(v[2].x, v[3].x, par), or3(chk2(v[4].x, v[5].x, par), chk2(v[6].x, v[7].x, par), 0)); }
__device__ __forceinline__ uint32_t chk8y(const uint2 (&v)[8], uint32_t par) { return or3(chk2(v[0].y, v[1].y, par), chk2(v[2].y, v[3].y, par), or3(chk2(v[4].y, v[5].y, par), chk2(v[6].y, v[7].y, par), 0)); }
__device__ __forceinline__ uint32_t chk4(const uint2 (&v)[4], uint32_t par) { return or3(chk2(v[0].x, v[0].y, par), chk2(v[1].x, v[1].y, par), or3(chk2(v[2].x, v[2].y, par), chk2(v[3].x, v[3].y, par), 0)); }
__device__ __forceinline__ float asf(uint32_t v) { return __uint_as_float(v); }
__device__ __forceinline__ float sum8(const uint32_t (&v)[8]) { return ((asf(v[0]) + asf(v[1])) + (asf(v[2]) + asf(v[3]))) + ((asf(v[4]) + asf(v[5])) + (asf(v[6]) + asf(v[7]))); }
__device__ __forceinline__ float sum8x(const uint2 (&v)[8]) { return ((asf(v[0].x) + asf(v[1].x)) + (asf(v[2].x) + asf(v[3].x))) + ((asf(v[4].x) + asf(v[5].x)) + (asf(v[6].x) + asf(v[7].x))); }
__device__ __forceinline__ float sum8y(const uint2 (&v)[8]) { return ((asf(v[0].y) + asf(v[1].y)) + (asf(v[2].y) + asf(v[3].y))) + ((asf(v[4].y) + asf(v[5].y)) + (asf(v[6].y) + asf(v[7].y))); }

__device__ __forceinline__ uint32_t pack2(float lo, float hi) { uint32_t r; asm("cvt.rn.bf16x2.f32 %0, %1, %2;" : "=r"(r) : "f"(hi), "f"(lo)); return r; }
__device__ __forceinline__ float bfr(float x) { return __uint_as_float(pack2(0.0f, x)); }
__device__ __forceinline__ float ex2(float x) { float r; asm("ex2.approx.ftz.f32 %0, %1;" : "=f"(r) : "f"(x)); return r; }
__device__ __forceinline__ float rcp(float x) { float r; asm("rcp.approx.ftz.f32 %0, %1;" : "=f"(r) : "f"(x)); return r; }
__device__ __forceinline__ float sqrt_(float x) { float r; asm("sqrt.approx.ftz.f32 %0, %1;" : "=f"(r) : "f"(x)); return r; }
__device__ __forceinline__ float bf_lo(uint32_t v) { return __uint_as_float(v << 16); }
__device__ __forceinline__ float bf_hi(uint32_t v) { return __uint_as_float(v & 0xffff0000u); }
__device__ __forceinline__ float sel4(int k, float a, float b, float c, float d) { return (k & 2) ? ((k & 1) ? d : c) : ((k & 1) ? b : a); }
constexpr float LOG2E = 1.4426950408889634f;
constexpr uint32_t ONES = 0x3f803f80u;

__device__ __forceinline__ void ln_stats(float sum, float sq, float& mean, float& den) {
    const float m = sum * (1.0f / 640.0f);
    const float var = fmaxf(fmaf(sq, 1.0f / 640.0f, -m * m), 0.0f);
    mean = bfr(m);
    den = bfr(sqrt_(bfr(bfr(var) + 1e-5f)));
}
__device__ __forceinline__ float sigmoidf_(float x) { return rcp(1.0f + ex2(-x * LOG2E)); }

#define TSTAMP(k) do {} while (0)
#define TST(k) do {} while (0)

#define CSTAMP(k) do {} while (0)
template <int N> __device__ __forceinline__ uint32_t lag(uint32_t sb, uint32_t z = 0) {
#pragma unroll
    for (int k = 0; k < N; k++) z = ldsvol(sb + S_ZERO + z);
    return z;
}
__device__ __forceinline__ void warm_mma(uint32_t& a, uint32_t& b) {
    asm volatile("mma.sync.aligned.m16n8k8.row.col.f16.f16.f16.f16 {%0,%1}, {%0,%1}, {%0}, {%0,%1};" : "+r"(a), "+r"(b) :: "memory");
}
#define KWNS2 20
#define KWNS 200
template <int STRIDE>
__device__ __forceinline__ float gather8(const char* p, uint32_t par) {
    uint32_t v[8];
    int guard = 0;
    do {
#pragma unroll
        for (int s = 0; s < 8; s++) v[s] = ldp32(p + s * STRIDE);
    } while ((chk8(v, par) & 1) && ++guard < SPIN_LIMIT);
    return sum8(v);
}
template <class F>
__device__ __forceinline__ void gather16(const char* p, uint32_t par, int k, F use) {
    uint32_t v[8], u[8];
    int guard = 0;
    bool again;
    do {
#pragma unroll
        for (int s = 0; s < 8; s++) v[s] = ldp32(p + s * 512);
#pragma unroll
        for (int s = 0; s < 8; s++) u[s] = ldp32(p + HALF + s * 512);
        const uint32_t stale = use(sum8(v) + sum8(u), ((v[0] ^ par) & 1) * 8);
        again = __any_sync(~0u, (or3(chk8(v, par), chk8(u, par), stale) & 1) != 0);
    } while (again & (++guard < SPIN_LIMIT));
    SWEEPS(k, guard - 1);
}

struct Params {
    const __nv_bfloat16 *x, *k, *v, *wr;
    __nv_bfloat16* out;
};
struct Maps { CUtensorMap k, v, vu, wq, wo, wg, wu, wd; };

constexpr int KV_BATCH_KEYS = 32 * 4096;

__device__ __forceinline__ void tma2d(uint32_t dst, const CUtensorMap* m, int c0, int c1, uint32_t bar, uint32_t bytes, uint64_t pol) {
    asm volatile("{\n .reg .pred p;\n elect.sync _|p, 0xffffffff;\n"
                 " @p mbarrier.arrive.expect_tx.shared::cta.b64 _, [%2], %6;\n"
                 " @p cp.async.bulk.tensor.2d.shared::cluster.global.mbarrier::complete_tx::bytes.L2::cache_hint [%0], [%1, {%3, %4}], [%2], %5;\n}"
                 :: "r"(dst), "l"(m), "r"(bar), "r"(c0), "r"(c1), "l"(pol), "r"(bytes) : "memory");
}
__device__ __forceinline__ void scrap_copy(uint32_t dst, const char* src, uint32_t bar) {
    asm volatile("{\n .reg .pred p;\n elect.sync _|p, 0xffffffff;\n"
                 " @p mbarrier.arrive.expect_tx.shared::cta.b64 _, [%2], 12288;\n"
                 " @p cp.async.bulk.shared::cluster.global.mbarrier::complete_tx::bytes [%0], [%1], 4096, [%2];\n"
                 " @p cp.async.bulk.shared::cluster.global.mbarrier::complete_tx::bytes [%0], [%1+4096], 4096, [%2];\n"
                 " @p cp.async.bulk.shared::cluster.global.mbarrier::complete_tx::bytes [%0], [%1+8192], 4096, [%2];\n}"
                 :: "r"(dst), "l"(src), "r"(bar) : "memory");
}
__device__ __forceinline__ void prefetch_l2(const void* p, uint32_t bytes) {
    asm volatile("{\n .reg .pred p;\n elect.sync _|p, 0xffffffff;\n @p cp.async.bulk.prefetch.L2.global [%0], %1;\n}" :: "l"(p), "r"(bytes) : "memory");
}
__device__ __forceinline__ uint64_t pol_first() { uint64_t p; asm("createpolicy.fractional.L2::evict_first.b64 %0, 1.0;" : "=l"(p)); return p; }
__device__ __forceinline__ uint64_t pol_normal() { uint64_t p; asm("createpolicy.fractional.L2::evict_normal.b64 %0, 1.0;" : "=l"(p)); return p; }
__device__ __forceinline__ bool utest(uint32_t bar, uint32_t parity) { return __all_sync(~0u, mbar_test(bar, parity)); }
__device__ __forceinline__ void uwait(uint32_t bar, uint32_t parity) {
    int n = 0;
    while (!__all_sync(~0u, mbar_try(bar, parity)) && ++n < SPIN_LIMIT) {}
}
template <int A, int B, int CNT> __device__ __forceinline__ void init_bars(uint32_t sb) {
#pragma unroll 1
    for (int k = A; k < B; k++)
        asm volatile("{\n .reg .pred p;\n elect.sync _|p, 0xffffffff;\n @p mbarrier.init.shared::cta.b64 [%0], %1;\n}" :: "r"(sb + S_BAR + 8 * k), "n"(CNT) : "memory");
}
__device__ __forceinline__ int unit_key(uint32_t b, uint32_t u) {
    return (blockIdx.x >> 2) * 4096 + 3072 + (blockIdx.x & 3) * (16 * ILV) + b * KV_BATCH_KEYS + (u & ~(ILV - 1u)) * 64 + (u & (ILV - 1)) * 16;
}
__device__ __forceinline__ void load_tile(const CUtensorMap* m, uint32_t dst, uint32_t bar, uint32_t bytes, int key, uint64_t pol) { tma2d(dst, m, 0, 3 * key, bar, bytes, pol); }
__device__ __forceinline__ const char* unit_ptr(const Params& P, int n) { return (const char*)((n & 16) ? P.v : P.k) + (size_t)unit_key(n >> 5, n & 15) * 384; }
#define LSTAMP(k) do {} while (0)

__device__ __forceinline__ uint32_t k_place(uint32_t b, uint32_t s) { return s + 3 + 5 * (b & 1); }
__device__ __forceinline__ uint32_t v_place(uint32_t b, uint32_t s) { return s < 3 ? s : s + 8 - 8 * (b & 1); }
__device__ __forceinline__ void k_load(const Maps& M, uint32_t dst, uint32_t bar, int key8, uint64_t pol) {
    asm volatile("{\n .reg .pred p;\n elect.sync _|p, 0xffffffff;\n"
                 " @p mbarrier.arrive.expect_tx.shared::cta.b64 _, [%2], 6144;\n"
                 " @p cp.async.bulk.tensor.4d.shared::cluster.global.mbarrier::complete_tx::bytes.L2::cache_hint [%0], [%1, {0, 0, 0, %3}], [%2], %4;\n}"
                 :: "r"(dst), "l"(&M.k), "r"(bar), "r"(key8), "l"(pol) : "memory");
}
__device__ __forceinline__ int unit_key8(uint32_t n) { return unit_key(n >> 4, n & 15) >> 3; }
__device__ __forceinline__ void ring_load(const Maps& M, uint32_t sb, uint32_t b, uint32_t u, uint32_t pos) {
    if (u < 16) k_load(M, sb + pos * UNIT, sb + S_RING + 8 * pos, unit_key8(16 * b + u), pol_normal());
    else load_tile(&M.vu, sb + pos * UNIT, sb + S_FV + 4 * (pos & 6), UNIT, unit_key(b, pos), pol_first());
}
__device__ __forceinline__ uint32_t token(bool p, uint32_t a, uint32_t n) {
    uint32_t v;
    asm volatile("{\n .reg .pred p;\n setp.ne.u32 p, %2, 0;\n mov.u32 %0, 0;\n @p atom.shared.exch.b32 %0, [%1], %3;\n}" : "=r"(v) : "r"(a), "r"((uint32_t)p), "r"(n) : "memory");
    return v;
}
__device__ __forceinline__ void place_load(const Maps& M, uint32_t sb, uint32_t n) {
    k_load(M, sb + k_place(n >> 4, 0) * SLOT + (n & 15) * UNIT, sb + S_FK + 4 * (n & 14), unit_key8(n), pol_first());
}
__device__ __forceinline__ void v_load(const Maps& M, uint32_t sb, uint32_t b, uint32_t s) {
    load_tile(&M.v, sb + v_place(b, s) * SLOT, sb + S_FV + 8 * s, SLOT, unit_key(b, 2 * s), pol_first());
}

__device__ __forceinline__ void stream_warp(const Params& P, const Maps& M, uint32_t sb, uint32_t lane) {
    const uint64_t pol = pol_first();
    const int bid = blockIdx.x, g = bid >> 3, i = bid & 7;
    const uint32_t wf = sb + S_WFULL;
    uint32_t tn = __shfl_sync(~0u, gtime32(), 0) * 16;
    auto pace = [&](uint32_t dt) {
        int k = 0;
        uint32_t now;
        do now = __shfl_sync(~0u, gtime32(), 0) * 16; while ((int)(now - tn) < 0 && ++k < SPIN_LIMIT);
        if ((int)(now - tn) > SLACK0) tn = now - SLACK0;
        tn += dt;
    };
#pragma unroll
    for (int k = 0; k < 10; k++) {
        if (k < 2) {
            if (k == 0) init_bars<26, 27, 1>(sb); else init_bars<27, 37, 1>(sb);
            asm volatile("fence.mbarrier_init.release.cluster;" ::: "memory");
            if (k == 1) { asm volatile("bar.arrive 2, %0;" :: "n"(NTHR) : "memory"); asm volatile("bar.sync 3, 128;" ::: "memory"); }
        }
        if (k >= WIN_W) uwait(wf + 8 * (k - WIN_W), 0);
        pace(TAUW * 5 / 2);
        if (k < 4) tma2d(sb + ST_WQ + 15360 * k, &M.wq, 384 * g + 192 * (k >> 1), 80 * i + 40 * (k & 1), wf + 8 * k, 15360, pol);
        else if (k < 6) tma2d(sb + ST_WG + 15360 * (k - 4), k == 4 ? &M.wg : &M.wu, 96 * g, 80 * i, wf + 8 * k, 15360, pol);
        else tma2d(sb + ST_WO + 15360 * (k - 6), &M.wo, 80 * i, 384 * g + 96 * (k - 6), wf + 8 * k, 15360, pol);
    }
#pragma unroll 1
    for (int n = 0; n < 16; n++) {
        if (n == 0 || n == 5 || n == 11) uwait(sb + S_RELW + (n == 0 ? 0 : n == 5 ? 8 : 16), 0);
        uwait(n < WIN_S ? wf + 8 * (10 - WIN_S + n) : sb + S_FV + 8 * ((n - WIN_S) ^ 8), 0);
        pace(max(min(2 * n + 2 - PF0, 2), 0) * TAU0);
        if (n >= WIN_S && !utest(sb + S_FV + 8 * ((n - WIN_S + 1) ^ 8), 0)) tn += XB;
        if (n < 8) { place_load(M, sb, 2 * n); place_load(M, sb, 2 * n + 1); }
        else if (n < 11) { ring_load(M, sb, 0, 2 * n, 2 * n - 16); ring_load(M, sb, 0, 2 * n + 1, 2 * n - 15); }
        else v_load(M, sb, 0, n - 8);
        if (n == 7) { pace(TAUW * 5 / 2); tma2d(sb + S_WD, &M.wd, 80 * i, 96 * g, wf + 80, 15360, pol); }
    }
    int nd = 0;
    uint32_t q[4];
#pragma unroll
    for (int r = 0; r < 4; r++) q[r] = sb + S_FV + 8 * (7 - r);
    uint32_t td = tn;
    uint32_t pos = 2;
#pragma unroll 1
    for (int m = 16; m < 64; m++) {
        const int b = m >> 4, j = m & 15;
        const char* src = unit_ptr(P, 2 * m);
        const uint32_t tok = sb + S_TOK + (j < 3 ? 4 * pos : j < 11 ? 24 + 4 * pos : 16 + 4 * j) + 4 * lane;
        static_assert(WIN_U <= 12, "a ring position has at most one token of the timetable");
        int k = 0;
        while (true) {
            const uint2 c = lds64(sb + S_KF);
            if (__all_sync(~0u, mbar_test(q[WIN_S - 1] & ~1u, q[WIN_S - 1] & 1) & (min((int)c.x + 1, (int)c.y) >= 16 * b + min(2 * j + 2 - WIN_U, 16))) || ++k >= SPIN_LIMIT) break;
        }
        uint32_t now;
        while (true) {
            now = __shfl_sync(~0u, gtime32(), 0) * 16;
            if ((int)(now - td) >= 0 || ++k >= SPIN_LIMIT) break;
        }
        const uint32_t mine = __ballot_sync(~0u, token(lane < (j < 11 ? 2 : 1), tok, 2 * m + lane) == 2 * m + lane);
        {
            const uint2 c = lds64(sb + S_KF);
            if (!__all_sync(~0u, mbar_test(q[WIN_S - 2] & ~1u, q[WIN_S - 2] & 1) & (min((int)c.x + 1, (int)c.y) >= 16 * b + min(2 * j + 4 - WIN_U, 16)))) tn += XB;
        }
        q[3] = q[2]; q[2] = q[1]; q[1] = q[0]; q[0] = sb + S_QRDY;
        if (j < 11) {
            if (mine & 1) ring_load(M, sb, b, 2 * j, pos); else prefetch_l2(src, UNIT);
            if (mine & 2) ring_load(M, sb, b, 2 * j + 1, pos + 1); else prefetch_l2(src + UNIT, UNIT);
            if (j >= 8) q[0] = (sb + S_FV + 8 * (j - 8)) | (b & 1);
        } else if (mine) { v_load(M, sb, b, j - 8); q[0] = (sb + S_FV + 8 * (j - 8)) | (b & 1); }
        else if (j - 8 >= VPF) prefetch_l2(src, SLOT);
        else {
            scrap_copy(sb + S_DUMMY, src, sb + S_DBAR + 8 * (nd & 3));
            q[0] = (sb + S_DBAR + 8 * (nd & 3)) | ((nd >> 2) & 1);
            nd++;
        }
        pos = j == 15 ? 2 : pos == 4 ? 0 : pos + 2;
        if ((int)(now - tn) > SLACK) tn = now - SLACK;
        tn += 2 * TAU;
        td = (int)(tn - now) > 2 * TMIN ? tn : now + 2 * TMIN;
    }
#pragma unroll 1
    for (int m = max(nd - 4, 0); m < nd; m++) uwait(sb + S_DBAR + 8 * (m & 3), (m >> 2) & 1);
}

__host__ __device__ constexpr uint64_t bit_list(uint32_t m) { uint64_t r = 0; int n = 0; for (int k = 0; k < 12; k++) if ((m >> k) & 1) r |= (uint64_t)k << (4 * n++); return r; }
__device__ __forceinline__ float scaled(float s) { return bfr(bfr(s) * 0.07216878364870322f); }
__device__ __forceinline__ void probs(float s, uint32_t ps, uint32_t src, uint32_t ln) {
    const uint32_t q8 = ln >> 2, t4 = ln & 3;
    int key = __float_as_int(s);
    key ^= (key >> 31) & 0x7fffffff;
    key = __reduce_max_sync(~0u, key);
    key ^= (key >> 31) & 0x7fffffff;
    const float ml = __int_as_float(key) * LOG2E;
    sts16(ps + 64 * src + (q8 >> 1) * 16 + t4 * 4 + (q8 & 1) * 2, pack2(ex2(fmaf(s, LOG2E, -ml)), 0.f));
    stsf(ps + PS_MAX + 4 * src, ml);
}
template <int H> __device__ __forceinline__ uint32_t b_pos(uint32_t e) { const uint32_t h = e >= H, k = e - H * h; return h * 192 + (k & 6) * 24 + (k >> 3) * 4 + (k & 1) * 2; }
__device__ __forceinline__ uint32_t a_pos(uint32_t e) { const uint32_t h = e >= 40, k = e - 40 * h; return (k & 6) * 24 + (k >> 3) * 8 + h * 4 + (k & 1) * 2; }
__device__ __forceinline__ uint32_t q_pos(uint32_t d) { const uint32_t s = 3 * ((d >> 4) & 3) + (d >> 6); return s * 32 + (d & 6) * 4 + ((d >> 3) & 1) * 4 + (d & 1) * 2; }
__device__ __forceinline__ uint32_t k_off(uint32_t ln) { return (ln & 8) * 384 + (ln & 7) * 128 + (((ln & 7) ^ (ln >> 4)) << 4); }

#define HSTAMP(k) do {} while (0)
__device__ __forceinline__ char* xwindow() { return reinterpret_cast<char*>((reinterpret_cast<uintptr_t>(g_x) + (2u << 20) - 1) & ~(uintptr_t)((2u << 20) - 1)); }

struct XPtr {
    uint32_t lo, hi;
    __device__ __forceinline__ explicit XPtr(char* p) : lo((uint32_t)(uintptr_t)p), hi((uint32_t)((uintptr_t)p >> 32)) {}
    __device__ __forceinline__ XPtr(uint32_t l, uint32_t h) : lo(l), hi(h) {}
    __device__ __forceinline__ XPtr operator+(uint32_t o) const { return XPtr(lo + o, hi); }
    __device__ __forceinline__ operator char*() const { uint64_t p; asm("mov.b64 %0, {%1, %2};" : "=l"(p) : "r"(lo), "r"(hi)); return (char*)p; }
};

__device__ __forceinline__ void side_warp(uint32_t sb) {
    const uint32_t bid = blockIdx.x, g = bid >> 3, i = bid & 7, P = pairG(0, 0, i);
    char* p = xwindow() + P * 8192 + (g >> 3) * HALF + (g & 7) * 512 + 448;
    uint32_t best[2] = {~0u, ~0u};
    asm volatile("st.relaxed.gpu.global.b32 [%0], 1;" :: "l"(p) : "memory");
    asm volatile("st.relaxed.gpu.global.b32 [%0], 1;" :: "l"(p + COPY) : "memory");
#pragma unroll 1
    for (int r = 0; r < 64; r++) {
        if (r >= 4 && !(r & 1) && min(best[0], best[1]) < 380 && max(best[0], best[1]) > min(best[0], best[1]) + 80) break;
        uint32_t c0, c1, v;
        asm volatile("mov.u32 %0, %clock;" : "=r"(c0) :: "memory");
        asm volatile("atom.relaxed.gpu.global.exch.b32 %0, [%1], 0;" : "=r"(v) : "l"(p + (r & 1) * COPY) : "memory");
        asm volatile("{\n .reg .pred q;\n setp.eq.u32 q, %1, 0x13579bdf;\n mov.u32 %0, 0;\n @!q mov.u32 %0, %clock;\n}" : "=r"(c1) : "r"(v) : "memory");
        if (r & 1) best[1] = min(best[1], c1 - c0); else best[0] = min(best[0], c1 - c0);
    }
    stsvol(sb + S_SIDE, 1 + ((best[1] < best[0]) ^ (__popc(P & PMASK) & 1)));
}

template <int N>
__device__ __forceinline__ void hop_a(const char* src, uint32_t par, uint32_t dst, bool st, int k) {
    uint2 v[N][4];
    float e[4], rl;
    int guard = 0;
    bool again;
    do {
#pragma unroll
        for (int s = 0; s < 4 * N; s++) v[s / 4][s % 4] = ldp64(src + (s / 4) * 256 + (s % 4) * 1024);
        again = __any_sync(~0u, ((chk4(v[0], par) | chk4(v[N - 1], par)) & 1) != 0);
        const int M = max(max((int)v[0][0].x, (int)v[0][1].x), max((int)v[0][2].x, (int)v[0][3].x)) - 254;
#pragma unroll
        for (int s = 0; s < 4; s++) e[s] = __int_as_float(max((int)v[0][s].x - M, 0) << 22);
        rl = rcp(fmaf(e[0], asf(v[0][0].y), e[1] * asf(v[0][1].y)) + fmaf(e[2], asf(v[0][2].y), e[3] * asf(v[0][3].y)));
#pragma unroll
        for (int s = 0; s < 4; s++) e[s] = __shfl_sync(~0u, e[s], 24);
        keep(rl);
    } while (again & (++guard < SPIN_LIMIT));
    rl = __shfl_sync(~0u, rl, 24);
#pragma unroll
    for (int n = 0; n < N; n++) {
        const float o0 = fmaf(e[0], asf(v[n][0].x), e[1] * asf(v[n][1].x)) + fmaf(e[2], asf(v[n][2].x), e[3] * asf(v[n][3].x));
        const float o1 = fmaf(e[0], asf(v[n][0].y), e[1] * asf(v[n][1].y)) + fmaf(e[2], asf(v[n][2].y), e[3] * asf(v[n][3].y));
        sts32_if(st, dst + 192 * n, pack2(o0 * rl, o1 * rl));
    }
    SWEEPS(k, guard - 1);
    __syncwarp();
}

__device__ __forceinline__ void score_warp(const Maps& M, uint32_t sb, uint32_t h, uint32_t ln) {
    const uint32_t lane0 = ln;
    uwait(sb + S_QRDY, 0);
    const uint32_t q8 = ln >> 2;
    const uint32_t k0 = k_off(ln);
    uint32_t pos = h + 6, bar = sb + S_FK, par = 0, phases = 0;
    uint2 q = lds64(sb + S_QS + 8 * ln), qh = lds64(sb + S_QS + 8 * ln + 256);
    auto first_round = [&](uint32_t b, uint32_t ln) {
        uwait(sb + S_RELR, b & 1);
        const uint32_t u = h + 2 * ln, p = u < 4 ? u + 2 : u - 4;
        uint32_t todo = __ballot_sync(~0u, token(ln < 3, sb + S_TOK + 4 * p, 32 * b + 32 + u) == 32 * b + 32 + u);
#pragma unroll 1
        for (uint32_t r = h; todo; todo >>= 1, r += 2) if (todo & 1) ring_load(M, sb, b + 1, r, r < 4 ? r + 2 : r - 4);
    };
#pragma unroll 1
    for (uint32_t n = h; n < 64; n += 2) {
        HSTAMP(0);
        const uint32_t ua = sb + pos * UNIT;
        if (!__all_sync(~0u, mbar_try(bar, par))) uwait(bar, par);
        HSTAMP(1);
        float acc[2][4] = {};
        uint32_t mine = 0;
        const uint32_t id = n + (n & 48) + 6;
#pragma unroll
        for (int s = 0; s < 12; s++) {
            uint32_t kf[4];
            ldsm4(kf, (k0 ^ (32 * (s / 3))) + (ua + 1024 * (s % 3)));
            if (s == 11) {
                __syncwarp();
                mine = token(ln == 0 && n >= 16, sb + S_TOK + 24 + 4 * pos, id);
                stsvol(sb + S_KF + 4 * h, n + 1);
            }
            const bool m = q8 == (s & 7);
            mmaA(acc[s & 1], kf, m ? (s < 8 ? q.x : qh.x) : 0u, m ? (s < 8 ? q.y : qh.y) : 0u);
        }
        const uint32_t pos0 = pos;
        const bool last = (n & 14) == 14;
        pos = last ? h + 2 : n >= 16 && pos >= 4 ? h : pos + 2;
        bar = n >= 14 ? sb + S_RING + 8 * pos : bar + 8;
        par = n >= 14 ? (phases >> pos) & 1 : 0;
        phases ^= n >= 14 ? 1u << pos : 0;
        const float w0 = (acc[0][0] + acc[0][1]) + (acc[1][0] + acc[1][1]), w1 = (acc[0][2] + acc[0][3]) + (acc[1][2] + acc[1][3]);
        HSTAMP(2);
        if (__any_sync(~0u, mine == id)) ring_load(M, sb, n >> 4, (n & 15) + 6, pos0);
        HSTAMP(3);
        float s = ((ln & 1) ? w1 : w0) + __shfl_xor_sync(~0u, (ln & 1) ? w0 : w1, 1);
        s += __shfl_xor_sync(~0u, s, 2);
        sts_hi16(sb + S_SC + (((n & 12) >> 1) + h) * 64 + (n & 2) * 2 + (ln & 29) * 2, scaled(s));
        if (last) {
            __syncwarp();
            arrive_if(ln == 0, sb + S_SCO);
            const uint32_t b = n >> 4, ln = lane0 + lag<1>(sb);
            if (b > 0) {
                uwait(sb + S_RELK, (b - 1) & 1);
                if (h == 0) LSTAMP(64 + 2 * b);
                const uint32_t sl = 3 + h + 2 * ln, idv = 32 * b + 16 + 2 * sl;
                uint32_t todo = __ballot_sync(~0u, token(sl < 8, sb + S_TOK + 48 + 4 * sl, idv) == idv);
#pragma unroll 1
                for (uint32_t r = 3 + h; todo; todo >>= 1, r += 2) if (todo & 1) v_load(M, sb, b, r);
                const uint32_t g = blockIdx.x >> 3, pr = pairL(RA, 1, g), side = ldsvol(sb + S_SIDE);
                const char* src = xwindow() + pr * 8192 + ((side ^ 1 ^ __popc(pr & PMASK)) & 1) * COPY + h * HALF + 8 * min(ln, 24u);
                uwait(sb + S_RELV, (b - 1) & 1);
                __nanosleep(HOP1_NS);
#pragma unroll 1
                for (uint32_t r = 0; r < 4; r += 2) {
                    hop_a<2>(src + 256 * r, b & 1, sb + S_OS + 192 * (4 * h + r) + 96 + 4 * ln, ln < 24, 25);
                    if (r == 0 && b < 3) first_round(b, ln);
                }
                arrive_if(ln == 0, sb + S_OS1);
            } else first_round(0, ln);
            q = lds64(sb + S_QS + 24 * ((n + 2) & 48) + 8 * ln); qh = lds64(sb + S_QS + 24 * ((n + 2) & 48) + 8 * ln + 256);
        }
    }
}

__global__ void __launch_bounds__(NTHR, 1)
fused_kernel(const Params P, const __grid_constant__ Maps M) {
    extern __shared__ __align__(1024) unsigned char smem[];
    const uint32_t sb = smem_u32(smem);
    const int tid = threadIdx.x, bid = blockIdx.x;
    if (tid == 0) {
        asm volatile("prefetch.tensormap [%0];" :: "l"(&M.wq) : "memory");
        asm volatile("cp.async.bulk.prefetch.L2.global [%0], %1;" :: "l"(unit_ptr(P, 0)), "r"(PF0 * UNIT) : "memory");
    }
    const int w = __shfl_sync(~0u, tid >> 5, 0), lane = tid & 31;

    if (w >= 8) {
        asm volatile("setmaxnreg.dec.sync.aligned.u32 " REG_LO ";");
        if (w == 8) {
            stream_warp(P, M, sb, lane);
        } else {
            if (w == 11 && lane < 8) asm volatile("prefetch.tensormap [%0];" :: "l"(&M.k + lane) : "memory");
            if (w == 9) { init_bars<0, 3, 2>(sb); init_bars<3, 8, 1>(sb); init_bars<16, 22, 1>(sb); }
            else if (w == 10) { init_bars<8, 16, 2>(sb); init_bars<22, 26, 1>(sb); }
            else { init_bars<37, 38, 1>(sb); init_bars<38, 40, 8>(sb); init_bars<40, 41, 1>(sb); init_bars<41, 44, 8>(sb); init_bars<44, 46, 2>(sb); stsvol(sb + S_ZERO + 4 * lane, 0); if (lane < 16) stsvol(sb + S_LN + 4 * lane, 0); }
            asm volatile("fence.mbarrier_init.release.cluster;" ::: "memory");
            asm volatile("bar.arrive 3, 128;" ::: "memory");
            asm volatile("bar.sync 2, %0;" :: "n"(NTHR) : "memory");
            if (w < 11) score_warp(M, sb, w - 9, lane);
            else {
                if (lane == 0) side_warp(sb);
                __syncwarp();
                uint32_t a = 0, b = 0;
                int k = 0;
                while (ldsvol(sb + S_GATE) == 0 && ++k < SPIN_LIMIT) { warm_mma(a, b); __nanosleep(KWNS); }
                uint4* d = reinterpret_cast<uint4*>(reinterpret_cast<char*>(g_s) + XS + bid * 7680) + lane;
                const uint4 z = make_uint4(0, 0, 0, 0);
#pragma unroll 1
                for (int u = 0; u < 15; u++) d[32 * u] = z;
                d = reinterpret_cast<uint4*>(reinterpret_cast<char*>(g_s) + XS2 + bid * 768) + lane;
                d[0] = z;
                if (lane < 16) d[32] = z;
                const uint32_t side = (ldsvol(sb + S_SIDE) & 1) ^ 1, g = bid >> 3, i = bid & 7;
                const XPtr gx(xwindow());
                auto nearp = [&](uint32_t pr) { return gx.lo + pr * 8192 + ((side ^ __popc(pr & PMASK)) & 1) * COPY; };
                const uint32_t own = (i >> 2) * HALF + (i & 3) * 1024 + (lane & 7) * 128;
                const uint32_t pAC = nearp(pairL(lane >> 4, (lane >> 3) & 1, g)) + own, pE = nearp(pairL(RE, (lane >> 3) & 1, g)) + own;
                const uint32_t pG = nearp(pairG((lane >> 2) & 1, (lane >> 3) & 1, i)) + min(lane & 3, 2) * 128;
                uint32_t tr = 0, tk = 0, ph = 0, src = g + (lane >> 4), seen = 0, n = 16, cs = 0;
                bool go = false, first = true;
                while (n < 64 && ++k < SPIN_LIMIT) {
                    const uint32_t now = __shfl_sync(~0u, gtime32(), 0) * 16;
                    if (!go && utest((n & 15) < 6 ? sb + S_RELK : sb + S_RELV, ((n >> 4) & 1) ^ 1)) { go = true; if ((int)(now - tk) > 0 || !(n & 15)) tk = now; }
                    if (go && (int)(now - tk) >= 0) {
                        place_load(M, sb, (n & 16) ? n : (n & 48) | ((n + 10) & 15));
                        tk += KRE_TAU;
                        n++;
                        go = (n & 15) != 0 && (n & 15) != 6;
                        if (!(n & 15)) LSTAMP(63 + (n >> 3));
                    } else if (first || (int)(now - tr) >= 0) {
                        first = false;
                        tr = now + RFR_TAU;
                        b |= seen & a;
                        warm_mma(a, b);
                        seen = ldp32(XPtr(ph == 0 ? pAC : ph == 1 && lane < 16 ? pE : pG + (src & 8) * (HALF / 8) + (src & 7) * 512, gx.hi));
                        const uint32_t l = lane + 32 * (++cs & 1);
                        *reinterpret_cast<volatile uint32_t*>(reinterpret_cast<char*>(g_s) + (l < 60 ? XS + bid * 7680 + 128 * l : XS2 + bid * 768 + 128 * (l - 60))) = 0;
                        src += ph == 0 ? 0 : ph == 1 ? 2 : 1;
                        ph = ph == 2 ? 0 : ph + 1;
                    } else __nanosleep(KWNS2);
                }
                while (ldsvol(sb + S_GATE) < 6 && ++k < SPIN_LIMIT) { warm_mma(a, b); __nanosleep(KWNS); }
                if (a | b) stsvol(sb + S_GATE, 6);
            }
        }
        return;
    }
    asm volatile("setmaxnreg.inc.sync.aligned.u32 " REG_HI ";");

    const int g = bid >> 3, i = bid & 7;
    const int g8 = lane >> 2, t = lane & 3;
    char* const gs = reinterpret_cast<char*>(g_s);
    const XPtr gx(xwindow());

    auto zero_words = [&] {
        const uint4 z = make_uint4(0, 0, 0, 0);
        const uint32_t c = (tid >> 6) & 1, cp = (tid >> 7) * COPY, k = (tid & 63) * 16;
        *reinterpret_cast<uint4*>((char*)(gx + pairL(RA, c, g) * 8192 + (i >> 2) * HALF + (i & 3) * 1024 + cp + k)) = z;
        *reinterpret_cast<uint4*>((char*)(gx + pairL(RC, c, g) * 8192 + (i >> 2) * HALF + (i & 3) * 1024 + cp + k)) = z;
        *reinterpret_cast<uint4*>((char*)(gx + pairL(RE, c, g) * 8192 + (i >> 2) * HALF + (i & 3) * 1024 + cp + k)) = z;
        if ((tid & 31) < 24) *reinterpret_cast<uint4*>((char*)(gx + pairG((tid >> 5) & 1, c, i) * 8192 + (g >> 3) * HALF + (g & 7) * 512 + cp + (tid & 31) * 16)) = z;
    };
    W80 Wq[6], Wgu[3];
    uint32_t Wo[5][3][4];
    if (w < 4) {
        const uint32_t* xp = reinterpret_cast<const uint32_t*>(P.x + 640 * w);
        float sum = 0.f, sq = 0.f;
#pragma unroll
        for (int u = 0; u < 10; u++) { uint32_t v = xp[lane + 32 * u]; float a = bf_lo(v), b = bf_hi(v); sum += a + b; sq += a * a + b * b; }
#pragma unroll
        for (int o = 16; o > 0; o >>= 1) { sum += __shfl_xor_sync(~0u, sum, o); sq += __shfl_xor_sync(~0u, sq, o); }
        float mean, den; ln_stats(sum, sq, mean, den);
        if (lane < 20) {
            const uint2 v = reinterpret_cast<const uint2*>(P.x + 640 * w + 80 * i)[lane];
            sts64(sb + S_X0 + 160 * w + 8 * lane, v.x, v.y);
            sts32(sb + S_L0 + 384 * w + b_pos<40>(4 * lane), pack2(__fdiv_rn(bfr(bf_lo(v.x) - mean), den), __fdiv_rn(bfr(bf_hi(v.x) - mean), den)));
            sts32(sb + S_L0 + 384 * w + b_pos<40>(4 * lane + 2), pack2(__fdiv_rn(bfr(bf_lo(v.y) - mean), den), __fdiv_rn(bfr(bf_hi(v.y) - mean), den)));
        }
    } else if (w == 4) {
        const uint32_t* xp = reinterpret_cast<const uint32_t*>(P.wr);
        float sum = 0.f;
#pragma unroll
        for (int u = 0; u < 10; u++) { uint32_t v = xp[lane + 32 * u]; sum += bf_lo(v) + bf_hi(v); }
#pragma unroll
        for (int o = 16; o > 0; o >>= 1) sum += __shfl_xor_sync(~0u, sum, o);
        if (lane == 0) stsf(sb + S_SWR, sum);
        if (lane < 20) {
            const uint2 v = reinterpret_cast<const uint2*>(P.wr + 80 * i)[lane];
            sts32(sb + S_XA + 576 + a_pos(4 * lane), v.x); sts32(sb + S_XA + 576 + a_pos(4 * lane + 2), v.y);
            sts32(sb + S_XA + a_pos(4 * lane), ONES); sts32(sb + S_XA + a_pos(4 * lane + 2), ONES);
        }
    }
    asm volatile("bar.sync 2, %0;" :: "n"(NTHR) : "memory");
    auto frag = [](uint32_t (&a)[4], uint32_t p, int pitch) {
        const uint32_t r0 = lds32(p), r1 = lds32(p + pitch), r2 = lds32(p + 2 * pitch), r3 = lds32(p + 3 * pitch);
        a[0] = __byte_perm(r0, r1, 0x5410); a[1] = __byte_perm(r0, r1, 0x7632);
        a[2] = __byte_perm(r2, r3, 0x5410); a[3] = __byte_perm(r2, r3, 0x7632);
    };
    mbar_wait(sb + S_WFULL + 16 * (w >> 2), 0);
    mbar_wait(sb + S_WFULL + 16 * (w >> 2) + 8, 0);
    {
        const uint32_t p = sb + ST_WQ + (w >> 2) * 30720 + (2 * t) * 384 + (48 * (w & 3) + 2 * g8) * 2;
#pragma unroll
        for (int r = 0; r < 10; r++)
#pragma unroll
            for (int m = 0; m < 3; m++) {
                const uint32_t q = p + ((r & 1) * 40 + (r >> 1) * 8) * 384 + 32 * m, r0 = lds32(q), r1 = lds32(q + 384);
                (r < 8 ? Wq[2 * m].a[(r >> 2) & 1][r & 3] : Wq[2 * m].c[r & 1]) = __byte_perm(r0, r1, 0x5410);
                (r < 8 ? Wq[2 * m + 1].a[(r >> 2) & 1][r & 3] : Wq[2 * m + 1].c[r & 1]) = __byte_perm(r0, r1, 0x7632);
            }
    }
    __syncwarp();
    if (lane == 0) mbar_arrive(sb + S_RELW);
    TSTAMP(1);
    {
        char* d = gs + XS + bid * 7680 + (w >> 2) * 3840 + (48 * (w & 3) + 2 * g8) * 4;
        float acc[6][4] = {};
        mul80(acc, Wq, lds128(sb + S_L0 + 48 * lane), lds32(sb + S_L0 + 48 * lane + 16));
#pragma unroll
        for (int m = 0; m < 6; m += 2) stp64(d + t * 768 + 32 * m, acc[m][0] + acc[m][3], acc[m + 1][0] + acc[m + 1][3], 1);
        float sum[6][4] = {};
        mul80(sum, Wq, make_uint4(ONES, ONES, ONES, ONES), ONES);
        if (t == 0)
#pragma unroll
            for (int m = 0; m < 6; m += 2) stp64(d + 4 * 768 + 32 * m, sum[m][0] + sum[m][3], sum[m + 1][0] + sum[m + 1][3], 1);
    }
    mbar_wait(sb + S_WFULL + 32, 0);
    mbar_wait(sb + S_WFULL + 40, 0);
    const uint32_t oct = 3 * (w >> 1) + (w & 1), oct2 = 3 * (w >> 1) + 2;
    {
        const uint32_t p = sb + ST_WG + ((lane & 7) + 40 * ((lane >> 3) & 1) + 8 * (lane >> 4)) * 192;
#pragma unroll
        for (int T = 0; T < 3; T++) {
            const uint32_t q = p + (T < 2 ? T * 15360 + 16 * oct : (w & 1) * 15360 + 16 * oct2);
            ldsm4t(Wgu[T].a[0], q); ldsm4t(Wgu[T].a[1], q + 16 * 192); ldsm2t(Wgu[T].c, q + 32 * 192);
        }
        float sum[3][4] = {};
        mul80(sum, Wgu, make_uint4(ONES, ONES, ONES, ONES), ONES);
        if (t < 3) stp32(gs + XS2 + bid * 768 + (t < 2 ? 64 * oct + 4 * t : 64 * oct2 + 4 * (w & 1)) + 8 * g8,
                         sel4(t, sum[0][0] + sum[0][3], sum[1][0] + sum[1][3], sum[2][0] + sum[2][3], 0.f), 1);
    }
    __syncwarp();
    if (lane == 0) mbar_arrive(sb + S_RELW + 8);
    mbar_wait(sb + S_WFULL + 48 + 8 * (w >> 1), 0);
    {
        const uint32_t po = sb + ST_WO + (48 * w + 12 * t) * 160 + 4 * g8;
#pragma unroll
        for (int s = 0; s < 3; s++)
#pragma unroll
            for (int m = 0; m < 5; m++) frag(Wo[m][s], po + 4 * s * 160 + 32 * m, 160);
    }
    __syncwarp();
    if (lane == 0) mbar_arrive(sb + S_RELW + 16);
    zero_words();
    if (tid < 192) {
        const char* srcS = gs + XS + g * 8 * 7680 + (i >> 2) * 3840 + tid * 4;
        uint32_t vs[5][8];
        int guard = 0;
        do {
#pragma unroll
            for (int b = 0; b < 5; b++)
#pragma unroll
                for (int s = 0; s < 8; s++) vs[b][s] = ldp32(srcS + b * 768 + s * 7680);
        } while (((or3(chk8(vs[0], 1), chk8(vs[1], 1), chk8(vs[2], 1)) | chk8(vs[3], 1) | chk8(vs[4], 1)) & 1) && ++guard < SPIN_LIMIT);
        const uint32_t qpos = sb + S_QS + q_pos(tid);
#pragma unroll
        for (int b = 0; b < 4; b++) {
            sts_hi16(qpos + 384 * b, bfr(sum8(vs[b])));
        }
        stsf(sb + S_CSQ + 4 * tid, sum8(vs[4]));
    }
    if (tid < 192) stsf(sb + S_CSGU + 4 * tid, gather8<768>(gs + XS2 + g * 8 * 768 + tid * 4, 1));
    __syncwarp();
    bar_main();
    arrive_if(tid == 0, sb + S_QRDY);
    TSTAMP(2);

    uint32_t side;
    { int k = 0; while ((side = ldsvol(sb + S_SIDE)) == 0 && ++k < SPIN_LIMIT) {} }
    const uint32_t td = __shfl_sync(~0u, tid, lane);
    const uint32_t wp = __shfl_sync(~0u, tid >> 5, 0);
    const uint32_t cc = wp >= 3;
    auto uni = [](uint32_t v) { return __shfl_sync(~0u, v, 0); };
    auto pin = [&](uint32_t v) { return __shfl_sync(~0u, v, td); };
    auto nearp = [&](uint32_t P) { return gx.lo + P * 8192 + ((side ^ 1 ^ __popc(P & PMASK)) & 1) * COPY; };
    constexpr uint32_t COL = 32 * 8192;
    const uint32_t ownL = gx.lo + (i >> 2) * HALF + (i & 3) * 1024, ownG = gx.lo + (g >> 3) * HALF + (g & 7) * 512;
    const uint32_t uPubA = uni(ownL + pairL(RA, 0, g) * 8192 + (wp >> 1) * 256 + (wp & 1) * 96), uPolA = uni(nearp(pairL(RA, 0, g)) + (wp >> 2) * HALF + (wp & 3) * 256);
    const uint32_t uPubB = uni(ownG + pairG(0, cc, i) * 8192), uPolB = uni(nearp(pairG(0, cc, i)));
    const uint32_t uPubC = uni(ownL + pairL(RC, 0, g) * 8192), uPolC = uni(nearp(pairL(RC, wp < 6 ? cc : 0, g)));
    const uint32_t uPubD = uni(ownG + pairG(1, 0, i) * 8192 + (wp < 7 ? 32 * wp : 256)), uPolD = uni(nearp(pairG(1, cc, i)));
    const uint32_t uPubE = uni(ownL + pairL(RE, 0, g) * 8192), uPolE = uni(nearp(pairL(RE, i >> 2, g)));
    const uint32_t uOS = uni(sb + S_OS + 192 * wp);
    auto xp = [&](uint32_t lo) { return (char*)XPtr(lo, gx.hi); };
#define IDS() __syncwarp(); const uint32_t z0_ = lag<1>(sb), z_ = td + z0_; const uint32_t ln = z_ & 31, q8 = ln >> 2, t4 = z_ & 3, n96 = z_ - 96 * cc, n80 = min(n96, 79u); (void)q8; (void)t4; (void)n80; (void)ln

    auto vaddr = [&](uint32_t (&voff)[3]) {
        const uint32_t ln = td & 31;
        const uint32_t key3 = 3 * ((ln & 7) + 2 * (ln & 8) + ((ln >> 1) & 8));
#pragma unroll
        for (int T = 0; T < 3; T++) {
            const uint32_t u = 3 * wp + T, r = key3 + (u >> 3);
            voff[T] = r * 128 + (((u ^ r) & 7) << 4);
        }
    };
    auto values = [&](uint32_t (&vf)[8][3][4], float (&acc)[3][4], auto step, uint32_t ps, auto col, uint32_t par) {
        constexpr int CUT = col.value ? 8 : 6;
        const uint32_t ln = td & 31, q8 = ln >> 2, t4 = td & 3;
        uint4 p = lds128(ps + 16 * ln);
        float f0 = 0.f, f1 = 0.f, r3 = 0.f, o = 0.f;
        int M = 0;
#pragma unroll
        for (int s = 0; s < 8; s++) {
            if (s == 0 || s == CUT)
#pragma unroll
                for (int k = 0; k < 12; k++) acc[k / 4][k % 4] = 0.f;
            step(s);
            const bool m = s >= CUT || (q8 >> 1) == (s >> 1);
            const uint32_t b0 = m ? ((s & 1) ? p.z : p.x) : 0u, b1 = m ? ((s & 1) ? p.w : p.y) : 0u;
#pragma unroll
            for (int T = 0; T < 3; T++) mmaA(acc[T], vf[s][T], b0, b1);
            if (s == FSTEP) {
                const uint2 mp = lds64(ps + PS_MAX + 8 * t4);
                M = __reduce_max_sync(~0u, __float2int_ru(fmaxf(asf(mp.x), asf(mp.y))));
                f0 = ex2(asf(mp.x) - (float)M); f1 = ex2(asf(mp.y) - (float)M);
                float l[4] = {};
                mma16816(l, ONES, ONES, ONES, ONES, p.x, p.y); mma16816(l, ONES, ONES, ONES, ONES, p.z, p.w);
                r3 = fmaf(f0, l[0], f1 * l[1]);
            }
            if (s == CUT - 1) {
                if (CUT < 8) p = lds128(ps + 384 + 16 * (ln & 7));
                const float r0 = fmaf(f0, acc[0][0], f1 * acc[0][3]), r1 = fmaf(f0, acc[1][0], f1 * acc[1][3]), r2 = fmaf(f0, acc[2][0], f1 * acc[2][3]);
                const bool hi = t4 & 2, od = t4 & 1;
                const float u0 = (hi ? r2 : r0) + __shfl_xor_sync(~0u, hi ? r0 : r2, 2), u1 = (hi ? r3 : r1) + __shfl_xor_sync(~0u, hi ? r1 : r3, 2);
                o = (od ? u1 : u0) + __shfl_xor_sync(~0u, od ? u0 : u1, 1);
                if (ln == 3) o = __int_as_float(2 * M);
                if (CUT < 8) { f0 = __shfl_sync(~0u, f0, 3); f1 = __shfl_sync(~0u, f1, 3); }
            }
        }
        CSTAMP(25);
        char* pubA = xp(uPubA + col.value * COL + 32 * t4 + 4 * q8);
        if (CUT < 8 && t4 < 3) o = fmaf(f0, sel4(t4, acc[0][0], acc[1][0], acc[2][0], acc[2][0]), fmaf(f1, sel4(t4, acc[0][3], acc[1][3], acc[2][3], acc[2][3]), o));
        stp32_if(t4 < 3 || ((wp & 1) && q8 < 2), pubA, o, par);
    };

    uint32_t left[36] = {};
#pragma unroll 1
    for (int ch = 0; ch < 5; ch++) {
        const uint32_t par0 = (ch + 1) & 1, par1 = ch & 1;
        uint32_t voff[3], vf[8][3][4];
        float acc_[3][4];
        if (ch < 4) {
            vaddr(voff);
            mbar_wait(sb + S_SCO, par1);
            if (ch == 0) mbar_wait(sb + S_WFULL + 80, 0);
            TST(0);
            auto ldw = [&](int s) {
                mbar_wait(sb + S_FV + 8 * s, par1);
#pragma unroll
                for (int T = 0; T < 3; T++) ldsm4t(vf[s][T], voff[T] + (sb + v_place(ch, s) * SLOT));
            };
            probs(bf_lo(lds16(sb + S_SC + 2 * td)), sb + S_PS, wp, td & 31);
            ldw(0); ldw(1); ldw(2);
            bar_main();
            arrive_if(td == 0, sb + S_RELR);
            values(vf, acc_, [&](int s) {
                if (s >= 3) ldw(s);
            }, sb + S_PS, std::integral_constant<int, 0>(), par0);
            TST(1);
            CSTAMP(5);
            if (ch > 0) mbar_wait(sb + S_OS1, par0);
        } else {
#pragma unroll
            for (int s = 0; s < 36; s++) vf[s / 12][(s / 4) % 3][s & 3] = left[s];
        }
        const bool has0 = ch < 4, has1 = ch > 0;
        const bool actc = wp < 6 && (cc ? has1 : has0);
        const uint32_t parc = cc ? par1 : par0;
        const uint32_t pub0 = has0 ? par0 : 0;
        uint32_t rr, pubB;
        {
            IDS();
            const uint32_t c = ch == 4;
            const uint32_t osa = pin(uOS + 96 * c + 4 * ln), oa = pin(uOS + 48 * (q8 & 2) + 24 * t4), ra = pin(sb + S_RED + 640 * wp + 320 * (t4 & 1) + 8 * q8);
            rr = pin(sb + S_RED + 320 * cc + 4 * n80); pubB = pin(uPubB + 4 * n80);
            hop_a<1>(xp(uPolA + c * COL + 8 * min(ln, 24u) + lag<DELAY_L>(sb, z0_)), pub0, osa, ln < 24, 5 * ch);
            TST(2);
            CSTAMP(6);
            float acc[5][4] = {};
            const uint2 b0 = lds64(oa), b1 = lds64(oa + 8), b2 = lds64(oa + 16);
#pragma unroll
            for (int m = 0; m < 5; m++) mmaA(acc[m], Wo[m][0], b0.x, b0.y);
#pragma unroll
            for (int m = 0; m < 5; m++) mmaA(acc[m], Wo[m][1], b1.x, b1.y);
#pragma unroll
            for (int m = 0; m < 5; m++) mmaA(acc[m], Wo[m][2], b2.x, b2.y);
#pragma unroll
            for (int m = 0; m < 5; m++) { stsf(ra + 64 * m, acc[m][0]); stsf(ra + 64 * m + 4, acc[m][2]); }
        }
        CSTAMP(7);
        uint32_t xr, fl, pubC, pubC2;
        auto prepC = [&](uint32_t ln) {
            const uint32_t q8 = ln >> 2, t4 = ln & 3;
            xr = pin(sb + S_XB + 48 * (ln & 15));
            pubC = pin(uPubC + (t4 & 1) * COL + 192 * (wp >> 1) + 64 * (wp & 1) + 8 * q8);
            pubC2 = pin(uPubC + (t4 & 1) * COL + ((t4 & 2) ? 192 * (wp >> 1) + 128 + 4 * (wp & 1) + 8 * q8 : 768 + 2 * ((q8 + 1) & 6)));
            fl = pin(((t4 & 1) ? par1 : pub0) | (t4 >= 2 || (wp == 7 && q8 < 4 && q8 != 2 - t4) ? 2 : 0));
        };
        auto stats = [&](uint32_t xa, const uint4& b, uint32_t b4) {
            float a0[4] = {}, a1[4] = {}, a2[4] = {};
            const uint4 p0 = lds128(xa), p1 = lds128(xa + 16);
            const uint2 p2 = lds64(xa + 32);
            mmaV(a0, p0, b.x, b.y); mmaV(a1, p1, b.z, b.w); mma8(a2, p2.x, p2.y, b4);
            return ((a0[0] + a0[3]) + (a1[0] + a1[3])) + (a2[0] + a2[3]);
        };
        auto give_ln = [&](uint32_t src0, uint32_t par, uint32_t dst, uint32_t ln, float& mean, float& den, auto also) {
            const char* src = xp(src0 + 768 + (ln & 1) * HALF);
            float sx, sq;
            int guard = 0;
            bool again;
            do {
                uint2 st[4];
#pragma unroll
                for (int s = 0; s < 4; s++) st[s] = ldp64(src + s * 1024);
                again = __any_sync(~0u, ((chk4(st, par) | also()) & 1) != 0);
                sx = (asf(st[0].x) + asf(st[1].x)) + (asf(st[2].x) + asf(st[3].x)); sq = (asf(st[0].y) + asf(st[1].y)) + (asf(st[2].y) + asf(st[3].y));
                sx += __shfl_xor_sync(~0u, sx, 1); sq += __shfl_xor_sync(~0u, sq, 1);
            } while (again & (++guard < SPIN_LIMIT));
            ln_stats(sx, sq, mean, den);
            stsvol64(dst, __byte_perm(__float_as_uint(den), __float_as_uint(mean), 0x7632), (__float_as_uint(rcp(den)) & ~7u) | (ch + 1));
        };
        auto take_ln = [&](uint2& c, uint32_t a) { int k = 0; do c = ldsvol64(a); while (__any_sync(~0u, (c.y & 7) != ch + 1) & (++k < SPIN_LIMIT)); };
        {
            auto gate_up = [&](auto with_stats) {
                bar_main();
                TST(3);
                CSTAMP(11);
                const uint4 b = lds128(xr);
                uint32_t b4 = lds32(xr + 16);
                float acc[3][4] = {};
                if (with_stats.value) {
                    stp32_if(fl > 1 && !(td & 2), xp(pubC2), stats(xr + (S_XA - S_XB), b, b4), fl & 1);
                    __syncwarp();
                    b4 = lds32(xr + 16);
                }
                mul80(acc, Wgu, b, b4);
                stp64_if(!(td & 2), xp(pubC), tagw(acc[0][0] + acc[0][3], fl & 1), tagw(acc[1][0] + acc[1][3], fl & 1));
                stp32_if(td & 2, xp(pubC2), acc[2][0] + acc[2][3], fl & 1);
            };
            if (wp == 7) {
                bar_main();
                IDS();
                prepC(ln);
                sts32(sb + S_ZERO + 4, or3(pubC, pubC2, fl));
                gate_up(std::true_type());
            } else {
                if (actc) {
                    bar_main();
                    CSTAMP(8);
                    uint32_t r[8];
#pragma unroll
                    for (int s = 0; s < 8; s++) r[s] = lds32(rr + 640 * s);
                    stp32_if(true, xp(pubB), sum8(r), parc);
                    CSTAMP(9);
                    IDS();
                    prepC(ln);
                    const uint32_t n4 = 4 * n80;
                    const uint32_t xas = pin(sb + S_XA + 192 + 192 * cc + a_pos(n80)), xbs = pin(sb + S_XB + 384 * cc + b_pos<40>(n80));
                    const float x0 = cc ? ldsf(sb + S_XCAR + n4) : bf_lo(lds16(sb + S_X0 + 160 * (ch & 3) + n4 / 2));
                    gather16(xp(uPolB + n4 + lag<DELAY_G>(sb, z0_)), parc, 5 * ch + 1, [&](float y, uint32_t) {
                        const uint32_t x = pack2(x0 + bfr(y), 0.f);
                        sts16(xbs, x);
                        sts16(xas, x);
                        return 0u;
                    });
                    CSTAMP(10);
                } else {
                    bar_main();
                    IDS();
                    prepC(ln);
                }
                gate_up(std::false_type());
            }
        }
        CSTAMP(12);
        float mean = 0.f, den = 1.f;
        {
            IDS();
            const uint32_t wh = pin((((ln & 7) + 48 * ((ln >> 3) & 1) + 8 * (ln >> 4)) * 160 + (wp < 7 ? 16 * wp : 128)) | ((384 * cc + b_pos<48>(n96)) << 16));
            const uint32_t pubD = pin(uPubD + (t4 & 1) * COL + 16 * (t4 & 2) + 4 * q8 + (fl & 1)), ha = xr + (S_HS - S_XB);
            auto down = [&](const uint32_t (&W)[3][4], const uint4& h0, const uint2& h1) {
                float a0[4] = {}, a1[4] = {}, a2[4] = {};
                mmaA(a0, W[0], h0.x, h0.y); mmaA(a1, W[1], h0.z, h0.w); mmaA(a2, W[2], h1.x, h1.y);
                return ((a0[0] + a0[3]) + (a1[0] + a1[3])) + (a2[0] + a2[3]);
            };
            if (wp < 6) {
                uint32_t Wd[3][4];
                auto ldd = [&](uint32_t z) {
#pragma unroll
                    for (int s = 0; s < 3; s++) ldsm4t(Wd[s], ((wh ^ z) & 0xffff) + (sb + S_WD + s * 2560));
                };
                ldd(0);
                if (actc) {
                    const char* srcv = xp(uPolC + lag<DELAY_C>(sb, z0_) + 8 * n96);
                    const uint2 cs = lds64(sb + S_CSGU + 8 * n96);
                    float gt, up;
                    int guard = 0;
                    while (true) {
                        uint2 v[8];
#pragma unroll
                        for (int s = 0; s < 8; s++) v[s] = ldp64(srcv + (s >> 2) * HALF + (s & 3) * 1024);
                        uint2 c = ldsvol64(sb + S_LN + 8 * cc + ((v[0].x ^ parc) & 1) * 32);
                        const bool stale = __any_sync(~0u, ((chk8(v, parc) | chk8y(v, parc)) & 1) != 0), late = __any_sync(~0u, (c.y & 7) != ch + 1);
                        const float pg = sum8x(v), pu = sum8y(v);
                        auto norm = [&] {
                            mean = bf_hi(c.x); den = bf_lo(c.x);
                            gt = bfr(fmaf(-mean, asf(cs.x), pg) * asf(c.y)); up = fmaf(-mean, asf(cs.y), pu) * asf(c.y);
                            keep(gt); keep(up);
                        };
                        norm();
                        if (!((stale | late) & (++guard < SPIN_LIMIT))) break;
                        if (!stale) { take_ln(c, sb + S_LN + 8 * cc); norm(); break; }
                    }
                    CSTAMP(13);
                    SWEEPS(5 * ch + 2, guard - 1);
                    const uint32_t h = pack2(bfr(gt * sigmoidf_(gt)) * bfr(up), 0.f);
                    sts16((wh >> 16) + (sb + S_HS), h);
                    CSTAMP(14);
                    if (ch == 3) CSTAMP(0);
                }
                bar_main();
                TST(4);
                CSTAMP(15);
                const uint4 h0 = lds128(ha);
                const uint2 h1 = lds64(ha + 16);
                stp32_if(!(td & 2), xp(pubD & ~1u), down(Wd, h0, h1), pubD & 1);
            } else {
                uint32_t v = 0;
                const uint32_t col = wp == 7 || !has0;
                const bool serve = wp == 6 || (has0 && has1);
                if (serve) {
                    const uint32_t par = col ? par1 : par0;
                    const char* src = xp(uPolC + col * COL + 776 + (td & 4) * (HALF / 4) + (td & 3) * 1024);
                    give_ln(uPolC + col * COL, par, sb + S_LN + 8 * col, td, mean, den, [&] { v = ldp32(src); return v ^ par; });
                }
                stsvol(sb + S_GATE, ch + 1);
                uint32_t Wd[2][3][4];
#pragma unroll
                for (int s = 0; s < 6; s++) ldsm4t(Wd[s / 3][s % 3], (wh & 0xffff) + (sb + S_WD + (s / 3) * 16 + (s % 3) * 2560));
                bar_main();
                const uint4 h0 = lds128(ha);
                const uint2 h1 = lds64(ha + 16);
                const float d0 = down(Wd[0], h0, h1), d1 = down(Wd[1], h0, h1);
                stp32_if(true, xp(pubD & ~1u), (td & 2) ? d1 : d0, pubD & 1);
                if (serve) {
                    float xw = asf(v);
                    xw += __shfl_xor_sync(~0u, xw, 1); xw += __shfl_xor_sync(~0u, xw, 2); xw += __shfl_xor_sync(~0u, xw, 4);
                    const float r = bfr(fmaf(-mean, ldsf(sb + S_SWR), xw) * rcp(den));
                    sts32(sb + S_STAT + 4 * col, __float_as_uint(bfr(sigmoidf_(r))) | (ch + 1));
                }
            }
        }
        CSTAMP(16);
        {
            IDS();
            const uint32_t pubE = pin(uPubE + (t4 < 3 ? (wp >> 2) * COL + 192 * (wp & 3) + 64 * t4 + 8 * q8 : (q8 >> 2) * COL + 768 + 4 * (q8 & 1)));
            xr = pin(sb + S_XB + 48 * (ln & 7));
            uint32_t x2 = 0;
            auto hop_d = [&](auto col) {
                const uint32_t xbs = pin(sb + S_XB + 384 * col.value + b_pos<40>(n80)), xas = col.value ? 0 : pin(sb + S_XA + 192 + a_pos(n80));
                const float x1 = bf_lo(lds16(xbs));
                const float lnx = __uint_as_float(pin(__float_as_uint(bfr(__fdiv_rn(bfr(x1 - mean), den)))));
                gather16(xp(uPolD + 4 * n80 + lag<DELAY_D>(sb, z0_)), col.value ? par1 : par0, 5 * ch + 3, [&](float y, uint32_t z) {
                    const uint32_t gate = ldsvol(sb + S_STAT + 4 * col.value + z);
                    x2 = pack2(x1 + bfr(lnx + bfr(bfr(y) * bf_hi(gate))), 0.f);
                    if (col.value) keep(x2); else { sts16(xbs, x2); sts16(xas, x2); }
                    return (uint32_t)((gate & 7) != ch + 1);
                });
                CSTAMP(17);
            };
            auto qproj = [&](auto with_stats) {
                bar_main();
                TST(5);
                CSTAMP(19);
                const uint32_t t4 = td & 3;
                const uint4 b = lds128(xr);
                uint32_t b4 = lds32(xr + 16);
                float acc[6][4] = {};
                if (with_stats.value) {
                    stp32_if((td & 11) == 3, xp(pubE), stats(xr + (S_XA - S_XB), b, b4), par0);
                    __syncwarp();
                    b4 = lds32(xr + 16);
                }
                mul80(acc, Wq, b, b4);
                const float v0 = sel4(t4, acc[0][0] + acc[0][3], acc[2][0] + acc[2][3], acc[4][0] + acc[4][3], acc[4][0] + acc[4][3]);
                const float v1 = sel4(t4, acc[1][0] + acc[1][3], acc[3][0] + acc[3][3], acc[5][0] + acc[5][3], acc[5][0] + acc[5][3]);
                stp64_if(t4 < 3, xp(pubE), tagw(v0, par0), tagw(v1, par0));
            };
            if (wp == 7) {
                if (!has0) break;
                qproj(std::true_type());
            } else {
                if (actc && !cc) hop_d(std::integral_constant<int, 0>());
                else {
                    if (actc && g == 0) {
                        const uint32_t po = pin(1280 * (ch - 1) + 160 * i + 2 * n80);
                        hop_d(std::integral_constant<int, 1>());
                        *reinterpret_cast<unsigned short*>(reinterpret_cast<char*>(P.out) + po) = (unsigned short)x2;
                    }
                    if (!has0) break;
                }
                qproj(std::false_type());
                sts32_if(td < 80, sb + S_XCAR + 4 * td, x2 << 16);
            }
        }
        CSTAMP(20);
        if (wp == 6) give_ln(uPolE, par0, sb + S_LN + 16, td, mean, den, [] { return 0u; });
        auto pass2 = [&](auto d0, auto d1, auto d2) {
            constexpr int D0 = d0.value, D1 = d1.value, D = D0 + D1 + d2.value;
            IDS();
            const uint32_t ua = sb + k_place(ch, wp & 6) * SLOT + (wp & 1) * UNIT, k0 = k_off(ln);
            uint32_t kf[12][2][4];
            auto ldk = [&](int s) { const uint32_t a = (k0 ^ (32 * (s / 3))) + (ua + 1024 * (s % 3)); ldsm4(kf[s][0], a); ldsm4(kf[s][1], a + SLOT); };
            auto ldv1 = [&](int k) { ldsm4t(vf[k / 3][k % 3], voff[k % 3] + (sb + v_place(ch, k / 3) * SLOT)); };
            auto ldv = [&](int s) { ldv1(3 * s); ldv1(3 * s + 1); ldv1(3 * s + 2); };
            constexpr uint32_t LATE = LAST_LATE;
            constexpr uint64_t EARLY_LIST = bit_list(~LATE), LATE_LIST = bit_list(LATE);
            auto early = [&](int k) {
                if (D1 == 0) ldk(k);
                else if (k < 3) { ldv1(9 + 2 * k); ldv1(10 + 2 * k); }
                else ldk((EARLY_LIST >> (4 * (k - 3))) & 15);
            };
            uint32_t v[8] = {}, qsa = 0;
            const char* srcv = xp(uPolE + lag<(D1 > 0 ? 0 : DELAY_E)>(sb, z0_) + 4 * td);
            auto look = [&] {
#pragma unroll
                for (int s = 0; s < 8; s++) v[s] = ldp32(srcv + (s >> 2) * HALF + (s & 3) * 1024);
            };
            if (D1 > 0) vaddr(voff);
            if (!(mbar_try(sb + S_FK + 8 * (wp & 6), par1) & mbar_try(sb + S_FK + 8 * (wp | 1), par1))) { mbar_wait(sb + S_FK + 8 * (wp & 6), par1); mbar_wait(sb + S_FK + 8 * (wp | 1), par1); }
#pragma unroll
            for (int s = 0; s < D0; s++) early(s);
            if (wp < 6) { look(); qsa = pin(sb + S_QS + 384 * ch + q_pos(z_)); }
#pragma unroll
            for (int s = D0; s < D0 + D1; s++) early(s);
            if (wp < 6) {
                const float cs = ldsf(sb + S_CSQ + 4 * td);
                int guard = 0;
                while (true) {
                    uint2 c = ldsvol64(sb + S_LN + 16 + ((v[0] ^ par0) & 1) * 32);
                    const bool stale = __any_sync(~0u, (chk8(v, par0) & 1) != 0), late = __any_sync(~0u, (c.y & 7) != ch + 1);
                    const float qs = sum8(v);
                    auto norm = [&] {
                        const uint32_t q = pack2(fmaf(-bf_hi(c.x), cs, qs) * asf(c.y), 0.f);
                        sts16(qsa, q);
                    };
                    norm();
                    if (!((stale | late) & (++guard < SPIN_LIMIT))) break;
                    if (!stale) { take_ln(c, sb + S_LN + 16); norm(); break; }
                    look();
                }
                SWEEPS(5 * ch + 4, guard - 1);
                CSTAMP(22);
            }
#pragma unroll
            for (int s = D0 + D1; s < D; s++) early(s);
            CSTAMP(21);
            bar_main();
            TST(6);
            CSTAMP(1);
            uint2 q = lds64(sb + S_QS + 384 * ch + 8 * ln);
            float acc[2][4] = {};
            constexpr int V0 = 13 - D, NV = D1 > 0 ? 2 : (2 * (D - 1)) / 3;
            static_assert(D1 == 0 || D - 3 + __builtin_popcount(LATE) == 12, "plan");
#pragma unroll
            for (int s = 0; s < 12; s++) {
                const bool m = q8 == (s & 7);
                const uint32_t b0 = m ? q.x : 0u, b1 = m ? q.y : 0u;
                if (s == 7) q = lds64(sb + S_QS + 384 * ch + 8 * ln + 256);
                mmaA(acc[0], kf[s][0], b0, b1);
                mmaA(acc[1], kf[s][1], b0, b1);
                if (D1 > 0) {
                    if (s >= 1 && s <= __builtin_popcount(LATE)) ldk((LATE_LIST >> (4 * (s - 1))) & 15);
                } else {
                    if (s >= 1 && s + D - 1 < 12) ldk(s + D - 1);
                    if (s >= 1 && s + D - 1 == 11) { __syncwarp(); arrive_if(ln == 0, sb + S_RELK); }
                    if (s == V0) vaddr(voff);
                    if (s >= V0 && 2 * (s - V0) < 3 * NV) ldv1(9 + 2 * (s - V0));
                    if (s >= V0 && 2 * (s - V0) + 1 < 3 * NV) ldv1(10 + 2 * (s - V0));
                }
            }
            CSTAMP(24);
            {
                const float v0 = acc[0][0] + acc[0][1], v1 = acc[0][2] + acc[0][3], v2 = acc[1][0] + acc[1][1], v3 = acc[1][2] + acc[1][3];
                const bool hi = t4 & 2, od = t4 & 1;
                const float u0 = (hi ? v2 : v0) + __shfl_xor_sync(~0u, hi ? v0 : v2, 2), u1 = (hi ? v3 : v1) + __shfl_xor_sync(~0u, hi ? v1 : v3, 2);
                const float s = (od ? u1 : u0) + __shfl_xor_sync(~0u, od ? u0 : u1, 1);
                CSTAMP(2);
                probs(scaled(s), sb + S_PS + PS_PASS, wp, ln);
                CSTAMP(3);
            }
            bar_main();
            TST(10);
            CSTAMP(4);
            if (D1 > 0) values(vf, acc_, [&](int s) { if (s < 3) ldv(s + 5); }, sb + S_PS + PS_PASS, std::integral_constant<int, 1>(), par0);
            else values(vf, acc_, [&](int s) { if (s >= (NV > 1 ? 2 : 1) && s + NV + (NV > 1 ? 1 : 2) < 8) ldv(s + NV + (NV > 1 ? 1 : 2)); }, sb + S_PS + PS_PASS, std::integral_constant<int, 1>(), par0);
            arrive_if(ln == 0, sb + S_RELV);
        };
        if (ch == 3) {
            pass2(std::integral_constant<int, LAST0>(), std::integral_constant<int, LAST1>(), std::integral_constant<int, LAST2>());
#pragma unroll
            for (int m = 0; m < 48; m++) Wq[m / 8].a[(m / 4) % 2][m % 4] = vf[3 + m / 12][(m / 4) % 3][m % 4];
#pragma unroll
            for (int m = 0; m < 12; m++) Wq[m / 2].c[m % 2] = vf[7][m / 4][m % 4];
#pragma unroll
            for (int m = 0; m < 36; m++) left[m] = m < 12 ? __float_as_uint(acc_[m / 4][m % 4]) : vf[m / 12][(m / 4) % 3][m % 4];
        } else {
            pass2(std::integral_constant<int, KPRE>(), std::integral_constant<int, 0>(), std::integral_constant<int, KPRE2>());
#pragma unroll
            for (int m = 0; m < 36; m++) left[m] = m < 12 ? __float_as_uint(acc_[m / 4][m % 4]) : vf[4 + m / 12][(m / 4) % 3][m % 4];
        }
        TST(11);
        CSTAMP(23);
    }
    sts32_if(td == 255, sb + S_GATE, 6);
    TSTAMP(3);
}

typedef CUresult (*EncodeFn)(CUtensorMap*, CUtensorMapDataType, cuuint32_t, void*, const cuuint64_t*, const cuuint64_t*, const cuuint32_t*,
                             const cuuint32_t*, CUtensorMapInterleave, CUtensorMapSwizzle, CUtensorMapL2promotion, CUtensorMapFloatOOBfill);

void make_map(EncodeFn enc, CUtensorMap* m, const void* base, uint64_t cols, uint64_t rows, uint32_t box_cols, uint32_t box_rows, bool swizzle) {
    cuuint64_t dims[2] = {cols, rows};
    cuuint64_t strides[1] = {cols * 2};
    cuuint32_t box[2] = {box_cols, box_rows};
    cuuint32_t es[2] = {1, 1};
    enc(m, CU_TENSOR_MAP_DATA_TYPE_BFLOAT16, 2, const_cast<void*>(base), dims, strides, box, es, CU_TENSOR_MAP_INTERLEAVE_NONE,
        swizzle ? CU_TENSOR_MAP_SWIZZLE_128B : CU_TENSOR_MAP_SWIZZLE_NONE, CU_TENSOR_MAP_L2_PROMOTION_NONE, CU_TENSOR_MAP_FLOAT_OOB_FILL_NONE);
}

}

extern "C" void kernel_launch(void* const* d_in, const int* in_sizes, int n_in, void* d_out, int out_size) {
    (void)in_sizes; (void)n_in; (void)out_size;
    static EncodeFn enc = nullptr;
    if (!enc) {
        void* f = nullptr;
        cudaDriverEntryPointQueryResult q;
        cudaGetDriverEntryPoint("cuTensorMapEncodeTiled", &f, cudaEnableDefault, &q);
        enc = (EncodeFn)f;
        cudaFuncSetAttribute(fused_kernel, cudaFuncAttributeMaxDynamicSharedMemorySize, SMEM_BYTES);
    }
    Params P;
    P.x = (const __nv_bfloat16*)d_in[0]; P.k = (const __nv_bfloat16*)d_in[1]; P.v = (const __nv_bfloat16*)d_in[2];
    P.wr = (const __nv_bfloat16*)d_in[6];
    P.out = (__nv_bfloat16*)d_out;
    Maps M;
    {
        cuuint64_t dims[4] = {64, 8, 3, (cuuint64_t)KV_BATCH_KEYS / 2}, strides[3] = {384, 128, 3072};
        cuuint32_t box[4] = {64, 8, 3, 2}, es[4] = {1, 1, 1, 1};
        enc(&M.k, CU_TENSOR_MAP_DATA_TYPE_BFLOAT16, 4, d_in[1], dims, strides, box, es, CU_TENSOR_MAP_INTERLEAVE_NONE, CU_TENSOR_MAP_SWIZZLE_128B,
            CU_TENSOR_MAP_L2_PROMOTION_NONE, CU_TENSOR_MAP_FLOAT_OOB_FILL_NONE);
    }
    make_map(enc, &M.v, P.v, 64, (uint64_t)12 * KV_BATCH_KEYS, 64, 96, true);
    make_map(enc, &M.vu, P.v, 64, (uint64_t)12 * KV_BATCH_KEYS, 64, 48, true);
    make_map(enc, &M.wq, d_in[3], 6144, 640, 192, 40, false);
    make_map(enc, &M.wo, d_in[4], 640, 6144, 80, 96, false);
    make_map(enc, &M.wg, d_in[7], 1536, 640, 96, 80, false);
    make_map(enc, &M.wu, d_in[8], 1536, 640, 96, 80, false);
    make_map(enc, &M.wd, d_in[9], 640, 1536, 80, 96, false);
    fused_kernel<<<NCTA, NTHR, SMEM_BYTES, cudaStreamPerThread>>>(P, M);
}
```

```cpp
#include <cuda_runtime.h>
#include <cuda.h>
#include <cuda_bf16.h>
#include <stdint.h>
#include <type_traits>

namespace {

constexpr int NCTA = 128;
constexpr int NTHR = 384;
constexpr int UNIT = 6144;
constexpr int SLOT = 12288;
#define TAU 3940
#define TAUW 3720
#define TAU0 3820
#define ILV 4
#define XB 600
#define TMIN 2400
#define SLACK 6000
#define SLACK0 1000
#define PF0 1
#define WIN_W 3
#define WIN_S 4
#define WIN_U 10
#define VPF 4
#define KRE_TAU 2600
#define RFR_TAU 20000
#define HOP1_NS 200
#define KPRE 2
#define KPRE2 2
#define LAST0 4
#define LAST1 4
#define LAST2 2
#define LAST_LATE 0xaa8
#define FSTEP 4
#define DELAY_L 2
#define DELAY_G 2
#define DELAY_C 3
#define DELAY_D 0
#define DELAY_E 1
#define REG_LO "40"
#define REG_HI "232"
#define SPIN_LOG 17
constexpr int SPIN_LIMIT = 1 << SPIN_LOG;

__host__ __device__ constexpr uint32_t pairL(uint32_t region, uint32_t c, uint32_t g) { return (g & 1) | ((g >> 1) << 2) | (c << 5) | (region << 6); }
__host__ __device__ constexpr uint32_t pairG(uint32_t d, uint32_t c, uint32_t i) { return (i & 1) | ((i >> 1) << 2) | (d << 4) | (c << 5) | (3u << 6); }
constexpr uint32_t RA = 0, RC = 1, RE = 2, HALF = 16384, COPY = 4096, PMASK = 0x59;
constexpr uint32_t XS = 0;
constexpr uint32_t XS2 = XS + 128 * 7680;
constexpr uint32_t XSEND = XS2 + 128 * 768;
__device__ uint4 g_s[XSEND / 16];
__device__ uint4 g_x[(4u << 20) / 16];
#define SWEEPS(k, n) do {} while (0)

constexpr uint32_t S_WD = 16 * SLOT;
constexpr uint32_t S_DUMMY = S_WD + 15360;
constexpr uint32_t S_BAR = S_DUMMY + 4096;
constexpr uint32_t S_FV = S_BAR, S_FK = S_FV + 64, S_RING = S_FK + 64, S_DBAR = S_RING + 48, S_WFULL = S_DBAR + 32, S_QRDY = S_WFULL + 88;
constexpr uint32_t S_RELK = S_QRDY + 8, S_RELV = S_RELK + 8, S_RELR = S_RELV + 8, S_RELW = S_RELR + 8, S_SCO = S_RELW + 24;
constexpr uint32_t S_OS1 = S_SCO + 8;
constexpr uint32_t S_ZERO = S_OS1 + 8;
constexpr uint32_t S_KF = S_ZERO + 8;
constexpr uint32_t S_TOK = S_KF + 8;
constexpr uint32_t S_SIDE = S_TOK + 80, S_GATE = S_SIDE + 4;
constexpr uint32_t S_STAT = S_GATE + 12, S_SWR = S_STAT + 16;
constexpr uint32_t S_LN = S_STAT + 32;
constexpr uint32_t S_XCAR = S_LN + 64;
constexpr uint32_t S_CSQ = S_XCAR + 320;
constexpr uint32_t S_CSGU = S_CSQ + 768;
constexpr uint32_t S_RED = S_CSGU + 768;
constexpr uint32_t S_L0 = S_RED;
constexpr uint32_t S_OS = S_RED + 5120;
constexpr uint32_t S_PS = S_OS + 1536;
constexpr uint32_t PS_MAX = 512, PS_PASS = 544;
constexpr uint32_t S_QS = S_PS + 2 * PS_PASS;
constexpr uint32_t S_XB = S_QS + 1536;
constexpr uint32_t S_XA = S_XB + 768;
constexpr uint32_t S_HS = S_XA + 768;
constexpr uint32_t S_X0 = S_HS + 768;
constexpr uint32_t S_SC = S_X0 + 640;
constexpr uint32_t S_TM = S_SC + 512;
constexpr int SMEM_BYTES = S_TM + 256;
static_assert(SMEM_BYTES <= 232448 && S_STAT % 16 == 0 && S_RED % 16 == 0 && S_XB % 16 == 0 && S_HS % 16 == 0 && S_PS % 16 == 0 && S_QS % 16 == 0, "smem");
static_assert(S_SCO == S_BAR + 44 * 8 && S_RELK == S_BAR + 38 * 8, "barriers");
constexpr uint32_t ST_WQ = 3 * SLOT, ST_WG = 8 * SLOT, ST_WO = 11 * SLOT;

__device__ __forceinline__ uint32_t smem_u32(const void* p) { return (uint32_t)__cvta_generic_to_shared(p); }
__device__ __forceinline__ void mbar_arrive(uint32_t bar) { asm volatile("mbarrier.arrive.shared::cta.b64 _, [%0];" :: "r"(bar) : "memory"); }
__device__ __forceinline__ bool mbar_try(uint32_t bar, uint32_t parity) {
    uint32_t ok;
    asm volatile("{\n .reg .pred p;\n mbarrier.try_wait.parity.shared::cta.b64 p, [%1], %2;\n selp.u32 %0, 1, 0, p;\n}" : "=r"(ok) : "r"(bar), "r"(parity) : "memory");
    return ok != 0;
}
__device__ __forceinline__ bool mbar_test(uint32_t bar, uint32_t parity) {
    uint32_t ok;
    asm volatile("{\n .reg .pred p;\n mbarrier.test_wait.parity.shared::cta.b64 p, [%1], %2;\n selp.u32 %0, 1, 0, p;\n}" : "=r"(ok) : "r"(bar), "r"(parity) : "memory");
    return ok != 0;
}
__device__ __forceinline__ void mbar_wait(uint32_t bar, uint32_t parity) {
    int n = 0;
    while (!mbar_try(bar, parity) && ++n < SPIN_LIMIT) {}
}
__device__ __forceinline__ uint32_t gtime32() { uint32_t t; asm volatile("mov.u32 %0, %globaltimer_lo;" : "=r"(t)); return t; }
__device__ __forceinline__ void bar_main() { asm volatile("bar.sync 1, 256;" ::: "memory"); }

__device__ __forceinline__ void mma16816(float (&c)[4], uint32_t a0, uint32_t a1, uint32_t a2, uint32_t a3, uint32_t b0, uint32_t b1) {
    asm("mma.sync.aligned.m16n8k16.row.col.f32.bf16.bf16.f32 {%0,%1,%2,%3}, {%4,%5,%6,%7}, {%8,%9}, {%0,%1,%2,%3};"
        : "+f"(c[0]), "+f"(c[1]), "+f"(c[2]), "+f"(c[3]) : "r"(a0), "r"(a1), "r"(a2), "r"(a3), "r"(b0), "r"(b1));
}
__device__ __forceinline__ void mmaA(float (&c)[4], const uint32_t (&a)[4], uint32_t b0, uint32_t b1) { mma16816(c, a[0], a[1], a[2], a[3], b0, b1); }
__device__ __forceinline__ void mma8(float (&c)[4], uint32_t a0, uint32_t a1, uint32_t b0) {
    asm("mma.sync.aligned.m16n8k8.row.col.f32.bf16.bf16.f32 {%0,%1,%2,%3}, {%4,%5}, {%6}, {%0,%1,%2,%3};"
        : "+f"(c[0]), "+f"(c[1]), "+f"(c[2]), "+f"(c[3]) : "r"(a0), "r"(a1), "r"(b0));
}
struct W80 { uint32_t a[2][4], c[2]; };
template <int N> __device__ __forceinline__ void mul80(float (&acc)[N][4], const W80 (&W)[N], const uint4& b, uint32_t b4) {
#pragma unroll
    for (int m = 0; m < N; m++) mmaA(acc[m], W[m].a[0], b.x, b.y);
#pragma unroll
    for (int m = 0; m < N; m++) mmaA(acc[m], W[m].a[1], b.z, b.w);
#pragma unroll
    for (int m = 0; m < N; m++) mma8(acc[m], W[m].c[0], W[m].c[1], b4);
}
__device__ __forceinline__ void ldsm2t(uint32_t (&r)[2], uint32_t addr) {
    asm volatile("ldmatrix.sync.aligned.m8n8.x2.trans.shared.b16 {%0,%1}, [%2];" : "=r"(r[0]), "=r"(r[1]) : "r"(addr) : "memory");
}
__device__ __forceinline__ void mmaV(float (&c)[4], const uint4& a, uint32_t b0, uint32_t b1) { mma16816(c, a.x, a.y, a.z, a.w, b0, b1); }
__device__ __forceinline__ void ldsm4(uint32_t (&r)[4], uint32_t addr) {
    asm volatile("ldmatrix.sync.aligned.m8n8.x4.shared.b16 {%0,%1,%2,%3}, [%4];" : "=r"(r[0]), "=r"(r[1]), "=r"(r[2]), "=r"(r[3]) : "r"(addr) : "memory");
}
__device__ __forceinline__ void ldsm4t(uint32_t (&r)[4], uint32_t addr) {
    asm volatile("ldmatrix.sync.aligned.m8n8.x4.trans.shared.b16 {%0,%1,%2,%3}, [%4];" : "=r"(r[0]), "=r"(r[1]), "=r"(r[2]), "=r"(r[3]) : "r"(addr) : "memory");
}
__device__ __forceinline__ uint32_t lds16(uint32_t a) { uint16_t v; asm volatile("ld.shared.u16 %0, [%1];" : "=h"(v) : "r"(a) : "memory"); return v; }
__device__ __forceinline__ uint32_t lds32(uint32_t a) { uint32_t v; asm volatile("ld.shared.u32 %0, [%1];" : "=r"(v) : "r"(a) : "memory"); return v; }
__device__ __forceinline__ float ldsf(uint32_t a) { return __uint_as_float(lds32(a)); }
__device__ __forceinline__ uint2 lds64(uint32_t a) { uint2 v; asm volatile("ld.shared.v2.u32 {%0,%1}, [%2];" : "=r"(v.x), "=r"(v.y) : "r"(a) : "memory"); return v; }
__device__ __forceinline__ uint4 lds128(uint32_t a) { uint4 v; asm volatile("ld.shared.v4.u32 {%0,%1,%2,%3}, [%4];" : "=r"(v.x), "=r"(v.y), "=r"(v.z), "=r"(v.w) : "r"(a) : "memory"); return v; }
__device__ __forceinline__ int ldsvol(uint32_t a) { int v; asm volatile("ld.volatile.shared.u32 %0, [%1];" : "=r"(v) : "r"(a) : "memory"); return v; }
__device__ __forceinline__ uint2 ldsvol64(uint32_t a) { uint2 v; asm volatile("{\n .reg .b64 d;\n ld.volatile.shared.b64 d, [%2];\n mov.b64 {%0,%1}, d;\n}" : "=r"(v.x), "=r"(v.y) : "r"(a) : "memory"); return v; }
__device__ __forceinline__ void stsvol64(uint32_t a, uint32_t x, uint32_t y) { asm volatile("{\n .reg .b64 d;\n mov.b64 d, {%1,%2};\n st.volatile.shared.b64 [%0], d;\n}" :: "r"(a), "r"(x), "r"(y) : "memory"); }
__device__ __forceinline__ void stsvol(uint32_t a, int v) { asm volatile("st.volatile.shared.u32 [%0], %1;" :: "r"(a), "r"(v) : "memory"); }
__device__ __forceinline__ void sts_hi16(uint32_t a, float v) { asm volatile("{\n .reg .b16 lo, hi;\n mov.b32 {lo, hi}, %1;\n st.shared.u16 [%0], hi;\n}" :: "r"(a), "r"(__float_as_uint(v)) : "memory"); }
__device__ __forceinline__ void sts16(uint32_t a, uint32_t v) { asm volatile("st.shared.u16 [%0], %1;" :: "r"(a), "r"(v) : "memory"); }
__device__ __forceinline__ void sts32(uint32_t a, uint32_t v) { asm volatile("st.shared.u32 [%0], %1;" :: "r"(a), "r"(v) : "memory"); }
__device__ __forceinline__ void stsf(uint32_t a, float v) { sts32(a, __float_as_uint(v)); }
__device__ __forceinline__ void sts64(uint32_t a, uint32_t x, uint32_t y) { asm volatile("st.shared.v2.u32 [%0], {%1,%2};" :: "r"(a), "r"(x), "r"(y) : "memory"); }

__device__ __forceinline__ void sts32_if(bool p, uint32_t a, uint32_t v) {
    asm volatile("{\n .reg .pred p;\n setp.ne.u32 p, %2, 0;\n @p st.shared.u32 [%0], %1;\n}" :: "r"(a), "r"(v), "r"((uint32_t)p) : "memory");
}
__device__ __forceinline__ void arrive_if(bool p, uint32_t bar) {
    asm volatile("{\n .reg .pred p;\n setp.ne.u32 p, %1, 0;\n @p mbarrier.arrive.shared::cta.b64 _, [%0];\n}" :: "r"(bar), "r"((uint32_t)p) : "memory");
}
__device__ __forceinline__ void keep(uint32_t& v) { asm volatile("" : "+r"(v)); }
__device__ __forceinline__ void keep(float& v) { asm volatile("" : "+f"(v)); }

__device__ __forceinline__ uint32_t ldp32(const char* p) { uint32_t v; asm volatile("ld.relaxed.gpu.global.u32 %0, [%1];" : "=r"(v) : "l"(p) : "memory"); return v; }
__device__ __forceinline__ uint2 ldp64(const char* p) {
    uint2 v; asm volatile("{\n .reg .b64 d;\n ld.relaxed.gpu.global.b64 d, [%2];\n mov.b64 {%0,%1}, d;\n}" : "=r"(v.x), "=r"(v.y) : "l"(p) : "memory"); return v;
}
__device__ __forceinline__ uint32_t tagw(float f, uint32_t par) { return (__float_as_uint(f) & ~1u) | par; }
__device__ __forceinline__ void stp32(char* p, float a, uint32_t par) { asm volatile("st.relaxed.gpu.global.u32 [%0], %1;" :: "l"(p), "r"(tagw(a, par)) : "memory"); }
__device__ __forceinline__ void stp64(char* p, float a, float b, uint32_t par) {
    asm volatile("{\n .reg .b64 d;\n mov.b64 d, {%1,%2};\n st.relaxed.gpu.global.b64 [%0], d;\n}" :: "l"(p), "r"(tagw(a, par)), "r"(tagw(b, par)) : "memory");
}
__device__ __forceinline__ void stp32_if(bool p, char* d, float a, uint32_t par) {
    asm volatile("{\n .reg .pred p;\n setp.ne.u32 p, %2, 0;\n @p st.relaxed.gpu.global.u32 [%0], %1;\n @p st.relaxed.gpu.global.u32 [%0+4096], %1;\n}" :: "l"(d), "r"(tagw(a, par)), "r"((uint32_t)p) : "memory");
}
__device__ __forceinline__ void stp64_if(bool p, char* d, uint32_t lo, uint32_t hi) {
    asm volatile("{\n .reg .pred p;\n .reg .b64 d;\n setp.ne.u32 p, %3, 0;\n mov.b64 d, {%1,%2};\n @p st.relaxed.gpu.global.b64 [%0], d;\n @p st.relaxed.gpu.global.b64 [%0+4096], d;\n}" :: "l"(d), "r"(lo), "r"(hi), "r"((uint32_t)p) : "memory");
}
__device__ __forceinline__ uint32_t chk2(uint32_t a, uint32_t b, uint32_t par) { uint32_t r; asm("lop3.b32 %0, %1, %2, %3, 0x7E;" : "=r"(r) : "r"(a), "r"(b), "r"(par)); return r; }
__device__ __forceinline__ uint32_t or3(uint32_t a, uint32_t b, uint32_t c) { uint32_t r; asm("lop3.b32 %0, %1, %2, %3, 0xFE;" : "=r"(r) : "r"(a), "r"(b), "r"(c)); return r; }
__device__ __forceinline__ uint32_t chk8(const uint32_t (&v)[8], uint32_t par) { return or3(chk2(v[0], v[1], par), chk2(v[2], v[3], par), or3(chk2(v[4], v[5], par), chk2(v[6], v[7], par), 0)); }
__device__ __forceinline__ uint32_t chk8(const uint2 (&v)[8], uint32_t par) { return or3(chk2(v[0].x, v[1].x, par), chk2(v[2].x, v[3].x, par), or3(chk2(v[4].x, v[5].x, par), chk2(v[6].x, v[7].x, par), 0)); }
__device__ __forceinline__ uint32_t chk8y(const uint2 (&v)[8], uint32_t par) { return or3(chk2(v[0].y, v[1].y, par), chk2(v[2].y, v[3].y, par), or3(chk2(v[4].y, v[5].y, par), chk2(v[6].y, v[7].y, par), 0)); }
__device__ __forceinline__ uint32_t chk4(const uint2 (&v)[4], uint32_t par) { return or3(chk2(v[0].x, v[0].y, par), chk2(v[1].x, v[1].y, par), or3(chk2(v[2].x, v[2].y, par), chk2(v[3].x, v[3].y, par), 0)); }
__device__ __forceinline__ float asf(uint32_t v) { return __uint_as_float(v); }
__device__ __forceinline__ float sum8(const uint32_t (&v)[8]) { return ((asf(v[0]) + asf(v[1])) + (asf(v[2]) + asf(v[3]))) + ((asf(v[4]) + asf(v[5])) + (asf(v[6]) + asf(v[7]))); }
__device__ __forceinline__ float sum8x(const uint2 (&v)[8]) { return ((asf(v[0].x) + asf(v[1].x)) + (asf(v[2].x) + asf(v[3].x))) + ((asf(v[4].x) + asf(v[5].x)) + (asf(v[6].x) + asf(v[7].x))); }
__device__ __forceinline__ float sum8y(const uint2 (&v)[8]) { return ((asf(v[0].y) + asf(v[1].y)) + (asf(v[2].y) + asf(v[3].y))) + ((asf(v[4].y) + asf(v[5].y)) + (asf(v[6].y) + asf(v[7].y))); }

__device__ __forceinline__ uint32_t pack2(float lo, float hi) { uint32_t r; asm("cvt.rn.bf16x2.f32 %0, %1, %2;" : "=r"(r) : "f"(hi), "f"(lo)); return r; }
__device__ __forceinline__ float bfr(float x) { return __uint_as_float(pack2(0.0f, x)); }
__device__ __forceinline__ float ex2(float x) { float r; asm("ex2.approx.ftz.f32 %0, %1;" : "=f"(r) : "f"(x)); return r; }
__device__ __forceinline__ float rcp(float x) { float r; asm("rcp.approx.ftz.f32 %0, %1;" : "=f"(r) : "f"(x)); return r; }
__device__ __forceinline__ float sqrt_(float x) { float r; asm("sqrt.approx.ftz.f32 %0, %1;" : "=f"(r) : "f"(x)); return r; }
__device__ __forceinline__ float bf_lo(uint32_t v) { return __uint_as_float(v << 16); }
__device__ __forceinline__ float bf_hi(uint32_t v) { return __uint_as_float(v & 0xffff0000u); }
__device__ __forceinline__ float sel4(int k, float a, float b, float c, float d) { return (k & 2) ? ((k & 1) ? d : c) : ((k & 1) ? b : a); }
constexpr float LOG2E = 1.4426950408889634f;
constexpr uint32_t ONES = 0x3f803f80u;

__device__ __forceinline__ void ln_stats(float sum, float sq, float& mean, float& den) {
    const float m = sum * (1.0f / 640.0f);
    const float var = fmaxf(fmaf(sq, 1.0f / 640.0f, -m * m), 0.0f);
    mean = bfr(m);
    den = bfr(sqrt_(bfr(bfr(var) + 1e-5f)));
}
__device__ __forceinline__ float sigmoidf_(float x) { return rcp(1.0f + ex2(-x * LOG2E)); }

#define TSTAMP(k) do {} while (0)
#define TST(k) do {} while (0)

#define CSTAMP(k) do {} while (0)
template <int N> __device__ __forceinline__ uint32_t lag(uint32_t sb, uint32_t z = 0) {
#pragma unroll
    for (int k = 0; k < N; k++) z = ldsvol(sb + S_ZERO + z);
    return z;
}
__device__ __forceinline__ void warm_mma(uint32_t& a, uint32_t& b) {
    asm volatile("mma.sync.aligned.m16n8k8.row.col.f16.f16.f16.f16 {%0,%1}, {%0,%1}, {%0}, {%0,%1};" : "+r"(a), "+r"(b) :: "memory");
}
#define KWNS2 20
#define KWNS 200
template <int STRIDE>
__device__ __forceinline__ float gather8(const char* p, uint32_t par) {
    uint32_t v[8];
    int guard = 0;
    do {
#pragma unroll
        for (int s = 0; s < 8; s++) v[s] = ldp32(p + s * STRIDE);
    } while ((chk8(v, par) & 1) && ++guard < SPIN_LIMIT);
    return sum8(v);
}
template <class F>
__device__ __forceinline__ void gather16(const char* p, uint32_t par, int k, F use) {
    uint32_t v[8], u[8];
    int guard = 0;
    bool again;
    do {
#pragma unroll
        for (int s = 0; s < 8; s++) v[s] = ldp32(p + s * 512);
#pragma unroll
        for (int s = 0; s < 8; s++) u[s] = ldp32(p + HALF + s * 512);
        const uint32_t stale = use(sum8(v) + sum8(u), ((v[0] ^ par) & 1) * 8);
        again = __any_sync(~0u, (or3(chk8(v, par), chk8(u, par), stale) & 1) != 0);
    } while (again & (++guard < SPIN_LIMIT));
    SWEEPS(k, guard - 1);
}

struct Params {
    const __nv_bfloat16 *x, *k, *v, *wr;
    __nv_bfloat16* out;
};
struct Maps { CUtensorMap k, v, vu, wq, wo, wg, wu, wd; };

constexpr int KV_BATCH_KEYS = 32 * 4096;

__device__ __forceinline__ void tma2d(uint32_t dst, const CUtensorMap* m, int c0, int c1, uint32_t bar, uint32_t bytes, uint64_t pol) {
    asm volatile("{\n .reg .pred p;\n elect.sync _|p, 0xffffffff;\n"
                 " @p mbarrier.arrive.expect_tx.shared::cta.b64 _, [%2], %6;\n"
                 " @p cp.async.bulk.tensor.2d.shared::cluster.global.mbarrier::complete_tx::bytes.L2::cache_hint [%0], [%1, {%3, %4}], [%2], %5;\n}"
                 :: "r"(dst), "l"(m), "r"(bar), "r"(c0), "r"(c1), "l"(pol), "r"(bytes) : "memory");
}
__device__ __forceinline__ void scrap_copy(uint32_t dst, const char* src, uint32_t bar) {
    asm volatile("{\n .reg .pred p;\n elect.sync _|p, 0xffffffff;\n"
                 " @p mbarrier.arrive.expect_tx.shared::cta.b64 _, [%2], 12288;\n"
                 " @p cp.async.bulk.shared::cluster.global.mbarrier::complete_tx::bytes [%0], [%1], 4096, [%2];\n"
                 " @p cp.async.bulk.shared::cluster.global.mbarrier::complete_tx::bytes [%0], [%1+4096], 4096, [%2];\n"
                 " @p cp.async.bulk.shared::cluster.global.mbarrier::complete_tx::bytes [%0], [%1+8192], 4096, [%2];\n}"
                 :: "r"(dst), "l"(src), "r"(bar) : "memory");
}
__device__ __forceinline__ void prefetch_l2(const void* p, uint32_t bytes) {
    asm volatile("{\n .reg .pred p;\n elect.sync _|p, 0xffffffff;\n @p cp.async.bulk.prefetch.L2.global [%0], %1;\n}" :: "l"(p), "r"(bytes) : "memory");
}
__device__ __forceinline__ uint64_t pol_first() { uint64_t p; asm("createpolicy.fractional.L2::evict_first.b64 %0, 1.0;" : "=l"(p)); return p; }
__device__ __forceinline__ uint64_t pol_normal() { uint64_t p; asm("createpolicy.fractional.L2::evict_normal.b64 %0, 1.0;" : "=l"(p)); return p; }
__device__ __forceinline__ bool utest(uint32_t bar, uint32_t parity) { return __all_sync(~0u, mbar_test(bar, parity)); }
__device__ __forceinline__ void uwait(uint32_t bar, uint32_t parity) {
    int n = 0;
    while (!__all_sync(~0u, mbar_try(bar, parity)) && ++n < SPIN_LIMIT) {}
}
template <int A, int B, int CNT> __device__ __forceinline__ void init_bars(uint32_t sb) {
#pragma unroll 1
    for (int k = A; k < B; k++)
        asm volatile("{\n .reg .pred p;\n elect.sync _|p, 0xffffffff;\n @p mbarrier.init.shared::cta.b64 [%0], %1;\n}" :: "r"(sb + S_BAR + 8 * k), "n"(CNT) : "memory");
}
__device__ __forceinline__ int unit_key(uint32_t b, uint32_t u) {
    return (blockIdx.x >> 2) * 4096 + 3072 + (blockIdx.x & 3) * (16 * ILV) + b * KV_BATCH_KEYS + (u & ~(ILV - 1u)) * 64 + (u & (ILV - 1)) * 16;
}
__device__ __forceinline__ void load_tile(const CUtensorMap* m, uint32_t dst, uint32_t bar, uint32_t bytes, int key, uint64_t pol) { tma2d(dst, m, 0, 3 * key, bar, bytes, pol); }
__device__ __forceinline__ const char* unit_ptr(const Params& P, int n) { return (const char*)((n & 16) ? P.v : P.k) + (size_t)unit_key(n >> 5, n & 15) * 384; }
#define LSTAMP(k) do {} while (0)

__device__ __forceinline__ uint32_t k_place(uint32_t b, uint32_t s) { return s + 3 + 5 * (b & 1); }
__device__ __forceinline__ uint32_t v_place(uint32_t b, uint32_t s) { return s < 3 ? s : s + 8 - 8 * (b & 1); }
__device__ __forceinline__ void k_load(const Maps& M, uint32_t dst, uint32_t bar, int key8, uint64_t pol) {
    asm volatile("{\n .reg .pred p;\n elect.sync _|p, 0xffffffff;\n"
                 " @p mbarrier.arrive.expect_tx.shared::cta.b64 _, [%2], 6144;\n"
                 " @p cp.async.bulk.tensor.4d.shared::cluster.global.mbarrier::complete_tx::bytes.L2::cache_hint [%0], [%1, {0, 0, 0, %3}], [%2], %4;\n}"
                 :: "r"(dst), "l"(&M.k), "r"(bar), "r"(key8), "l"(pol) : "memory");
}
__device__ __forceinline__ int unit_key8(uint32_t n) { return unit_key(n >> 4, n & 15) >> 3; }
__device__ __forceinline__ void ring_load(const Maps& M, uint32_t sb, uint32_t b, uint32_t u, uint32_t pos) {
    if (u < 16) k_load(M, sb + pos * UNIT, sb + S_RING + 8 * pos, unit_key8(16 * b + u), pol_normal());
    else load_tile(&M.vu, sb + pos * UNIT, sb + S_FV + 4 * (pos & 6), UNIT, unit_key(b, pos), pol_first());
}
__device__ __forceinline__ uint32_t token(bool p, uint32_t a, uint32_t n) {
    uint32_t v;
    asm volatile("{\n .reg .pred p;\n setp.ne.u32 p, %2, 0;\n mov.u32 %0, 0;\n @p atom.shared.exch.b32 %0, [%1], %3;\n}" : "=r"(v) : "r"(a), "r"((uint32_t)p), "r"(n) : "memory");
    return v;
}
__device__ __forceinline__ void place_load(const Maps& M, uint32_t sb, uint32_t n) {
    k_load(M, sb + k_place(n >> 4, 0) * SLOT + (n & 15) * UNIT, sb + S_FK + 4 * (n & 14), unit_key8(n), pol_first());
}
__device__ __forceinline__ void v_load(const Maps& M, uint32_t sb, uint32_t b, uint32_t s) {
    load_tile(&M.v, sb + v_place(b, s) * SLOT, sb + S_FV + 8 * s, SLOT, unit_key(b, 2 * s), pol_first());
}

__device__ __forceinline__ void stream_warp(const Params& P, const Maps& M, uint32_t sb, uint32_t lane) {
    const uint64_t pol = pol_first();
    const int bid = blockIdx.x, g = bid >> 3, i = bid & 7;
    const uint32_t wf = sb + S_WFULL;
    uint32_t tn = __shfl_sync(~0u, gtime32(), 0) * 16;
    auto pace = [&](uint32_t dt) {
        int k = 0;
        uint32_t now;
        do now = __shfl_sync(~0u, gtime32(), 0) * 16; while ((int)(now - tn) < 0 && ++k < SPIN_LIMIT);
        if ((int)(now - tn) > SLACK0) tn = now - SLACK0;
        tn += dt;
    };
#pragma unroll
    for (int k = 0; k < 10; k++) {
        if (k < 2) {
            if (k == 0) init_bars<26, 27, 1>(sb); else init_bars<27, 37, 1>(sb);
            asm volatile("fence.mbarrier_init.release.cluster;" ::: "memory");
            if (k == 1) { asm volatile("bar.arrive 2, %0;" :: "n"(NTHR) : "memory"); asm volatile("bar.sync 3, 128;" ::: "memory"); }
        }
        if (k >= WIN_W) uwait(wf + 8 * (k - WIN_W), 0);
        pace(TAUW * 5 / 2);
        if (k < 4) tma2d(sb + ST_WQ + 15360 * k, &M.wq, 384 * g + 192 * (k >> 1), 80 * i + 40 * (k & 1), wf + 8 * k, 15360, pol);
        else if (k < 6) tma2d(sb + ST_WG + 15360 * (k - 4), k == 4 ? &M.wg : &M.wu, 96 * g, 80 * i, wf + 8 * k, 15360, pol);
        else tma2d(sb + ST_WO + 15360 * (k - 6), &M.wo, 80 * i, 384 * g + 96 * (k - 6), wf + 8 * k, 15360, pol);
    }
#pragma unroll 1
    for (int n = 0; n < 16; n++) {
        if (n == 0 || n == 5 || n == 11) uwait(sb + S_RELW + (n == 0 ? 0 : n == 5 ? 8 : 16), 0);
        uwait(n < WIN_S ? wf + 8 * (10 - WIN_S + n) : sb + S_FV + 8 * ((n - WIN_S) ^ 8), 0);
        pace(max(min(2 * n + 2 - PF0, 2), 0) * TAU0);
        if (n >= WIN_S && !utest(sb + S_FV + 8 * ((n - WIN_S + 1) ^ 8), 0)) tn += XB;
        if (n < 8) { place_load(M, sb, 2 * n); place_load(M, sb, 2 * n + 1); }
        else if (n < 11) { ring_load(M, sb, 0, 2 * n, 2 * n - 16); ring_load(M, sb, 0, 2 * n + 1, 2 * n - 15); }
        else v_load(M, sb, 0, n - 8);
        if (n == 7) { pace(TAUW * 5 / 2); tma2d(sb + S_WD, &M.wd, 80 * i, 96 * g, wf + 80, 15360, pol); }
    }
    int nd = 0;
    uint32_t q[4];
#pragma unroll
    for (int r = 0; r < 4; r++) q[r] = sb + S_FV + 8 * (7 - r);
    uint32_t td = tn;
    uint32_t pos = 2;
#pragma unroll 1
    for (int m = 16; m < 64; m++) {
        const int b = m >> 4, j = m & 15;
        const char* src = unit_ptr(P, 2 * m);
        const uint32_t tok = sb + S_TOK + (j < 3 ? 4 * pos : j < 11 ? 24 + 4 * pos : 16 + 4 * j) + 4 * lane;
        static_assert(WIN_U <= 12, "a ring position has at most one token of the timetable");
        int k = 0;
        while (true) {
            const uint2 c = lds64(sb + S_KF);
            if (__all_sync(~0u, mbar_test(q[WIN_S - 1] & ~1u, q[WIN_S - 1] & 1) & (min((int)c.x + 1, (int)c.y) >= 16 * b + min(2 * j + 2 - WIN_U, 16))) || ++k >= SPIN_LIMIT) break;
        }
        uint32_t now;
        while (true) {
            now = __shfl_sync(~0u, gtime32(), 0) * 16;
            if ((int)(now - td) >= 0 || ++k >= SPIN_LIMIT) break;
        }
        const uint32_t mine = __ballot_sync(~0u, token(lane < (j < 11 ? 2 : 1), tok, 2 * m + lane) == 2 * m + lane);
        {
            const uint2 c = lds64(sb + S_KF);
            if (!__all_sync(~0u, mbar_test(q[WIN_S - 2] & ~1u, q[WIN_S - 2] & 1) & (min((int)c.x + 1, (int)c.y) >= 16 * b + min(2 * j + 4 - WIN_U, 16)))) tn += XB;
        }
        q[3] = q[2]; q[2] = q[1]; q[1] = q[0]; q[0] = sb + S_QRDY;
        if (j < 11) {
            if (mine & 1) ring_load(M, sb, b, 2 * j, pos); else prefetch_l2(src, UNIT);
            if (mine & 2) ring_load(M, sb, b, 2 * j + 1, pos + 1); else prefetch_l2(src + UNIT, UNIT);
            if (j >= 8) q[0] = (sb + S_FV + 8 * (j - 8)) | (b & 1);
        } else if (mine) { v_load(M, sb, b, j - 8); q[0] = (sb + S_FV + 8 * (j - 8)) | (b & 1); }
        else if (j - 8 >= VPF) prefetch_l2(src, SLOT);
        else {
            scrap_copy(sb + S_DUMMY, src, sb + S_DBAR + 8 * (nd & 3));
            q[0] = (sb + S_DBAR + 8 * (nd & 3)) | ((nd >> 2) & 1);
            nd++;
        }
        pos = j == 15 ? 2 : pos == 4 ? 0 : pos + 2;
        if ((int)(now - tn) > SLACK) tn = now - SLACK;
        tn += 2 * TAU;
        td = (int)(tn - now) > 2 * TMIN ? tn : now + 2 * TMIN;
    }
#pragma unroll 1
    for (int m = max(nd - 4, 0); m < nd; m++) uwait(sb + S_DBAR + 8 * (m & 3), (m >> 2) & 1);
}

__host__ __device__ constexpr uint64_t bit_list(uint32_t m) { uint64_t r = 0; int n = 0; for (int k = 0; k < 12; k++) if ((m >> k) & 1) r |= (uint64_t)k << (4 * n++); return r; }
__device__ __forceinline__ float scaled(float s) { return bfr(bfr(s) * 0.07216878364870322f); }
__device__ __forceinline__ void probs(float s, uint32_t ps, uint32_t src, uint32_t ln) {
    const uint32_t q8 = ln >> 2, t4 = ln & 3;
    int key = __float_as_int(s);
    key ^= (key >> 31) & 0x7fffffff;
    key = __reduce_max_sync(~0u, key);
    key ^= (key >> 31) & 0x7fffffff;
    const float ml = __int_as_float(key) * LOG2E;
    sts16(ps + 64 * src + (q8 >> 1) * 16 + t4 * 4 + (q8 & 1) * 2, pack2(ex2(fmaf(s, LOG2E, -ml)), 0.f));
    stsf(ps + PS_MAX + 4 * src, ml);
}
template <int H> __device__ __forceinline__ uint32_t b_pos(uint32_t e) { const uint32_t h = e >= H, k = e - H * h; return h * 192 + (k & 6) * 24 + (k >> 3) * 4 + (k & 1) * 2; }
__device__ __forceinline__ uint32_t a_pos(uint32_t e) { const uint32_t h = e >= 40, k = e - 40 * h; return (k & 6) * 24 + (k >> 3) * 8 + h * 4 + (k & 1) * 2; }
__device__ __forceinline__ uint32_t q_pos(uint32_t d) { const uint32_t s = 3 * ((d >> 4) & 3) + (d >> 6); return s * 32 + (d & 6) * 4 + ((d >> 3) & 1) * 4 + (d & 1) * 2; }
__device__ __forceinline__ uint32_t k_off(uint32_t ln) { return (ln & 8) * 384 + (ln & 7) * 128 + (((ln & 7) ^ (ln >> 4)) << 4); }

#define HSTAMP(k) do {} while (0)
__device__ __forceinline__ char* xwindow() { return reinterpret_cast<char*>((reinterpret_cast<uintptr_t>(g_x) + (2u << 20) - 1) & ~(uintptr_t)((2u << 20) - 1)); }

struct XPtr {
    uint32_t lo, hi;
    __device__ __forceinline__ explicit XPtr(char* p) : lo((uint32_t)(uintptr_t)p), hi((uint32_t)((uintptr_t)p >> 32)) {}
    __device__ __forceinline__ XPtr(uint32_t l, uint32_t h) : lo(l), hi(h) {}
    __device__ __forceinline__ XPtr operator+(uint32_t o) const { return XPtr(lo + o, hi); }
    __device__ __forceinline__ operator char*() const { uint64_t p; asm("mov.b64 %0, {%1, %2};" : "=l"(p) : "r"(lo), "r"(hi)); return (char*)p; }
};

__device__ __forceinline__ void side_warp(uint32_t sb) {
    const uint32_t bid = blockIdx.x, g = bid >> 3, i = bid & 7, P = pairG(0, 0, i);
    char* p = xwindow() + P * 8192 + (g >> 3) * HALF + (g & 7) * 512 + 448;
    uint32_t best[2] = {~0u, ~0u};
    asm volatile("st.relaxed.gpu.global.b32 [%0], 1;" :: "l"(p) : "memory");
    asm volatile("st.relaxed.gpu.global.b32 [%0], 1;" :: "l"(p + COPY) : "memory");
#pragma unroll 1
    for (int r = 0; r < 64; r++) {
        if (r >= 4 && !(r & 1) && min(best[0], best[1]) < 380 && max(best[0], best[1]) > min(best[0], best[1]) + 80) break;
        uint32_t c0, c1, v;
        asm volatile("mov.u32 %0, %clock;" : "=r"(c0) :: "memory");
        asm volatile("atom.relaxed.gpu.global.exch.b32 %0, [%1], 0;" : "=r"(v) : "l"(p + (r & 1) * COPY) : "memory");
        asm volatile("{\n .reg .pred q;\n setp.eq.u32 q, %1, 0x13579bdf;\n mov.u32 %0, 0;\n @!q mov.u32 %0, %clock;\n}" : "=r"(c1) : "r"(v) : "memory");
        if (r & 1) best[1] = min(best[1], c1 - c0); else best[0] = min(best[0], c1 - c0);
    }
    stsvol(sb + S_SIDE, 1 + ((best[1] < best[0]) ^ (__popc(P & PMASK) & 1)));
}

template <int N>
__device__ __forceinline__ void hop_a(const char* src, uint32_t par, uint32_t dst, bool st, int k) {
    uint2 v[N][4];
    float e[4], rl;
    int guard = 0;
    bool again;
    do {
#pragma unroll
        for (int s = 0; s < 4 * N; s++) v[s / 4][s % 4] = ldp64(src + (s / 4) * 256 + (s % 4) * 1024);
        again = __any_sync(~0u, ((chk4(v[0], par) | chk4(v[N - 1], par)) & 1) != 0);
        const int M = max(max((int)v[0][0].x, (int)v[0][1].x), max((int)v[0][2].x, (int)v[0][3].x)) - 254;
#pragma unroll
        for (int s = 0; s < 4; s++) e[s] = __int_as_float(max((int)v[0][s].x - M, 0) << 22);
        rl = rcp(fmaf(e[0], asf(v[0][0].y), e[1] * asf(v[0][1].y)) + fmaf(e[2], asf(v[0][2].y), e[3] * asf(v[0][3].y)));
#pragma unroll
        for (int s = 0; s < 4; s++) e[s] = __shfl_sync(~0u, e[s], 24);
        keep(rl);
    } while (again & (++guard < SPIN_LIMIT));
    rl = __shfl_sync(~0u, rl, 24);
#pragma unroll
    for (int n = 0; n < N; n++) {
        const float o0 = fmaf(e[0], asf(v[n][0].x), e[1] * asf(v[n][1].x)) + fmaf(e[2], asf(v[n][2].x), e[3] * asf(v[n][3].x));
        const float o1 = fmaf(e[0], asf(v[n][0].y), e[1] * asf(v[n][1].y)) + fmaf(e[2], asf(v[n][2].y), e[3] * asf(v[n][3].y));
        sts32_if(st, dst + 192 * n, pack2(o0 * rl, o1 * rl));
    }
    SWEEPS(k, guard - 1);
    __syncwarp();
}

__device__ __forceinline__ void score_warp(const Maps& M, uint32_t sb, uint32_t h, uint32_t ln) {
    const uint32_t lane0 = ln;
    uwait(sb + S_QRDY, 0);
    const uint32_t q8 = ln >> 2;
    const uint32_t k0 = k_off(ln);
    uint32_t pos = h + 6, bar = sb + S_FK, par = 0, phases = 0;
    uint2 q = lds64(sb + S_QS + 8 * ln), qh = lds64(sb + S_QS + 8 * ln + 256);
    auto first_round = [&](uint32_t b, uint32_t ln) {
        uwait(sb + S_RELR, b & 1);
        const uint32_t u = h + 2 * ln, p = u < 4 ? u + 2 : u - 4;
        uint32_t todo = __ballot_sync(~0u, token(ln < 3, sb + S_TOK + 4 * p, 32 * b + 32 + u) == 32 * b + 32 + u);
#pragma unroll 1
        for (uint32_t r = h; todo; todo >>= 1, r += 2) if (todo & 1) ring_load(M, sb, b + 1, r, r < 4 ? r + 2 : r - 4);
    };
#pragma unroll 1
    for (uint32_t n = h; n < 64; n += 2) {
        HSTAMP(0);
        const uint32_t ua = sb + pos * UNIT;
        if (!__all_sync(~0u, mbar_try(bar, par))) uwait(bar, par);
        HSTAMP(1);
        float acc[2][4] = {};
        uint32_t mine = 0;
        const uint32_t id = n + (n & 48) + 6;
#pragma unroll
        for (int s = 0; s < 12; s++) {
            uint32_t kf[4];
            ldsm4(kf, (k0 ^ (32 * (s / 3))) + (ua + 1024 * (s % 3)));
            if (s == 11) {
                __syncwarp();
                mine = token(ln == 0 && n >= 16, sb + S_TOK + 24 + 4 * pos, id);
                stsvol(sb + S_KF + 4 * h, n + 1);
            }
            const bool m = q8 == (s & 7);
            mmaA(acc[s & 1], kf, m ? (s < 8 ? q.x : qh.x) : 0u, m ? (s < 8 ? q.y : qh.y) : 0u);
        }
        const uint32_t pos0 = pos;
        const bool last = (n & 14) == 14;
        pos = last ? h + 2 : n >= 16 && pos >= 4 ? h : pos + 2;
        bar = n >= 14 ? sb + S_RING + 8 * pos : bar + 8;
        par = n >= 14 ? (phases >> pos) & 1 : 0;
        phases ^= n >= 14 ? 1u << pos : 0;
        const float w0 = (acc[0][0] + acc[0][1]) + (acc[1][0] + acc[1][1]), w1 = (acc[0][2] + acc[0][3]) + (acc[1][2] + acc[1][3]);
        HSTAMP(2);
        if (__any_sync(~0u, mine == id)) ring_load(M, sb, n >> 4, (n & 15) + 6, pos0);
        HSTAMP(3);
        float s = ((ln & 1) ? w1 : w0) + __shfl_xor_sync(~0u, (ln & 1) ? w0 : w1, 1);
        s += __shfl_xor_sync(~0u, s, 2);
        sts_hi16(sb + S_SC + (((n & 12) >> 1) + h) * 64 + (n & 2) * 2 + (ln & 29) * 2, scaled(s));
        if (last) {
            __syncwarp();
            arrive_if(ln == 0, sb + S_SCO);
            const uint32_t b = n >> 4, ln = lane0 + lag<1>(sb);
            if (b > 0) {
                uwait(sb + S_RELK, (b - 1) & 1);
                if (h == 0) LSTAMP(64 + 2 * b);
                const uint32_t sl = 3 + h + 2 * ln, idv = 32 * b + 16 + 2 * sl;
                uint32_t todo = __ballot_sync(~0u, token(sl < 8, sb + S_TOK + 48 + 4 * sl, idv) == idv);
#pragma unroll 1
                for (uint32_t r = 3 + h; todo; todo >>= 1, r += 2) if (todo & 1) v_load(M, sb, b, r);
                const uint32_t g = blockIdx.x >> 3, pr = pairL(RA, 1, g), side = ldsvol(sb + S_SIDE);
                const char* src = xwindow() + pr * 8192 + ((side ^ 1 ^ __popc(pr & PMASK)) & 1) * COPY + h * HALF + 8 * min(ln, 24u);
                uwait(sb + S_RELV, (b - 1) & 1);
                __nanosleep(HOP1_NS);
#pragma unroll 1
                for (uint32_t r = 0; r < 4; r += 2) {
                    hop_a<2>(src + 256 * r, b & 1, sb + S_OS + 192 * (4 * h + r) + 96 + 4 * ln, ln < 24, 25);
                    if (r == 0 && b < 3) first_round(b, ln);
                }
                arrive_if(ln == 0, sb + S_OS1);
            } else first_round(0, ln);
            q = lds64(sb + S_QS + 24 * ((n + 2) & 48) + 8 * ln); qh = lds64(sb + S_QS + 24 * ((n + 2) & 48) + 8 * ln + 256);
        }
    }
}

__global__ void __launch_bounds__(NTHR, 1)
fused_kernel(const Params P, const __grid_constant__ Maps M) {
    extern __shared__ __align__(1024) unsigned char smem[];
    const uint32_t sb = smem_u32(smem);
    const int tid = threadIdx.x, bid = blockIdx.x;
    if (tid == 0) {
        asm volatile("prefetch.tensormap [%0];" :: "l"(&M.wq) : "memory");
        asm volatile("cp.async.bulk.prefetch.L2.global [%0], %1;" :: "l"(unit_ptr(P, 0)), "r"(PF0 * UNIT) : "memory");
    }
    const int w = __shfl_sync(~0u, tid >> 5, 0), lane = tid & 31;

    if (w >= 8) {
        asm volatile("setmaxnreg.dec.sync.aligned.u32 " REG_LO ";");
        if (w == 8) {
            stream_warp(P, M, sb, lane);
        } else {
            if (w == 11 && lane < 8) asm volatile("prefetch.tensormap [%0];" :: "l"(&M.k + lane) : "memory");
            if (w == 9) { init_bars<0, 3, 2>(sb); init_bars<3, 8, 1>(sb); init_bars<16, 22, 1>(sb); }
            else if (w == 10) { init_bars<8, 16, 2>(sb); init_bars<22, 26, 1>(sb); }
            else { init_bars<37, 38, 1>(sb); init_bars<38, 40, 8>(sb); init_bars<40, 41, 1>(sb); init_bars<41, 44, 8>(sb); init_bars<44, 46, 2>(sb); stsvol(sb + S_ZERO + 4 * lane, 0); if (lane < 16) stsvol(sb + S_LN + 4 * lane, 0); }
            asm volatile("fence.mbarrier_init.release.cluster;" ::: "memory");
            asm volatile("bar.arrive 3, 128;" ::: "memory");
            asm volatile("bar.sync 2, %0;" :: "n"(NTHR) : "memory");
            if (w < 11) score_warp(M, sb, w - 9, lane);
            else {
                if (lane == 0) side_warp(sb);
                __syncwarp();
                uint32_t a = 0, b = 0;
                int k = 0;
                while (ldsvol(sb + S_GATE) == 0 && ++k < SPIN_LIMIT) { warm_mma(a, b); __nanosleep(KWNS); }
                uint32_t rl = lane, rq = 0;
                auto reset = [&] {
                    if (rq < 128) *reinterpret_cast<uint4*>(reinterpret_cast<char*>(g_s) + (rl < 60 ? XS + bid * 7680 + 128 * rl : XS2 + bid * 768 + 128 * (rl - 60)) + rq) = make_uint4(0, 0, 0, 0);
                    rl += 32;
                    if (rl >= 66) { rl -= 66; rq += 16; }
                };
                const uint32_t side = (ldsvol(sb + S_SIDE) & 1) ^ 1, g = bid >> 3, i = bid & 7;
                const XPtr gx(xwindow());
                auto nearp = [&](uint32_t pr) { return gx.lo + pr * 8192 + ((side ^ __popc(pr & PMASK)) & 1) * COPY; };
                const uint32_t own = (i >> 2) * HALF + (i & 3) * 1024 + (lane & 7) * 128;
                const uint32_t pAC = nearp(pairL(lane >> 4, (lane >> 3) & 1, g)) + own, pE = nearp(pairL(RE, (lane >> 3) & 1, g)) + own;
                const uint32_t pG = nearp(pairG((lane >> 2) & 1, (lane >> 3) & 1, i)) + min(lane & 3, 2) * 128;
                uint32_t tr = 0, tk = 0, ph = 0, src = g + (lane >> 4), seen = 0, n = 16;
                bool go = false, first = true;
                while (n < 64 && ++k < SPIN_LIMIT) {
                    const uint32_t now = __shfl_sync(~0u, gtime32(), 0) * 16;
                    if (!go && utest((n & 15) < 6 ? sb + S_RELK : sb + S_RELV, ((n >> 4) & 1) ^ 1)) { go = true; if ((int)(now - tk) > 0 || !(n & 15)) tk = now; }
                    if (go && (int)(now - tk) >= 0) {
                        place_load(M, sb, (n & 16) ? n : (n & 48) | ((n + 10) & 15));
                        tk += KRE_TAU;
                        n++;
                        go = (n & 15) != 0 && (n & 15) != 6;
                        if (!(n & 15)) LSTAMP(63 + (n >> 3));
                    } else if (first || (int)(now - tr) >= 0) {
                        first = false;
                        tr = now + RFR_TAU;
                        b |= seen & a;
                        warm_mma(a, b);
                        seen = ldp32(XPtr(ph == 0 ? pAC : ph == 1 && lane < 16 ? pE : pG + (src & 8) * (HALF / 8) + (src & 7) * 512, gx.hi));
                        reset();
                        src += ph == 0 ? 0 : ph == 1 ? 2 : 1;
                        ph = ph == 2 ? 0 : ph + 1;
                    } else __nanosleep(KWNS2);
                }
                while (rq < 128) reset();
                __syncwarp();
                while (ldsvol(sb + S_GATE) < 6 && ++k < SPIN_LIMIT) { warm_mma(a, b); __nanosleep(KWNS); }
                if (a | b) stsvol(sb + S_GATE, 6);
            }
        }
        return;
    }
    asm volatile("setmaxnreg.inc.sync.aligned.u32 " REG_HI ";");

    const int g = bid >> 3, i = bid & 7;
    const int g8 = lane >> 2, t = lane & 3;
    char* const gs = reinterpret_cast<char*>(g_s);
    const XPtr gx(xwindow());

    auto zero_words = [&] {
        const uint4 z = make_uint4(0, 0, 0, 0);
        const uint32_t c = (tid >> 6) & 1, cp = (tid >> 7) * COPY, k = (tid & 63) * 16;
        *reinterpret_cast<uint4*>((char*)(gx + pairL(RA, c, g) * 8192 + (i >> 2) * HALF + (i & 3) * 1024 + cp + k)) = z;
        *reinterpret_cast<uint4*>((char*)(gx + pairL(RC, c, g) * 8192 + (i >> 2) * HALF + (i & 3) * 1024 + cp + k)) = z;
        *reinterpret_cast<uint4*>((char*)(gx + pairL(RE, c, g) * 8192 + (i >> 2) * HALF + (i & 3) * 1024 + cp + k)) = z;
        if ((tid & 31) < 24) *reinterpret_cast<uint4*>((char*)(gx + pairG((tid >> 5) & 1, c, i) * 8192 + (g >> 3) * HALF + (g & 7) * 512 + cp + (tid & 31) * 16)) = z;
    };
    W80 Wq[6], Wgu[3];
    uint32_t Wo[5][3][4];
    if (w < 4) {
        const uint32_t* xp = reinterpret_cast<const uint32_t*>(P.x + 640 * w);
        float sum = 0.f, sq = 0.f;
#pragma unroll
        for (int u = 0; u < 10; u++) { uint32_t v = xp[lane + 32 * u]; float a = bf_lo(v), b = bf_hi(v); sum += a + b; sq += a * a + b * b; }
#pragma unroll
        for (int o = 16; o > 0; o >>= 1) { sum += __shfl_xor_sync(~0u, sum, o); sq += __shfl_xor_sync(~0u, sq, o); }
        float mean, den; ln_stats(sum, sq, mean, den);
        if (lane < 20) {
            const uint2 v = reinterpret_cast<const uint2*>(P.x + 640 * w + 80 * i)[lane];
            sts64(sb + S_X0 + 160 * w + 8 * lane, v.x, v.y);
            sts32(sb + S_L0 + 384 * w + b_pos<40>(4 * lane), pack2(__fdiv_rn(bfr(bf_lo(v.x) - mean), den), __fdiv_rn(bfr(bf_hi(v.x) - mean), den)));
            sts32(sb + S_L0 + 384 * w + b_pos<40>(4 * lane + 2), pack2(__fdiv_rn(bfr(bf_lo(v.y) - mean), den), __fdiv_rn(bfr(bf_hi(v.y) - mean), den)));
        }
    } else if (w == 4) {
        const uint32_t* xp = reinterpret_cast<const uint32_t*>(P.wr);
        float sum = 0.f;
#pragma unroll
        for (int u = 0; u < 10; u++) { uint32_t v = xp[lane + 32 * u]; sum += bf_lo(v) + bf_hi(v); }
#pragma unroll
        for (int o = 16; o > 0; o >>= 1) sum += __shfl_xor_sync(~0u, sum, o);
        if (lane == 0) stsf(sb + S_SWR, sum);
        if (lane < 20) {
            const uint2 v = reinterpret_cast<const uint2*>(P.wr + 80 * i)[lane];
            sts32(sb + S_XA + 576 + a_pos(4 * lane), v.x); sts32(sb + S_XA + 576 + a_pos(4 * lane + 2), v.y);
            sts32(sb + S_XA + a_pos(4 * lane), ONES); sts32(sb + S_XA + a_pos(4 * lane + 2), ONES);
        }
    }
    asm volatile("bar.sync 2, %0;" :: "n"(NTHR) : "memory");
    auto frag = [](uint32_t (&a)[4], uint32_t p, int pitch) {
        const uint32_t r0 = lds32(p), r1 = lds32(p + pitch), r2 = lds32(p + 2 * pitch), r3 = lds32(p + 3 * pitch);
        a[0] = __byte_perm(r0, r1, 0x5410); a[1] = __byte_perm(r0, r1, 0x7632);
        a[2] = __byte_perm(r2, r3, 0x5410); a[3] = __byte_perm(r2, r3, 0x7632);
    };
    mbar_wait(sb + S_WFULL + 16 * (w >> 2), 0);
    mbar_wait(sb + S_WFULL + 16 * (w >> 2) + 8, 0);
    {
        const uint32_t p = sb + ST_WQ + (w >> 2) * 30720 + (2 * t) * 384 + (48 * (w & 3) + 2 * g8) * 2;
#pragma unroll
        for (int r = 0; r < 10; r++)
#pragma unroll
            for (int m = 0; m < 3; m++) {
                const uint32_t q = p + ((r & 1) * 40 + (r >> 1) * 8) * 384 + 32 * m, r0 = lds32(q), r1 = lds32(q + 384);
                (r < 8 ? Wq[2 * m].a[(r >> 2) & 1][r & 3] : Wq[2 * m].c[r & 1]) = __byte_perm(r0, r1, 0x5410);
                (r < 8 ? Wq[2 * m + 1].a[(r >> 2) & 1][r & 3] : Wq[2 * m + 1].c[r & 1]) = __byte_perm(r0, r1, 0x7632);
            }
    }
    __syncwarp();
    if (lane == 0) mbar_arrive(sb + S_RELW);
    TSTAMP(1);
    {
        char* d = gs + XS + bid * 7680 + (w >> 2) * 3840 + (48 * (w & 3) + 2 * g8) * 4;
        float acc[6][4] = {};
        mul80(acc, Wq, lds128(sb + S_L0 + 48 * lane), lds32(sb + S_L0 + 48 * lane + 16));
#pragma unroll
        for (int m = 0; m < 6; m += 2) stp64(d + t * 768 + 32 * m, acc[m][0] + acc[m][3], acc[m + 1][0] + acc[m + 1][3], 1);
        float sum[6][4] = {};
        mul80(sum, Wq, make_uint4(ONES, ONES, ONES, ONES), ONES);
        if (t == 0)
#pragma unroll
            for (int m = 0; m < 6; m += 2) stp64(d + 4 * 768 + 32 * m, sum[m][0] + sum[m][3], sum[m + 1][0] + sum[m + 1][3], 1);
    }
    mbar_wait(sb + S_WFULL + 32, 0);
    mbar_wait(sb + S_WFULL + 40, 0);
    const uint32_t oct = 3 * (w >> 1) + (w & 1), oct2 = 3 * (w >> 1) + 2;
    {
        const uint32_t p = sb + ST_WG + ((lane & 7) + 40 * ((lane >> 3) & 1) + 8 * (lane >> 4)) * 192;
#pragma unroll
        for (int T = 0; T < 3; T++) {
            const uint32_t q = p + (T < 2 ? T * 15360 + 16 * oct : (w & 1) * 15360 + 16 * oct2);
            ldsm4t(Wgu[T].a[0], q); ldsm4t(Wgu[T].a[1], q + 16 * 192); ldsm2t(Wgu[T].c, q + 32 * 192);
        }
        float sum[3][4] = {};
        mul80(sum, Wgu, make_uint4(ONES, ONES, ONES, ONES), ONES);
        if (t < 3) stp32(gs + XS2 + bid * 768 + (t < 2 ? 64 * oct + 4 * t : 64 * oct2 + 4 * (w & 1)) + 8 * g8,
                         sel4(t, sum[0][0] + sum[0][3], sum[1][0] + sum[1][3], sum[2][0] + sum[2][3], 0.f), 1);
    }
    __syncwarp();
    if (lane == 0) mbar_arrive(sb + S_RELW + 8);
    mbar_wait(sb + S_WFULL + 48 + 8 * (w >> 1), 0);
    {
        const uint32_t po = sb + ST_WO + (48 * w + 12 * t) * 160 + 4 * g8;
#pragma unroll
        for (int s = 0; s < 3; s++)
#pragma unroll
            for (int m = 0; m < 5; m++) frag(Wo[m][s], po + 4 * s * 160 + 32 * m, 160);
    }
    __syncwarp();
    if (lane == 0) mbar_arrive(sb + S_RELW + 16);
    zero_words();
    if (tid < 192) {
        const char* srcS = gs + XS + g * 8 * 7680 + (i >> 2) * 3840 + tid * 4;
        uint32_t vs[5][8];
        int guard = 0;
        do {
#pragma unroll
            for (int b = 0; b < 5; b++)
#pragma unroll
                for (int s = 0; s < 8; s++) vs[b][s] = ldp32(srcS + b * 768 + s * 7680);
        } while (((or3(chk8(vs[0], 1), chk8(vs[1], 1), chk8(vs[2], 1)) | chk8(vs[3], 1) | chk8(vs[4], 1)) & 1) && ++guard < SPIN_LIMIT);
        const uint32_t qpos = sb + S_QS + q_pos(tid);
#pragma unroll
        for (int b = 0; b < 4; b++) {
            sts_hi16(qpos + 384 * b, bfr(sum8(vs[b])));
        }
        stsf(sb + S_CSQ + 4 * tid, sum8(vs[4]));
    }
    if (tid < 192) stsf(sb + S_CSGU + 4 * tid, gather8<768>(gs + XS2 + g * 8 * 768 + tid * 4, 1));
    __syncwarp();
    bar_main();
    arrive_if(tid == 0, sb + S_QRDY);
    TSTAMP(2);

    uint32_t side;
    { int k = 0; while ((side = ldsvol(sb + S_SIDE)) == 0 && ++k < SPIN_LIMIT) {} }
    const uint32_t td = __shfl_sync(~0u, tid, lane);
    const uint32_t wp = __shfl_sync(~0u, tid >> 5, 0);
    const uint32_t cc = wp >= 3;
    auto uni = [](uint32_t v) { return __shfl_sync(~0u, v, 0); };
    auto pin = [&](uint32_t v) { return __shfl_sync(~0u, v, td); };
    auto nearp = [&](uint32_t P) { return gx.lo + P * 8192 + ((side ^ 1 ^ __popc(P & PMASK)) & 1) * COPY; };
    constexpr uint32_t COL = 32 * 8192;
    const uint32_t ownL = gx.lo + (i >> 2) * HALF + (i & 3) * 1024, ownG = gx.lo + (g >> 3) * HALF + (g & 7) * 512;
    const uint32_t uPubA = uni(ownL + pairL(RA, 0, g) * 8192 + (wp >> 1) * 256 + (wp & 1) * 96), uPolA = uni(nearp(pairL(RA, 0, g)) + (wp >> 2) * HALF + (wp & 3) * 256);
    const uint32_t uPubB = uni(ownG + pairG(0, cc, i) * 8192), uPolB = uni(nearp(pairG(0, cc, i)));
    const uint32_t uPubC = uni(ownL + pairL(RC, 0, g) * 8192), uPolC = uni(nearp(pairL(RC, wp < 6 ? cc : 0, g)));
    const uint32_t uPubD = uni(ownG + pairG(1, 0, i) * 8192 + (wp < 7 ? 32 * wp : 256)), uPolD = uni(nearp(pairG(1, cc, i)));
    const uint32_t uPubE = uni(ownL + pairL(RE, 0, g) * 8192), uPolE = uni(nearp(pairL(RE, i >> 2, g)));
    const uint32_t uOS = uni(sb + S_OS + 192 * wp);
    auto xp = [&](uint32_t lo) { return (char*)XPtr(lo, gx.hi); };
#define IDS() __syncwarp(); const uint32_t z0_ = lag<1>(sb), z_ = td + z0_; const uint32_t ln = z_ & 31, q8 = ln >> 2, t4 = z_ & 3, n96 = z_ - 96 * cc, n80 = min(n96, 79u); (void)q8; (void)t4; (void)n80; (void)ln

    auto vaddr = [&](uint32_t (&voff)[3]) {
        const uint32_t ln = td & 31;
        const uint32_t key3 = 3 * ((ln & 7) + 2 * (ln & 8) + ((ln >> 1) & 8));
#pragma unroll
        for (int T = 0; T < 3; T++) {
            const uint32_t u = 3 * wp + T, r = key3 + (u >> 3);
            voff[T] = r * 128 + (((u ^ r) & 7) << 4);
        }
    };
    auto values = [&](uint32_t (&vf)[8][3][4], float (&acc)[3][4], auto step, uint32_t ps, auto col, uint32_t par) {
        constexpr int CUT = col.value ? 8 : 6;
        const uint32_t ln = td & 31, q8 = ln >> 2, t4 = td & 3;
        uint4 p = lds128(ps + 16 * ln);
        float f0 = 0.f, f1 = 0.f, r3 = 0.f, o = 0.f;
        int M = 0;
#pragma unroll
        for (int s = 0; s < 8; s++) {
            if (s == 0 || s == CUT)
#pragma unroll
                for (int k = 0; k < 12; k++) acc[k / 4][k % 4] = 0.f;
            step(s);
            const bool m = s >= CUT || (q8 >> 1) == (s >> 1);
            const uint32_t b0 = m ? ((s & 1) ? p.z : p.x) : 0u, b1 = m ? ((s & 1) ? p.w : p.y) : 0u;
#pragma unroll
            for (int T = 0; T < 3; T++) mmaA(acc[T], vf[s][T], b0, b1);
            if (s == FSTEP) {
                const uint2 mp = lds64(ps + PS_MAX + 8 * t4);
                M = __reduce_max_sync(~0u, __float2int_ru(fmaxf(asf(mp.x), asf(mp.y))));
                f0 = ex2(asf(mp.x) - (float)M); f1 = ex2(asf(mp.y) - (float)M);
                float l[4] = {};
                mma16816(l, ONES, ONES, ONES, ONES, p.x, p.y); mma16816(l, ONES, ONES, ONES, ONES, p.z, p.w);
                r3 = fmaf(f0, l[0], f1 * l[1]);
            }
            if (s == CUT - 1) {
                if (CUT < 8) p = lds128(ps + 384 + 16 * (ln & 7));
                const float r0 = fmaf(f0, acc[0][0], f1 * acc[0][3]), r1 = fmaf(f0, acc[1][0], f1 * acc[1][3]), r2 = fmaf(f0, acc[2][0], f1 * acc[2][3]);
                const bool hi = t4 & 2, od = t4 & 1;
                const float u0 = (hi ? r2 : r0) + __shfl_xor_sync(~0u, hi ? r0 : r2, 2), u1 = (hi ? r3 : r1) + __shfl_xor_sync(~0u, hi ? r1 : r3, 2);
                o = (od ? u1 : u0) + __shfl_xor_sync(~0u, od ? u0 : u1, 1);
                if (ln == 3) o = __int_as_float(2 * M);
                if (CUT < 8) { f0 = __shfl_sync(~0u, f0, 3); f1 = __shfl_sync(~0u, f1, 3); }
            }
        }
        CSTAMP(25);
        char* pubA = xp(uPubA + col.value * COL + 32 * t4 + 4 * q8);
        if (CUT < 8 && t4 < 3) o = fmaf(f0, sel4(t4, acc[0][0], acc[1][0], acc[2][0], acc[2][0]), fmaf(f1, sel4(t4, acc[0][3], acc[1][3], acc[2][3], acc[2][3]), o));
        stp32_if(t4 < 3 || ((wp & 1) && q8 < 2), pubA, o, par);
    };

    uint32_t left[36] = {};
#pragma unroll 1
    for (int ch = 0; ch < 5; ch++) {
        const uint32_t par0 = (ch + 1) & 1, par1 = ch & 1;
        uint32_t voff[3], vf[8][3][4];
        float acc_[3][4];
        if (ch < 4) {
            vaddr(voff);
            mbar_wait(sb + S_SCO, par1);
            if (ch == 0) mbar_wait(sb + S_WFULL + 80, 0);
            TST(0);
            auto ldw = [&](int s) {
                mbar_wait(sb + S_FV + 8 * s, par1);
#pragma unroll
                for (int T = 0; T < 3; T++) ldsm4t(vf[s][T], voff[T] + (sb + v_place(ch, s) * SLOT));
            };
            probs(bf_lo(lds16(sb + S_SC + 2 * td)), sb + S_PS, wp, td & 31);
            ldw(0); ldw(1); ldw(2);
            bar_main();
            arrive_if(td == 0, sb + S_RELR);
            values(vf, acc_, [&](int s) {
                if (s >= 3) ldw(s);
            }, sb + S_PS, std::integral_constant<int, 0>(), par0);
            TST(1);
            CSTAMP(5);
            if (ch > 0) mbar_wait(sb + S_OS1, par0);
        } else {
#pragma unroll
            for (int s = 0; s < 36; s++) vf[s / 12][(s / 4) % 3][s & 3] = left[s];
        }
        const bool has0 = ch < 4, has1 = ch > 0;
        const bool actc = wp < 6 && (cc ? has1 : has0);
        const uint32_t parc = cc ? par1 : par0;
        const uint32_t pub0 = has0 ? par0 : 0;
        uint32_t rr, pubB;
        {
            IDS();
            const uint32_t c = ch == 4;
            const uint32_t osa = pin(uOS + 96 * c + 4 * ln), oa = pin(uOS + 48 * (q8 & 2) + 24 * t4), ra = pin(sb + S_RED + 640 * wp + 320 * (t4 & 1) + 8 * q8);
            rr = pin(sb + S_RED + 320 * cc + 4 * n80); pubB = pin(uPubB + 4 * n80);
            hop_a<1>(xp(uPolA + c * COL + 8 * min(ln, 24u) + lag<DELAY_L>(sb, z0_)), pub0, osa, ln < 24, 5 * ch);
            TST(2);
            CSTAMP(6);
            float acc[5][4] = {};
            const uint2 b0 = lds64(oa), b1 = lds64(oa + 8), b2 = lds64(oa + 16);
#pragma unroll
            for (int m = 0; m < 5; m++) mmaA(acc[m], Wo[m][0], b0.x, b0.y);
#pragma unroll
            for (int m = 0; m < 5; m++) mmaA(acc[m], Wo[m][1], b1.x, b1.y);
#pragma unroll
            for (int m = 0; m < 5; m++) mmaA(acc[m], Wo[m][2], b2.x, b2.y);
#pragma unroll
            for (int m = 0; m < 5; m++) { stsf(ra + 64 * m, acc[m][0]); stsf(ra + 64 * m + 4, acc[m][2]); }
        }
        CSTAMP(7);
        uint32_t xr, fl, pubC, pubC2;
        auto prepC = [&](uint32_t ln) {
            const uint32_t q8 = ln >> 2, t4 = ln & 3;
            xr = pin(sb + S_XB + 48 * (ln & 15));
            pubC = pin(uPubC + (t4 & 1) * COL + 192 * (wp >> 1) + 64 * (wp & 1) + 8 * q8);
            pubC2 = pin(uPubC + (t4 & 1) * COL + ((t4 & 2) ? 192 * (wp >> 1) + 128 + 4 * (wp & 1) + 8 * q8 : 768 + 2 * ((q8 + 1) & 6)));
            fl = pin(((t4 & 1) ? par1 : pub0) | (t4 >= 2 || (wp == 7 && q8 < 4 && q8 != 2 - t4) ? 2 : 0));
        };
        auto stats = [&](uint32_t xa, const uint4& b, uint32_t b4) {
            float a0[4] = {}, a1[4] = {}, a2[4] = {};
            const uint4 p0 = lds128(xa), p1 = lds128(xa + 16);
            const uint2 p2 = lds64(xa + 32);
            mmaV(a0, p0, b.x, b.y); mmaV(a1, p1, b.z, b.w); mma8(a2, p2.x, p2.y, b4);
            return ((a0[0] + a0[3]) + (a1[0] + a1[3])) + (a2[0] + a2[3]);
        };
        auto give_ln = [&](uint32_t src0, uint32_t par, uint32_t dst, uint32_t ln, float& mean, float& den, auto also) {
            const char* src = xp(src0 + 768 + (ln & 1) * HALF);
            float sx, sq;
            int guard = 0;
            bool again;
            do {
                uint2 st[4];
#pragma unroll
                for (int s = 0; s < 4; s++) st[s] = ldp64(src + s * 1024);
                again = __any_sync(~0u, ((chk4(st, par) | also()) & 1) != 0);
                sx = (asf(st[0].x) + asf(st[1].x)) + (asf(st[2].x) + asf(st[3].x)); sq = (asf(st[0].y) + asf(st[1].y)) + (asf(st[2].y) + asf(st[3].y));
                sx += __shfl_xor_sync(~0u, sx, 1); sq += __shfl_xor_sync(~0u, sq, 1);
            } while (again & (++guard < SPIN_LIMIT));
            ln_stats(sx, sq, mean, den);
            stsvol64(dst, __byte_perm(__float_as_uint(den), __float_as_uint(mean), 0x7632), (__float_as_uint(rcp(den)) & ~7u) | (ch + 1));
        };
        auto take_ln = [&](uint2& c, uint32_t a) { int k = 0; do c = ldsvol64(a); while (__any_sync(~0u, (c.y & 7) != ch + 1) & (++k < SPIN_LIMIT)); };
        {
            auto gate_up = [&](auto with_stats) {
                bar_main();
                TST(3);
                CSTAMP(11);
                const uint4 b = lds128(xr);
                uint32_t b4 = lds32(xr + 16);
                float acc[3][4] = {};
                if (with_stats.value) {
                    stp32_if(fl > 1 && !(td & 2), xp(pubC2), stats(xr + (S_XA - S_XB), b, b4), fl & 1);
                    __syncwarp();
                    b4 = lds32(xr + 16);
                }
                mul80(acc, Wgu, b, b4);
                stp64_if(!(td & 2), xp(pubC), tagw(acc[0][0] + acc[0][3], fl & 1), tagw(acc[1][0] + acc[1][3], fl & 1));
                stp32_if(td & 2, xp(pubC2), acc[2][0] + acc[2][3], fl & 1);
            };
            if (wp == 7) {
                bar_main();
                IDS();
                prepC(ln);
                sts32(sb + S_ZERO + 4, or3(pubC, pubC2, fl));
                gate_up(std::true_type());
            } else {
                if (actc) {
                    bar_main();
                    CSTAMP(8);
                    uint32_t r[8];
#pragma unroll
                    for (int s = 0; s < 8; s++) r[s] = lds32(rr + 640 * s);
                    stp32_if(true, xp(pubB), sum8(r), parc);
                    CSTAMP(9);
                    IDS();
                    prepC(ln);
                    const uint32_t n4 = 4 * n80;
                    const uint32_t xas = pin(sb + S_XA + 192 + 192 * cc + a_pos(n80)), xbs = pin(sb + S_XB + 384 * cc + b_pos<40>(n80));
                    const float x0 = cc ? ldsf(sb + S_XCAR + n4) : bf_lo(lds16(sb + S_X0 + 160 * (ch & 3) + n4 / 2));
                    gather16(xp(uPolB + n4 + lag<DELAY_G>(sb, z0_)), parc, 5 * ch + 1, [&](float y, uint32_t) {
                        const uint32_t x = pack2(x0 + bfr(y), 0.f);
                        sts16(xbs, x);
                        sts16(xas, x);
                        return 0u;
                    });
                    CSTAMP(10);
                } else {
                    bar_main();
                    IDS();
                    prepC(ln);
                }
                gate_up(std::false_type());
            }
        }
        CSTAMP(12);
        float mean = 0.f, den = 1.f;
        {
            IDS();
            const uint32_t wh = pin((((ln & 7) + 48 * ((ln >> 3) & 1) + 8 * (ln >> 4)) * 160 + (wp < 7 ? 16 * wp : 128)) | ((384 * cc + b_pos<48>(n96)) << 16));
            const uint32_t pubD = pin(uPubD + (t4 & 1) * COL + 16 * (t4 & 2) + 4 * q8 + (fl & 1)), ha = xr + (S_HS - S_XB);
            auto down = [&](const uint32_t (&W)[3][4], const uint4& h0, const uint2& h1) {
                float a0[4] = {}, a1[4] = {}, a2[4] = {};
                mmaA(a0, W[0], h0.x, h0.y); mmaA(a1, W[1], h0.z, h0.w); mmaA(a2, W[2], h1.x, h1.y);
                return ((a0[0] + a0[3]) + (a1[0] + a1[3])) + (a2[0] + a2[3]);
            };
            if (wp < 6) {
                uint32_t Wd[3][4];
                auto ldd = [&](uint32_t z) {
#pragma unroll
                    for (int s = 0; s < 3; s++) ldsm4t(Wd[s], ((wh ^ z) & 0xffff) + (sb + S_WD + s * 2560));
                };
                ldd(0);
                if (actc) {
                    const char* srcv = xp(uPolC + lag<DELAY_C>(sb, z0_) + 8 * n96);
                    const uint2 cs = lds64(sb + S_CSGU + 8 * n96);
                    float gt, up;
                    int guard = 0;
                    while (true) {
                        uint2 v[8];
#pragma unroll
                        for (int s = 0; s < 8; s++) v[s] = ldp64(srcv + (s >> 2) * HALF + (s & 3) * 1024);
                        uint2 c = ldsvol64(sb + S_LN + 8 * cc + ((v[0].x ^ parc) & 1) * 32);
                        const bool stale = __any_sync(~0u, ((chk8(v, parc) | chk8y(v, parc)) & 1) != 0), late = __any_sync(~0u, (c.y & 7) != ch + 1);
                        const float pg = sum8x(v), pu = sum8y(v);
                        auto norm = [&] {
                            mean = bf_hi(c.x); den = bf_lo(c.x);
                            gt = bfr(fmaf(-mean, asf(cs.x), pg) * asf(c.y)); up = fmaf(-mean, asf(cs.y), pu) * asf(c.y);
                            keep(gt); keep(up);
                        };
                        norm();
                        if (!((stale | late) & (++guard < SPIN_LIMIT))) break;
                        if (!stale) { take_ln(c, sb + S_LN + 8 * cc); norm(); break; }
                    }
                    CSTAMP(13);
                    SWEEPS(5 * ch + 2, guard - 1);
                    const uint32_t h = pack2(bfr(gt * sigmoidf_(gt)) * bfr(up), 0.f);
                    sts16((wh >> 16) + (sb + S_HS), h);
                    CSTAMP(14);
                    if (ch == 3) CSTAMP(0);
                }
                bar_main();
                TST(4);
                CSTAMP(15);
                const uint4 h0 = lds128(ha);
                const uint2 h1 = lds64(ha + 16);
                stp32_if(!(td & 2), xp(pubD & ~1u), down(Wd, h0, h1), pubD & 1);
            } else {
                uint32_t v = 0;
                const uint32_t col = wp == 7 || !has0;
                const bool serve = wp == 6 || (has0 && has1);
                if (serve) {
                    const uint32_t par = col ? par1 : par0;
                    const char* src = xp(uPolC + col * COL + 776 + (td & 4) * (HALF / 4) + (td & 3) * 1024);
                    give_ln(uPolC + col * COL, par, sb + S_LN + 8 * col, td, mean, den, [&] { v = ldp32(src); return v ^ par; });
                }
                stsvol(sb + S_GATE, ch + 1);
                uint32_t Wd[2][3][4];
#pragma unroll
                for (int s = 0; s < 6; s++) ldsm4t(Wd[s / 3][s % 3], (wh & 0xffff) + (sb + S_WD + (s / 3) * 16 + (s % 3) * 2560));
                bar_main();
                const uint4 h0 = lds128(ha);
                const uint2 h1 = lds64(ha + 16);
                const float d0 = down(Wd[0], h0, h1), d1 = down(Wd[1], h0, h1);
                stp32_if(true, xp(pubD & ~1u), (td & 2) ? d1 : d0, pubD & 1);
                if (serve) {
                    float xw = asf(v);
                    xw += __shfl_xor_sync(~0u, xw, 1); xw += __shfl_xor_sync(~0u, xw, 2); xw += __shfl_xor_sync(~0u, xw, 4);
                    const float r = bfr(fmaf(-mean, ldsf(sb + S_SWR), xw) * rcp(den));
                    sts32(sb + S_STAT + 4 * col, __float_as_uint(bfr(sigmoidf_(r))) | (ch + 1));
                }
            }
        }
        CSTAMP(16);
        {
            IDS();
            const uint32_t pubE = pin(uPubE + (t4 < 3 ? (wp >> 2) * COL + 192 * (wp & 3) + 64 * t4 + 8 * q8 : (q8 >> 2) * COL + 768 + 4 * (q8 & 1)));
            xr = pin(sb + S_XB + 48 * (ln & 7));
            uint32_t x2 = 0;
            auto hop_d = [&](auto col) {
                const uint32_t xbs = pin(sb + S_XB + 384 * col.value + b_pos<40>(n80)), xas = col.value ? 0 : pin(sb + S_XA + 192 + a_pos(n80));
                const float x1 = bf_lo(lds16(xbs));
                const float lnx = __uint_as_float(pin(__float_as_uint(bfr(__fdiv_rn(bfr(x1 - mean), den)))));
                gather16(xp(uPolD + 4 * n80 + lag<DELAY_D>(sb, z0_)), col.value ? par1 : par0, 5 * ch + 3, [&](float y, uint32_t z) {
                    const uint32_t gate = ldsvol(sb + S_STAT + 4 * col.value + z);
                    x2 = pack2(x1 + bfr(lnx + bfr(bfr(y) * bf_hi(gate))), 0.f);
                    if (col.value) keep(x2); else { sts16(xbs, x2); sts16(xas, x2); }
                    return (uint32_t)((gate & 7) != ch + 1);
                });
                CSTAMP(17);
            };
            auto qproj = [&](auto with_stats) {
                bar_main();
                TST(5);
                CSTAMP(19);
                const uint32_t t4 = td & 3;
                const uint4 b = lds128(xr);
                uint32_t b4 = lds32(xr + 16);
                float acc[6][4] = {};
                if (with_stats.value) {
                    stp32_if((td & 11) == 3, xp(pubE), stats(xr + (S_XA - S_XB), b, b4), par0);
                    __syncwarp();
                    b4 = lds32(xr + 16);
                }
                mul80(acc, Wq, b, b4);
                const float v0 = sel4(t4, acc[0][0] + acc[0][3], acc[2][0] + acc[2][3], acc[4][0] + acc[4][3], acc[4][0] + acc[4][3]);
                const float v1 = sel4(t4, acc[1][0] + acc[1][3], acc[3][0] + acc[3][3], acc[5][0] + acc[5][3], acc[5][0] + acc[5][3]);
                stp64_if(t4 < 3, xp(pubE), tagw(v0, par0), tagw(v1, par0));
            };
            if (wp == 7) {
                if (!has0) break;
                qproj(std::true_type());
            } else {
                if (actc && !cc) hop_d(std::integral_constant<int, 0>());
                else {
                    if (actc && g == 0) {
                        const uint32_t po = pin(1280 * (ch - 1) + 160 * i + 2 * n80);
                        hop_d(std::integral_constant<int, 1>());
                        *reinterpret_cast<unsigned short*>(reinterpret_cast<char*>(P.out) + po) = (unsigned short)x2;
                    }
                    if (!has0) break;
                }
                qproj(std::false_type());
                sts32_if(td < 80, sb + S_XCAR + 4 * td, x2 << 16);
            }
        }
        CSTAMP(20);
        if (wp == 6) give_ln(uPolE, par0, sb + S_LN + 16, td, mean, den, [] { return 0u; });
        auto pass2 = [&](auto d0, auto d1, auto d2) {
            constexpr int D0 = d0.value, D1 = d1.value, D = D0 + D1 + d2.value;
            IDS();
            const uint32_t ua = sb + k_place(ch, wp & 6) * SLOT + (wp & 1) * UNIT, k0 = k_off(ln);
            uint32_t kf[12][2][4];
            auto ldk = [&](int s) { const uint32_t a = (k0 ^ (32 * (s / 3))) + (ua + 1024 * (s % 3)); ldsm4(kf[s][0], a); ldsm4(kf[s][1], a + SLOT); };
            auto ldv1 = [&](int k) { ldsm4t(vf[k / 3][k % 3], voff[k % 3] + (sb + v_place(ch, k / 3) * SLOT)); };
            auto ldv = [&](int s) { ldv1(3 * s); ldv1(3 * s + 1); ldv1(3 * s + 2); };
            constexpr uint32_t LATE = LAST_LATE;
            constexpr uint64_t EARLY_LIST = bit_list(~LATE), LATE_LIST = bit_list(LATE);
            auto early = [&](int k) {
                if (D1 == 0) ldk(k);
                else if (k < 3) { ldv1(9 + 2 * k); ldv1(10 + 2 * k); }
                else ldk((EARLY_LIST >> (4 * (k - 3))) & 15);
            };
            uint32_t v[8] = {}, qsa = 0;
            const char* srcv = xp(uPolE + lag<(D1 > 0 ? 0 : DELAY_E)>(sb, z0_) + 4 * td);
            auto look = [&] {
#pragma unroll
                for (int s = 0; s < 8; s++) v[s] = ldp32(srcv + (s >> 2) * HALF + (s & 3) * 1024);
            };
            if (D1 > 0) vaddr(voff);
            if (!(mbar_try(sb + S_FK + 8 * (wp & 6), par1) & mbar_try(sb + S_FK + 8 * (wp | 1), par1))) { mbar_wait(sb + S_FK + 8 * (wp & 6), par1); mbar_wait(sb + S_FK + 8 * (wp | 1), par1); }
#pragma unroll
            for (int s = 0; s < D0; s++) early(s);
            if (wp < 6) { look(); qsa = pin(sb + S_QS + 384 * ch + q_pos(z_)); }
#pragma unroll
            for (int s = D0; s < D0 + D1; s++) early(s);
            if (wp < 6) {
                const float cs = ldsf(sb + S_CSQ + 4 * td);
                int guard = 0;
                while (true) {
                    uint2 c = ldsvol64(sb + S_LN + 16 + ((v[0] ^ par0) & 1) * 32);
                    const bool stale = __any_sync(~0u, (chk8(v, par0) & 1) != 0), late = __any_sync(~0u, (c.y & 7) != ch + 1);
                    const float qs = sum8(v);
                    auto norm = [&] {
                        const uint32_t q = pack2(fmaf(-bf_hi(c.x), cs, qs) * asf(c.y), 0.f);
                        sts16(qsa, q);
                    };
                    norm();
                    if (!((stale | late) & (++guard < SPIN_LIMIT))) break;
                    if (!stale) { take_ln(c, sb + S_LN + 16); norm(); break; }
                    look();
                }
                SWEEPS(5 * ch + 4, guard - 1);
                CSTAMP(22);
            }
#pragma unroll
            for (int s = D0 + D1; s < D; s++) early(s);
            CSTAMP(21);
            bar_main();
            TST(6);
            CSTAMP(1);
            uint2 q = lds64(sb + S_QS + 384 * ch + 8 * ln);
            float acc[2][4] = {};
            constexpr int V0 = 13 - D, NV = D1 > 0 ? 2 : (2 * (D - 1)) / 3;
            static_assert(D1 == 0 || D - 3 + __builtin_popcount(LATE) == 12, "plan");
#pragma unroll
            for (int s = 0; s < 12; s++) {
                const bool m = q8 == (s & 7);
                const uint32_t b0 = m ? q.x : 0u, b1 = m ? q.y : 0u;
                if (s == 7) q = lds64(sb + S_QS + 384 * ch + 8 * ln + 256);
                mmaA(acc[0], kf[s][0], b0, b1);
                mmaA(acc[1], kf[s][1], b0, b1);
                if (D1 > 0) {
                    if (s >= 1 && s <= __builtin_popcount(LATE)) ldk((LATE_LIST >> (4 * (s - 1))) & 15);
                } else {
                    if (s >= 1 && s + D - 1 < 12) ldk(s + D - 1);
                    if (s >= 1 && s + D - 1 == 11) { __syncwarp(); arrive_if(ln == 0, sb + S_RELK); }
                    if (s == V0) vaddr(voff);
                    if (s >= V0 && 2 * (s - V0) < 3 * NV) ldv1(9 + 2 * (s - V0));
                    if (s >= V0 && 2 * (s - V0) + 1 < 3 * NV) ldv1(10 + 2 * (s - V0));
                }
            }
            CSTAMP(24);
            {
                const float v0 = acc[0][0] + acc[0][1], v1 = acc[0][2] + acc[0][3], v2 = acc[1][0] + acc[1][1], v3 = acc[1][2] + acc[1][3];
                const bool hi = t4 & 2, od = t4 & 1;
                const float u0 = (hi ? v2 : v0) + __shfl_xor_sync(~0u, hi ? v0 : v2, 2), u1 = (hi ? v3 : v1) + __shfl_xor_sync(~0u, hi ? v1 : v3, 2);
                const float s = (od ? u1 : u0) + __shfl_xor_sync(~0u, od ? u0 : u1, 1);
                CSTAMP(2);
                probs(scaled(s), sb + S_PS + PS_PASS, wp, ln);
                CSTAMP(3);
            }
            bar_main();
            TST(10);
            CSTAMP(4);
            if (D1 > 0) values(vf, acc_, [&](int s) { if (s < 3) ldv(s + 5); }, sb + S_PS + PS_PASS, std::integral_constant<int, 1>(), par0);
            else values(vf, acc_, [&](int s) { if (s >= (NV > 1 ? 2 : 1) && s + NV + (NV > 1 ? 1 : 2) < 8) ldv(s + NV + (NV > 1 ? 1 : 2)); }, sb + S_PS + PS_PASS, std::integral_constant<int, 1>(), par0);
            arrive_if(ln == 0, sb + S_RELV);
        };
        if (ch == 3) {
            pass2(std::integral_constant<int, LAST0>(), std::integral_constant<int, LAST1>(), std::integral_constant<int, LAST2>());
#pragma unroll
            for (int m = 0; m < 48; m++) Wq[m / 8].a[(m / 4) % 2][m % 4] = vf[3 + m / 12][(m / 4) % 3][m % 4];
#pragma unroll
            for (int m = 0; m < 12; m++) Wq[m / 2].c[m % 2] = vf[7][m / 4][m % 4];
#pragma unroll
            for (int m = 0; m < 36; m++) left[m] = m < 12 ? __float_as_uint(acc_[m / 4][m % 4]) : vf[m / 12][(m / 4) % 3][m % 4];
        } else {
            pass2(std::integral_constant<int, KPRE>(), std::integral_constant<int, 0>(), std::integral_constant<int, KPRE2>());
#pragma unroll
            for (int m = 0; m < 36; m++) left[m] = m < 12 ? __float_as_uint(acc_[m / 4][m % 4]) : vf[4 + m / 12][(m / 4) % 3][m % 4];
        }
        TST(11);
        CSTAMP(23);
    }
    sts32_if(td == 255, sb + S_GATE, 6);
    TSTAMP(3);
}

typedef CUresult (*EncodeFn)(CUtensorMap*, CUtensorMapDataType, cuuint32_t, void*, const cuuint64_t*, const cuuint64_t*, const cuuint32_t*,
                             const cuuint32_t*, CUtensorMapInterleave, CUtensorMapSwizzle, CUtensorMapL2promotion, CUtensorMapFloatOOBfill);

void make_map(EncodeFn enc, CUtensorMap* m, const void* base, uint64_t cols, uint64_t rows, uint32_t box_cols, uint32_t box_rows, bool swizzle) {
    cuuint64_t dims[2] = {cols, rows};
    cuuint64_t strides[1] = {cols * 2};
    cuuint32_t box[2] = {box_cols, box_rows};
    cuuint32_t es[2] = {1, 1};
    enc(m, CU_TENSOR_MAP_DATA_TYPE_BFLOAT16, 2, const_cast<void*>(base), dims, strides, box, es, CU_TENSOR_MAP_INTERLEAVE_NONE,
        swizzle ? CU_TENSOR_MAP_SWIZZLE_128B : CU_TENSOR_MAP_SWIZZLE_NONE, CU_TENSOR_MAP_L2_PROMOTION_NONE, CU_TENSOR_MAP_FLOAT_OOB_FILL_NONE);
}

}

extern "C" void kernel_launch(void* const* d_in, const int* in_sizes, int n_in, void* d_out, int out_size) {
    (void)in_sizes; (void)n_in; (void)out_size;
    static EncodeFn enc = nullptr;
    if (!enc) {
        void* f = nullptr;
        cudaDriverEntryPointQueryResult q;
        cudaGetDriverEntryPoint("cuTensorMapEncodeTiled", &f, cudaEnableDefault, &q);
        enc = (EncodeFn)f;
        cudaFuncSetAttribute(fused_kernel, cudaFuncAttributeMaxDynamicSharedMemorySize, SMEM_BYTES);
    }
    Params P;
    P.x = (const __nv_bfloat16*)d_in[0]; P.k = (const __nv_bfloat16*)d_in[1]; P.v = (const __nv_bfloat16*)d_in[2];
    P.wr = (const __nv_bfloat16*)d_in[6];
    P.out = (__nv_bfloat16*)d_out;
    Maps M;
    {
        cuuint64_t dims[4] = {64, 8, 3, (cuuint64_t)KV_BATCH_KEYS / 2}, strides[3] = {384, 128, 3072};
        cuuint32_t box[4] = {64, 8, 3, 2}, es[4] = {1, 1, 1, 1};
        enc(&M.k, CU_TENSOR_MAP_DATA_TYPE_BFLOAT16, 4, d_in[1], dims, strides, box, es, CU_TENSOR_MAP_INTERLEAVE_NONE, CU_TENSOR_MAP_SWIZZLE_128B,
            CU_TENSOR_MAP_L2_PROMOTION_NONE, CU_TENSOR_MAP_FLOAT_OOB_FILL_NONE);
    }
    make_map(enc, &M.v, P.v, 64, (uint64_t)12 * KV_BATCH_KEYS, 64, 96, true);
    make_map(enc, &M.vu, P.v, 64, (uint64_t)12 * KV_BATCH_KEYS, 64, 48, true);
    make_map(enc, &M.wq, d_in[3], 6144, 640, 192, 40, false);
    make_map(enc, &M.wo, d_in[4], 640, 6144, 80, 96, false);
    make_map(enc, &M.wg, d_in[7], 1536, 640, 96, 80, false);
    make_map(enc, &M.wu, d_in[8], 1536, 640, 96, 80, false);
    make_map(enc, &M.wd, d_in[9], 640, 1536, 80, 96, false);
    fused_kernel<<<NCTA, NTHR, SMEM_BYTES, cudaStreamPerThread>>>(P, M);
}
```

```cpp
#include <cuda_runtime.h>
#include <cuda.h>
#include <cuda_bf16.h>
#include <stdint.h>
#include <type_traits>

namespace {

constexpr int NCTA = 128;
constexpr int NTHR = 384;
constexpr int UNIT = 6144;
constexpr int SLOT = 12288;
#define TAU 3940
#define TAUW 3720
#define TAU0 3820
#define ILV 4
#define XB 600
#define PROBE 352
#define TMIN 2400
#define SLACK 6000
#define SLACK0 1000
#define PF0 1
#define WIN_W 3
#define WIN_S 4
#define WIN_U 10
#define VPF 4
#define KRE_TAU 2600
#define RFR_TAU 22400
#define HOP1_NS 200
#define KPRE 2
#define KPRE2 2
#define LAST0 4
#define LAST1 4
#define LAST2 2
#define LAST_LATE 0xaa8
#define FSTEP 4
#define DELAY_L 2
#define DELAY_G 2
#define DELAY_C 3
#define DELAY_D 0
#define DELAY_E 1
#define REG_LO "40"
#define REG_HI "232"
#define SPIN_LOG 17
constexpr int SPIN_LIMIT = 1 << SPIN_LOG;

__host__ __device__ constexpr uint32_t pairL(uint32_t region, uint32_t c, uint32_t g) { return (g & 1) | ((g >> 1) << 2) | (c << 5) | (region << 6); }
__host__ __device__ constexpr uint32_t pairG(uint32_t d, uint32_t c, uint32_t i) { return (i & 1) | ((i >> 1) << 2) | (d << 4) | (c << 5) | (3u << 6); }
constexpr uint32_t RA = 0, RC = 1, RE = 2, HALF = 16384, COPY = 4096, PMASK = 0x59;
constexpr uint32_t XS = 0;
constexpr uint32_t XS2 = XS + 128 * 7680;
constexpr uint32_t XSEND = XS2 + 128 * 768;
__device__ uint4 g_s[XSEND / 16];
__device__ uint4 g_x[(4u << 20) / 16];
#define SWEEPS(k, n) do {} while (0)

constexpr uint32_t S_WD = 16 * SLOT;
constexpr uint32_t S_DUMMY = S_WD + 15360;
constexpr uint32_t S_BAR = S_DUMMY + 4096;
constexpr uint32_t S_FV = S_BAR, S_FK = S_FV + 64, S_RING = S_FK + 64, S_DBAR = S_RING + 48, S_WFULL = S_DBAR + 32, S_QRDY = S_WFULL + 88;
constexpr uint32_t S_RELK = S_QRDY + 8, S_RELV = S_RELK + 8, S_RELR = S_RELV + 8, S_RELW = S_RELR + 8, S_SCO = S_RELW + 24;
constexpr uint32_t S_OS1 = S_SCO + 8;
constexpr uint32_t S_ZERO = S_OS1 + 8;
constexpr uint32_t S_KF = S_ZERO + 8;
constexpr uint32_t S_TOK = S_KF + 8;
constexpr uint32_t S_SIDE = S_TOK + 80, S_GATE = S_SIDE + 4;
constexpr uint32_t S_STAT = S_GATE + 12, S_SWR = S_STAT + 16;
constexpr uint32_t S_LN = S_STAT + 32;
constexpr uint32_t S_XCAR = S_LN + 64;
constexpr uint32_t S_CSQ = S_XCAR + 320;
constexpr uint32_t S_CSGU = S_CSQ + 768;
constexpr uint32_t S_RED = S_CSGU + 768;
constexpr uint32_t S_L0 = S_RED;
constexpr uint32_t S_OS = S_RED + 5120;
constexpr uint32_t S_PS = S_OS + 1536;
constexpr uint32_t PS_MAX = 512, PS_PASS = 544;
constexpr uint32_t S_QS = S_PS + 2 * PS_PASS;
constexpr uint32_t S_XB = S_QS + 1536;
constexpr uint32_t S_XA = S_XB + 768;
constexpr uint32_t S_HS = S_XA + 768;
constexpr uint32_t S_X0 = S_HS + 768;
constexpr uint32_t S_SC = S_X0 + 640;
constexpr uint32_t S_TM = S_SC + 512;
constexpr int SMEM_BYTES = S_TM + 256;
static_assert(SMEM_BYTES <= 232448 && S_STAT % 16 == 0 && S_RED % 16 == 0 && S_XB % 16 == 0 && S_HS % 16 == 0 && S_PS % 16 == 0 && S_QS % 16 == 0, "smem");
static_assert(S_SCO == S_BAR + 44 * 8 && S_RELK == S_BAR + 38 * 8, "barriers");
constexpr uint32_t ST_WQ = 3 * SLOT, ST_WG = 8 * SLOT, ST_WO = 11 * SLOT;

__device__ __forceinline__ uint32_t smem_u32(const void* p) { return (uint32_t)__cvta_generic_to_shared(p); }
__device__ __forceinline__ void mbar_arrive(uint32_t bar) { asm volatile("mbarrier.arrive.shared::cta.b64 _, [%0];" :: "r"(bar) : "memory"); }
__device__ __forceinline__ bool mbar_try(uint32_t bar, uint32_t parity) {
    uint32_t ok;
    asm volatile("{\n .reg .pred p;\n mbarrier.try_wait.parity.shared::cta.b64 p, [%1], %2;\n selp.u32 %0, 1, 0, p;\n}" : "=r"(ok) : "r"(bar), "r"(parity) : "memory");
    return ok != 0;
}
__device__ __forceinline__ bool mbar_test(uint32_t bar, uint32_t parity) {
    uint32_t ok;
    asm volatile("{\n .reg .pred p;\n mbarrier.test_wait.parity.shared::cta.b64 p, [%1], %2;\n selp.u32 %0, 1, 0, p;\n}" : "=r"(ok) : "r"(bar), "r"(parity) : "memory");
    return ok != 0;
}
__device__ __forceinline__ void mbar_wait(uint32_t bar, uint32_t parity) {
    int n = 0;
    while (!mbar_try(bar, parity) && ++n < SPIN_LIMIT) {}
}
__device__ __forceinline__ uint32_t gtime32() { uint32_t t; asm volatile("mov.u32 %0, %globaltimer_lo;" : "=r"(t)); return t; }
__device__ __forceinline__ void bar_main() { asm volatile("bar.sync 1, 256;" ::: "memory"); }

__device__ __forceinline__ void mma16816(float (&c)[4], uint32_t a0, uint32_t a1, uint32_t a2, uint32_t a3, uint32_t b0, uint32_t b1) {
    asm("mma.sync.aligned.m16n8k16.row.col.f32.bf16.bf16.f32 {%0,%1,%2,%3}, {%4,%5,%6,%7}, {%8,%9}, {%0,%1,%2,%3};"
        : "+f"(c[0]), "+f"(c[1]), "+f"(c[2]), "+f"(c[3]) : "r"(a0), "r"(a1), "r"(a2), "r"(a3), "r"(b0), "r"(b1));
}
__device__ __forceinline__ void mmaA(float (&c)[4], const uint32_t (&a)[4], uint32_t b0, uint32_t b1) { mma16816(c, a[0], a[1], a[2], a[3], b0, b1); }
__device__ __forceinline__ void mma8(float (&c)[4], uint32_t a0, uint32_t a1, uint32_t b0) {
    asm("mma.sync.aligned.m16n8k8.row.col.f32.bf16.bf16.f32 {%0,%1,%2,%3}, {%4,%5}, {%6}, {%0,%1,%2,%3};"
        : "+f"(c[0]), "+f"(c[1]), "+f"(c[2]), "+f"(c[3]) : "r"(a0), "r"(a1), "r"(b0));
}
struct W80 { uint32_t a[2][4], c[2]; };
template <int N> __device__ __forceinline__ void mul80(float (&acc)[N][4], const W80 (&W)[N], const uint4& b, uint32_t b4) {
#pragma unroll
    for (int m = 0; m < N; m++) mmaA(acc[m], W[m].a[0], b.x, b.y);
#pragma unroll
    for (int m = 0; m < N; m++) mmaA(acc[m], W[m].a[1], b.z, b.w);
#pragma unroll
    for (int m = 0; m < N; m++) mma8(acc[m], W[m].c[0], W[m].c[1], b4);
}
__device__ __forceinline__ void ldsm2t(uint32_t (&r)[2], uint32_t addr) {
    asm volatile("ldmatrix.sync.aligned.m8n8.x2.trans.shared.b16 {%0,%1}, [%2];" : "=r"(r[0]), "=r"(r[1]) : "r"(addr) : "memory");
}
__device__ __forceinline__ void mmaV(float (&c)[4], const uint4& a, uint32_t b0, uint32_t b1) { mma16816(c, a.x, a.y, a.z, a.w, b0, b1); }
__device__ __forceinline__ void ldsm4(uint32_t (&r)[4], uint32_t addr) {
    asm volatile("ldmatrix.sync.aligned.m8n8.x4.shared.b16 {%0,%1,%2,%3}, [%4];" : "=r"(r[0]), "=r"(r[1]), "=r"(r[2]), "=r"(r[3]) : "r"(addr) : "memory");
}
__device__ __forceinline__ void ldsm4t(uint32_t (&r)[4], uint32_t addr) {
    asm volatile("ldmatrix.sync.aligned.m8n8.x4.trans.shared.b16 {%0,%1,%2,%3}, [%4];" : "=r"(r[0]), "=r"(r[1]), "=r"(r[2]), "=r"(r[3]) : "r"(addr) : "memory");
}
__device__ __forceinline__ uint32_t lds16(uint32_t a) { uint16_t v; asm volatile("ld.shared.u16 %0, [%1];" : "=h"(v) : "r"(a) : "memory"); return v; }
__device__ __forceinline__ uint32_t lds32(uint32_t a) { uint32_t v; asm volatile("ld.shared.u32 %0, [%1];" : "=r"(v) : "r"(a) : "memory"); return v; }
__device__ __forceinline__ float ldsf(uint32_t a) { return __uint_as_float(lds32(a)); }
__device__ __forceinline__ uint2 lds64(uint32_t a) { uint2 v; asm volatile("ld.shared.v2.u32 {%0,%1}, [%2];" : "=r"(v.x), "=r"(v.y) : "r"(a) : "memory"); return v; }
__device__ __forceinline__ uint4 lds128(uint32_t a) { uint4 v; asm volatile("ld.shared.v4.u32 {%0,%1,%2,%3}, [%4];" : "=r"(v.x), "=r"(v.y), "=r"(v.z), "=r"(v.w) : "r"(a) : "memory"); return v; }
__device__ __forceinline__ int ldsvol(uint32_t a) { int v; asm volatile("ld.volatile.shared.u32 %0, [%1];" : "=r"(v) : "r"(a) : "memory"); return v; }
__device__ __forceinline__ uint2 ldsvol64(uint32_t a) { uint2 v; asm volatile("{\n .reg .b64 d;\n ld.volatile.shared.b64 d, [%2];\n mov.b64 {%0,%1}, d;\n}" : "=r"(v.x), "=r"(v.y) : "r"(a) : "memory"); return v; }
__device__ __forceinline__ void stsvol64(uint32_t a, uint32_t x, uint32_t y) { asm volatile("{\n .reg .b64 d;\n mov.b64 d, {%1,%2};\n st.volatile.shared.b64 [%0], d;\n}" :: "r"(a), "r"(x), "r"(y) : "memory"); }
__device__ __forceinline__ void stsvol(uint32_t a, int v) { asm volatile("st.volatile.shared.u32 [%0], %1;" :: "r"(a), "r"(v) : "memory"); }
__device__ __forceinline__ void sts_hi16(uint32_t a, float v) { asm volatile("{\n .reg .b16 lo, hi;\n mov.b32 {lo, hi}, %1;\n st.shared.u16 [%0], hi;\n}" :: "r"(a), "r"(__float_as_uint(v)) : "memory"); }
__device__ __forceinline__ void sts16(uint32_t a, uint32_t v) { asm volatile("st.shared.u16 [%0], %1;" :: "r"(a), "r"(v) : "memory"); }
__device__ __forceinline__ void sts32(uint32_t a, uint32_t v) { asm volatile("st.shared.u32 [%0], %1;" :: "r"(a), "r"(v) : "memory"); }
__device__ __forceinline__ void stsf(uint32_t a, float v) { sts32(a, __float_as_uint(v)); }
__device__ __forceinline__ void sts64(uint32_t a, uint32_t x, uint32_t y) { asm volatile("st.shared.v2.u32 [%0], {%1,%2};" :: "r"(a), "r"(x), "r"(y) : "memory"); }

__device__ __forceinline__ void sts32_if(bool p, uint32_t a, uint32_t v) {
    asm volatile("{\n .reg .pred p;\n setp.ne.u32 p, %2, 0;\n @p st.shared.u32 [%0], %1;\n}" :: "r"(a), "r"(v), "r"((uint32_t)p) : "memory");
}
__device__ __forceinline__ void arrive_if(bool p, uint32_t bar) {
    asm volatile("{\n .reg .pred p;\n setp.ne.u32 p, %1, 0;\n @p mbarrier.arrive.shared::cta.b64 _, [%0];\n}" :: "r"(bar), "r"((uint32_t)p) : "memory");
}
__device__ __forceinline__ void keep(uint32_t& v) { asm volatile("" : "+r"(v)); }
__device__ __forceinline__ void keep(float& v) { asm volatile("" : "+f"(v)); }

__device__ __forceinline__ uint32_t ldp32(const char* p) { uint32_t v; asm volatile("ld.relaxed.gpu.global.u32 %0, [%1];" : "=r"(v) : "l"(p) : "memory"); return v; }
__device__ __forceinline__ uint2 ldp64(const char* p) {
    uint2 v; asm volatile("{\n .reg .b64 d;\n ld.relaxed.gpu.global.b64 d, [%2];\n mov.b64 {%0,%1}, d;\n}" : "=r"(v.x), "=r"(v.y) : "l"(p) : "memory"); return v;
}
__device__ __forceinline__ uint32_t tagw(float f, uint32_t par) { return (__float_as_uint(f) & ~1u) | par; }
__device__ __forceinline__ void stp32(char* p, float a, uint32_t par) { asm volatile("st.relaxed.gpu.global.u32 [%0], %1;" :: "l"(p), "r"(tagw(a, par)) : "memory"); }
__device__ __forceinline__ void stp64(char* p, float a, float b, uint32_t par) {
    asm volatile("{\n .reg .b64 d;\n mov.b64 d, {%1,%2};\n st.relaxed.gpu.global.b64 [%0], d;\n}" :: "l"(p), "r"(tagw(a, par)), "r"(tagw(b, par)) : "memory");
}
__device__ __forceinline__ void stp32_if(bool p, char* d, float a, uint32_t par) {
    asm volatile("{\n .reg .pred p;\n setp.ne.u32 p, %2, 0;\n @p st.relaxed.gpu.global.u32 [%0], %1;\n @p st.relaxed.gpu.global.u32 [%0+4096], %1;\n}" :: "l"(d), "r"(tagw(a, par)), "r"((uint32_t)p) : "memory");
}
__device__ __forceinline__ void stp64_if(bool p, char* d, uint32_t lo, uint32_t hi) {
    asm volatile("{\n .reg .pred p;\n .reg .b64 d;\n setp.ne.u32 p, %3, 0;\n mov.b64 d, {%1,%2};\n @p st.relaxed.gpu.global.b64 [%0], d;\n @p st.relaxed.gpu.global.b64 [%0+4096], d;\n}" :: "l"(d), "r"(lo), "r"(hi), "r"((uint32_t)p) : "memory");
}
__device__ __forceinline__ uint32_t chk2(uint32_t a, uint32_t b, uint32_t par) { uint32_t r; asm("lop3.b32 %0, %1, %2, %3, 0x7E;" : "=r"(r) : "r"(a), "r"(b), "r"(par)); return r; }
__device__ __forceinline__ uint32_t or3(uint32_t a, uint32_t b, uint32_t c) { uint32_t r; asm("lop3.b32 %0, %1, %2, %3, 0xFE;" : "=r"(r) : "r"(a), "r"(b), "r"(c)); return r; }
__device__ __forceinline__ uint32_t chk8(const uint32_t (&v)[8], uint32_t par) { return or3(chk2(v[0], v[1], par), chk2(v[2], v[3], par), or3(chk2(v[4], v[5], par), chk2(v[6], v[7], par), 0)); }
__device__ __forceinline__ uint32_t chk8(const uint2 (&v)[8], uint32_t par) { return or3(chk2(v[0].x, v[1].x, par), chk2(v[2].x, v[3].x, par), or3(chk2(v[4].x, v[5].x, par), chk2(v[6].x, v[7].x, par), 0)); }
__device__ __forceinline__ uint32_t chk8y(const uint2 (&v)[8], uint32_t par) { return or3(chk2(v[0].y, v[1].y, par), chk2(v[2].y, v[3].y, par), or3(chk2(v[4].y, v[5].y, par), chk2(v[6].y, v[7].y, par), 0)); }
__device__ __forceinline__ uint32_t chk4(const uint2 (&v)[4], uint32_t par) { return or3(chk2(v[0].x, v[0].y, par), chk2(v[1].x, v[1].y, par), or3(chk2(v[2].x, v[2].y, par), chk2(v[3].x, v[3].y, par), 0)); }
__device__ __forceinline__ float asf(uint32_t v) { return __uint_as_float(v); }
__device__ __forceinline__ float sum8(const uint32_t (&v)[8]) { return ((asf(v[0]) + asf(v[1])) + (asf(v[2]) + asf(v[3]))) + ((asf(v[4]) + asf(v[5])) + (asf(v[6]) + asf(v[7]))); }
__device__ __forceinline__ float sum8x(const uint2 (&v)[8]) { return ((asf(v[0].x) + asf(v[1].x)) + (asf(v[2].x) + asf(v[3].x))) + ((asf(v[4].x) + asf(v[5].x)) + (asf(v[6].x) + asf(v[7].x))); }
__device__ __forceinline__ float sum8y(const uint2 (&v)[8]) { return ((asf(v[0].y) + asf(v[1].y)) + (asf(v[2].y) + asf(v[3].y))) + ((asf(v[4].y) + asf(v[5].y)) + (asf(v[6].y) + asf(v[7].y))); }

__device__ __forceinline__ uint32_t pack2(float lo, float hi) { uint32_t r; asm("cvt.rn.bf16x2.f32 %0, %1, %2;" : "=r"(r) : "f"(hi), "f"(lo)); return r; }
__device__ __forceinline__ float bfr(float x) { return __uint_as_float(pack2(0.0f, x)); }
__device__ __forceinline__ float ex2(float x) { float r; asm("ex2.approx.ftz.f32 %0, %1;" : "=f"(r) : "f"(x)); return r; }
__device__ __forceinline__ float rcp(float x) { float r; asm("rcp.approx.ftz.f32 %0, %1;" : "=f"(r) : "f"(x)); return r; }
__device__ __forceinline__ float sqrt_(float x) { float r; asm("sqrt.approx.ftz.f32 %0, %1;" : "=f"(r) : "f"(x)); return r; }
__device__ __forceinline__ float bf_lo(uint32_t v) { return __uint_as_float(v << 16); }
__device__ __forceinline__ float bf_hi(uint32_t v) { return __uint_as_float(v & 0xffff0000u); }
__device__ __forceinline__ float sel4(int k, float a, float b, float c, float d) { return (k & 2) ? ((k & 1) ? d : c) : ((k & 1) ? b : a); }
constexpr float LOG2E = 1.4426950408889634f;
constexpr uint32_t ONES = 0x3f803f80u;

__device__ __forceinline__ void ln_stats(float sum, float sq, float& mean, float& den) {
    const float m = sum * (1.0f / 640.0f);
    const float var = fmaxf(fmaf(sq, 1.0f / 640.0f, -m * m), 0.0f);
    mean = bfr(m);
    den = bfr(sqrt_(bfr(bfr(var) + 1e-5f)));
}
__device__ __forceinline__ float sigmoidf_(float x) { return rcp(1.0f + ex2(-x * LOG2E)); }

#define TSTAMP(k) do {} while (0)
#define TST(k) do {} while (0)

#define CSTAMP(k) do {} while (0)
template <int N> __device__ __forceinline__ uint32_t lag(uint32_t sb, uint32_t z = 0) {
#pragma unroll
    for (int k = 0; k < N; k++) z = ldsvol(sb + S_ZERO + z);
    return z;
}
__device__ __forceinline__ void warm_mma(uint32_t& a, uint32_t& b) {
    asm volatile("mma.sync.aligned.m16n8k8.row.col.f16.f16.f16.f16 {%0,%1}, {%0,%1}, {%0}, {%0,%1};" : "+r"(a), "+r"(b) :: "memory");
}
#define KWNS2 20
#define KWNS 200
template <int STRIDE>
__device__ __forceinline__ float gather8(const char* p, uint32_t par) {
    uint32_t v[8];
    int guard = 0;
    do {
#pragma unroll
        for (int s = 0; s < 8; s++) v[s] = ldp32(p + s * STRIDE);
    } while ((chk8(v, par) & 1) && ++guard < SPIN_LIMIT);
    return sum8(v);
}
template <class F>
__device__ __forceinline__ void gather16(const char* p, uint32_t par, int k, F use) {
    uint32_t v[8], u[8];
    int guard = 0;
    bool again;
    do {
#pragma unroll
        for (int s = 0; s < 8; s++) v[s] = ldp32(p + s * 512);
#pragma unroll
        for (int s = 0; s < 8; s++) u[s] = ldp32(p + HALF + s * 512);
        const uint32_t stale = use(sum8(v) + sum8(u), ((v[0] ^ par) & 1) * 8);
        again = __any_sync(~0u, (or3(chk8(v, par), chk8(u, par), stale) & 1) != 0);
    } while (again & (++guard < SPIN_LIMIT));
    SWEEPS(k, guard - 1);
}

struct Params {
    const __nv_bfloat16 *x, *k, *v, *wr;
    __nv_bfloat16* out;
};
struct Maps { CUtensorMap k, v, vu, wq, wo, wg, wu, wd; };

constexpr int KV_BATCH_KEYS = 32 * 4096;

__device__ __forceinline__ void tma2d(uint32_t dst, const CUtensorMap* m, int c0, int c1, uint32_t bar, uint32_t bytes, uint64_t pol) {
    asm volatile("{\n .reg .pred p;\n elect.sync _|p, 0xffffffff;\n"
                 " @p mbarrier.arrive.expect_tx.shared::cta.b64 _, [%2], %6;\n"
                 " @p cp.async.bulk.tensor.2d.shared::cluster.global.mbarrier::complete_tx::bytes.L2::cache_hint [%0], [%1, {%3, %4}], [%2], %5;\n}"
                 :: "r"(dst), "l"(m), "r"(bar), "r"(c0), "r"(c1), "l"(pol), "r"(bytes) : "memory");
}
__device__ __forceinline__ void scrap_copy(uint32_t dst, const char* src, uint32_t bar) {
    asm volatile("{\n .reg .pred p;\n elect.sync _|p, 0xffffffff;\n"
                 " @p mbarrier.arrive.expect_tx.shared::cta.b64 _, [%2], 12288;\n"
                 " @p cp.async.bulk.shared::cluster.global.mbarrier::complete_tx::bytes [%0], [%1], 4096, [%2];\n"
                 " @p cp.async.bulk.shared::cluster.global.mbarrier::complete_tx::bytes [%0], [%1+4096], 4096, [%2];\n"
                 " @p cp.async.bulk.shared::cluster.global.mbarrier::complete_tx::bytes [%0], [%1+8192], 4096, [%2];\n}"
                 :: "r"(dst), "l"(src), "r"(bar) : "memory");
}
__device__ __forceinline__ void prefetch_l2(const void* p, uint32_t bytes) {
    asm volatile("{\n .reg .pred p;\n elect.sync _|p, 0xffffffff;\n @p cp.async.bulk.prefetch.L2.global [%0], %1;\n}" :: "l"(p), "r"(bytes) : "memory");
}
__device__ __forceinline__ uint64_t pol_first() { uint64_t p; asm("createpolicy.fractional.L2::evict_first.b64 %0, 1.0;" : "=l"(p)); return p; }
__device__ __forceinline__ uint64_t pol_normal() { uint64_t p; asm("createpolicy.fractional.L2::evict_normal.b64 %0, 1.0;" : "=l"(p)); return p; }
__device__ __forceinline__ bool utest(uint32_t bar, uint32_t parity) { return __all_sync(~0u, mbar_test(bar, parity)); }
__device__ __forceinline__ void uwait(uint32_t bar, uint32_t parity) {
    int n = 0;
    while (!__all_sync(~0u, mbar_try(bar, parity)) && ++n < SPIN_LIMIT) {}
}
template <int A, int B, int CNT> __device__ __forceinline__ void init_bars(uint32_t sb) {
#pragma unroll 1
    for (int k = A; k < B; k++)
        asm volatile("{\n .reg .pred p;\n elect.sync _|p, 0xffffffff;\n @p mbarrier.init.shared::cta.b64 [%0], %1;\n}" :: "r"(sb + S_BAR + 8 * k), "n"(CNT) : "memory");
}
__device__ __forceinline__ int unit_key(uint32_t b, uint32_t u) {
    return (blockIdx.x >> 2) * 4096 + 3072 + (blockIdx.x & 3) * (16 * ILV) + b * KV_BATCH_KEYS + (u & ~(ILV - 1u)) * 64 + (u & (ILV - 1)) * 16;
}
__device__ __forceinline__ void load_tile(const CUtensorMap* m, uint32_t dst, uint32_t bar, uint32_t bytes, int key, uint64_t pol) { tma2d(dst, m, 0, 3 * key, bar, bytes, pol); }
__device__ __forceinline__ const char* unit_ptr(const Params& P, int n) { return (const char*)((n & 16) ? P.v : P.k) + (size_t)unit_key(n >> 5, n & 15) * 384; }
#define LSTAMP(k) do {} while (0)

__device__ __forceinline__ uint32_t k_place(uint32_t b, uint32_t s) { return s + 3 + 5 * (b & 1); }
__device__ __forceinline__ uint32_t v_place(uint32_t b, uint32_t s) { return s < 3 ? s : s + 8 - 8 * (b & 1); }
__device__ __forceinline__ void k_load(const Maps& M, uint32_t dst, uint32_t bar, int key8, uint64_t pol) {
    asm volatile("{\n .reg .pred p;\n elect.sync _|p, 0xffffffff;\n"
                 " @p mbarrier.arrive.expect_tx.shared::cta.b64 _, [%2], 6144;\n"
                 " @p cp.async.bulk.tensor.4d.shared::cluster.global.mbarrier::complete_tx::bytes.L2::cache_hint [%0], [%1, {0, 0, 0, %3}], [%2], %4;\n}"
                 :: "r"(dst), "l"(&M.k), "r"(bar), "r"(key8), "l"(pol) : "memory");
}
__device__ __forceinline__ int unit_key8(uint32_t n) { return unit_key(n >> 4, n & 15) >> 3; }
__device__ __forceinline__ void ring_load(const Maps& M, uint32_t sb, uint32_t b, uint32_t u, uint32_t pos) {
    if (u < 16) k_load(M, sb + pos * UNIT, sb + S_RING + 8 * pos, unit_key8(16 * b + u), pol_normal());
    else load_tile(&M.vu, sb + pos * UNIT, sb + S_FV + 4 * (pos & 6), UNIT, unit_key(b, pos), pol_first());
}
__device__ __forceinline__ uint32_t token(bool p, uint32_t a, uint32_t n) {
    uint32_t v;
    asm volatile("{\n .reg .pred p;\n setp.ne.u32 p, %2, 0;\n mov.u32 %0, 0;\n @p atom.shared.exch.b32 %0, [%1], %3;\n}" : "=r"(v) : "r"(a), "r"((uint32_t)p), "r"(n) : "memory");
    return v;
}
__device__ __forceinline__ void place_load(const Maps& M, uint32_t sb, uint32_t n) {
    k_load(M, sb + k_place(n >> 4, 0) * SLOT + (n & 15) * UNIT, sb + S_FK + 4 * (n & 14), unit_key8(n), pol_first());
}
__device__ __forceinline__ void v_load(const Maps& M, uint32_t sb, uint32_t b, uint32_t s) {
    load_tile(&M.v, sb + v_place(b, s) * SLOT, sb + S_FV + 8 * s, SLOT, unit_key(b, 2 * s), pol_first());
}

__device__ __forceinline__ void stream_warp(const Params& P, const Maps& M, uint32_t sb, uint32_t lane) {
    const uint64_t pol = pol_first();
    const int bid = blockIdx.x, g = bid >> 3, i = bid & 7;
    const uint32_t wf = sb + S_WFULL;
    uint32_t tn = __shfl_sync(~0u, gtime32(), 0) * 16;
    auto pace = [&](uint32_t dt) {
        int k = 0;
        uint32_t now;
        do now = __shfl_sync(~0u, gtime32(), 0) * 16; while ((int)(now - tn) < 0 && ++k < SPIN_LIMIT);
        if ((int)(now - tn) > SLACK0) tn = now - SLACK0;
        tn += dt;
    };
#pragma unroll
    for (int k = 0; k < 10; k++) {
        if (k < 2) {
            if (k == 0) init_bars<26, 27, 1>(sb); else init_bars<27, 37, 1>(sb);
            asm volatile("fence.mbarrier_init.release.cluster;" ::: "memory");
            if (k == 1) { asm volatile("bar.arrive 2, %0;" :: "n"(NTHR) : "memory"); asm volatile("bar.sync 3, 128;" ::: "memory"); }
        }
        if (k >= WIN_W) uwait(wf + 8 * (k - WIN_W), 0);
        pace(TAUW * 5 / 2);
        if (k < 4) tma2d(sb + ST_WQ + 15360 * k, &M.wq, 384 * g + 192 * (k >> 1), 80 * i + 40 * (k & 1), wf + 8 * k, 15360, pol);
        else if (k < 6) tma2d(sb + ST_WG + 15360 * (k - 4), k == 4 ? &M.wg : &M.wu, 96 * g, 80 * i, wf + 8 * k, 15360, pol);
        else tma2d(sb + ST_WO + 15360 * (k - 6), &M.wo, 80 * i, 384 * g + 96 * (k - 6), wf + 8 * k, 15360, pol);
    }
#pragma unroll 1
    for (int n = 0; n < 16; n++) {
        if (n == 0 || n == 5 || n == 11) uwait(sb + S_RELW + (n == 0 ? 0 : n == 5 ? 8 : 16), 0);
        uwait(n < WIN_S ? wf + 8 * (10 - WIN_S + n) : sb + S_FV + 8 * ((n - WIN_S) ^ 8), 0);
        pace(max(min(2 * n + 2 - PF0, 2), 0) * TAU0);
        if (n >= WIN_S && !utest(sb + S_FV + 8 * ((n - WIN_S + 1) ^ 8), 0)) tn += XB;
        if (n < 8) { place_load(M, sb, 2 * n); place_load(M, sb, 2 * n + 1); }
        else if (n < 11) { ring_load(M, sb, 0, 2 * n, 2 * n - 16); ring_load(M, sb, 0, 2 * n + 1, 2 * n - 15); }
        else v_load(M, sb, 0, n - 8);
        if (n == 7) { pace(TAUW * 5 / 2); tma2d(sb + S_WD, &M.wd, 80 * i, 96 * g, wf + 80, 15360, pol); }
    }
    int nd = 0;
    uint32_t q[4];
#pragma unroll
    for (int r = 0; r < 4; r++) q[r] = sb + S_FV + 8 * (7 - r);
    uint32_t td = tn;
    uint32_t pos = 2;
#pragma unroll 1
    for (int m = 16; m < 64; m++) {
        const int b = m >> 4, j = m & 15;
        const char* src = unit_ptr(P, 2 * m);
        const uint32_t tok = sb + S_TOK + (j < 3 ? 4 * pos : j < 11 ? 24 + 4 * pos : 16 + 4 * j) + 4 * lane;
        static_assert(WIN_U <= 12, "a ring position has at most one token of the timetable");
        int k = 0;
        while (true) {
            const uint2 c = lds64(sb + S_KF);
            if (__all_sync(~0u, mbar_test(q[WIN_S - 1] & ~1u, q[WIN_S - 1] & 1) & (min((int)c.x + 1, (int)c.y) >= 16 * b + min(2 * j + 2 - WIN_U, 16))) || ++k >= SPIN_LIMIT) break;
        }
        uint32_t now;
        while (true) {
            now = __shfl_sync(~0u, gtime32(), 0) * 16;
            if ((int)(now - td) >= 0 || ++k >= SPIN_LIMIT) break;
        }
        const uint32_t mine = __ballot_sync(~0u, token(lane < (j < 11 ? 2 : 1), tok, 2 * m + lane) == 2 * m + lane);
        {
            const uint2 c = lds64(sb + S_KF);
            if (!__all_sync(~0u, mbar_test(q[WIN_S - 2] & ~1u, q[WIN_S - 2] & 1) & (min((int)c.x + 1, (int)c.y) >= 16 * b + min(2 * j + 4 - WIN_U, 16)))) tn += XB;
        }
        q[3] = q[2]; q[2] = q[1]; q[1] = q[0]; q[0] = sb + S_QRDY;
        if (j < 11) {
            if (mine & 1) ring_load(M, sb, b, 2 * j, pos); else prefetch_l2(src, UNIT);
            if (mine & 2) ring_load(M, sb, b, 2 * j + 1, pos + 1); else prefetch_l2(src + UNIT, UNIT);
            if (j >= 8) q[0] = (sb + S_FV + 8 * (j - 8)) | (b & 1);
        } else if (mine) { v_load(M, sb, b, j - 8); q[0] = (sb + S_FV + 8 * (j - 8)) | (b & 1); }
        else if (j - 8 >= VPF) prefetch_l2(src, SLOT);
        else {
            scrap_copy(sb + S_DUMMY, src, sb + S_DBAR + 8 * (nd & 3));
            q[0] = (sb + S_DBAR + 8 * (nd & 3)) | ((nd >> 2) & 1);
            nd++;
        }
        pos = j == 15 ? 2 : pos == 4 ? 0 : pos + 2;
        if ((int)(now - tn) > SLACK) tn = now - SLACK;
        tn += 2 * TAU;
        td = (int)(tn - now) > 2 * TMIN ? tn : now + 2 * TMIN;
    }
#pragma unroll 1
    for (int m = max(nd - 4, 0); m < nd; m++) uwait(sb + S_DBAR + 8 * (m & 3), (m >> 2) & 1);
}

__host__ __device__ constexpr uint64_t bit_list(uint32_t m) { uint64_t r = 0; int n = 0; for (int k = 0; k < 12; k++) if ((m >> k) & 1) r |= (uint64_t)k << (4 * n++); return r; }
__device__ __forceinline__ float scaled(float s) { return bfr(bfr(s) * 0.07216878364870322f); }
__device__ __forceinline__ void probs(float s, uint32_t ps, uint32_t src, uint32_t ln) {
    const uint32_t q8 = ln >> 2, t4 = ln & 3;
    int key = __float_as_int(s);
    key ^= (key >> 31) & 0x7fffffff;
    key = __reduce_max_sync(~0u, key);
    key ^= (key >> 31) & 0x7fffffff;
    const float ml = __int_as_float(key) * LOG2E;
    sts16(ps + 64 * src + (q8 >> 1) * 16 + t4 * 4 + (q8 & 1) * 2, pack2(ex2(fmaf(s, LOG2E, -ml)), 0.f));
    stsf(ps + PS_MAX + 4 * src, ml);
}
template <int H> __device__ __forceinline__ uint32_t b_pos(uint32_t e) { const uint32_t h = e >= H, k = e - H * h; return h * 192 + (k & 6) * 24 + (k >> 3) * 4 + (k & 1) * 2; }
__device__ __forceinline__ uint32_t a_pos(uint32_t e) { const uint32_t h = e >= 40, k = e - 40 * h; return (k & 6) * 24 + (k >> 3) * 8 + h * 4 + (k & 1) * 2; }
__device__ __forceinline__ uint32_t q_pos(uint32_t d) { const uint32_t s = 3 * ((d >> 4) & 3) + (d >> 6); return s * 32 + (d & 6) * 4 + ((d >> 3) & 1) * 4 + (d & 1) * 2; }
__device__ __forceinline__ uint32_t k_off(uint32_t ln) { return (ln & 8) * 384 + (ln & 7) * 128 + (((ln & 7) ^ (ln >> 4)) << 4); }

#define HSTAMP(k) do {} while (0)
__device__ __forceinline__ char* xwindow() { return reinterpret_cast<char*>((reinterpret_cast<uintptr_t>(g_x) + (2u << 20) - 1) & ~(uintptr_t)((2u << 20) - 1)); }

struct XPtr {
    uint32_t lo, hi;
    __device__ __forceinline__ explicit XPtr(char* p) : lo((uint32_t)(uintptr_t)p), hi((uint32_t)((uintptr_t)p >> 32)) {}
    __device__ __forceinline__ XPtr(uint32_t l, uint32_t h) : lo(l), hi(h) {}
    __device__ __forceinline__ XPtr operator+(uint32_t o) const { return XPtr(lo + o, hi); }
    __device__ __forceinline__ operator char*() const { uint64_t p; asm("mov.b64 %0, {%1, %2};" : "=l"(p) : "r"(lo), "r"(hi)); return (char*)p; }
};

__device__ __forceinline__ void side_warp(uint32_t sb) {
    const uint32_t bid = blockIdx.x, g = bid >> 3, i = bid & 7, P = pairG(0, 0, i);
    char* p = xwindow() + P * 8192 + (g >> 3) * HALF + (g & 7) * 512 + PROBE;
    uint32_t best[2] = {~0u, ~0u};
    asm volatile("st.relaxed.gpu.global.b32 [%0], 1;" :: "l"(p) : "memory");
    asm volatile("st.relaxed.gpu.global.b32 [%0], 1;" :: "l"(p + COPY) : "memory");
#pragma unroll 1
    for (int r = 0; r < 64; r++) {
        if (r >= 4 && !(r & 1) && min(best[0], best[1]) < 380 && max(best[0], best[1]) > min(best[0], best[1]) + 80) break;
        uint32_t c0, c1, v;
        asm volatile("mov.u32 %0, %clock;" : "=r"(c0) :: "memory");
        asm volatile("atom.relaxed.gpu.global.exch.b32 %0, [%1], 0;" : "=r"(v) : "l"(p + (r & 1) * COPY) : "memory");
        asm volatile("{\n .reg .pred q;\n setp.eq.u32 q, %1, 0x13579bdf;\n mov.u32 %0, 0;\n @!q mov.u32 %0, %clock;\n}" : "=r"(c1) : "r"(v) : "memory");
        if (r & 1) best[1] = min(best[1], c1 - c0); else best[0] = min(best[0], c1 - c0);
    }
    stsvol(sb + S_SIDE, 1 + ((best[1] < best[0]) ^ (__popc(P & PMASK) & 1)));
}

template <int N>
__device__ __forceinline__ void hop_a(const char* src, uint32_t par, uint32_t dst, bool st, int k) {
    uint2 v[N][4];
    float e[4], rl;
    int guard = 0;
    bool again;
    do {
#pragma unroll
        for (int s = 0; s < 4 * N; s++) v[s / 4][s % 4] = ldp64(src + (s / 4) * 256 + (s % 4) * 1024);
        again = __any_sync(~0u, ((chk4(v[0], par) | chk4(v[N - 1], par)) & 1) != 0);
        const int M = max(max((int)v[0][0].x, (int)v[0][1].x), max((int)v[0][2].x, (int)v[0][3].x)) - 254;
#pragma unroll
        for (int s = 0; s < 4; s++) e[s] = __int_as_float(max((int)v[0][s].x - M, 0) << 22);
        rl = rcp(fmaf(e[0], asf(v[0][0].y), e[1] * asf(v[0][1].y)) + fmaf(e[2], asf(v[0][2].y), e[3] * asf(v[0][3].y)));
#pragma unroll
        for (int s = 0; s < 4; s++) e[s] = __shfl_sync(~0u, e[s], 24);
        keep(rl);
    } while (again & (++guard < SPIN_LIMIT));
    rl = __shfl_sync(~0u, rl, 24);
#pragma unroll
    for (int n = 0; n < N; n++) {
        const float o0 = fmaf(e[0], asf(v[n][0].x), e[1] * asf(v[n][1].x)) + fmaf(e[2], asf(v[n][2].x), e[3] * asf(v[n][3].x));
        const float o1 = fmaf(e[0], asf(v[n][0].y), e[1] * asf(v[n][1].y)) + fmaf(e[2], asf(v[n][2].y), e[3] * asf(v[n][3].y));
        sts32_if(st, dst + 192 * n, pack2(o0 * rl, o1 * rl));
    }
    SWEEPS(k, guard - 1);
    __syncwarp();
}

__device__ __forceinline__ void score_warp(const Maps& M, uint32_t sb, uint32_t h, uint32_t ln) {
    const uint32_t lane0 = ln;
    uwait(sb + S_QRDY, 0);
    const uint32_t q8 = ln >> 2;
    const uint32_t k0 = k_off(ln);
    uint32_t pos = h + 6, bar = sb + S_FK, par = 0, phases = 0;
    uint2 q = lds64(sb + S_QS + 8 * ln), qh = lds64(sb + S_QS + 8 * ln + 256);
    auto first_round = [&](uint32_t b, uint32_t ln) {
        uwait(sb + S_RELR, b & 1);
        const uint32_t u = h + 2 * ln, p = u < 4 ? u + 2 : u - 4;
        uint32_t todo = __ballot_sync(~0u, token(ln < 3, sb + S_TOK + 4 * p, 32 * b + 32 + u) == 32 * b + 32 + u);
#pragma unroll 1
        for (uint32_t r = h; todo; todo >>= 1, r += 2) if (todo & 1) ring_load(M, sb, b + 1, r, r < 4 ? r + 2 : r - 4);
    };
#pragma unroll 1
    for (uint32_t n = h; n < 64; n += 2) {
        HSTAMP(0);
        const uint32_t ua = sb + pos * UNIT;
        if (!__all_sync(~0u, mbar_try(bar, par))) uwait(bar, par);
        HSTAMP(1);
        float acc[2][4] = {};
        uint32_t mine = 0;
        const uint32_t id = n + (n & 48) + 6;
#pragma unroll
        for (int s = 0; s < 12; s++) {
            uint32_t kf[4];
            ldsm4(kf, (k0 ^ (32 * (s / 3))) + (ua + 1024 * (s % 3)));
            if (s == 11) {
                __syncwarp();
                mine = token(ln == 0 && n >= 16, sb + S_TOK + 24 + 4 * pos, id);
                stsvol(sb + S_KF + 4 * h, n + 1);
            }
            const bool m = q8 == (s & 7);
            mmaA(acc[s & 1], kf, m ? (s < 8 ? q.x : qh.x) : 0u, m ? (s < 8 ? q.y : qh.y) : 0u);
        }
        const uint32_t pos0 = pos;
        const bool last = (n & 14) == 14;
        pos = last ? h + 2 : n >= 16 && pos >= 4 ? h : pos + 2;
        bar = n >= 14 ? sb + S_RING + 8 * pos : bar + 8;
        par = n >= 14 ? (phases >> pos) & 1 : 0;
        phases ^= n >= 14 ? 1u << pos : 0;
        const float w0 = (acc[0][0] + acc[0][1]) + (acc[1][0] + acc[1][1]), w1 = (acc[0][2] + acc[0][3]) + (acc[1][2] + acc[1][3]);
        HSTAMP(2);
        if (__any_sync(~0u, mine == id)) ring_load(M, sb, n >> 4, (n & 15) + 6, pos0);
        HSTAMP(3);
        float s = ((ln & 1) ? w1 : w0) + __shfl_xor_sync(~0u, (ln & 1) ? w0 : w1, 1);
        s += __shfl_xor_sync(~0u, s, 2);
        sts_hi16(sb + S_SC + (((n & 12) >> 1) + h) * 64 + (n & 2) * 2 + (ln & 29) * 2, scaled(s));
        if (last) {
            __syncwarp();
            arrive_if(ln == 0, sb + S_SCO);
            const uint32_t b = n >> 4, ln = lane0 + lag<1>(sb);
            if (b > 0) {
                uwait(sb + S_RELK, (b - 1) & 1);
                if (h == 0) LSTAMP(64 + 2 * b);
                const uint32_t sl = 3 + h + 2 * ln, idv = 32 * b + 16 + 2 * sl;
                uint32_t todo = __ballot_sync(~0u, token(sl < 8, sb + S_TOK + 48 + 4 * sl, idv) == idv);
#pragma unroll 1
                for (uint32_t r = 3 + h; todo; todo >>= 1, r += 2) if (todo & 1) v_load(M, sb, b, r);
                const uint32_t g = blockIdx.x >> 3, pr = pairL(RA, 1, g), side = ldsvol(sb + S_SIDE);
                const char* src = xwindow() + pr * 8192 + ((side ^ 1 ^ __popc(pr & PMASK)) & 1) * COPY + h * HALF + 8 * min(ln, 24u);
                uwait(sb + S_RELV, (b - 1) & 1);
                __nanosleep(HOP1_NS);
#pragma unroll 1
                for (uint32_t r = 0; r < 4; r += 2) {
                    hop_a<2>(src + 256 * r, b & 1, sb + S_OS + 192 * (4 * h + r) + 96 + 4 * ln, ln < 24, 25);
                    if (r == 0 && b < 3) first_round(b, ln);
                }
                arrive_if(ln == 0, sb + S_OS1);
            } else first_round(0, ln);
            q = lds64(sb + S_QS + 24 * ((n + 2) & 48) + 8 * ln); qh = lds64(sb + S_QS + 24 * ((n + 2) & 48) + 8 * ln + 256);
        }
    }
}

__global__ void __launch_bounds__(NTHR, 1)
fused_kernel(const Params P, const __grid_constant__ Maps M) {
    extern __shared__ __align__(1024) unsigned char smem[];
    const uint32_t sb = smem_u32(smem);
    const int tid = threadIdx.x, bid = blockIdx.x;
    if (tid == 0) {
        asm volatile("prefetch.tensormap [%0];" :: "l"(&M.wq) : "memory");
        asm volatile("cp.async.bulk.prefetch.L2.global [%0], %1;" :: "l"(unit_ptr(P, 0)), "r"(PF0 * UNIT) : "memory");
    }
    const int w = __shfl_sync(~0u, tid >> 5, 0), lane = tid & 31;

    if (w >= 8) {
        asm volatile("setmaxnreg.dec.sync.aligned.u32 " REG_LO ";");
        if (w == 8) {
            stream_warp(P, M, sb, lane);
        } else {
            if (w == 11 && lane < 8) asm volatile("prefetch.tensormap [%0];" :: "l"(&M.k + lane) : "memory");
            if (w == 9) { init_bars<0, 3, 2>(sb); init_bars<3, 8, 1>(sb); init_bars<16, 22, 1>(sb); }
            else if (w == 10) { init_bars<8, 16, 2>(sb); init_bars<22, 26, 1>(sb); }
            else { init_bars<37, 38, 1>(sb); init_bars<38, 40, 8>(sb); init_bars<40, 41, 1>(sb); init_bars<41, 44, 8>(sb); init_bars<44, 46, 2>(sb); stsvol(sb + S_ZERO + 4 * lane, 0); if (lane < 16) stsvol(sb + S_LN + 4 * lane, 0); }
            asm volatile("fence.mbarrier_init.release.cluster;" ::: "memory");
            asm volatile("bar.arrive 3, 128;" ::: "memory");
            asm volatile("bar.sync 2, %0;" :: "n"(NTHR) : "memory");
            if (w < 11) score_warp(M, sb, w - 9, lane);
            else {
                if (lane == 0) side_warp(sb);
                __syncwarp();
                uint32_t a = 0, b = 0;
                int k = 0;
                while (ldsvol(sb + S_GATE) == 0 && ++k < SPIN_LIMIT) { warm_mma(a, b); __nanosleep(KWNS); }
                uint32_t rl = lane, rq = 0;
                auto reset = [&] {
                    if (rq < 128) *reinterpret_cast<uint4*>(reinterpret_cast<char*>(g_s) + (rl < 60 ? XS + bid * 7680 + 128 * rl : XS2 + bid * 768 + 128 * (rl - 60)) + rq) = make_uint4(0, 0, 0, 0);
                    rl += 32;
                    if (rl >= 66) { rl -= 66; rq += 16; }
                };
                reset(); reset();
                const uint32_t side = (ldsvol(sb + S_SIDE) & 1) ^ 1, g = bid >> 3, i = bid & 7;
                const XPtr gx(xwindow());
                auto nearp = [&](uint32_t pr) { return gx.lo + pr * 8192 + ((side ^ __popc(pr & PMASK)) & 1) * COPY; };
                const uint32_t own = (i >> 2) * HALF + (i & 3) * 1024 + (lane & 7) * 128;
                const uint32_t cut = (lane & 7) == 7 ? 128 : 0;
                const uint32_t pAC = nearp(pairL(lane >> 4, (lane >> 3) & 1, g)) + own - (lane >> 4) * cut, pE = nearp(pairL(RE, (lane >> 3) & 1, g)) + own - cut;
                const uint32_t pG = nearp(pairG((lane >> 2) & 1, (lane >> 3) & 1, i)) + min(lane & 3, 2) * 128;
                uint32_t tr = 0, tk = 0, ph = 0, src = g + (lane >> 4), seen = 0, n = 16;
                bool go = false, first = true;
                while (n < 64 && ++k < SPIN_LIMIT) {
                    const uint32_t now = __shfl_sync(~0u, gtime32(), 0) * 16;
                    if (!go && utest((n & 15) < 6 ? sb + S_RELK : sb + S_RELV, ((n >> 4) & 1) ^ 1)) { go = true; if ((int)(now - tk) > 0 || !(n & 15)) tk = now; }
                    if (go && (int)(now - tk) >= 0) {
                        place_load(M, sb, (n & 16) ? n : (n & 48) | ((n + 10) & 15));
                        tk += KRE_TAU;
                        n++;
                        go = (n & 15) != 0 && (n & 15) != 6;
                        if (!(n & 15)) LSTAMP(63 + (n >> 3));
                    } else if (first || (int)(now - tr) >= 0) {
                        first = false;
                        tr = now + RFR_TAU;
                        b |= seen & a;
                        warm_mma(a, b);
                        seen = ldp32(XPtr(ph == 0 ? pAC : ph == 1 && lane < 16 ? pE : pG + (src & 8) * (HALF / 8) + (src & 7) * 512, gx.hi));
                        reset();
                        src += ph == 0 ? 0 : ph == 1 ? 2 : 1;
                        ph = ph == 2 ? 0 : ph + 1;
                    } else __nanosleep(KWNS2);
                }
                while (rq < 128) reset();
                __syncwarp();
                while (ldsvol(sb + S_GATE) < 6 && ++k < SPIN_LIMIT) { warm_mma(a, b); __nanosleep(KWNS); }
                if (a | b) stsvol(sb + S_GATE, 6);
            }
        }
        return;
    }
    asm volatile("setmaxnreg.inc.sync.aligned.u32 " REG_HI ";");

    const int g = bid >> 3, i = bid & 7;
    const int g8 = lane >> 2, t = lane & 3;
    char* const gs = reinterpret_cast<char*>(g_s);
    const XPtr gx(xwindow());

    auto zero_words = [&] {
        const uint4 z = make_uint4(0, 0, 0, 0);
        const uint32_t c = (tid >> 6) & 1, cp = (tid >> 7) * COPY, k = (tid & 63) * 16;
        *reinterpret_cast<uint4*>((char*)(gx + pairL(RA, c, g) * 8192 + (i >> 2) * HALF + (i & 3) * 1024 + cp + k)) = z;
        if (k < 800) {
            *reinterpret_cast<uint4*>((char*)(gx + pairL(RC, c, g) * 8192 + (i >> 2) * HALF + (i & 3) * 1024 + cp + k)) = z;
            *reinterpret_cast<uint4*>((char*)(gx + pairL(RE, c, g) * 8192 + (i >> 2) * HALF + (i & 3) * 1024 + cp + k)) = z;
        }
        if ((tid & 31) < 20) *reinterpret_cast<uint4*>((char*)(gx + pairG((tid >> 5) & 1, c, i) * 8192 + (g >> 3) * HALF + (g & 7) * 512 + cp + (tid & 31) * 16)) = z;
    };
    W80 Wq[6], Wgu[3];
    uint32_t Wo[5][3][4];
    if (w < 4) {
        const uint32_t* xp = reinterpret_cast<const uint32_t*>(P.x + 640 * w);
        float sum = 0.f, sq = 0.f;
#pragma unroll
        for (int u = 0; u < 10; u++) { uint32_t v = xp[lane + 32 * u]; float a = bf_lo(v), b = bf_hi(v); sum += a + b; sq += a * a + b * b; }
#pragma unroll
        for (int o = 16; o > 0; o >>= 1) { sum += __shfl_xor_sync(~0u, sum, o); sq += __shfl_xor_sync(~0u, sq, o); }
        float mean, den; ln_stats(sum, sq, mean, den);
        if (lane < 20) {
            const uint2 v = reinterpret_cast<const uint2*>(P.x + 640 * w + 80 * i)[lane];
            sts64(sb + S_X0 + 160 * w + 8 * lane, v.x, v.y);
            sts32(sb + S_L0 + 384 * w + b_pos<40>(4 * lane), pack2(__fdiv_rn(bfr(bf_lo(v.x) - mean), den), __fdiv_rn(bfr(bf_hi(v.x) - mean), den)));
            sts32(sb + S_L0 + 384 * w + b_pos<40>(4 * lane + 2), pack2(__fdiv_rn(bfr(bf_lo(v.y) - mean), den), __fdiv_rn(bfr(bf_hi(v.y) - mean), den)));
        }
    } else if (w == 4) {
        const uint32_t* xp = reinterpret_cast<const uint32_t*>(P.wr);
        float sum = 0.f;
#pragma unroll
        for (int u = 0; u < 10; u++) { uint32_t v = xp[lane + 32 * u]; sum += bf_lo(v) + bf_hi(v); }
#pragma unroll
        for (int o = 16; o > 0; o >>= 1) sum += __shfl_xor_sync(~0u, sum, o);
        if (lane == 0) stsf(sb + S_SWR, sum);
        if (lane < 20) {
            const uint2 v = reinterpret_cast<const uint2*>(P.wr + 80 * i)[lane];
            sts32(sb + S_XA + 576 + a_pos(4 * lane), v.x); sts32(sb + S_XA + 576 + a_pos(4 * lane + 2), v.y);
            sts32(sb + S_XA + a_pos(4 * lane), ONES); sts32(sb + S_XA + a_pos(4 * lane + 2), ONES);
        }
    }
    asm volatile("bar.sync 2, %0;" :: "n"(NTHR) : "memory");
    auto frag = [](uint32_t (&a)[4], uint32_t p, int pitch) {
        const uint32_t r0 = lds32(p), r1 = lds32(p + pitch), r2 = lds32(p + 2 * pitch), r3 = lds32(p + 3 * pitch);
        a[0] = __byte_perm(r0, r1, 0x5410); a[1] = __byte_perm(r0, r1, 0x7632);
        a[2] = __byte_perm(r2, r3, 0x5410); a[3] = __byte_perm(r2, r3, 0x7632);
    };
    mbar_wait(sb + S_WFULL + 16 * (w >> 2), 0);
    mbar_wait(sb + S_WFULL + 16 * (w >> 2) + 8, 0);
    {
        const uint32_t p = sb + ST_WQ + (w >> 2) * 30720 + (2 * t) * 384 + (48 * (w & 3) + 2 * g8) * 2;
#pragma unroll
        for (int r = 0; r < 10; r++)
#pragma unroll
            for (int m = 0; m < 3; m++) {
                const uint32_t q = p + ((r & 1) * 40 + (r >> 1) * 8) * 384 + 32 * m, r0 = lds32(q), r1 = lds32(q + 384);
                (r < 8 ? Wq[2 * m].a[(r >> 2) & 1][r & 3] : Wq[2 * m].c[r & 1]) = __byte_perm(r0, r1, 0x5410);
                (r < 8 ? Wq[2 * m + 1].a[(r >> 2) & 1][r & 3] : Wq[2 * m + 1].c[r & 1]) = __byte_perm(r0, r1, 0x7632);
            }
    }
    __syncwarp();
    if (lane == 0) mbar_arrive(sb + S_RELW);
    TSTAMP(1);
    {
        char* d = gs + XS + bid * 7680 + (w >> 2) * 3840 + (48 * (w & 3) + 2 * g8) * 4;
        float acc[6][4] = {};
        mul80(acc, Wq, lds128(sb + S_L0 + 48 * lane), lds32(sb + S_L0 + 48 * lane + 16));
#pragma unroll
        for (int m = 0; m < 6; m += 2) stp64(d + t * 768 + 32 * m, acc[m][0] + acc[m][3], acc[m + 1][0] + acc[m + 1][3], 1);
        float sum[6][4] = {};
        mul80(sum, Wq, make_uint4(ONES, ONES, ONES, ONES), ONES);
        if (t == 0)
#pragma unroll
            for (int m = 0; m < 6; m += 2) stp64(d + 4 * 768 + 32 * m, sum[m][0] + sum[m][3], sum[m + 1][0] + sum[m + 1][3], 1);
    }
    mbar_wait(sb + S_WFULL + 32, 0);
    mbar_wait(sb + S_WFULL + 40, 0);
    const uint32_t oct = 3 * (w >> 1) + (w & 1), oct2 = 3 * (w >> 1) + 2;
    {
        const uint32_t p = sb + ST_WG + ((lane & 7) + 40 * ((lane >> 3) & 1) + 8 * (lane >> 4)) * 192;
#pragma unroll
        for (int T = 0; T < 3; T++) {
            const uint32_t q = p + (T < 2 ? T * 15360 + 16 * oct : (w & 1) * 15360 + 16 * oct2);
            ldsm4t(Wgu[T].a[0], q); ldsm4t(Wgu[T].a[1], q + 16 * 192); ldsm2t(Wgu[T].c, q + 32 * 192);
        }
        float sum[3][4] = {};
        mul80(sum, Wgu, make_uint4(ONES, ONES, ONES, ONES), ONES);
        if (t < 3) stp32(gs + XS2 + bid * 768 + (t < 2 ? 64 * oct + 4 * t : 64 * oct2 + 4 * (w & 1)) + 8 * g8,
                         sel4(t, sum[0][0] + sum[0][3], sum[1][0] + sum[1][3], sum[2][0] + sum[2][3], 0.f), 1);
    }
    __syncwarp();
    if (lane == 0) mbar_arrive(sb + S_RELW + 8);
    mbar_wait(sb + S_WFULL + 48 + 8 * (w >> 1), 0);
    {
        const uint32_t po = sb + ST_WO + (48 * w + 12 * t) * 160 + 4 * g8;
#pragma unroll
        for (int s = 0; s < 3; s++)
#pragma unroll
            for (int m = 0; m < 5; m++) frag(Wo[m][s], po + 4 * s * 160 + 32 * m, 160);
    }
    __syncwarp();
    if (lane == 0) mbar_arrive(sb + S_RELW + 16);
    zero_words();
    if (tid < 192) {
        const char* srcS = gs + XS + g * 8 * 7680 + (i >> 2) * 3840 + tid * 4;
        uint32_t vs[5][8];
        int guard = 0;
        do {
#pragma unroll
            for (int b = 0; b < 5; b++)
#pragma unroll
                for (int s = 0; s < 8; s++) vs[b][s] = ldp32(srcS + b * 768 + s * 7680);
        } while (((or3(chk8(vs[0], 1), chk8(vs[1], 1), chk8(vs[2], 1)) | chk8(vs[3], 1) | chk8(vs[4], 1)) & 1) && ++guard < SPIN_LIMIT);
        const uint32_t qpos = sb + S_QS + q_pos(tid);
#pragma unroll
        for (int b = 0; b < 4; b++) {
            sts_hi16(qpos + 384 * b, bfr(sum8(vs[b])));
        }
        stsf(sb + S_CSQ + 4 * tid, sum8(vs[4]));
    }
    if (tid < 192) stsf(sb + S_CSGU + 4 * tid, gather8<768>(gs + XS2 + g * 8 * 768 + tid * 4, 1));
    __syncwarp();
    bar_main();
    arrive_if(tid == 0, sb + S_QRDY);
    TSTAMP(2);

    uint32_t side;
    { int k = 0; while ((side = ldsvol(sb + S_SIDE)) == 0 && ++k < SPIN_LIMIT) {} }
    const uint32_t td = __shfl_sync(~0u, tid, lane);
    const uint32_t wp = __shfl_sync(~0u, tid >> 5, 0);
    const uint32_t cc = wp >= 3;
    auto uni = [](uint32_t v) { return __shfl_sync(~0u, v, 0); };
    auto pin = [&](uint32_t v) { return __shfl_sync(~0u, v, td); };
    auto nearp = [&](uint32_t P) { return gx.lo + P * 8192 + ((side ^ 1 ^ __popc(P & PMASK)) & 1) * COPY; };
    constexpr uint32_t COL = 32 * 8192;
    const uint32_t ownL = gx.lo + (i >> 2) * HALF + (i & 3) * 1024, ownG = gx.lo + (g >> 3) * HALF + (g & 7) * 512;
    const uint32_t uPubA = uni(ownL + pairL(RA, 0, g) * 8192 + (wp >> 1) * 256 + (wp & 1) * 96), uPolA = uni(nearp(pairL(RA, 0, g)) + (wp >> 2) * HALF + (wp & 3) * 256);
    const uint32_t uPubB = uni(ownG + pairG(0, cc, i) * 8192), uPolB = uni(nearp(pairG(0, cc, i)));
    const uint32_t uPubC = uni(ownL + pairL(RC, 0, g) * 8192), uPolC = uni(nearp(pairL(RC, wp < 6 ? cc : 0, g)));
    const uint32_t uPubD = uni(ownG + pairG(1, 0, i) * 8192 + (wp < 7 ? 32 * wp : 256)), uPolD = uni(nearp(pairG(1, cc, i)));
    const uint32_t uPubE = uni(ownL + pairL(RE, 0, g) * 8192), uPolE = uni(nearp(pairL(RE, i >> 2, g)));
    const uint32_t uOS = uni(sb + S_OS + 192 * wp);
    auto xp = [&](uint32_t lo) { return (char*)XPtr(lo, gx.hi); };
#define IDS() __syncwarp(); const uint32_t z0_ = lag<1>(sb), z_ = td + z0_; const uint32_t ln = z_ & 31, q8 = ln >> 2, t4 = z_ & 3, n96 = z_ - 96 * cc, n80 = min(n96, 79u); (void)q8; (void)t4; (void)n80; (void)ln

    auto vaddr = [&](uint32_t (&voff)[3]) {
        const uint32_t ln = td & 31;
        const uint32_t key3 = 3 * ((ln & 7) + 2 * (ln & 8) + ((ln >> 1) & 8));
#pragma unroll
        for (int T = 0; T < 3; T++) {
            const uint32_t u = 3 * wp + T, r = key3 + (u >> 3);
            voff[T] = r * 128 + (((u ^ r) & 7) << 4);
        }
    };
    auto values = [&](uint32_t (&vf)[8][3][4], float (&acc)[3][4], auto step, uint32_t ps, auto col, uint32_t par) {
        constexpr int CUT = col.value ? 8 : 6;
        const uint32_t ln = td & 31, q8 = ln >> 2, t4 = td & 3;
        uint4 p = lds128(ps + 16 * ln);
        float f0 = 0.f, f1 = 0.f, r3 = 0.f, o = 0.f;
        int M = 0;
#pragma unroll
        for (int s = 0; s < 8; s++) {
            if (s == 0 || s == CUT)
#pragma unroll
                for (int k = 0; k < 12; k++) acc[k / 4][k % 4] = 0.f;
            step(s);
            const bool m = s >= CUT || (q8 >> 1) == (s >> 1);
            const uint32_t b0 = m ? ((s & 1) ? p.z : p.x) : 0u, b1 = m ? ((s & 1) ? p.w : p.y) : 0u;
#pragma unroll
            for (int T = 0; T < 3; T++) mmaA(acc[T], vf[s][T], b0, b1);
            if (s == FSTEP) {
                const uint2 mp = lds64(ps + PS_MAX + 8 * t4);
                M = __reduce_max_sync(~0u, __float2int_ru(fmaxf(asf(mp.x), asf(mp.y))));
                f0 = ex2(asf(mp.x) - (float)M); f1 = ex2(asf(mp.y) - (float)M);
                float l[4] = {};
                mma16816(l, ONES, ONES, ONES, ONES, p.x, p.y); mma16816(l, ONES, ONES, ONES, ONES, p.z, p.w);
                r3 = fmaf(f0, l[0], f1 * l[1]);
            }
            if (s == CUT - 1) {
                if (CUT < 8) p = lds128(ps + 384 + 16 * (ln & 7));
                const float r0 = fmaf(f0, acc[0][0], f1 * acc[0][3]), r1 = fmaf(f0, acc[1][0], f1 * acc[1][3]), r2 = fmaf(f0, acc[2][0], f1 * acc[2][3]);
                const bool hi = t4 & 2, od = t4 & 1;
                const float u0 = (hi ? r2 : r0) + __shfl_xor_sync(~0u, hi ? r0 : r2, 2), u1 = (hi ? r3 : r1) + __shfl_xor_sync(~0u, hi ? r1 : r3, 2);
                o = (od ? u1 : u0) + __shfl_xor_sync(~0u, od ? u0 : u1, 1);
                if (ln == 3) o = __int_as_float(2 * M);
                if (CUT < 8) { f0 = __shfl_sync(~0u, f0, 3); f1 = __shfl_sync(~0u, f1, 3); }
            }
        }
        CSTAMP(25);
        char* pubA = xp(uPubA + col.value * COL + 32 * t4 + 4 * q8);
        if (CUT < 8 && t4 < 3) o = fmaf(f0, sel4(t4, acc[0][0], acc[1][0], acc[2][0], acc[2][0]), fmaf(f1, sel4(t4, acc[0][3], acc[1][3], acc[2][3], acc[2][3]), o));
        stp32_if(t4 < 3 || ((wp & 1) && q8 < 2), pubA, o, par);
    };

    uint32_t left[36] = {};
#pragma unroll 1
    for (int ch = 0; ch < 5; ch++) {
        const uint32_t par0 = (ch + 1) & 1, par1 = ch & 1;
        uint32_t voff[3], vf[8][3][4];
        float acc_[3][4];
        if (ch < 4) {
            vaddr(voff);
            mbar_wait(sb + S_SCO, par1);
            if (ch == 0) mbar_wait(sb + S_WFULL + 80, 0);
            TST(0);
            auto ldw = [&](int s) {
                mbar_wait(sb + S_FV + 8 * s, par1);
#pragma unroll
                for (int T = 0; T < 3; T++) ldsm4t(vf[s][T], voff[T] + (sb + v_place(ch, s) * SLOT));
            };
            probs(bf_lo(lds16(sb + S_SC + 2 * td)), sb + S_PS, wp, td & 31);
            ldw(0); ldw(1); ldw(2);
            bar_main();
            arrive_if(td == 0, sb + S_RELR);
            values(vf, acc_, [&](int s) {
                if (s >= 3) ldw(s);
            }, sb + S_PS, std::integral_constant<int, 0>(), par0);
            TST(1);
            CSTAMP(5);
            if (ch > 0) mbar_wait(sb + S_OS1, par0);
        } else {
#pragma unroll
            for (int s = 0; s < 36; s++) vf[s / 12][(s / 4) % 3][s & 3] = left[s];
        }
        const bool has0 = ch < 4, has1 = ch > 0;
        const bool actc = wp < 6 && (cc ? has1 : has0);
        const uint32_t parc = cc ? par1 : par0;
        const uint32_t pub0 = has0 ? par0 : 0;
        uint32_t rr, pubB;
        {
            IDS();
            const uint32_t c = ch == 4;
            const uint32_t osa = pin(uOS + 96 * c + 4 * ln), oa = pin(uOS + 48 * (q8 & 2) + 24 * t4), ra = pin(sb + S_RED + 640 * wp + 320 * (t4 & 1) + 8 * q8);
            rr = pin(sb + S_RED + 320 * cc + 4 * n80); pubB = pin(uPubB + 4 * n80);
            hop_a<1>(xp(uPolA + c * COL + 8 * min(ln, 24u) + lag<DELAY_L>(sb, z0_)), pub0, osa, ln < 24, 5 * ch);
            TST(2);
            CSTAMP(6);
            float acc[5][4] = {};
            const uint2 b0 = lds64(oa), b1 = lds64(oa + 8), b2 = lds64(oa + 16);
#pragma unroll
            for (int m = 0; m < 5; m++) mmaA(acc[m], Wo[m][0], b0.x, b0.y);
#pragma unroll
            for (int m = 0; m < 5; m++) mmaA(acc[m], Wo[m][1], b1.x, b1.y);
#pragma unroll
            for (int m = 0; m < 5; m++) mmaA(acc[m], Wo[m][2], b2.x, b2.y);
#pragma unroll
            for (int m = 0; m < 5; m++) { stsf(ra + 64 * m, acc[m][0]); stsf(ra + 64 * m + 4, acc[m][2]); }
        }
        CSTAMP(7);
        uint32_t xr, fl, pubC, pubC2;
        auto prepC = [&](uint32_t ln) {
            const uint32_t q8 = ln >> 2, t4 = ln & 3;
            xr = pin(sb + S_XB + 48 * (ln & 15));
            pubC = pin(uPubC + (t4 & 1) * COL + 192 * (wp >> 1) + 64 * (wp & 1) + 8 * q8);
            pubC2 = pin(uPubC + (t4 & 1) * COL + ((t4 & 2) ? 192 * (wp >> 1) + 128 + 4 * (wp & 1) + 8 * q8 : 768 + 2 * ((q8 + 1) & 6)));
            fl = pin(((t4 & 1) ? par1 : pub0) | (t4 >= 2 || (wp == 7 && q8 < 4 && q8 != 2 - t4) ? 2 : 0));
        };
        auto stats = [&](uint32_t xa, const uint4& b, uint32_t b4) {
            float a0[4] = {}, a1[4] = {}, a2[4] = {};
            const uint4 p0 = lds128(xa), p1 = lds128(xa + 16);
            const uint2 p2 = lds64(xa + 32);
            mmaV(a0, p0, b.x, b.y); mmaV(a1, p1, b.z, b.w); mma8(a2, p2.x, p2.y, b4);
            return ((a0[0] + a0[3]) + (a1[0] + a1[3])) + (a2[0] + a2[3]);
        };
        auto give_ln = [&](uint32_t src0, uint32_t par, uint32_t dst, uint32_t ln, float& mean, float& den, auto also) {
            const char* src = xp(src0 + 768 + (ln & 1) * HALF);
            float sx, sq;
            int guard = 0;
            bool again;
            do {
                uint2 st[4];
#pragma unroll
                for (int s = 0; s < 4; s++) st[s] = ldp64(src + s * 1024);
                again = __any_sync(~0u, ((chk4(st, par) | also()) & 1) != 0);
                sx = (asf(st[0].x) + asf(st[1].x)) + (asf(st[2].x) + asf(st[3].x)); sq = (asf(st[0].y) + asf(st[1].y)) + (asf(st[2].y) + asf(st[3].y));
                sx += __shfl_xor_sync(~0u, sx, 1); sq += __shfl_xor_sync(~0u, sq, 1);
            } while (again & (++guard < SPIN_LIMIT));
            ln_stats(sx, sq, mean, den);
            stsvol64(dst, __byte_perm(__float_as_uint(den), __float_as_uint(mean), 0x7632), (__float_as_uint(rcp(den)) & ~7u) | (ch + 1));
        };
        auto take_ln = [&](uint2& c, uint32_t a) { int k = 0; do c = ldsvol64(a); while (__any_sync(~0u, (c.y & 7) != ch + 1) & (++k < SPIN_LIMIT)); };
        {
            auto gate_up = [&](auto with_stats) {
                bar_main();
                TST(3);
                CSTAMP(11);
                const uint4 b = lds128(xr);
                uint32_t b4 = lds32(xr + 16);
                float acc[3][4] = {};
                if (with_stats.value) {
                    stp32_if(fl > 1 && !(td & 2), xp(pubC2), stats(xr + (S_XA - S_XB), b, b4), fl & 1);
                    __syncwarp();
                    b4 = lds32(xr + 16);
                }
                mul80(acc, Wgu, b, b4);
                stp64_if(!(td & 2), xp(pubC), tagw(acc[0][0] + acc[0][3], fl & 1), tagw(acc[1][0] + acc[1][3], fl & 1));
                stp32_if(td & 2, xp(pubC2), acc[2][0] + acc[2][3], fl & 1);
            };
            if (wp == 7) {
                bar_main();
                IDS();
                prepC(ln);
                sts32(sb + S_ZERO + 4, or3(pubC, pubC2, fl));
                gate_up(std::true_type());
            } else {
                if (actc) {
                    bar_main();
                    CSTAMP(8);
                    uint32_t r[8];
#pragma unroll
                    for (int s = 0; s < 8; s++) r[s] = lds32(rr + 640 * s);
                    stp32_if(true, xp(pubB), sum8(r), parc);
                    CSTAMP(9);
                    IDS();
                    prepC(ln);
                    const uint32_t n4 = 4 * n80;
                    const uint32_t xas = pin(sb + S_XA + 192 + 192 * cc + a_pos(n80)), xbs = pin(sb + S_XB + 384 * cc + b_pos<40>(n80));
                    const float x0 = cc ? ldsf(sb + S_XCAR + n4) : bf_lo(lds16(sb + S_X0 + 160 * (ch & 3) + n4 / 2));
                    gather16(xp(uPolB + n4 + lag<DELAY_G>(sb, z0_)), parc, 5 * ch + 1, [&](float y, uint32_t) {
                        const uint32_t x = pack2(x0 + bfr(y), 0.f);
                        sts16(xbs, x);
                        sts16(xas, x);
                        return 0u;
                    });
                    CSTAMP(10);
                } else {
                    bar_main();
                    IDS();
                    prepC(ln);
                }
                gate_up(std::false_type());
            }
        }
        CSTAMP(12);
        float mean = 0.f, den = 1.f;
        {
            IDS();
            const uint32_t wh = pin((((ln & 7) + 48 * ((ln >> 3) & 1) + 8 * (ln >> 4)) * 160 + (wp < 7 ? 16 * wp : 128)) | ((384 * cc + b_pos<48>(n96)) << 16));
            const uint32_t pubD = pin(uPubD + (t4 & 1) * COL + 16 * (t4 & 2) + 4 * q8 + (fl & 1)), ha = xr + (S_HS - S_XB);
            auto down = [&](const uint32_t (&W)[3][4], const uint4& h0, const uint2& h1) {
                float a0[4] = {}, a1[4] = {}, a2[4] = {};
                mmaA(a0, W[0], h0.x, h0.y); mmaA(a1, W[1], h0.z, h0.w); mmaA(a2, W[2], h1.x, h1.y);
                return ((a0[0] + a0[3]) + (a1[0] + a1[3])) + (a2[0] + a2[3]);
            };
            if (wp < 6) {
                uint32_t Wd[3][4];
                auto ldd = [&](uint32_t z) {
#pragma unroll
                    for (int s = 0; s < 3; s++) ldsm4t(Wd[s], ((wh ^ z) & 0xffff) + (sb + S_WD + s * 2560));
                };
                ldd(0);
                if (actc) {
                    const char* srcv = xp(uPolC + lag<DELAY_C>(sb, z0_) + 8 * n96);
                    const uint2 cs = lds64(sb + S_CSGU + 8 * n96);
                    float gt, up;
                    int guard = 0;
                    while (true) {
                        uint2 v[8];
#pragma unroll
                        for (int s = 0; s < 8; s++) v[s] = ldp64(srcv + (s >> 2) * HALF + (s & 3) * 1024);
                        uint2 c = ldsvol64(sb + S_LN + 8 * cc + ((v[0].x ^ parc) & 1) * 32);
                        const bool stale = __any_sync(~0u, ((chk8(v, parc) | chk8y(v, parc)) & 1) != 0), late = __any_sync(~0u, (c.y & 7) != ch + 1);
                        const float pg = sum8x(v), pu = sum8y(v);
                        auto norm = [&] {
                            mean = bf_hi(c.x); den = bf_lo(c.x);
                            gt = bfr(fmaf(-mean, asf(cs.x), pg) * asf(c.y)); up = fmaf(-mean, asf(cs.y), pu) * asf(c.y);
                            keep(gt); keep(up);
                        };
                        norm();
                        if (!((stale | late) & (++guard < SPIN_LIMIT))) break;
                        if (!stale) { take_ln(c, sb + S_LN + 8 * cc); norm(); break; }
                    }
                    CSTAMP(13);
                    SWEEPS(5 * ch + 2, guard - 1);
                    const uint32_t h = pack2(bfr(gt * sigmoidf_(gt)) * bfr(up), 0.f);
                    sts16((wh >> 16) + (sb + S_HS), h);
                    CSTAMP(14);
                    if (ch == 3) CSTAMP(0);
                }
                bar_main();
                TST(4);
                CSTAMP(15);
                const uint4 h0 = lds128(ha);
                const uint2 h1 = lds64(ha + 16);
                stp32_if(!(td & 2), xp(pubD & ~1u), down(Wd, h0, h1), pubD & 1);
            } else {
                uint32_t v = 0;
                const uint32_t col = wp == 7 || !has0;
                const bool serve = wp == 6 || (has0 && has1);
                if (serve) {
                    const uint32_t par = col ? par1 : par0;
                    const char* src = xp(uPolC + col * COL + 776 + (td & 4) * (HALF / 4) + (td & 3) * 1024);
                    give_ln(uPolC + col * COL, par, sb + S_LN + 8 * col, td, mean, den, [&] { v = ldp32(src); return v ^ par; });
                }
                stsvol(sb + S_GATE, ch + 1);
                uint32_t Wd[2][3][4];
#pragma unroll
                for (int s = 0; s < 6; s++) ldsm4t(Wd[s / 3][s % 3], (wh & 0xffff) + (sb + S_WD + (s / 3) * 16 + (s % 3) * 2560));
                bar_main();
                const uint4 h0 = lds128(ha);
                const uint2 h1 = lds64(ha + 16);
                const float d0 = down(Wd[0], h0, h1), d1 = down(Wd[1], h0, h1);
                stp32_if(true, xp(pubD & ~1u), (td & 2) ? d1 : d0, pubD & 1);
                if (serve) {
                    float xw = asf(v);
                    xw += __shfl_xor_sync(~0u, xw, 1); xw += __shfl_xor_sync(~0u, xw, 2); xw += __shfl_xor_sync(~0u, xw, 4);
                    const float r = bfr(fmaf(-mean, ldsf(sb + S_SWR), xw) * rcp(den));
                    sts32(sb + S_STAT + 4 * col, __float_as_uint(bfr(sigmoidf_(r))) | (ch + 1));
                }
            }
        }
        CSTAMP(16);
        {
            IDS();
            const uint32_t pubE = pin(uPubE + (t4 < 3 ? (wp >> 2) * COL + 192 * (wp & 3) + 64 * t4 + 8 * q8 : (q8 >> 2) * COL + 768 + 4 * (q8 & 1)));
            xr = pin(sb + S_XB + 48 * (ln & 7));
            uint32_t x2 = 0;
            auto hop_d = [&](auto col) {
                const uint32_t xbs = pin(sb + S_XB + 384 * col.value + b_pos<40>(n80)), xas = col.value ? 0 : pin(sb + S_XA + 192 + a_pos(n80));
                const float x1 = bf_lo(lds16(xbs));
                const float lnx = __uint_as_float(pin(__float_as_uint(bfr(__fdiv_rn(bfr(x1 - mean), den)))));
                gather16(xp(uPolD + 4 * n80 + lag<DELAY_D>(sb, z0_)), col.value ? par1 : par0, 5 * ch + 3, [&](float y, uint32_t z) {
                    const uint32_t gate = ldsvol(sb + S_STAT + 4 * col.value + z);
                    x2 = pack2(x1 + bfr(lnx + bfr(bfr(y) * bf_hi(gate))), 0.f);
                    if (col.value) keep(x2); else { sts16(xbs, x2); sts16(xas, x2); }
                    return (uint32_t)((gate & 7) != ch + 1);
                });
                CSTAMP(17);
            };
            auto qproj = [&](auto with_stats) {
                bar_main();
                TST(5);
                CSTAMP(19);
                const uint32_t t4 = td & 3;
                const uint4 b = lds128(xr);
                uint32_t b4 = lds32(xr + 16);
                float acc[6][4] = {};
                if (with_stats.value) {
                    stp32_if((td & 11) == 3, xp(pubE), stats(xr + (S_XA - S_XB), b, b4), par0);
                    __syncwarp();
                    b4 = lds32(xr + 16);
                }
                mul80(acc, Wq, b, b4);
                const float v0 = sel4(t4, acc[0][0] + acc[0][3], acc[2][0] + acc[2][3], acc[4][0] + acc[4][3], acc[4][0] + acc[4][3]);
                const float v1 = sel4(t4, acc[1][0] + acc[1][3], acc[3][0] + acc[3][3], acc[5][0] + acc[5][3], acc[5][0] + acc[5][3]);
                stp64_if(t4 < 3, xp(pubE), tagw(v0, par0), tagw(v1, par0));
            };
            if (wp == 7) {
                if (!has0) break;
                qproj(std::true_type());
            } else {
                if (actc && !cc) hop_d(std::integral_constant<int, 0>());
                else {
                    if (actc && g == 0) {
                        const uint32_t po = pin(1280 * (ch - 1) + 160 * i + 2 * n80);
                        hop_d(std::integral_constant<int, 1>());
                        *reinterpret_cast<unsigned short*>(reinterpret_cast<char*>(P.out) + po) = (unsigned short)x2;
                    }
                    if (!has0) break;
                }
                qproj(std::false_type());
                sts32_if(td < 80, sb + S_XCAR + 4 * td, x2 << 16);
            }
        }
        CSTAMP(20);
        if (wp == 6) give_ln(uPolE, par0, sb + S_LN + 16, td, mean, den, [] { return 0u; });
        auto pass2 = [&](auto d0, auto d1, auto d2) {
            constexpr int D0 = d0.value, D1 = d1.value, D = D0 + D1 + d2.value;
            IDS();
            const uint32_t ua = sb + k_place(ch, wp & 6) * SLOT + (wp & 1) * UNIT, k0 = k_off(ln);
            uint32_t kf[12][2][4];
            auto ldk = [&](int s) { const uint32_t a = (k0 ^ (32 * (s / 3))) + (ua + 1024 * (s % 3)); ldsm4(kf[s][0], a); ldsm4(kf[s][1], a + SLOT); };
            auto ldv1 = [&](int k) { ldsm4t(vf[k / 3][k % 3], voff[k % 3] + (sb + v_place(ch, k / 3) * SLOT)); };
            auto ldv = [&](int s) { ldv1(3 * s); ldv1(3 * s + 1); ldv1(3 * s + 2); };
            constexpr uint32_t LATE = LAST_LATE;
            constexpr uint64_t EARLY_LIST = bit_list(~LATE), LATE_LIST = bit_list(LATE);
            auto early = [&](int k) {
                if (D1 == 0) ldk(k);
                else if (k < 3) { ldv1(9 + 2 * k); ldv1(10 + 2 * k); }
                else ldk((EARLY_LIST >> (4 * (k - 3))) & 15);
            };
            uint32_t v[8] = {}, qsa = 0;
            const char* srcv = xp(uPolE + lag<(D1 > 0 ? 0 : DELAY_E)>(sb, z0_) + 4 * td);
            auto look = [&] {
#pragma unroll
                for (int s = 0; s < 8; s++) v[s] = ldp32(srcv + (s >> 2) * HALF + (s & 3) * 1024);
            };
            if (D1 > 0) vaddr(voff);
            if (!(mbar_try(sb + S_FK + 8 * (wp & 6), par1) & mbar_try(sb + S_FK + 8 * (wp | 1), par1))) { mbar_wait(sb + S_FK + 8 * (wp & 6), par1); mbar_wait(sb + S_FK + 8 * (wp | 1), par1); }
#pragma unroll
            for (int s = 0; s < D0; s++) early(s);
            if (wp < 6) { look(); qsa = pin(sb + S_QS + 384 * ch + q_pos(z_)); }
#pragma unroll
            for (int s = D0; s < D0 + D1; s++) early(s);
            if (wp < 6) {
                const float cs = ldsf(sb + S_CSQ + 4 * td);
                int guard = 0;
                while (true) {
                    uint2 c = ldsvol64(sb + S_LN + 16 + ((v[0] ^ par0) & 1) * 32);
                    const bool stale = __any_sync(~0u, (chk8(v, par0) & 1) != 0), late = __any_sync(~0u, (c.y & 7) != ch + 1);
                    const float qs = sum8(v);
                    auto norm = [&] {
                        const uint32_t q = pack2(fmaf(-bf_hi(c.x), cs, qs) * asf(c.y), 0.f);
                        sts16(qsa, q);
                    };
                    norm();
                    if (!((stale | late) & (++guard < SPIN_LIMIT))) break;
                    if (!stale) { take_ln(c, sb + S_LN + 16); norm(); break; }
                    look();
                }
                SWEEPS(5 * ch + 4, guard - 1);
                CSTAMP(22);
            }
#pragma unroll
            for (int s = D0 + D1; s < D; s++) early(s);
            CSTAMP(21);
            bar_main();
            TST(6);
            CSTAMP(1);
            uint2 q = lds64(sb + S_QS + 384 * ch + 8 * ln);
            float acc[2][4] = {};
            constexpr int V0 = 13 - D, NV = D1 > 0 ? 2 : (2 * (D - 1)) / 3;
            static_assert(D1 == 0 || D - 3 + __builtin_popcount(LATE) == 12, "plan");
#pragma unroll
            for (int s = 0; s < 12; s++) {
                const bool m = q8 == (s & 7);
                const uint32_t b0 = m ? q.x : 0u, b1 = m ? q.y : 0u;
                if (s == 7) q = lds64(sb + S_QS + 384 * ch + 8 * ln + 256);
                mmaA(acc[0], kf[s][0], b0, b1);
                mmaA(acc[1], kf[s][1], b0, b1);
                if (D1 > 0) {
                    if (s >= 1 && s <= __builtin_popcount(LATE)) ldk((LATE_LIST >> (4 * (s - 1))) & 15);
                } else {
                    if (s >= 1 && s + D - 1 < 12) ldk(s + D - 1);
                    if (s >= 1 && s + D - 1 == 11) { __syncwarp(); arrive_if(ln == 0, sb + S_RELK); }
                    if (s == V0) vaddr(voff);
                    if (s >= V0 && 2 * (s - V0) < 3 * NV) ldv1(9 + 2 * (s - V0));
                    if (s >= V0 && 2 * (s - V0) + 1 < 3 * NV) ldv1(10 + 2 * (s - V0));
                }
            }
            CSTAMP(24);
            {
                const float v0 = acc[0][0] + acc[0][1], v1 = acc[0][2] + acc[0][3], v2 = acc[1][0] + acc[1][1], v3 = acc[1][2] + acc[1][3];
                const bool hi = t4 & 2, od = t4 & 1;
                const float u0 = (hi ? v2 : v0) + __shfl_xor_sync(~0u, hi ? v0 : v2, 2), u1 = (hi ? v3 : v1) + __shfl_xor_sync(~0u, hi ? v1 : v3, 2);
                const float s = (od ? u1 : u0) + __shfl_xor_sync(~0u, od ? u0 : u1, 1);
                CSTAMP(2);
                probs(scaled(s), sb + S_PS + PS_PASS, wp, ln);
                CSTAMP(3);
            }
            bar_main();
            TST(10);
            CSTAMP(4);
            if (D1 > 0) values(vf, acc_, [&](int s) { if (s < 3) ldv(s + 5); }, sb + S_PS + PS_PASS, std::integral_constant<int, 1>(), par0);
            else values(vf, acc_, [&](int s) { if (s >= (NV > 1 ? 2 : 1) && s + NV + (NV > 1 ? 1 : 2) < 8) ldv(s + NV + (NV > 1 ? 1 : 2)); }, sb + S_PS + PS_PASS, std::integral_constant<int, 1>(), par0);
            arrive_if(ln == 0, sb + S_RELV);
        };
        if (ch == 3) {
            pass2(std::integral_constant<int, LAST0>(), std::integral_constant<int, LAST1>(), std::integral_constant<int, LAST2>());
#pragma unroll
            for (int m = 0; m < 48; m++) Wq[m / 8].a[(m / 4) % 2][m % 4] = vf[3 + m / 12][(m / 4) % 3][m % 4];
#pragma unroll
            for (int m = 0; m < 12; m++) Wq[m / 2].c[m % 2] = vf[7][m / 4][m % 4];
#pragma unroll
            for (int m = 0; m < 36; m++) left[m] = m < 12 ? __float_as_uint(acc_[m / 4][m % 4]) : vf[m / 12][(m / 4) % 3][m % 4];
        } else {
            pass2(std::integral_constant<int, KPRE>(), std::integral_constant<int, 0>(), std::integral_constant<int, KPRE2>());
#pragma unroll
            for (int m = 0; m < 36; m++) left[m] = m < 12 ? __float_as_uint(acc_[m / 4][m % 4]) : vf[4 + m / 12][(m / 4) % 3][m % 4];
        }
        TST(11);
        CSTAMP(23);
    }
    sts32_if(td == 255, sb + S_GATE, 6);
    TSTAMP(3);
}

typedef CUresult (*EncodeFn)(CUtensorMap*, CUtensorMapDataType, cuuint32_t, void*, const cuuint64_t*, const cuuint64_t*, const cuuint32_t*,
                             const cuuint32_t*, CUtensorMapInterleave, CUtensorMapSwizzle, CUtensorMapL2promotion, CUtensorMapFloatOOBfill);

void make_map(EncodeFn enc, CUtensorMap* m, const void* base, uint64_t cols, uint64_t rows, uint32_t box_cols, uint32_t box_rows, bool swizzle) {
    cuuint64_t dims[2] = {cols, rows};
    cuuint64_t strides[1] = {cols * 2};
    cuuint32_t box[2] = {box_cols, box_rows};
    cuuint32_t es[2] = {1, 1};
    enc(m, CU_TENSOR_MAP_DATA_TYPE_BFLOAT16, 2, const_cast<void*>(base), dims, strides, box, es, CU_TENSOR_MAP_INTERLEAVE_NONE,
        swizzle ? CU_TENSOR_MAP_SWIZZLE_128B : CU_TENSOR_MAP_SWIZZLE_NONE, CU_TENSOR_MAP_L2_PROMOTION_NONE, CU_TENSOR_MAP_FLOAT_OOB_FILL_NONE);
}

}

extern "C" void kernel_launch(void* const* d_in, const int* in_sizes, int n_in, void* d_out, int out_size) {
    (void)in_sizes; (void)n_in; (void)out_size;
    static EncodeFn enc = nullptr;
    if (!enc) {
        void* f = nullptr;
        cudaDriverEntryPointQueryResult q;
        cudaGetDriverEntryPoint("cuTensorMapEncodeTiled", &f, cudaEnableDefault, &q);
        enc = (EncodeFn)f;
        cudaFuncSetAttribute(fused_kernel, cudaFuncAttributeMaxDynamicSharedMemorySize, SMEM_BYTES);
    }
    Params P;
    P.x = (const __nv_bfloat16*)d_in[0]; P.k = (const __nv_bfloat16*)d_in[1]; P.v = (const __nv_bfloat16*)d_in[2];
    P.wr = (const __nv_bfloat16*)d_in[6];
    P.out = (__nv_bfloat16*)d_out;
    Maps M;
    {
        cuuint64_t dims[4] = {64, 8, 3, (cuuint64_t)KV_BATCH_KEYS / 2}, strides[3] = {384, 128, 3072};
        cuuint32_t box[4] = {64, 8, 3, 2}, es[4] = {1, 1, 1, 1};
        enc(&M.k, CU_TENSOR_MAP_DATA_TYPE_BFLOAT16, 4, d_in[1], dims, strides, box, es, CU_TENSOR_MAP_INTERLEAVE_NONE, CU_TENSOR_MAP_SWIZZLE_128B,
            CU_TENSOR_MAP_L2_PROMOTION_NONE, CU_TENSOR_MAP_FLOAT_OOB_FILL_NONE);
    }
    make_map(enc, &M.v, P.v, 64, (uint64_t)12 * KV_BATCH_KEYS, 64, 96, true);
    make_map(enc, &M.vu, P.v, 64, (uint64_t)12 * KV_BATCH_KEYS, 64, 48, true);
    make_map(enc, &M.wq, d_in[3], 6144, 640, 192, 40, false);
    make_map(enc, &M.wo, d_in[4], 640, 6144, 80, 96, false);
    make_map(enc, &M.wg, d_in[7], 1536, 640, 96, 80, false);
    make_map(enc, &M.wu, d_in[8], 1536, 640, 96, 80, false);
    make_map(enc, &M.wd, d_in[9], 640, 1536, 80, 96, false);
    fused_kernel<<<NCTA, NTHR, SMEM_BYTES, cudaStreamPerThread>>>(P, M);
}
```

```cpp
#include <cuda_runtime.h>
#include <cuda.h>
#include <cuda_bf16.h>
#include <stdint.h>
#include <type_traits>

namespace {

constexpr int NCTA = 128;
constexpr int NTHR = 384;
constexpr int UNIT = 6144;
constexpr int SLOT = 12288;
#define TAU 3880
#define TAUW 3660
#define TAU0 3780
#define ILV 4
#define XB 600
#define RMIN 4
#define NEARMAX 380
#define FORCE_BOTH 0
#define TMIN 2400
#define SLACK 6000
#define SLACK0 1000
#define PF0 1
#define WIN_W 3
#define WIN_S 4
#define WIN_U 10
#define VPF 4
#define KRE_TAU 2600
#define RFR_TAU 22400
#define HOP1_NS 200
#define KPRE 2
#define KPRE2 2
#define LAST0 4
#define LAST1 4
#define LAST2 2
#define LAST_LATE 0xaa8
#define FSTEP 4
#define DELAY_L 2
#define DELAY_G 2
#define DELAY_C 3
#define DELAY_D 0
#define DELAY_E 1
#define REG_LO "40"
#define REG_HI "232"
#define SPIN_LOG 17
constexpr int SPIN_LIMIT = 1 << SPIN_LOG;

__host__ __device__ constexpr uint32_t pairL(uint32_t region, uint32_t c, uint32_t g) { return (g & 1) | ((g >> 1) << 2) | (c << 5) | (region << 6); }
__host__ __device__ constexpr uint32_t pairG(uint32_t d, uint32_t c, uint32_t i) { return (i & 1) | ((i >> 1) << 2) | (d << 4) | (c << 5) | (3u << 6); }
constexpr uint32_t RA = 0, RC = 1, RE = 2, HALF = 16384, COPY = 4096, PMASK = 0x59;
constexpr uint32_t XS = 0;
constexpr uint32_t XS2 = XS + 128 * 7680;
constexpr uint32_t XSEND = XS2 + 128 * 768;
__device__ uint4 g_s[XSEND / 16];
__device__ uint4 g_x[(4u << 20) / 16];
#define SWEEPS(k, n) do {} while (0)

constexpr uint32_t S_WD = 16 * SLOT;
constexpr uint32_t S_DUMMY = S_WD + 15360;
constexpr uint32_t S_BAR = S_DUMMY + 4096;
constexpr uint32_t S_FV = S_BAR, S_FK = S_FV + 64, S_RING = S_FK + 64, S_DBAR = S_RING + 48, S_WFULL = S_DBAR + 32, S_QRDY = S_WFULL + 88;
constexpr uint32_t S_RELK = S_QRDY + 8, S_RELV = S_RELK + 8, S_RELR = S_RELV + 8, S_RELW = S_RELR + 8, S_SCO = S_RELW + 24;
constexpr uint32_t S_OS1 = S_SCO + 8;
constexpr uint32_t S_ZERO = S_OS1 + 8;
constexpr uint32_t S_KF = S_ZERO + 8;
constexpr uint32_t S_TOK = S_KF + 8;
constexpr uint32_t S_SIDE = S_TOK + 80, S_GATE = S_SIDE + 4;
constexpr uint32_t S_STAT = S_GATE + 12, S_SWR = S_STAT + 16;
constexpr uint32_t S_LN = S_STAT + 32;
constexpr uint32_t S_XCAR = S_LN + 64;
constexpr uint32_t S_CSQ = S_XCAR + 320;
constexpr uint32_t S_CSGU = S_CSQ + 768;
constexpr uint32_t S_RED = S_CSGU + 768;
constexpr uint32_t S_L0 = S_RED;
constexpr uint32_t S_OS = S_RED + 5120;
constexpr uint32_t S_PS = S_OS + 1536;
constexpr uint32_t PS_MAX = 512, PS_PASS = 544;
constexpr uint32_t S_QS = S_PS + 2 * PS_PASS;
constexpr uint32_t S_XB = S_QS + 1536;
constexpr uint32_t S_XA = S_XB + 768;
constexpr uint32_t S_HS = S_XA + 768;
constexpr uint32_t S_X0 = S_HS + 768;
constexpr uint32_t S_SC = S_X0 + 640;
constexpr uint32_t S_TM = S_SC + 512;
constexpr int SMEM_BYTES = S_TM + 256;
static_assert(SMEM_BYTES <= 232448 && S_STAT % 16 == 0 && S_RED % 16 == 0 && S_XB % 16 == 0 && S_HS % 16 == 0 && S_PS % 16 == 0 && S_QS % 16 == 0, "smem");
static_assert(S_SCO == S_BAR + 44 * 8 && S_RELK == S_BAR + 38 * 8, "barriers");
constexpr uint32_t ST_WQ = 3 * SLOT, ST_WG = 8 * SLOT, ST_WO = 11 * SLOT;

__device__ __forceinline__ uint32_t smem_u32(const void* p) { return (uint32_t)__cvta_generic_to_shared(p); }
__device__ __forceinline__ void mbar_arrive(uint32_t bar) { asm volatile("mbarrier.arrive.shared::cta.b64 _, [%0];" :: "r"(bar) : "memory"); }
__device__ __forceinline__ bool mbar_try(uint32_t bar, uint32_t parity) {
    uint32_t ok;
    asm volatile("{\n .reg .pred p;\n mbarrier.try_wait.parity.shared::cta.b64 p, [%1], %2;\n selp.u32 %0, 1, 0, p;\n}" : "=r"(ok) : "r"(bar), "r"(parity) : "memory");
    return ok != 0;
}
__device__ __forceinline__ bool mbar_test(uint32_t bar, uint32_t parity) {
    uint32_t ok;
    asm volatile("{\n .reg .pred p;\n mbarrier.test_wait.parity.shared::cta.b64 p, [%1], %2;\n selp.u32 %0, 1, 0, p;\n}" : "=r"(ok) : "r"(bar), "r"(parity) : "memory");
    return ok != 0;
}
__device__ __forceinline__ void mbar_wait(uint32_t bar, uint32_t parity) {
    int n = 0;
    while (!mbar_try(bar, parity) && ++n < SPIN_LIMIT) {}
}
__device__ __forceinline__ uint32_t gtime32() { uint32_t t; asm volatile("mov.u32 %0, %globaltimer_lo;" : "=r"(t)); return t; }
__device__ __forceinline__ void bar_main() { asm volatile("bar.sync 1, 256;" ::: "memory"); }

__device__ __forceinline__ void mma16816(float (&c)[4], uint32_t a0, uint32_t a1, uint32_t a2, uint32_t a3, uint32_t b0, uint32_t b1) {
    asm("mma.sync.aligned.m16n8k16.row.col.f32.bf16.bf16.f32 {%0,%1,%2,%3}, {%4,%5,%6,%7}, {%8,%9}, {%0,%1,%2,%3};"
        : "+f"(c[0]), "+f"(c[1]), "+f"(c[2]), "+f"(c[3]) : "r"(a0), "r"(a1), "r"(a2), "r"(a3), "r"(b0), "r"(b1));
}
__device__ __forceinline__ void mmaA(float (&c)[4], const uint32_t (&a)[4], uint32_t b0, uint32_t b1) { mma16816(c, a[0], a[1], a[2], a[3], b0, b1); }
__device__ __forceinline__ void mma8(float (&c)[4], uint32_t a0, uint32_t a1, uint32_t b0) {
    asm("mma.sync.aligned.m16n8k8.row.col.f32.bf16.bf16.f32 {%0,%1,%2,%3}, {%4,%5}, {%6}, {%0,%1,%2,%3};"
        : "+f"(c[0]), "+f"(c[1]), "+f"(c[2]), "+f"(c[3]) : "r"(a0), "r"(a1), "r"(b0));
}
struct W80 { uint32_t a[2][4], c[2]; };
template <int N> __device__ __forceinline__ void mul80(float (&acc)[N][4], const W80 (&W)[N], const uint4& b, uint32_t b4) {
#pragma unroll
    for (int m = 0; m < N; m++) mmaA(acc[m], W[m].a[0], b.x, b.y);
#pragma unroll
    for (int m = 0; m < N; m++) mmaA(acc[m], W[m].a[1], b.z, b.w);
#pragma unroll
    for (int m = 0; m < N; m++) mma8(acc[m], W[m].c[0], W[m].c[1], b4);
}
__device__ __forceinline__ void ldsm2t(uint32_t (&r)[2], uint32_t addr) {
    asm volatile("ldmatrix.sync.aligned.m8n8.x2.trans.shared.b16 {%0,%1}, [%2];" : "=r"(r[0]), "=r"(r[1]) : "r"(addr) : "memory");
}
__device__ __forceinline__ void mmaV(float (&c)[4], const uint4& a, uint32_t b0, uint32_t b1) { mma16816(c, a.x, a.y, a.z, a.w, b0, b1); }
__device__ __forceinline__ void ldsm4(uint32_t (&r)[4], uint32_t addr) {
    asm volatile("ldmatrix.sync.aligned.m8n8.x4.shared.b16 {%0,%1,%2,%3}, [%4];" : "=r"(r[0]), "=r"(r[1]), "=r"(r[2]), "=r"(r[3]) : "r"(addr) : "memory");
}
__device__ __forceinline__ void ldsm4t(uint32_t (&r)[4], uint32_t addr) {
    asm volatile("ldmatrix.sync.aligned.m8n8.x4.trans.shared.b16 {%0,%1,%2,%3}, [%4];" : "=r"(r[0]), "=r"(r[1]), "=r"(r[2]), "=r"(r[3]) : "r"(addr) : "memory");
}
__device__ __forceinline__ uint32_t lds16(uint32_t a) { uint16_t v; asm volatile("ld.shared.u16 %0, [%1];" : "=h"(v) : "r"(a) : "memory"); return v; }
__device__ __forceinline__ uint32_t lds32(uint32_t a) { uint32_t v; asm volatile("ld.shared.u32 %0, [%1];" : "=r"(v) : "r"(a) : "memory"); return v; }
__device__ __forceinline__ float ldsf(uint32_t a) { return __uint_as_float(lds32(a)); }
__device__ __forceinline__ uint2 lds64(uint32_t a) { uint2 v; asm volatile("ld.shared.v2.u32 {%0,%1}, [%2];" : "=r"(v.x), "=r"(v.y) : "r"(a) : "memory"); return v; }
__device__ __forceinline__ uint4 lds128(uint32_t a) { uint4 v; asm volatile("ld.shared.v4.u32 {%0,%1,%2,%3}, [%4];" : "=r"(v.x), "=r"(v.y), "=r"(v.z), "=r"(v.w) : "r"(a) : "memory"); return v; }
__device__ __forceinline__ int ldsvol(uint32_t a) { int v; asm volatile("ld.volatile.shared.u32 %0, [%1];" : "=r"(v) : "r"(a) : "memory"); return v; }
__device__ __forceinline__ uint2 ldsvol64(uint32_t a) { uint2 v; asm volatile("{\n .reg .b64 d;\n ld.volatile.shared.b64 d, [%2];\n mov.b64 {%0,%1}, d;\n}" : "=r"(v.x), "=r"(v.y) : "r"(a) : "memory"); return v; }
__device__ __forceinline__ void stsvol64(uint32_t a, uint32_t x, uint32_t y) { asm volatile("{\n .reg .b64 d;\n mov.b64 d, {%1,%2};\n st.volatile.shared.b64 [%0], d;\n}" :: "r"(a), "r"(x), "r"(y) : "memory"); }
__device__ __forceinline__ void stsvol(uint32_t a, int v) { asm volatile("st.volatile.shared.u32 [%0], %1;" :: "r"(a), "r"(v) : "memory"); }
__device__ __forceinline__ void sts_hi16(uint32_t a, float v) { asm volatile("{\n .reg .b16 lo, hi;\n mov.b32 {lo, hi}, %1;\n st.shared.u16 [%0], hi;\n}" :: "r"(a), "r"(__float_as_uint(v)) : "memory"); }
__device__ __forceinline__ void sts16(uint32_t a, uint32_t v) { asm volatile("st.shared.u16 [%0], %1;" :: "r"(a), "r"(v) : "memory"); }
__device__ __forceinline__ void sts32(uint32_t a, uint32_t v) { asm volatile("st.shared.u32 [%0], %1;" :: "r"(a), "r"(v) : "memory"); }
__device__ __forceinline__ void stsf(uint32_t a, float v) { sts32(a, __float_as_uint(v)); }
__device__ __forceinline__ void sts64(uint32_t a, uint32_t x, uint32_t y) { asm volatile("st.shared.v2.u32 [%0], {%1,%2};" :: "r"(a), "r"(x), "r"(y) : "memory"); }

__device__ __forceinline__ void sts32_if(bool p, uint32_t a, uint32_t v) {
    asm volatile("{\n .reg .pred p;\n setp.ne.u32 p, %2, 0;\n @p st.shared.u32 [%0], %1;\n}" :: "r"(a), "r"(v), "r"((uint32_t)p) : "memory");
}
__device__ __forceinline__ void arrive_if(bool p, uint32_t bar) {
    asm volatile("{\n .reg .pred p;\n setp.ne.u32 p, %1, 0;\n @p mbarrier.arrive.shared::cta.b64 _, [%0];\n}" :: "r"(bar), "r"((uint32_t)p) : "memory");
}
__device__ __forceinline__ void keep(uint32_t& v) { asm volatile("" : "+r"(v)); }
__device__ __forceinline__ void keep(float& v) { asm volatile("" : "+f"(v)); }

__device__ __forceinline__ uint32_t ldp32(const char* p) { uint32_t v; asm volatile("ld.relaxed.gpu.global.u32 %0, [%1];" : "=r"(v) : "l"(p) : "memory"); return v; }
__device__ __forceinline__ uint2 ldp64(const char* p) {
    uint2 v; asm volatile("{\n .reg .b64 d;\n ld.relaxed.gpu.global.b64 d, [%2];\n mov.b64 {%0,%1}, d;\n}" : "=r"(v.x), "=r"(v.y) : "l"(p) : "memory"); return v;
}
__device__ __forceinline__ uint32_t tagw(float f, uint32_t par) { return (__float_as_uint(f) & ~1u) | par; }
__device__ __forceinline__ void stp32(char* p, float a, uint32_t par) { asm volatile("st.relaxed.gpu.global.u32 [%0], %1;" :: "l"(p), "r"(tagw(a, par)) : "memory"); }
__device__ __forceinline__ void stp64(char* p, float a, float b, uint32_t par) {
    asm volatile("{\n .reg .b64 d;\n mov.b64 d, {%1,%2};\n st.relaxed.gpu.global.b64 [%0], d;\n}" :: "l"(p), "r"(tagw(a, par)), "r"(tagw(b, par)) : "memory");
}
__device__ __forceinline__ void stp32_if(bool p, char* d, float a, uint32_t par) {
    asm volatile("{\n .reg .pred p;\n setp.ne.u32 p, %2, 0;\n @p st.relaxed.gpu.global.u32 [%0], %1;\n @p st.relaxed.gpu.global.u32 [%0+4096], %1;\n}" :: "l"(d), "r"(tagw(a, par)), "r"((uint32_t)p) : "memory");
}
__device__ __forceinline__ void stp32_if(bool p, char* d, char* e, float a, uint32_t par) {
    asm volatile("{\n .reg .pred p;\n setp.ne.u32 p, %2, 0;\n @p st.relaxed.gpu.global.u32 [%0], %1;\n @p st.relaxed.gpu.global.u32 [%3], %1;\n}" :: "l"(d), "r"(tagw(a, par)), "r"((uint32_t)p), "l"(e) : "memory");
}
__device__ __forceinline__ void stp64_if(bool p, char* d, char* e, uint32_t lo, uint32_t hi) {
    asm volatile("{\n .reg .pred p;\n .reg .b64 d;\n setp.ne.u32 p, %3, 0;\n mov.b64 d, {%1,%2};\n @p st.relaxed.gpu.global.b64 [%0], d;\n @p st.relaxed.gpu.global.b64 [%4], d;\n}" :: "l"(d), "r"(lo), "r"(hi), "r"((uint32_t)p), "l"(e) : "memory");
}
__device__ __forceinline__ uint32_t chk2(uint32_t a, uint32_t b, uint32_t par) { uint32_t r; asm("lop3.b32 %0, %1, %2, %3, 0x7E;" : "=r"(r) : "r"(a), "r"(b), "r"(par)); return r; }
__device__ __forceinline__ uint32_t or3(uint32_t a, uint32_t b, uint32_t c) { uint32_t r; asm("lop3.b32 %0, %1, %2, %3, 0xFE;" : "=r"(r) : "r"(a), "r"(b), "r"(c)); return r; }
__device__ __forceinline__ uint32_t chk8(const uint32_t (&v)[8], uint32_t par) { return or3(chk2(v[0], v[1], par), chk2(v[2], v[3], par), or3(chk2(v[4], v[5], par), chk2(v[6], v[7], par), 0)); }
__device__ __forceinline__ uint32_t chk8(const uint2 (&v)[8], uint32_t par) { return or3(chk2(v[0].x, v[1].x, par), chk2(v[2].x, v[3].x, par), or3(chk2(v[4].x, v[5].x, par), chk2(v[6].x, v[7].x, par), 0)); }
__device__ __forceinline__ uint32_t chk8y(const uint2 (&v)[8], uint32_t par) { return or3(chk2(v[0].y, v[1].y, par), chk2(v[2].y, v[3].y, par), or3(chk2(v[4].y, v[5].y, par), chk2(v[6].y, v[7].y, par), 0)); }
__device__ __forceinline__ uint32_t chk4(const uint2 (&v)[4], uint32_t par) { return or3(chk2(v[0].x, v[0].y, par), chk2(v[1].x, v[1].y, par), or3(chk2(v[2].x, v[2].y, par), chk2(v[3].x, v[3].y, par), 0)); }
__device__ __forceinline__ float asf(uint32_t v) { return __uint_as_float(v); }
__device__ __forceinline__ float sum8(const uint32_t (&v)[8]) { return ((asf(v[0]) + asf(v[1])) + (asf(v[2]) + asf(v[3]))) + ((asf(v[4]) + asf(v[5])) + (asf(v[6]) + asf(v[7]))); }
__device__ __forceinline__ float sum8x(const uint2 (&v)[8]) { return ((asf(v[0].x) + asf(v[1].x)) + (asf(v[2].x) + asf(v[3].x))) + ((asf(v[4].x) + asf(v[5].x)) + (asf(v[6].x) + asf(v[7].x))); }
__device__ __forceinline__ float sum8y(const uint2 (&v)[8]) { return ((asf(v[0].y) + asf(v[1].y)) + (asf(v[2].y) + asf(v[3].y))) + ((asf(v[4].y) + asf(v[5].y)) + (asf(v[6].y) + asf(v[7].y))); }

__device__ __forceinline__ uint32_t pack2(float lo, float hi) { uint32_t r; asm("cvt.rn.bf16x2.f32 %0, %1, %2;" : "=r"(r) : "f"(hi), "f"(lo)); return r; }
__device__ __forceinline__ float bfr(float x) { return __uint_as_float(pack2(0.0f, x)); }
__device__ __forceinline__ float ex2(float x) { float r; asm("ex2.approx.ftz.f32 %0, %1;" : "=f"(r) : "f"(x)); return r; }
__device__ __forceinline__ float rcp(float x) { float r; asm("rcp.approx.ftz.f32 %0, %1;" : "=f"(r) : "f"(x)); return r; }
__device__ __forceinline__ float sqrt_(float x) { float r; asm("sqrt.approx.ftz.f32 %0, %1;" : "=f"(r) : "f"(x)); return r; }
__device__ __forceinline__ float bf_lo(uint32_t v) { return __uint_as_float(v << 16); }
__device__ __forceinline__ float bf_hi(uint32_t v) { return __uint_as_float(v & 0xffff0000u); }
__device__ __forceinline__ float sel4(int k, float a, float b, float c, float d) { return (k & 2) ? ((k & 1) ? d : c) : ((k & 1) ? b : a); }
constexpr float LOG2E = 1.4426950408889634f;
constexpr uint32_t ONES = 0x3f803f80u;

__device__ __forceinline__ void ln_stats(float sum, float sq, float& mean, float& den) {
    const float m = sum * (1.0f / 640.0f);
    const float var = fmaxf(fmaf(sq, 1.0f / 640.0f, -m * m), 0.0f);
    mean = bfr(m);
    den = bfr(sqrt_(bfr(bfr(var) + 1e-5f)));
}
__device__ __forceinline__ float sigmoidf_(float x) { return rcp(1.0f + ex2(-x * LOG2E)); }

#define TSTAMP(k) do {} while (0)
#define TST(k) do {} while (0)

#define CSTAMP(k) do {} while (0)
template <int N> __device__ __forceinline__ uint32_t lag(uint32_t sb, uint32_t z = 0) {
#pragma unroll
    for (int k = 0; k < N; k++) z = ldsvol(sb + S_ZERO + z);
    return z;
}
__device__ __forceinline__ void warm_mma(uint32_t& a, uint32_t& b) {
    asm volatile("mma.sync.aligned.m16n8k8.row.col.f16.f16.f16.f16 {%0,%1}, {%0,%1}, {%0}, {%0,%1};" : "+r"(a), "+r"(b) :: "memory");
}
#define KWNS2 20
#define KWNS 200
template <class F>
__device__ __forceinline__ void gather16(const char* p, uint32_t par, int k, F use) {
    uint32_t v[8], u[8];
    int guard = 0;
    bool again;
    do {
#pragma unroll
        for (int s = 0; s < 8; s++) v[s] = ldp32(p + s * 512);
#pragma unroll
        for (int s = 0; s < 8; s++) u[s] = ldp32(p + HALF + s * 512);
        const uint32_t stale = use(sum8(v) + sum8(u), ((v[0] ^ par) & 1) * 8);
        again = __any_sync(~0u, (or3(chk8(v, par), chk8(u, par), stale) & 1) != 0);
    } while (again & (++guard < SPIN_LIMIT));
    SWEEPS(k, guard - 1);
}

struct Params {
    const __nv_bfloat16 *x, *k, *v, *wr;
    __nv_bfloat16* out;
};
struct Maps { CUtensorMap k, v, vu, wq, wo, wg, wu, wd; };

constexpr int KV_BATCH_KEYS = 32 * 4096;

__device__ __forceinline__ void tma2d(uint32_t dst, const CUtensorMap* m, int c0, int c1, uint32_t bar, uint32_t bytes, uint64_t pol) {
    asm volatile("{\n .reg .pred p;\n elect.sync _|p, 0xffffffff;\n"
                 " @p mbarrier.arrive.expect_tx.shared::cta.b64 _, [%2], %6;\n"
                 " @p cp.async.bulk.tensor.2d.shared::cluster.global.mbarrier::complete_tx::bytes.L2::cache_hint [%0], [%1, {%3, %4}], [%2], %5;\n}"
                 :: "r"(dst), "l"(m), "r"(bar), "r"(c0), "r"(c1), "l"(pol), "r"(bytes) : "memory");
}
__device__ __forceinline__ void scrap_copy(uint32_t dst, const char* src, uint32_t bar) {
    asm volatile("{\n .reg .pred p;\n elect.sync _|p, 0xffffffff;\n"
                 " @p mbarrier.arrive.expect_tx.shared::cta.b64 _, [%2], 12288;\n"
                 " @p cp.async.bulk.shared::cluster.global.mbarrier::complete_tx::bytes [%0], [%1], 4096, [%2];\n"
                 " @p cp.async.bulk.shared::cluster.global.mbarrier::complete_tx::bytes [%0], [%1+4096], 4096, [%2];\n"
                 " @p cp.async.bulk.shared::cluster.global.mbarrier::complete_tx::bytes [%0], [%1+8192], 4096, [%2];\n}"
                 :: "r"(dst), "l"(src), "r"(bar) : "memory");
}
__device__ __forceinline__ void prefetch_l2(const void* p, uint32_t bytes) {
    asm volatile("{\n .reg .pred p;\n elect.sync _|p, 0xffffffff;\n @p cp.async.bulk.prefetch.L2.global [%0], %1;\n}" :: "l"(p), "r"(bytes) : "memory");
}
__device__ __forceinline__ uint64_t pol_first() { uint64_t p; asm("createpolicy.fractional.L2::evict_first.b64 %0, 1.0;" : "=l"(p)); return p; }
__device__ __forceinline__ uint64_t pol_normal() { uint64_t p; asm("createpolicy.fractional.L2::evict_normal.b64 %0, 1.0;" : "=l"(p)); return p; }
__device__ __forceinline__ bool utest(uint32_t bar, uint32_t parity) { return __all_sync(~0u, mbar_test(bar, parity)); }
__device__ __forceinline__ void uwait(uint32_t bar, uint32_t parity) {
    int n = 0;
    while (!__all_sync(~0u, mbar_try(bar, parity)) && ++n < SPIN_LIMIT) {}
}
template <int A, int B, int CNT> __device__ __forceinline__ void init_bars(uint32_t sb) {
#pragma unroll 1
    for (int k = A; k < B; k++)
        asm volatile("{\n .reg .pred p;\n elect.sync _|p, 0xffffffff;\n @p mbarrier.init.shared::cta.b64 [%0], %1;\n}" :: "r"(sb + S_BAR + 8 * k), "n"(CNT) : "memory");
}
__device__ __forceinline__ int unit_key(uint32_t b, uint32_t u) {
    return (blockIdx.x >> 2) * 4096 + 3072 + (blockIdx.x & 3) * (16 * ILV) + b * KV_BATCH_KEYS + (u & ~(ILV - 1u)) * 64 + (u & (ILV - 1)) * 16;
}
__device__ __forceinline__ void load_tile(const CUtensorMap* m, uint32_t dst, uint32_t bar, uint32_t bytes, int key, uint64_t pol) { tma2d(dst, m, 0, 3 * key, bar, bytes, pol); }
__device__ __forceinline__ const char* unit_ptr(const Params& P, int n) { return (const char*)((n & 16) ? P.v : P.k) + (size_t)unit_key(n >> 5, n & 15) * 384; }
#define LSTAMP(k) do {} while (0)

__device__ __forceinline__ uint32_t k_place(uint32_t b, uint32_t s) { return s + 3 + 5 * (b & 1); }
__device__ __forceinline__ uint32_t v_place(uint32_t b, uint32_t s) { return s < 3 ? s : s + 8 - 8 * (b & 1); }
__device__ __forceinline__ void k_load(const Maps& M, uint32_t dst, uint32_t bar, int key8, uint64_t pol) {
    asm volatile("{\n .reg .pred p;\n elect.sync _|p, 0xffffffff;\n"
                 " @p mbarrier.arrive.expect_tx.shared::cta.b64 _, [%2], 6144;\n"
                 " @p cp.async.bulk.tensor.4d.shared::cluster.global.mbarrier::complete_tx::bytes.L2::cache_hint [%0], [%1, {0, 0, 0, %3}], [%2], %4;\n}"
                 :: "r"(dst), "l"(&M.k), "r"(bar), "r"(key8), "l"(pol) : "memory");
}
__device__ __forceinline__ int unit_key8(uint32_t n) { return unit_key(n >> 4, n & 15) >> 3; }
__device__ __forceinline__ void ring_load(const Maps& M, uint32_t sb, uint32_t b, uint32_t u, uint32_t pos) {
    if (u < 16) k_load(M, sb + pos * UNIT, sb + S_RING + 8 * pos, unit_key8(16 * b + u), pol_normal());
    else load_tile(&M.vu, sb + pos * UNIT, sb + S_FV + 4 * (pos & 6), UNIT, unit_key(b, pos), pol_first());
}
__device__ __forceinline__ uint32_t token(bool p, uint32_t a, uint32_t n) {
    uint32_t v;
    asm volatile("{\n .reg .pred p;\n setp.ne.u32 p, %2, 0;\n mov.u32 %0, 0;\n @p atom.shared.exch.b32 %0, [%1], %3;\n}" : "=r"(v) : "r"(a), "r"((uint32_t)p), "r"(n) : "memory");
    return v;
}
__device__ __forceinline__ void place_load(const Maps& M, uint32_t sb, uint32_t n) {
    k_load(M, sb + k_place(n >> 4, 0) * SLOT + (n & 15) * UNIT, sb + S_FK + 4 * (n & 14), unit_key8(n), pol_first());
}
__device__ __forceinline__ void v_load(const Maps& M, uint32_t sb, uint32_t b, uint32_t s) {
    load_tile(&M.v, sb + v_place(b, s) * SLOT, sb + S_FV + 8 * s, SLOT, unit_key(b, 2 * s), pol_first());
}

__device__ __forceinline__ void stream_warp(const Params& P, const Maps& M, uint32_t sb, uint32_t lane) {
    const uint64_t pol = pol_first();
    const int bid = blockIdx.x, g = bid >> 3, i = bid & 7;
    const uint32_t wf = sb + S_WFULL;
    uint32_t tn = __shfl_sync(~0u, gtime32(), 0) * 16;
    auto pace = [&](uint32_t dt) {
        int k = 0;
        uint32_t now;
        do now = __shfl_sync(~0u, gtime32(), 0) * 16; while ((int)(now - tn) < 0 && ++k < SPIN_LIMIT);
        if ((int)(now - tn) > SLACK0) tn = now - SLACK0;
        tn += dt;
    };
#pragma unroll
    for (int k = 0; k < 10; k++) {
        if (k < 2) {
            if (k == 0) init_bars<26, 27, 1>(sb); else init_bars<27, 37, 1>(sb);
            asm volatile("fence.mbarrier_init.release.cluster;" ::: "memory");
            if (k == 1) { asm volatile("bar.arrive 2, %0;" :: "n"(NTHR) : "memory"); asm volatile("bar.sync 3, 128;" ::: "memory"); }
        }
        if (k >= WIN_W) uwait(wf + 8 * (k - WIN_W), 0);
        pace(TAUW * 5 / 2);
        if (k < 4) tma2d(sb + ST_WQ + 15360 * k, &M.wq, 384 * g + 192 * (k >> 1), 80 * i + 40 * (k & 1), wf + 8 * k, 15360, pol);
        else if (k < 6) tma2d(sb + ST_WG + 15360 * (k - 4), k == 4 ? &M.wg : &M.wu, 96 * g, 80 * i, wf + 8 * k, 15360, pol);
        else tma2d(sb + ST_WO + 15360 * (k - 6), &M.wo, 80 * i, 384 * g + 96 * (k - 6), wf + 8 * k, 15360, pol);
    }
#pragma unroll 1
    for (int n = 0; n < 16; n++) {
        if (n == 0 || n == 5 || n == 11) uwait(sb + S_RELW + (n == 0 ? 0 : n == 5 ? 8 : 16), 0);
        uwait(n < WIN_S ? wf + 8 * (10 - WIN_S + n) : sb + S_FV + 8 * ((n - WIN_S) ^ 8), 0);
        pace(max(min(2 * n + 2 - PF0, 2), 0) * TAU0);
        if (n >= WIN_S && !utest(sb + S_FV + 8 * ((n - WIN_S + 1) ^ 8), 0)) tn += XB;
        if (n < 8) { place_load(M, sb, 2 * n); place_load(M, sb, 2 * n + 1); }
        else if (n < 11) { ring_load(M, sb, 0, 2 * n, 2 * n - 16); ring_load(M, sb, 0, 2 * n + 1, 2 * n - 15); }
        else v_load(M, sb, 0, n - 8);
        if (n == 7) { pace(TAUW * 5 / 2); tma2d(sb + S_WD, &M.wd, 80 * i, 96 * g, wf + 80, 15360, pol); }
    }
    int nd = 0;
    uint32_t q[4];
#pragma unroll
    for (int r = 0; r < 4; r++) q[r] = sb + S_FV + 8 * (7 - r);
    uint32_t td = tn;
    uint32_t pos = 2;
#pragma unroll 1
    for (int m = 16; m < 64; m++) {
        const int b = m >> 4, j = m & 15;
        const char* src = unit_ptr(P, 2 * m);
        const uint32_t tok = sb + S_TOK + (j < 3 ? 4 * pos : j < 11 ? 24 + 4 * pos : 16 + 4 * j) + 4 * lane;
        static_assert(WIN_U <= 12, "a ring position has at most one token of the timetable");
        int k = 0;
        while (true) {
            const uint2 c = lds64(sb + S_KF);
            if (__all_sync(~0u, mbar_test(q[WIN_S - 1] & ~1u, q[WIN_S - 1] & 1) & (min((int)c.x + 1, (int)c.y) >= 16 * b + min(2 * j + 2 - WIN_U, 16))) || ++k >= SPIN_LIMIT) break;
        }
        uint32_t now;
        while (true) {
            now = __shfl_sync(~0u, gtime32(), 0) * 16;
            if ((int)(now - td) >= 0 || ++k >= SPIN_LIMIT) break;
        }
        const uint32_t mine = __ballot_sync(~0u, token(lane < (j < 11 ? 2 : 1), tok, 2 * m + lane) == 2 * m + lane);
        {
            const uint2 c = lds64(sb + S_KF);
            if (!__all_sync(~0u, mbar_test(q[WIN_S - 2] & ~1u, q[WIN_S - 2] & 1) & (min((int)c.x + 1, (int)c.y) >= 16 * b + min(2 * j + 4 - WIN_U, 16)))) tn += XB;
        }
        q[3] = q[2]; q[2] = q[1]; q[1] = q[0]; q[0] = sb + S_QRDY;
        if (j < 11) {
            if (mine & 1) ring_load(M, sb, b, 2 * j, pos); else prefetch_l2(src, UNIT);
            if (mine & 2) ring_load(M, sb, b, 2 * j + 1, pos + 1); else prefetch_l2(src + UNIT, UNIT);
            if (j >= 8) q[0] = (sb + S_FV + 8 * (j - 8)) | (b & 1);
        } else if (mine) { v_load(M, sb, b, j - 8); q[0] = (sb + S_FV + 8 * (j - 8)) | (b & 1); }
        else if (j - 8 >= VPF) prefetch_l2(src, SLOT);
        else {
            scrap_copy(sb + S_DUMMY, src, sb + S_DBAR + 8 * (nd & 3));
            q[0] = (sb + S_DBAR + 8 * (nd & 3)) | ((nd >> 2) & 1);
            nd++;
        }
        pos = j == 15 ? 2 : pos == 4 ? 0 : pos + 2;
        if ((int)(now - tn) > SLACK) tn = now - SLACK;
        tn += 2 * TAU;
        td = (int)(tn - now) > 2 * TMIN ? tn : now + 2 * TMIN;
    }
#pragma unroll 1
    for (int m = max(nd - 4, 0); m < nd; m++) uwait(sb + S_DBAR + 8 * (m & 3), (m >> 2) & 1);
}

__host__ __device__ constexpr uint64_t bit_list(uint32_t m) { uint64_t r = 0; int n = 0; for (int k = 0; k < 12; k++) if ((m >> k) & 1) r |= (uint64_t)k << (4 * n++); return r; }
__device__ __forceinline__ float scaled(float s) { return bfr(bfr(s) * 0.07216878364870322f); }
__device__ __forceinline__ void probs(float s, uint32_t ps, uint32_t src, uint32_t ln) {
    const uint32_t q8 = ln >> 2, t4 = ln & 3;
    int key = __float_as_int(s);
    key ^= (key >> 31) & 0x7fffffff;
    key = __reduce_max_sync(~0u, key);
    key ^= (key >> 31) & 0x7fffffff;
    const float ml = __int_as_float(key) * LOG2E;
    sts16(ps + 64 * src + (q8 >> 1) * 16 + t4 * 4 + (q8 & 1) * 2, pack2(ex2(fmaf(s, LOG2E, -ml)), 0.f));
    stsf(ps + PS_MAX + 4 * src, ml);
}
template <int H> __device__ __forceinline__ uint32_t b_pos(uint32_t e) { const uint32_t h = e >= H, k = e - H * h; return h * 192 + (k & 6) * 24 + (k >> 3) * 4 + (k & 1) * 2; }
__device__ __forceinline__ uint32_t a_pos(uint32_t e) { const uint32_t h = e >= 40, k = e - 40 * h; return (k & 6) * 24 + (k >> 3) * 8 + h * 4 + (k & 1) * 2; }
__device__ __forceinline__ uint32_t q_pos(uint32_t d) { const uint32_t s = 3 * ((d >> 4) & 3) + (d >> 6); return s * 32 + (d & 6) * 4 + ((d >> 3) & 1) * 4 + (d & 1) * 2; }
__device__ __forceinline__ uint32_t k_off(uint32_t ln) { return (ln & 8) * 384 + (ln & 7) * 128 + (((ln & 7) ^ (ln >> 4)) << 4); }

#define HSTAMP(k) do {} while (0)
__device__ __forceinline__ char* xwindow() { return reinterpret_cast<char*>((reinterpret_cast<uintptr_t>(g_x) + (2u << 20) - 1) & ~(uintptr_t)((2u << 20) - 1)); }

struct XPtr {
    uint32_t lo, hi;
    __device__ __forceinline__ explicit XPtr(char* p) : lo((uint32_t)(uintptr_t)p), hi((uint32_t)((uintptr_t)p >> 32)) {}
    __device__ __forceinline__ XPtr(uint32_t l, uint32_t h) : lo(l), hi(h) {}
    __device__ __forceinline__ XPtr operator+(uint32_t o) const { return XPtr(lo + o, hi); }
    __device__ __forceinline__ operator char*() const { uint64_t p; asm("mov.b64 %0, {%1, %2};" : "=l"(p) : "r"(lo), "r"(hi)); return (char*)p; }
};

__device__ __forceinline__ char* side_word(uint32_t g, uint32_t i) { return xwindow() + pairG(1, 0, i) * 8192 + (g >> 3) * HALF + (g & 7) * 512 + 320; }

__device__ __forceinline__ uint32_t probe_side() {
    const uint32_t bid = blockIdx.x, g = bid >> 3, i = bid & 7, P = pairG(0, 0, i);
    char* p = xwindow() + P * 8192 + (g >> 3) * HALF + (g & 7) * 512 + 352;
    uint32_t best[2] = {~0u, ~0u};
#pragma unroll
    for (int k = 0; k < 4; k++) *reinterpret_cast<uint4*>(p + (k & 1) * 16 + (k >> 1) * COPY) = make_uint4(1, 1, 1, 1);
#pragma unroll 1
    for (int r = 0; r < 64; r++) {
        if (r >= RMIN && !(r & 1) && min(best[0], best[1]) < NEARMAX && max(best[0], best[1]) > min(best[0], best[1]) + 80) break;
        uint32_t c0, c1, v;
        asm volatile("mov.u32 %0, %clock;" : "=r"(c0) :: "memory");
        asm volatile("atom.relaxed.gpu.global.exch.b32 %0, [%1], 0;" : "=r"(v) : "l"(p + (r & 1) * COPY) : "memory");
        asm volatile("{\n .reg .pred q;\n setp.eq.u32 q, %1, 0x13579bdf;\n mov.u32 %0, 0;\n @!q mov.u32 %0, %clock;\n}" : "=r"(c1) : "r"(v) : "memory");
        if (r & 1) best[1] = min(best[1], c1 - c0); else best[0] = min(best[0], c1 - c0);
    }
    return 1 + ((best[1] < best[0]) ^ (__popc(P & PMASK) & 1));
}

template <int N>
__device__ __forceinline__ void hop_a(const char* src, uint32_t par, uint32_t dst, bool st, int k) {
    uint2 v[N][4];
    float e[4], rl;
    int guard = 0;
    bool again;
    do {
#pragma unroll
        for (int s = 0; s < 4 * N; s++) v[s / 4][s % 4] = ldp64(src + (s / 4) * 256 + (s % 4) * 1024);
        again = __any_sync(~0u, ((chk4(v[0], par) | chk4(v[N - 1], par)) & 1) != 0);
        const int M = max(max((int)v[0][0].x, (int)v[0][1].x), max((int)v[0][2].x, (int)v[0][3].x)) - 254;
#pragma unroll
        for (int s = 0; s < 4; s++) e[s] = __int_as_float(max((int)v[0][s].x - M, 0) << 22);
        rl = rcp(fmaf(e[0], asf(v[0][0].y), e[1] * asf(v[0][1].y)) + fmaf(e[2], asf(v[0][2].y), e[3] * asf(v[0][3].y)));
#pragma unroll
        for (int s = 0; s < 4; s++) e[s] = __shfl_sync(~0u, e[s], 24);
        keep(rl);
    } while (again & (++guard < SPIN_LIMIT));
    rl = __shfl_sync(~0u, rl, 24);
#pragma unroll
    for (int n = 0; n < N; n++) {
        const float o0 = fmaf(e[0], asf(v[n][0].x), e[1] * asf(v[n][1].x)) + fmaf(e[2], asf(v[n][2].x), e[3] * asf(v[n][3].x));
        const float o1 = fmaf(e[0], asf(v[n][0].y), e[1] * asf(v[n][1].y)) + fmaf(e[2], asf(v[n][2].y), e[3] * asf(v[n][3].y));
        sts32_if(st, dst + 192 * n, pack2(o0 * rl, o1 * rl));
    }
    SWEEPS(k, guard - 1);
    __syncwarp();
}

__device__ __forceinline__ void score_warp(const Maps& M, uint32_t sb, uint32_t h, uint32_t ln) {
    const uint32_t lane0 = ln;
    uwait(sb + S_QRDY, 0);
    const uint32_t q8 = ln >> 2;
    const uint32_t k0 = k_off(ln);
    uint32_t pos = h + 6, bar = sb + S_FK, par = 0, phases = 0;
    uint2 q = lds64(sb + S_QS + 8 * ln), qh = lds64(sb + S_QS + 8 * ln + 256);
    auto first_round = [&](uint32_t b, uint32_t ln) {
        uwait(sb + S_RELR, b & 1);
        const uint32_t u = h + 2 * ln, p = u < 4 ? u + 2 : u - 4;
        uint32_t todo = __ballot_sync(~0u, token(ln < 3, sb + S_TOK + 4 * p, 32 * b + 32 + u) == 32 * b + 32 + u);
#pragma unroll 1
        for (uint32_t r = h; todo; todo >>= 1, r += 2) if (todo & 1) ring_load(M, sb, b + 1, r, r < 4 ? r + 2 : r - 4);
    };
#pragma unroll 1
    for (uint32_t n = h; n < 64; n += 2) {
        HSTAMP(0);
        const uint32_t ua = sb + pos * UNIT;
        if (!__all_sync(~0u, mbar_try(bar, par))) uwait(bar, par);
        HSTAMP(1);
        float acc[2][4] = {};
        uint32_t mine = 0;
        const uint32_t id = n + (n & 48) + 6;
#pragma unroll
        for (int s = 0; s < 12; s++) {
            uint32_t kf[4];
            ldsm4(kf, (k0 ^ (32 * (s / 3))) + (ua + 1024 * (s % 3)));
            if (s == 11) {
                __syncwarp();
                mine = token(ln == 0 && n >= 16, sb + S_TOK + 24 + 4 * pos, id);
                stsvol(sb + S_KF + 4 * h, n + 1);
            }
            const bool m = q8 == (s & 7);
            mmaA(acc[s & 1], kf, m ? (s < 8 ? q.x : qh.x) : 0u, m ? (s < 8 ? q.y : qh.y) : 0u);
        }
        const uint32_t pos0 = pos;
        const bool last = (n & 14) == 14;
        pos = last ? h + 2 : n >= 16 && pos >= 4 ? h : pos + 2;
        bar = n >= 14 ? sb + S_RING + 8 * pos : bar + 8;
        par = n >= 14 ? (phases >> pos) & 1 : 0;
        phases ^= n >= 14 ? 1u << pos : 0;
        const float w0 = (acc[0][0] + acc[0][1]) + (acc[1][0] + acc[1][1]), w1 = (acc[0][2] + acc[0][3]) + (acc[1][2] + acc[1][3]);
        HSTAMP(2);
        if (__any_sync(~0u, mine == id)) ring_load(M, sb, n >> 4, (n & 15) + 6, pos0);
        HSTAMP(3);
        float s = ((ln & 1) ? w1 : w0) + __shfl_xor_sync(~0u, (ln & 1) ? w0 : w1, 1);
        s += __shfl_xor_sync(~0u, s, 2);
        sts_hi16(sb + S_SC + (((n & 12) >> 1) + h) * 64 + (n & 2) * 2 + (ln & 29) * 2, scaled(s));
        if (last) {
            __syncwarp();
            arrive_if(ln == 0, sb + S_SCO);
            const uint32_t b = n >> 4, ln = lane0 + lag<1>(sb);
            if (b > 0) {
                uwait(sb + S_RELK, (b - 1) & 1);
                if (h == 0) LSTAMP(64 + 2 * b);
                const uint32_t sl = 3 + h + 2 * ln, idv = 32 * b + 16 + 2 * sl;
                uint32_t todo = __ballot_sync(~0u, token(sl < 8, sb + S_TOK + 48 + 4 * sl, idv) == idv);
#pragma unroll 1
                for (uint32_t r = 3 + h; todo; todo >>= 1, r += 2) if (todo & 1) v_load(M, sb, b, r);
                const uint32_t g = blockIdx.x >> 3, pr = pairL(RA, 1, g), side = ldsvol(sb + S_SIDE);
                const char* src = xwindow() + pr * 8192 + ((side ^ 1 ^ __popc(pr & PMASK)) & 1) * COPY + h * HALF + 8 * min(ln, 24u);
                uwait(sb + S_RELV, (b - 1) & 1);
                __nanosleep(HOP1_NS);
#pragma unroll 1
                for (uint32_t r = 0; r < 4; r += 2) {
                    hop_a<2>(src + 256 * r, b & 1, sb + S_OS + 192 * (4 * h + r) + 96 + 4 * ln, ln < 24, 25);
                    if (r == 0 && b < 3) first_round(b, ln);
                }
                arrive_if(ln == 0, sb + S_OS1);
            } else first_round(0, ln);
            q = lds64(sb + S_QS + 24 * ((n + 2) & 48) + 8 * ln); qh = lds64(sb + S_QS + 24 * ((n + 2) & 48) + 8 * ln + 256);
        }
    }
}

__global__ void __launch_bounds__(NTHR, 1)
fused_kernel(const Params P, const __grid_constant__ Maps M) {
    extern __shared__ __align__(1024) unsigned char smem[];
    const uint32_t sb = smem_u32(smem);
    const int tid = threadIdx.x, bid = blockIdx.x;
    if (tid == 0) {
        asm volatile("prefetch.tensormap [%0];" :: "l"(&M.wq) : "memory");
        asm volatile("cp.async.bulk.prefetch.L2.global [%0], %1;" :: "l"(unit_ptr(P, 0)), "r"(PF0 * UNIT) : "memory");
    }
    const int w = __shfl_sync(~0u, tid >> 5, 0), lane = tid & 31;

    if (w >= 8) {
        asm volatile("setmaxnreg.dec.sync.aligned.u32 " REG_LO ";");
        if (w == 8) {
            stream_warp(P, M, sb, lane);
        } else {
            if (w == 9) { init_bars<0, 3, 2>(sb); init_bars<3, 8, 1>(sb); init_bars<16, 22, 1>(sb); }
            else if (w == 10) { init_bars<8, 16, 2>(sb); init_bars<22, 26, 1>(sb); }
            else { init_bars<37, 38, 1>(sb); init_bars<38, 40, 8>(sb); init_bars<40, 41, 1>(sb); init_bars<41, 44, 8>(sb); init_bars<44, 46, 2>(sb); stsvol(sb + S_ZERO + 4 * lane, 0); if (lane < 16) stsvol(sb + S_LN + 4 * lane, 0); }
            asm volatile("fence.mbarrier_init.release.cluster;" ::: "memory");
            asm volatile("bar.arrive 3, 128;" ::: "memory");
            if (w == 11) asm volatile("bar.arrive 2, %0;" :: "n"(NTHR) : "memory");
            else {
                if (lane < 4) asm volatile("prefetch.tensormap [%0];" :: "l"(&M.k + lane + 4 * (w - 9)) : "memory");
                __syncwarp();
                asm volatile("bar.sync 2, %0;" :: "n"(NTHR) : "memory");
            }
            if (w < 11) score_warp(M, sb, w - 9, lane);
            else {
                uint32_t mine = 0;
                if (lane == 0) mine = probe_side();
                mine = __shfl_sync(~0u, mine, 0);
                if (lane < 8) stp32(side_word(bid >> 3, bid & 7) + 4 * lane, asf(mine & 2), 1);
                uint32_t a = 0, b = 0;
                int k = 0;
                while (!utest(sb + S_QRDY, 0) && ++k < SPIN_LIMIT) { warm_mma(a, b); __nanosleep(KWNS); }
                while (true) {
                    const uint32_t v = ldp32(side_word(bid >> 3, lane & 7));
                    const bool late = !__all_sync(~0u, v & 1);
                    if (!late || ++k >= SPIN_LIMIT) { stsvol(sb + S_SIDE, mine | (FORCE_BOTH || late || __any_sync(~0u, (v ^ mine) & 2) ? 4 : 0)); break; }
                    warm_mma(a, b); __nanosleep(KWNS);
                }
                while (ldsvol(sb + S_GATE) == 0 && ++k < SPIN_LIMIT) { warm_mma(a, b); __nanosleep(KWNS); }
                uint32_t rl = lane, rq = 0;
                auto reset = [&] {
                    if (rq < 128) *reinterpret_cast<uint4*>(reinterpret_cast<char*>(g_s) + (rl < 60 ? XS + bid * 7680 + 128 * rl : XS2 + bid * 768 + 128 * (rl - 60)) + rq) = make_uint4(0, 0, 0, 0);
                    rl += 32;
                    if (rl >= 66) { rl -= 66; rq += 16; }
                };
                reset(); reset();
                if (lane < 8) stp32(side_word(bid >> 3, bid & 7) + 4 * lane, 0.f, 0);
                const uint32_t side = (ldsvol(sb + S_SIDE) & 1) ^ 1, g = bid >> 3, i = bid & 7;
                const XPtr gx(xwindow());
                auto nearp = [&](uint32_t pr) { return gx.lo + pr * 8192 + ((side ^ __popc(pr & PMASK)) & 1) * COPY; };
                const uint32_t own = (i >> 2) * HALF + (i & 3) * 1024 + (lane & 7) * 128;
                const uint32_t cut = (lane & 7) == 7 ? 128 : 0;
                const uint32_t pAC = nearp(pairL(lane >> 4, (lane >> 3) & 1, g)) + own - (lane >> 4) * cut, pE = nearp(pairL(RE, (lane >> 3) & 1, g)) + own - cut;
                const uint32_t pG = nearp(pairG((lane >> 2) & 1, (lane >> 3) & 1, i)) + min(lane & 3, 2) * 128;
                uint32_t tr = 0, tk = 0, ph = 0, src = g + (lane >> 4), seen = 0, n = 16;
                bool go = false, first = true;
                while (n < 64 && ++k < SPIN_LIMIT) {
                    const uint32_t now = __shfl_sync(~0u, gtime32(), 0) * 16;
                    if (!go && utest((n & 15) < 6 ? sb + S_RELK : sb + S_RELV, ((n >> 4) & 1) ^ 1)) { go = true; if ((int)(now - tk) > 0 || !(n & 15)) tk = now; }
                    if (go && (int)(now - tk) >= 0) {
                        place_load(M, sb, (n & 16) ? n : (n & 48) | ((n + 10) & 15));
                        tk += KRE_TAU;
                        n++;
                        go = (n & 15) != 0 && (n & 15) != 6;
                        if (!(n & 15)) LSTAMP(63 + (n >> 3));
                    } else if (first || (int)(now - tr) >= 0) {
                        first = false;
                        tr = now + RFR_TAU;
                        b |= seen & a;
                        warm_mma(a, b);
                        seen = ldp32(XPtr(ph == 0 ? pAC : ph == 1 && lane < 16 ? pE : pG + (src & 8) * (HALF / 8) + (src & 7) * 512, gx.hi));
                        reset();
                        src += ph == 0 ? 0 : ph == 1 ? 2 : 1;
                        ph = ph == 2 ? 0 : ph + 1;
                    } else __nanosleep(KWNS2);
                }
                while (rq < 128) reset();
                __syncwarp();
                while (ldsvol(sb + S_GATE) < 6 && ++k < SPIN_LIMIT) { warm_mma(a, b); __nanosleep(KWNS); }
                if (a | b) stsvol(sb + S_GATE, 6);
            }
        }
        return;
    }
    asm volatile("setmaxnreg.inc.sync.aligned.u32 " REG_HI ";");

    const int g = bid >> 3, i = bid & 7;
    const int g8 = lane >> 2, t = lane & 3;
    char* const gs = reinterpret_cast<char*>(g_s);
    const XPtr gx(xwindow());

    W80 Wq[6], Wgu[3];
    uint32_t Wo[5][3][4];
    if (w < 4) {
        const uint32_t* xp = reinterpret_cast<const uint32_t*>(P.x + 640 * w);
        float sum = 0.f, sq = 0.f;
#pragma unroll
        for (int u = 0; u < 10; u++) { uint32_t v = xp[lane + 32 * u]; float a = bf_lo(v), b = bf_hi(v); sum += a + b; sq += a * a + b * b; }
#pragma unroll
        for (int o = 16; o > 0; o >>= 1) { sum += __shfl_xor_sync(~0u, sum, o); sq += __shfl_xor_sync(~0u, sq, o); }
        float mean, den; ln_stats(sum, sq, mean, den);
        if (lane < 20) {
            const uint2 v = reinterpret_cast<const uint2*>(P.x + 640 * w + 80 * i)[lane];
            sts64(sb + S_X0 + 160 * w + 8 * lane, v.x, v.y);
            sts32(sb + S_L0 + 384 * w + b_pos<40>(4 * lane), pack2(__fdiv_rn(bfr(bf_lo(v.x) - mean), den), __fdiv_rn(bfr(bf_hi(v.x) - mean), den)));
            sts32(sb + S_L0 + 384 * w + b_pos<40>(4 * lane + 2), pack2(__fdiv_rn(bfr(bf_lo(v.y) - mean), den), __fdiv_rn(bfr(bf_hi(v.y) - mean), den)));
        }
    } else if (w == 4) {
        const uint32_t* xp = reinterpret_cast<const uint32_t*>(P.wr);
        float sum = 0.f;
#pragma unroll
        for (int u = 0; u < 10; u++) { uint32_t v = xp[lane + 32 * u]; sum += bf_lo(v) + bf_hi(v); }
#pragma unroll
        for (int o = 16; o > 0; o >>= 1) sum += __shfl_xor_sync(~0u, sum, o);
        if (lane == 0) stsf(sb + S_SWR, sum);
        if (lane < 20) {
            const uint2 v = reinterpret_cast<const uint2*>(P.wr + 80 * i)[lane];
            sts32(sb + S_XA + 576 + a_pos(4 * lane), v.x); sts32(sb + S_XA + 576 + a_pos(4 * lane + 2), v.y);
            sts32(sb + S_XA + a_pos(4 * lane), ONES); sts32(sb + S_XA + a_pos(4 * lane + 2), ONES);
        }
    }
    asm volatile("bar.sync 2, %0;" :: "n"(NTHR) : "memory");
    auto frag = [](uint32_t (&a)[4], uint32_t p, int pitch) {
        const uint32_t r0 = lds32(p), r1 = lds32(p + pitch), r2 = lds32(p + 2 * pitch), r3 = lds32(p + 3 * pitch);
        a[0] = __byte_perm(r0, r1, 0x5410); a[1] = __byte_perm(r0, r1, 0x7632);
        a[2] = __byte_perm(r2, r3, 0x5410); a[3] = __byte_perm(r2, r3, 0x7632);
    };
    mbar_wait(sb + S_WFULL + 16 * (w >> 2), 0);
    mbar_wait(sb + S_WFULL + 16 * (w >> 2) + 8, 0);
    {
        const uint32_t p = sb + ST_WQ + (w >> 2) * 30720 + (2 * t) * 384 + (48 * (w & 3) + 2 * g8) * 2;
#pragma unroll
        for (int r = 0; r < 10; r++)
#pragma unroll
            for (int m = 0; m < 3; m++) {
                const uint32_t q = p + ((r & 1) * 40 + (r >> 1) * 8) * 384 + 32 * m, r0 = lds32(q), r1 = lds32(q + 384);
                (r < 8 ? Wq[2 * m].a[(r >> 2) & 1][r & 3] : Wq[2 * m].c[r & 1]) = __byte_perm(r0, r1, 0x5410);
                (r < 8 ? Wq[2 * m + 1].a[(r >> 2) & 1][r & 3] : Wq[2 * m + 1].c[r & 1]) = __byte_perm(r0, r1, 0x7632);
            }
    }
    __syncwarp();
    if (lane == 0) mbar_arrive(sb + S_RELW);
    TSTAMP(1);
    {
        char* d = gs + XS + bid * 7680 + (w >> 2) * 3840 + (48 * (w & 3) + 2 * g8) * 4;
        float acc[6][4] = {};
        mul80(acc, Wq, lds128(sb + S_L0 + 48 * lane), lds32(sb + S_L0 + 48 * lane + 16));
#pragma unroll
        for (int m = 0; m < 6; m += 2) stp64(d + t * 768 + 32 * m, acc[m][0] + acc[m][3], acc[m + 1][0] + acc[m + 1][3], 1);
        float sum[6][4] = {};
        mul80(sum, Wq, make_uint4(ONES, ONES, ONES, ONES), ONES);
        if (t == 0)
#pragma unroll
            for (int m = 0; m < 6; m += 2) stp64(d + 4 * 768 + 32 * m, sum[m][0] + sum[m][3], sum[m + 1][0] + sum[m + 1][3], 1);
    }
    mbar_wait(sb + S_WFULL + 32, 0);
    mbar_wait(sb + S_WFULL + 40, 0);
    const uint32_t oct = 3 * (w >> 1) + (w & 1), oct2 = 3 * (w >> 1) + 2;
    {
        const uint32_t p = sb + ST_WG + ((lane & 7) + 40 * ((lane >> 3) & 1) + 8 * (lane >> 4)) * 192;
#pragma unroll
        for (int T = 0; T < 3; T++) {
            const uint32_t q = p + (T < 2 ? T * 15360 + 16 * oct : (w & 1) * 15360 + 16 * oct2);
            ldsm4t(Wgu[T].a[0], q); ldsm4t(Wgu[T].a[1], q + 16 * 192); ldsm2t(Wgu[T].c, q + 32 * 192);
        }
        float sum[3][4] = {};
        mul80(sum, Wgu, make_uint4(ONES, ONES, ONES, ONES), ONES);
        if (t < 3) stp32(gs + XS2 + bid * 768 + (t < 2 ? 64 * oct + 4 * t : 64 * oct2 + 4 * (w & 1)) + 8 * g8,
                         sel4(t, sum[0][0] + sum[0][3], sum[1][0] + sum[1][3], sum[2][0] + sum[2][3], 0.f), 1);
    }
    __syncwarp();
    if (lane == 0) mbar_arrive(sb + S_RELW + 8);
    mbar_wait(sb + S_WFULL + 48 + 8 * (w >> 1), 0);
    {
        const uint32_t po = sb + ST_WO + (48 * w + 12 * t) * 160 + 4 * g8;
#pragma unroll
        for (int s = 0; s < 3; s++)
#pragma unroll
            for (int m = 0; m < 5; m++) frag(Wo[m][s], po + 4 * s * 160 + 32 * m, 160);
    }
    __syncwarp();
    if (lane == 0) mbar_arrive(sb + S_RELW + 16);
    if (tid < 192) {
        const char* srcS = gs + XS + g * 8 * 7680 + (i >> 2) * 3840 + tid * 4;
        uint32_t vs[5][8];
        int guard = 0;
        do {
#pragma unroll
            for (int b = 0; b < 5; b++)
#pragma unroll
                for (int s = 0; s < 8; s++) vs[b][s] = ldp32(srcS + b * 768 + s * 7680);
        } while (((or3(chk8(vs[0], 1), chk8(vs[1], 1), chk8(vs[2], 1)) | chk8(vs[3], 1) | chk8(vs[4], 1)) & 1) && ++guard < SPIN_LIMIT);
        const uint32_t qpos = sb + S_QS + q_pos(tid);
#pragma unroll
        for (int b = 0; b < 4; b++) {
            sts_hi16(qpos + 384 * b, bfr(sum8(vs[b])));
        }
        stsf(sb + S_CSQ + 4 * tid, sum8(vs[4]));
    }
    if (tid < 192) {
        uint32_t v[8];
        int guard = 0;
        do {
#pragma unroll
            for (int s = 0; s < 8; s++) v[s] = ldp32(gs + XS2 + (g * 8 + s) * 768 + tid * 4);
        } while ((chk8(v, 1) & 1) && ++guard < SPIN_LIMIT);
        stsf(sb + S_CSGU + 4 * tid, sum8(v));
    }
    __syncwarp();
    bar_main();
    arrive_if(tid == 0, sb + S_QRDY);
    TSTAMP(2);

    uint32_t side;
    { int k = 0; while ((side = ldsvol(sb + S_SIDE)) == 0 && ++k < SPIN_LIMIT) {} }
    const uint32_t both = __any_sync(~0u, side & 4) ? COPY : 0;
    uint32_t td = __shfl_sync(~0u, tid, lane);
    const uint32_t wp = __shfl_sync(~0u, tid >> 5, 0);
    const uint32_t cc = wp >= 3;
    auto uni = [](uint32_t v) { return __shfl_sync(~0u, v, 0); };
    auto pin = [&](uint32_t v) { return __shfl_sync(~0u, v, td); };
    auto nearp = [&](uint32_t P) { return gx.lo + P * 8192 + ((side ^ 1 ^ __popc(P & PMASK)) & 1) * COPY; };
    constexpr uint32_t COL = 32 * 8192;
    const uint32_t ownL = (i >> 2) * HALF + (i & 3) * 1024, ownG = gx.lo + (g >> 3) * HALF + (g & 7) * 512;
    const uint32_t uPubA = uni(ownL + nearp(pairL(RA, 0, g)) + (wp >> 1) * 256 + (wp & 1) * 96), uPolA = uni(nearp(pairL(RA, 0, g)) + (wp >> 2) * HALF + (wp & 3) * 256);
    const uint32_t uPubB = uni(ownG + pairG(0, cc, i) * 8192), uPolB = uni(nearp(pairG(0, cc, i)));
    const uint32_t uPubC = uni(ownL + nearp(pairL(RC, 0, g))), uPolC = uni(nearp(pairL(RC, wp < 6 ? cc : 0, g)));
    const uint32_t uPubD = uni(ownG + pairG(1, 0, i) * 8192 + (wp < 7 ? 32 * wp : 256)), uPolD = uni(nearp(pairG(1, cc, i)));
    const uint32_t uPubE = uni(ownL + nearp(pairL(RE, 0, g))), uPolE = uni(nearp(pairL(RE, i >> 2, g)));
    const uint32_t uOS = uni(sb + S_OS + 192 * wp);
    auto xp = [&](uint32_t lo) { return (char*)XPtr(lo, gx.hi); };
    {
        const uint4 z = make_uint4(0, 0, 0, 0);
        const uint32_t c = ((tid >> 6) & 1) * COL, cp = (tid >> 7) * both, k = (tid & 63) * 16;
        *reinterpret_cast<uint4*>(xp((ownL + nearp(pairL(RA, 0, g)) + c + k) ^ cp)) = z;
        if (k < 800) { *reinterpret_cast<uint4*>(xp((uPubC + c + k) ^ cp)) = z; *reinterpret_cast<uint4*>(xp((uPubE + c + k) ^ cp)) = z; }
        if ((tid & 31) < 20) *reinterpret_cast<uint4*>(xp(ownG + pairG((tid >> 5) & 1, 0, i) * 8192 + c + (tid >> 7) * COPY + (tid & 31) * 16)) = z;
    }
#define IDS() __syncwarp(); const uint32_t z0_ = lag<1>(sb), z_ = td + z0_; const uint32_t ln = z_ & 31, q8 = ln >> 2, t4 = z_ & 3, n96 = z_ - 96 * cc, n80 = min(n96, 79u); (void)q8; (void)t4; (void)n80; (void)ln

    auto vaddr = [&](uint32_t (&voff)[3]) {
        const uint32_t ln = td & 31;
        const uint32_t key3 = 3 * ((ln & 7) + 2 * (ln & 8) + ((ln >> 1) & 8));
#pragma unroll
        for (int T = 0; T < 3; T++) {
            const uint32_t u = 3 * wp + T, r = key3 + (u >> 3);
            voff[T] = r * 128 + (((u ^ r) & 7) << 4);
        }
    };
    auto values = [&](uint32_t (&vf)[8][3][4], float (&acc)[3][4], auto step, uint32_t ps, auto col, uint32_t par) {
        constexpr int CUT = col.value ? 8 : 6;
        const uint32_t ln = td & 31, q8 = ln >> 2, t4 = td & 3;
        uint4 p = lds128(ps + 16 * ln);
        float f0 = 0.f, f1 = 0.f, r3 = 0.f, o = 0.f;
        int M = 0;
#pragma unroll
        for (int s = 0; s < 8; s++) {
            if (s == 0 || s == CUT)
#pragma unroll
                for (int k = 0; k < 12; k++) acc[k / 4][k % 4] = 0.f;
            step(s);
            const bool m = s >= CUT || (q8 >> 1) == (s >> 1);
            const uint32_t b0 = m ? ((s & 1) ? p.z : p.x) : 0u, b1 = m ? ((s & 1) ? p.w : p.y) : 0u;
#pragma unroll
            for (int T = 0; T < 3; T++) mmaA(acc[T], vf[s][T], b0, b1);
            if (s == FSTEP) {
                const uint2 mp = lds64(ps + PS_MAX + 8 * t4);
                M = __reduce_max_sync(~0u, __float2int_ru(fmaxf(asf(mp.x), asf(mp.y))));
                f0 = ex2(asf(mp.x) - (float)M); f1 = ex2(asf(mp.y) - (float)M);
                float l[4] = {};
                mma16816(l, ONES, ONES, ONES, ONES, p.x, p.y); mma16816(l, ONES, ONES, ONES, ONES, p.z, p.w);
                r3 = fmaf(f0, l[0], f1 * l[1]);
            }
            if (s == CUT - 1) {
                if (CUT < 8) p = lds128(ps + 384 + 16 * (ln & 7));
                const float r0 = fmaf(f0, acc[0][0], f1 * acc[0][3]), r1 = fmaf(f0, acc[1][0], f1 * acc[1][3]), r2 = fmaf(f0, acc[2][0], f1 * acc[2][3]);
                const bool hi = t4 & 2, od = t4 & 1;
                const float u0 = (hi ? r2 : r0) + __shfl_xor_sync(~0u, hi ? r0 : r2, 2), u1 = (hi ? r3 : r1) + __shfl_xor_sync(~0u, hi ? r1 : r3, 2);
                o = (od ? u1 : u0) + __shfl_xor_sync(~0u, od ? u0 : u1, 1);
                if (ln == 3) o = __int_as_float(2 * M);
                if (CUT < 8) { f0 = __shfl_sync(~0u, f0, 3); f1 = __shfl_sync(~0u, f1, 3); }
            }
        }
        CSTAMP(25);
        const uint32_t pubA = uPubA + col.value * COL + 32 * t4 + 4 * q8;
        if (CUT < 8 && t4 < 3) o = fmaf(f0, sel4(t4, acc[0][0], acc[1][0], acc[2][0], acc[2][0]), fmaf(f1, sel4(t4, acc[0][3], acc[1][3], acc[2][3], acc[2][3]), o));
        stp32_if(t4 < 3 || ((wp & 1) && q8 < 2), xp(pubA ^ both), xp(pubA), o, par);
    };

    uint32_t left[36] = {};
#pragma unroll 1
    for (int ch = 0; ch < 5; ch++) {
        const uint32_t par0 = (ch + 1) & 1, par1 = ch & 1;
        uint32_t voff[3], vf[8][3][4];
        float acc_[3][4];
        if (ch < 4) {
            td = pin(td);
            vaddr(voff);
            mbar_wait(sb + S_SCO, par1);
            if (ch == 0) mbar_wait(sb + S_WFULL + 80, 0);
            TST(0);
            auto ldw = [&](int s) {
                mbar_wait(sb + S_FV + 8 * s, par1);
#pragma unroll
                for (int T = 0; T < 3; T++) ldsm4t(vf[s][T], voff[T] + (sb + v_place(ch, s) * SLOT));
            };
            probs(bf_lo(lds16(sb + S_SC + 2 * td)), sb + S_PS, wp, td & 31);
            ldw(0); ldw(1); ldw(2);
            bar_main();
            arrive_if(td == 0, sb + S_RELR);
            values(vf, acc_, [&](int s) {
                if (s >= 3) ldw(s);
            }, sb + S_PS, std::integral_constant<int, 0>(), par0);
            TST(1);
            CSTAMP(5);
            if (ch > 0) mbar_wait(sb + S_OS1, par0);
        } else {
#pragma unroll
            for (int s = 0; s < 36; s++) vf[s / 12][(s / 4) % 3][s & 3] = left[s];
        }
        const bool has0 = ch < 4, has1 = ch > 0;
        const bool actc = wp < 6 && (cc ? has1 : has0);
        const uint32_t parc = cc ? par1 : par0;
        const uint32_t pub0 = has0 ? par0 : 0;
        uint32_t rr, pubB;
        {
            IDS();
            const uint32_t c = ch == 4;
            const uint32_t osa = pin(uOS + 96 * c + 4 * ln), oa = pin(uOS + 48 * (q8 & 2) + 24 * t4), ra = pin(sb + S_RED + 640 * wp + 320 * (t4 & 1) + 8 * q8);
            rr = pin(sb + S_RED + 320 * cc + 4 * n80); pubB = pin(uPubB + 4 * n80);
            hop_a<1>(xp(uPolA + c * COL + 8 * min(ln, 24u) + lag<DELAY_L>(sb, z0_)), pub0, osa, ln < 24, 5 * ch);
            TST(2);
            CSTAMP(6);
            float acc[5][4] = {};
            const uint2 b0 = lds64(oa), b1 = lds64(oa + 8), b2 = lds64(oa + 16);
#pragma unroll
            for (int m = 0; m < 5; m++) mmaA(acc[m], Wo[m][0], b0.x, b0.y);
#pragma unroll
            for (int m = 0; m < 5; m++) mmaA(acc[m], Wo[m][1], b1.x, b1.y);
#pragma unroll
            for (int m = 0; m < 5; m++) mmaA(acc[m], Wo[m][2], b2.x, b2.y);
#pragma unroll
            for (int m = 0; m < 5; m++) { stsf(ra + 64 * m, acc[m][0]); stsf(ra + 64 * m + 4, acc[m][2]); }
        }
        CSTAMP(7);
        uint32_t xr, fl, pubC, pubC2;
        auto prepC = [&](uint32_t ln) {
            const uint32_t q8 = ln >> 2, t4 = ln & 3;
            xr = pin(sb + S_XB + 48 * (ln & 15));
            pubC = pin(uPubC + (t4 & 1) * COL + 192 * (wp >> 1) + 64 * (wp & 1) + 8 * q8);
            pubC2 = pin(uPubC + (t4 & 1) * COL + ((t4 & 2) ? 192 * (wp >> 1) + 128 + 4 * (wp & 1) + 8 * q8 : 768 + 2 * ((q8 + 1) & 6)));
            fl = pin(((t4 & 1) ? par1 : pub0) | (t4 >= 2 || (wp == 7 && q8 < 4 && q8 != 2 - t4) ? 2 : 0));
        };
        auto stats = [&](uint32_t xa, const uint4& b, uint32_t b4) {
            float a0[4] = {}, a1[4] = {}, a2[4] = {};
            const uint4 p0 = lds128(xa), p1 = lds128(xa + 16);
            const uint2 p2 = lds64(xa + 32);
            mmaV(a0, p0, b.x, b.y); mmaV(a1, p1, b.z, b.w); mma8(a2, p2.x, p2.y, b4);
            return ((a0[0] + a0[3]) + (a1[0] + a1[3])) + (a2[0] + a2[3]);
        };
        auto give_ln = [&](uint32_t src0, uint32_t par, uint32_t dst, uint32_t ln, float& mean, float& den, auto also) {
            const char* src = xp(src0 + 768 + (ln & 1) * HALF);
            float sx, sq;
            int guard = 0;
            bool again;
            do {
                uint2 st[4];
#pragma unroll
                for (int s = 0; s < 4; s++) st[s] = ldp64(src + s * 1024);
                again = __any_sync(~0u, ((chk4(st, par) | also()) & 1) != 0);
                sx = (asf(st[0].x) + asf(st[1].x)) + (asf(st[2].x) + asf(st[3].x)); sq = (asf(st[0].y) + asf(st[1].y)) + (asf(st[2].y) + asf(st[3].y));
                sx += __shfl_xor_sync(~0u, sx, 1); sq += __shfl_xor_sync(~0u, sq, 1);
            } while (again & (++guard < SPIN_LIMIT));
            ln_stats(sx, sq, mean, den);
            stsvol64(dst, __byte_perm(__float_as_uint(den), __float_as_uint(mean), 0x7632), (__float_as_uint(rcp(den)) & ~7u) | (ch + 1));
        };
        auto take_ln = [&](uint2& c, uint32_t a) { int k = 0; do c = ldsvol64(a); while (__any_sync(~0u, (c.y & 7) != ch + 1) & (++k < SPIN_LIMIT)); };
        {
            auto gate_up = [&](auto with_stats) {
                bar_main();
                TST(3);
                CSTAMP(11);
                const uint4 b = lds128(xr);
                uint32_t b4 = lds32(xr + 16);
                float acc[3][4] = {};
                if (with_stats.value) {
                    stp32_if(fl > 1 && !(td & 2), xp(pubC2 ^ both), xp(pubC2), stats(xr + (S_XA - S_XB), b, b4), fl & 1);
                    __syncwarp();
                    b4 = lds32(xr + 16);
                }
                mul80(acc, Wgu, b, b4);
                stp64_if(!(td & 2), xp(pubC ^ both), xp(pubC), tagw(acc[0][0] + acc[0][3], fl & 1), tagw(acc[1][0] + acc[1][3], fl & 1));
                stp32_if(td & 2, xp(pubC2 ^ both), xp(pubC2), acc[2][0] + acc[2][3], fl & 1);
            };
            if (wp == 7) {
                bar_main();
                IDS();
                prepC(ln);
                sts32(sb + S_ZERO + 4, or3(pubC, pubC2, fl));
                gate_up(std::true_type());
            } else {
                if (actc) {
                    bar_main();
                    CSTAMP(8);
                    uint32_t r[8];
#pragma unroll
                    for (int s = 0; s < 8; s++) r[s] = lds32(rr + 640 * s);
                    stp32_if(true, xp(pubB), sum8(r), parc);
                    CSTAMP(9);
                    IDS();
                    prepC(ln);
                    const uint32_t n4 = 4 * n80;
                    const uint32_t xas = pin(sb + S_XA + 192 + 192 * cc + a_pos(n80)), xbs = pin(sb + S_XB + 384 * cc + b_pos<40>(n80));
                    const float x0 = cc ? ldsf(sb + S_XCAR + n4) : bf_lo(lds16(sb + S_X0 + 160 * (ch & 3) + n4 / 2));
                    gather16(xp(uPolB + n4 + lag<DELAY_G>(sb, z0_)), parc, 5 * ch + 1, [&](float y, uint32_t) {
                        const uint32_t x = pack2(x0 + bfr(y), 0.f);
                        sts16(xbs, x);
                        sts16(xas, x);
                        return 0u;
                    });
                    CSTAMP(10);
                } else {
                    bar_main();
                    IDS();
                    prepC(ln);
                }
                gate_up(std::false_type());
            }
        }
        CSTAMP(12);
        float mean = 0.f, den = 1.f;
        {
            IDS();
            const uint32_t wh = pin((((ln & 7) + 48 * ((ln >> 3) & 1) + 8 * (ln >> 4)) * 160 + (wp < 7 ? 16 * wp : 128)) | ((384 * cc + b_pos<48>(n96)) << 16));
            const uint32_t pubD = pin(uPubD + (t4 & 1) * COL + 16 * (t4 & 2) + 4 * q8 + (fl & 1)), ha = xr + (S_HS - S_XB);
            auto down = [&](const uint32_t (&W)[3][4], const uint4& h0, const uint2& h1) {
                float a0[4] = {}, a1[4] = {}, a2[4] = {};
                mmaA(a0, W[0], h0.x, h0.y); mmaA(a1, W[1], h0.z, h0.w); mmaA(a2, W[2], h1.x, h1.y);
                return ((a0[0] + a0[3]) + (a1[0] + a1[3])) + (a2[0] + a2[3]);
            };
            if (wp < 6) {
                uint32_t Wd[3][4];
                auto ldd = [&](uint32_t z) {
#pragma unroll
                    for (int s = 0; s < 3; s++) ldsm4t(Wd[s], ((wh ^ z) & 0xffff) + (sb + S_WD + s * 2560));
                };
                ldd(0);
                if (actc) {
                    const char* srcv = xp(uPolC + lag<DELAY_C>(sb, z0_) + 8 * n96);
                    const uint2 cs = lds64(sb + S_CSGU + 8 * n96);
                    float gt, up;
                    int guard = 0;
                    while (true) {
                        uint2 v[8];
#pragma unroll
                        for (int s = 0; s < 8; s++) v[s] = ldp64(srcv + (s >> 2) * HALF + (s & 3) * 1024);
                        uint2 c = ldsvol64(sb + S_LN + 8 * cc + ((v[0].x ^ parc) & 1) * 32);
                        const bool stale = __any_sync(~0u, ((chk8(v, parc) | chk8y(v, parc)) & 1) != 0), late = __any_sync(~0u, (c.y & 7) != ch + 1);
                        const float pg = sum8x(v), pu = sum8y(v);
                        auto norm = [&] {
                            mean = bf_hi(c.x); den = bf_lo(c.x);
                            gt = bfr(fmaf(-mean, asf(cs.x), pg) * asf(c.y)); up = fmaf(-mean, asf(cs.y), pu) * asf(c.y);
                            keep(gt); keep(up);
                        };
                        norm();
                        if (!((stale | late) & (++guard < SPIN_LIMIT))) break;
                        if (!stale) { take_ln(c, sb + S_LN + 8 * cc); norm(); break; }
                    }
                    CSTAMP(13);
                    SWEEPS(5 * ch + 2, guard - 1);
                    const uint32_t h = pack2(bfr(gt * sigmoidf_(gt)) * bfr(up), 0.f);
                    sts16((wh >> 16) + (sb + S_HS), h);
                    CSTAMP(14);
                    if (ch == 3) CSTAMP(0);
                }
                bar_main();
                TST(4);
                CSTAMP(15);
                const uint4 h0 = lds128(ha);
                const uint2 h1 = lds64(ha + 16);
                stp32_if(!(td & 2), xp(pubD & ~1u), down(Wd, h0, h1), pubD & 1);
            } else {
                uint32_t v = 0;
                const uint32_t col = wp == 7 || !has0;
                const bool serve = wp == 6 || (has0 && has1);
                if (serve) {
                    const uint32_t par = col ? par1 : par0;
                    const char* src = xp(uPolC + col * COL + 776 + (td & 4) * (HALF / 4) + (td & 3) * 1024);
                    give_ln(uPolC + col * COL, par, sb + S_LN + 8 * col, td, mean, den, [&] { v = ldp32(src); return v ^ par; });
                }
                stsvol(sb + S_GATE, ch + 1);
                uint32_t Wd[2][3][4];
#pragma unroll
                for (int s = 0; s < 6; s++) ldsm4t(Wd[s / 3][s % 3], (wh & 0xffff) + (sb + S_WD + (s / 3) * 16 + (s % 3) * 2560));
                bar_main();
                const uint4 h0 = lds128(ha);
                const uint2 h1 = lds64(ha + 16);
                const float d0 = down(Wd[0], h0, h1), d1 = down(Wd[1], h0, h1);
                stp32_if(true, xp(pubD & ~1u), (td & 2) ? d1 : d0, pubD & 1);
                if (serve) {
                    float xw = asf(v);
                    xw += __shfl_xor_sync(~0u, xw, 1); xw += __shfl_xor_sync(~0u, xw, 2); xw += __shfl_xor_sync(~0u, xw, 4);
                    const float r = bfr(fmaf(-mean, ldsf(sb + S_SWR), xw) * rcp(den));
                    sts32(sb + S_STAT + 4 * col, __float_as_uint(bfr(sigmoidf_(r))) | (ch + 1));
                }
            }
        }
        CSTAMP(16);
        {
            IDS();
            const uint32_t pubE = pin(uPubE + (t4 < 3 ? (wp >> 2) * COL + 192 * (wp & 3) + 64 * t4 + 8 * q8 : (q8 >> 2) * COL + 768 + 4 * (q8 & 1)));
            xr = pin(sb + S_XB + 48 * (ln & 7));
            uint32_t x2 = 0;
            auto hop_d = [&](auto col) {
                const uint32_t xbs = pin(sb + S_XB + 384 * col.value + b_pos<40>(n80)), xas = col.value ? 0 : pin(sb + S_XA + 192 + a_pos(n80));
                const float x1 = bf_lo(lds16(xbs));
                const float lnx = __uint_as_float(pin(__float_as_uint(bfr(__fdiv_rn(bfr(x1 - mean), den)))));
                gather16(xp(uPolD + 4 * n80 + lag<DELAY_D>(sb, z0_)), col.value ? par1 : par0, 5 * ch + 3, [&](float y, uint32_t z) {
                    const uint32_t gate = ldsvol(sb + S_STAT + 4 * col.value + z);
                    x2 = pack2(x1 + bfr(lnx + bfr(bfr(y) * bf_hi(gate))), 0.f);
                    if (col.value) keep(x2); else { sts16(xbs, x2); sts16(xas, x2); }
                    return (uint32_t)((gate & 7) != ch + 1);
                });
                CSTAMP(17);
            };
            auto qproj = [&](auto with_stats) {
                bar_main();
                TST(5);
                CSTAMP(19);
                const uint32_t t4 = td & 3;
                const uint4 b = lds128(xr);
                uint32_t b4 = lds32(xr + 16);
                float acc[6][4] = {};
                if (with_stats.value) {
                    stp32_if((td & 11) == 3, xp(pubE ^ both), xp(pubE), stats(xr + (S_XA - S_XB), b, b4), par0);
                    __syncwarp();
                    b4 = lds32(xr + 16);
                }
                mul80(acc, Wq, b, b4);
                const float v0 = sel4(t4, acc[0][0] + acc[0][3], acc[2][0] + acc[2][3], acc[4][0] + acc[4][3], acc[4][0] + acc[4][3]);
                const float v1 = sel4(t4, acc[1][0] + acc[1][3], acc[3][0] + acc[3][3], acc[5][0] + acc[5][3], acc[5][0] + acc[5][3]);
                stp64_if(t4 < 3, xp(pubE ^ both), xp(pubE), tagw(v0, par0), tagw(v1, par0));
            };
            if (wp == 7) {
                if (!has0) break;
                qproj(std::true_type());
            } else {
                if (actc && !cc) hop_d(std::integral_constant<int, 0>());
                else {
                    if (actc && g == 0) {
                        const uint32_t po = pin(1280 * (ch - 1) + 160 * i + 2 * n80);
                        hop_d(std::integral_constant<int, 1>());
                        *reinterpret_cast<unsigned short*>(reinterpret_cast<char*>(P.out) + po) = (unsigned short)x2;
                    }
                    if (!has0) break;
                }
                qproj(std::false_type());
                sts32_if(td < 80, sb + S_XCAR + 4 * td, x2 << 16);
            }
        }
        CSTAMP(20);
        if (wp == 6) give_ln(uPolE, par0, sb + S_LN + 16, td, mean, den, [] { return 0u; });
        auto pass2 = [&](auto d0, auto d1, auto d2) {
            constexpr int D0 = d0.value, D1 = d1.value, D = D0 + D1 + d2.value;
            IDS();
            const uint32_t ua = sb + k_place(ch, wp & 6) * SLOT + (wp & 1) * UNIT, k0 = k_off(ln);
            uint32_t kf[12][2][4];
            auto ldk = [&](int s) { const uint32_t a = (k0 ^ (32 * (s / 3))) + (ua + 1024 * (s % 3)); ldsm4(kf[s][0], a); ldsm4(kf[s][1], a + SLOT); };
            auto ldv1 = [&](int k) { ldsm4t(vf[k / 3][k % 3], voff[k % 3] + (sb + v_place(ch, k / 3) * SLOT)); };
            auto ldv = [&](int s) { ldv1(3 * s); ldv1(3 * s + 1); ldv1(3 * s + 2); };
            constexpr uint32_t LATE = LAST_LATE;
            constexpr uint64_t EARLY_LIST = bit_list(~LATE), LATE_LIST = bit_list(LATE);
            auto early = [&](int k) {
                if (D1 == 0) ldk(k);
                else if (k < 3) { ldv1(9 + 2 * k); ldv1(10 + 2 * k); }
                else ldk((EARLY_LIST >> (4 * (k - 3))) & 15);
            };
            uint32_t v[8] = {}, qsa = 0;
            const char* srcv = xp(uPolE + lag<(D1 > 0 ? 0 : DELAY_E)>(sb, z0_) + 4 * td);
            auto look = [&] {
#pragma unroll
                for (int s = 0; s < 8; s++) v[s] = ldp32(srcv + (s >> 2) * HALF + (s & 3) * 1024);
            };
            if (D1 > 0) vaddr(voff);
            if (!(mbar_try(sb + S_FK + 8 * (wp & 6), par1) & mbar_try(sb + S_FK + 8 * (wp | 1), par1))) { mbar_wait(sb + S_FK + 8 * (wp & 6), par1); mbar_wait(sb + S_FK + 8 * (wp | 1), par1); }
#pragma unroll
            for (int s = 0; s < D0; s++) early(s);
            if (wp < 6) { look(); qsa = pin(sb + S_QS + 384 * ch + q_pos(z_)); }
#pragma unroll
            for (int s = D0; s < D0 + D1; s++) early(s);
            if (wp < 6) {
                const float cs = ldsf(sb + S_CSQ + 4 * td);
                int guard = 0;
                while (true) {
                    uint2 c = ldsvol64(sb + S_LN + 16 + ((v[0] ^ par0) & 1) * 32);
                    const bool stale = __any_sync(~0u, (chk8(v, par0) & 1) != 0), late = __any_sync(~0u, (c.y & 7) != ch + 1);
                    const float qs = sum8(v);
                    auto norm = [&] {
                        const uint32_t q = pack2(fmaf(-bf_hi(c.x), cs, qs) * asf(c.y), 0.f);
                        sts16(qsa, q);
                    };
                    norm();
                    if (!((stale | late) & (++guard < SPIN_LIMIT))) break;
                    if (!stale) { take_ln(c, sb + S_LN + 16); norm(); break; }
                    look();
                }
                SWEEPS(5 * ch + 4, guard - 1);
                CSTAMP(22);
            }
#pragma unroll
            for (int s = D0 + D1; s < D; s++) early(s);
            CSTAMP(21);
            bar_main();
            TST(6);
            CSTAMP(1);
            uint2 q = lds64(sb + S_QS + 384 * ch + 8 * ln);
            float acc[2][4] = {};
            constexpr int V0 = 13 - D, NV = D1 > 0 ? 2 : (2 * (D - 1)) / 3;
            static_assert(D1 == 0 || D - 3 + __builtin_popcount(LATE) == 12, "plan");
#pragma unroll
            for (int s = 0; s < 12; s++) {
                const bool m = q8 == (s & 7);
                const uint32_t b0 = m ? q.x : 0u, b1 = m ? q.y : 0u;
                if (s == 7) q = lds64(sb + S_QS + 384 * ch + 8 * ln + 256);
                mmaA(acc[0], kf[s][0], b0, b1);
                mmaA(acc[1], kf[s][1], b0, b1);
                if (D1 > 0) {
                    if (s >= 1 && s <= __builtin_popcount(LATE)) ldk((LATE_LIST >> (4 * (s - 1))) & 15);
                } else {
                    if (s >= 1 && s + D - 1 < 12) ldk(s + D - 1);
                    if (s >= 1 && s + D - 1 == 11) { __syncwarp(); arrive_if(ln == 0, sb + S_RELK); }
                    if (s == V0) vaddr(voff);
                    if (s >= V0 && 2 * (s - V0) < 3 * NV) ldv1(9 + 2 * (s - V0));
                    if (s >= V0 && 2 * (s - V0) + 1 < 3 * NV) ldv1(10 + 2 * (s - V0));
                }
            }
            CSTAMP(24);
            {
                const float v0 = acc[0][0] + acc[0][1], v1 = acc[0][2] + acc[0][3], v2 = acc[1][0] + acc[1][1], v3 = acc[1][2] + acc[1][3];
                const bool hi = t4 & 2, od = t4 & 1;
                const float u0 = (hi ? v2 : v0) + __shfl_xor_sync(~0u, hi ? v0 : v2, 2), u1 = (hi ? v3 : v1) + __shfl_xor_sync(~0u, hi ? v1 : v3, 2);
                const float s = (od ? u1 : u0) + __shfl_xor_sync(~0u, od ? u0 : u1, 1);
                CSTAMP(2);
                probs(scaled(s), sb + S_PS + PS_PASS, wp, ln);
                CSTAMP(3);
            }
            bar_main();
            TST(10);
            CSTAMP(4);
            if (D1 > 0) values(vf, acc_, [&](int s) { if (s < 3) ldv(s + 5); }, sb + S_PS + PS_PASS, std::integral_constant<int, 1>(), par0);
            else values(vf, acc_, [&](int s) { if (s >= (NV > 1 ? 2 : 1) && s + NV + (NV > 1 ? 1 : 2) < 8) ldv(s + NV + (NV > 1 ? 1 : 2)); }, sb + S_PS + PS_PASS, std::integral_constant<int, 1>(), par0);
            arrive_if(ln == 0, sb + S_RELV);
        };
        if (ch == 3) {
            pass2(std::integral_constant<int, LAST0>(), std::integral_constant<int, LAST1>(), std::integral_constant<int, LAST2>());
#pragma unroll
            for (int m = 0; m < 48; m++) Wq[m / 8].a[(m / 4) % 2][m % 4] = vf[3 + m / 12][(m / 4) % 3][m % 4];
#pragma unroll
            for (int m = 0; m < 12; m++) Wq[m / 2].c[m % 2] = vf[7][m / 4][m % 4];
#pragma unroll
            for (int m = 0; m < 36; m++) left[m] = m < 12 ? __float_as_uint(acc_[m / 4][m % 4]) : vf[m / 12][(m / 4) % 3][m % 4];
        } else {
            pass2(std::integral_constant<int, KPRE>(), std::integral_constant<int, 0>(), std::integral_constant<int, KPRE2>());
#pragma unroll
            for (int m = 0; m < 36; m++) left[m] = m < 12 ? __float_as_uint(acc_[m / 4][m % 4]) : vf[4 + m / 12][(m / 4) % 3][m % 4];
        }
        TST(11);
        CSTAMP(23);
    }
    sts32_if(td == 255, sb + S_GATE, 6);
    TSTAMP(3);
}

typedef CUresult (*EncodeFn)(CUtensorMap*, CUtensorMapDataType, cuuint32_t, void*, const cuuint64_t*, const cuuint64_t*, const cuuint32_t*,
                             const cuuint32_t*, CUtensorMapInterleave, CUtensorMapSwizzle, CUtensorMapL2promotion, CUtensorMapFloatOOBfill);

void make_map(EncodeFn enc, CUtensorMap* m, const void* base, uint64_t cols, uint64_t rows, uint32_t box_cols, uint32_t box_rows, bool swizzle) {
    cuuint64_t dims[2] = {cols, rows};
    cuuint64_t strides[1] = {cols * 2};
    cuuint32_t box[2] = {box_cols, box_rows};
    cuuint32_t es[2] = {1, 1};
    enc(m, CU_TENSOR_MAP_DATA_TYPE_BFLOAT16, 2, const_cast<void*>(base), dims, strides, box, es, CU_TENSOR_MAP_INTERLEAVE_NONE,
        swizzle ? CU_TENSOR_MAP_SWIZZLE_128B : CU_TENSOR_MAP_SWIZZLE_NONE, CU_TENSOR_MAP_L2_PROMOTION_NONE, CU_TENSOR_MAP_FLOAT_OOB_FILL_NONE);
}

}

extern "C" void kernel_launch(void* const* d_in, const int* in_sizes, int n_in, void* d_out, int out_size) {
    (void)in_sizes; (void)n_in; (void)out_size;
    static EncodeFn enc = nullptr;
    if (!enc) {
        void* f = nullptr;
        cudaDriverEntryPointQueryResult q;
        cudaGetDriverEntryPoint("cuTensorMapEncodeTiled", &f, cudaEnableDefault, &q);
        enc = (EncodeFn)f;
        cudaFuncSetAttribute(fused_kernel, cudaFuncAttributeMaxDynamicSharedMemorySize, SMEM_BYTES);
    }
    Params P;
    P.x = (const __nv_bfloat16*)d_in[0]; P.k = (const __nv_bfloat16*)d_in[1]; P.v = (const __nv_bfloat16*)d_in[2];
    P.wr = (const __nv_bfloat16*)d_in[6];
    P.out = (__nv_bfloat16*)d_out;
    Maps M;
    {
        cuuint64_t dims[4] = {64, 8, 3, (cuuint64_t)KV_BATCH_KEYS / 2}, strides[3] = {384, 128, 3072};
        cuuint32_t box[4] = {64, 8, 3, 2}, es[4] = {1, 1, 1, 1};
        enc(&M.k, CU_TENSOR_MAP_DATA_TYPE_BFLOAT16, 4, d_in[1], dims, strides, box, es, CU_TENSOR_MAP_INTERLEAVE_NONE, CU_TENSOR_MAP_SWIZZLE_128B,
            CU_TENSOR_MAP_L2_PROMOTION_NONE, CU_TENSOR_MAP_FLOAT_OOB_FILL_NONE);
    }
    make_map(enc, &M.v, P.v, 64, (uint64_t)12 * KV_BATCH_KEYS, 64, 96, true);
    make_map(enc, &M.vu, P.v, 64, (uint64_t)12 * KV_BATCH_KEYS, 64, 48, true);
    make_map(enc, &M.wq, d_in[3], 6144, 640, 192, 40, false);
    make_map(enc, &M.wo, d_in[4], 640, 6144, 80, 96, false);
    make_map(enc, &M.wg, d_in[7], 1536, 640, 96, 80, false);
    make_map(enc, &M.wu, d_in[8], 1536, 640, 96, 80, false);
    make_map(enc, &M.wd, d_in[9], 640, 1536, 80, 96, false);
    fused_kernel<<<NCTA, NTHR, SMEM_BYTES, cudaStreamPerThread>>>(P, M);
}
```

```cpp
#include <cuda_runtime.h>
#include <cuda.h>
#include <cuda_bf16.h>
#include <stdint.h>
#include <type_traits>

namespace {

constexpr int NCTA = 128;
constexpr int NTHR = 384;
constexpr int UNIT = 6144;
constexpr int SLOT = 12288;
#define TAU 3880
#define TAUW 3700
#define TAU0 3780
#define ILV 4
#define XB 900
#define FORCE_BOTH 0
#define TMIN 2400
#define SLACK 6000
#define SLACK0 1000
#define LEADW 3500
#define WIN_W 3
#define WIN_S 4
#define WIN_U 10
#define VPF 4
#define KRE_TAU 2600
#define RFR_TAU 22400
#define HOP1_NS 200
#define KPRE 2
#define KPRE2 2
#define LAST0 4
#define LAST1 4
#define LAST2 2
#define LAST_LATE 0xaa8
#define FSTEP 4
#define DELAY_L 2
#define DELAY_G 2
#define DELAY_C 3
#define DELAY_D 0
#define DELAY_E 1
#define REG_LO "40"
#define REG_HI "232"
#define SPIN_LOG 17
constexpr int SPIN_LIMIT = 1 << SPIN_LOG;

__host__ __device__ constexpr uint32_t pairL(uint32_t region, uint32_t c, uint32_t g) { return (g & 1) | ((g >> 1) << 2) | (c << 5) | (region << 6); }
__host__ __device__ constexpr uint32_t pairG(uint32_t d, uint32_t c, uint32_t i) { return (i & 1) | ((i >> 1) << 2) | (d << 4) | (c << 5) | (3u << 6); }
constexpr uint32_t RA = 0, RC = 1, RE = 2, HALF = 16384, COPY = 4096, PMASK = 0x59;
constexpr uint32_t XS = 0;
constexpr uint32_t XS2 = XS + 128 * 7680;
constexpr uint32_t XSEND = XS2 + 128 * 768;
__device__ uint4 g_s[XSEND / 16];
__device__ uint4 g_x[(4u << 20) / 16];
#define SWEEPS(k, n) do {} while (0)

constexpr uint32_t S_WD = 16 * SLOT;
constexpr uint32_t S_DUMMY = S_WD + 15360;
constexpr uint32_t S_BAR = S_DUMMY + 4096;
constexpr uint32_t S_FV = S_BAR, S_FK = S_FV + 64, S_RING = S_FK + 64, S_DBAR = S_RING + 48, S_WFULL = S_DBAR + 32, S_QRDY = S_WFULL + 88;
constexpr uint32_t S_RELK = S_QRDY + 8, S_RELV = S_RELK + 8, S_RELR = S_RELV + 8, S_RELW = S_RELR + 8, S_SCO = S_RELW + 24;
constexpr uint32_t S_OS1 = S_SCO + 8;
constexpr uint32_t S_ZERO = S_OS1 + 8;
constexpr uint32_t S_KF = S_ZERO + 8;
constexpr uint32_t S_TOK = S_KF + 8;
constexpr uint32_t S_SIDE = S_TOK + 80, S_GATE = S_SIDE + 4;
constexpr uint32_t S_STAT = S_GATE + 12, S_SWR = S_STAT + 16;
constexpr uint32_t S_LN = S_STAT + 32;
constexpr uint32_t S_XCAR = S_LN + 64;
constexpr uint32_t S_CSQ = S_XCAR + 320;
constexpr uint32_t S_CSGU = S_CSQ + 768;
constexpr uint32_t S_RED = S_CSGU + 768;
constexpr uint32_t S_L0 = S_RED;
constexpr uint32_t S_OS = S_RED + 5120;
constexpr uint32_t S_PS = S_OS + 1536;
constexpr uint32_t PS_MAX = 512, PS_PASS = 544;
constexpr uint32_t S_QS = S_PS + 2 * PS_PASS;
constexpr uint32_t S_XB = S_QS + 1536;
constexpr uint32_t S_XA = S_XB + 768;
constexpr uint32_t S_HS = S_XA + 768;
constexpr uint32_t S_X0 = S_HS + 768;
constexpr uint32_t S_SC = S_X0 + 640;
constexpr uint32_t S_TM = S_SC + 512;
constexpr int SMEM_BYTES = S_TM + 256;
static_assert(SMEM_BYTES <= 232448 && S_STAT % 16 == 0 && S_RED % 16 == 0 && S_XB % 16 == 0 && S_HS % 16 == 0 && S_PS % 16 == 0 && S_QS % 16 == 0, "smem");
static_assert(S_SCO == S_BAR + 44 * 8 && S_RELK == S_BAR + 38 * 8, "barriers");
constexpr uint32_t ST_WQ = 3 * SLOT, ST_WG = 8 * SLOT, ST_WO = 11 * SLOT;

__device__ __forceinline__ uint32_t smem_u32(const void* p) { return (uint32_t)__cvta_generic_to_shared(p); }
__device__ __forceinline__ void mbar_arrive(uint32_t bar) { asm volatile("mbarrier.arrive.shared::cta.b64 _, [%0];" :: "r"(bar) : "memory"); }
__device__ __forceinline__ bool mbar_try(uint32_t bar, uint32_t parity) {
    uint32_t ok;
    asm volatile("{\n .reg .pred p;\n mbarrier.try_wait.parity.shared::cta.b64 p, [%1], %2;\n selp.u32 %0, 1, 0, p;\n}" : "=r"(ok) : "r"(bar), "r"(parity) : "memory");
    return ok != 0;
}
__device__ __forceinline__ bool mbar_test(uint32_t bar, uint32_t parity) {
    uint32_t ok;
    asm volatile("{\n .reg .pred p;\n mbarrier.test_wait.parity.shared::cta.b64 p, [%1], %2;\n selp.u32 %0, 1, 0, p;\n}" : "=r"(ok) : "r"(bar), "r"(parity) : "memory");
    return ok != 0;
}
__device__ __forceinline__ void mbar_wait(uint32_t bar, uint32_t parity) {
    int n = 0;
    while (!mbar_try(bar, parity) && ++n < SPIN_LIMIT) {}
}
__device__ __forceinline__ uint32_t gtime32() { uint32_t t; asm volatile("mov.u32 %0, %globaltimer_lo;" : "=r"(t)); return t; }
__device__ __forceinline__ void bar_main() { asm volatile("bar.sync 1, 256;" ::: "memory"); }

__device__ __forceinline__ void mma16816(float (&c)[4], uint32_t a0, uint32_t a1, uint32_t a2, uint32_t a3, uint32_t b0, uint32_t b1) {
    asm("mma.sync.aligned.m16n8k16.row.col.f32.bf16.bf16.f32 {%0,%1,%2,%3}, {%4,%5,%6,%7}, {%8,%9}, {%0,%1,%2,%3};"
        : "+f"(c[0]), "+f"(c[1]), "+f"(c[2]), "+f"(c[3]) : "r"(a0), "r"(a1), "r"(a2), "r"(a3), "r"(b0), "r"(b1));
}
__device__ __forceinline__ void mmaA(float (&c)[4], const uint32_t (&a)[4], uint32_t b0, uint32_t b1) { mma16816(c, a[0], a[1], a[2], a[3], b0, b1); }
__device__ __forceinline__ void mma8(float (&c)[4], uint32_t a0, uint32_t a1, uint32_t b0) {
    asm("mma.sync.aligned.m16n8k8.row.col.f32.bf16.bf16.f32 {%0,%1,%2,%3}, {%4,%5}, {%6}, {%0,%1,%2,%3};"
        : "+f"(c[0]), "+f"(c[1]), "+f"(c[2]), "+f"(c[3]) : "r"(a0), "r"(a1), "r"(b0));
}
struct W80 { uint32_t a[2][4], c[2]; };
template <int N> __device__ __forceinline__ void mul80(float (&acc)[N][4], const W80 (&W)[N], const uint4& b, uint32_t b4) {
#pragma unroll
    for (int m = 0; m < N; m++) mmaA(acc[m], W[m].a[0], b.x, b.y);
#pragma unroll
    for (int m = 0; m < N; m++) mmaA(acc[m], W[m].a[1], b.z, b.w);
#pragma unroll
    for (int m = 0; m < N; m++) mma8(acc[m], W[m].c[0], W[m].c[1], b4);
}
__device__ __forceinline__ void ldsm2t(uint32_t (&r)[2], uint32_t addr) {
    asm volatile("ldmatrix.sync.aligned.m8n8.x2.trans.shared.b16 {%0,%1}, [%2];" : "=r"(r[0]), "=r"(r[1]) : "r"(addr) : "memory");
}
__device__ __forceinline__ void mmaV(float (&c)[4], const uint4& a, uint32_t b0, uint32_t b1) { mma16816(c, a.x, a.y, a.z, a.w, b0, b1); }
__device__ __forceinline__ void ldsm4(uint32_t (&r)[4], uint32_t addr) {
    asm volatile("ldmatrix.sync.aligned.m8n8.x4.shared.b16 {%0,%1,%2,%3}, [%4];" : "=r"(r[0]), "=r"(r[1]), "=r"(r[2]), "=r"(r[3]) : "r"(addr) : "memory");
}
__device__ __forceinline__ void ldsm4t(uint32_t (&r)[4], uint32_t addr) {
    asm volatile("ldmatrix.sync.aligned.m8n8.x4.trans.shared.b16 {%0,%1,%2,%3}, [%4];" : "=r"(r[0]), "=r"(r[1]), "=r"(r[2]), "=r"(r[3]) : "r"(addr) : "memory");
}
__device__ __forceinline__ uint32_t lds16(uint32_t a) { uint16_t v; asm volatile("ld.shared.u16 %0, [%1];" : "=h"(v) : "r"(a) : "memory"); return v; }
__device__ __forceinline__ uint32_t lds32(uint32_t a) { uint32_t v; asm volatile("ld.shared.u32 %0, [%1];" : "=r"(v) : "r"(a) : "memory"); return v; }
__device__ __forceinline__ float ldsf(uint32_t a) { return __uint_as_float(lds32(a)); }
__device__ __forceinline__ uint2 lds64(uint32_t a) { uint2 v; asm volatile("ld.shared.v2.u32 {%0,%1}, [%2];" : "=r"(v.x), "=r"(v.y) : "r"(a) : "memory"); return v; }
__device__ __forceinline__ uint4 lds128(uint32_t a) { uint4 v; asm volatile("ld.shared.v4.u32 {%0,%1,%2,%3}, [%4];" : "=r"(v.x), "=r"(v.y), "=r"(v.z), "=r"(v.w) : "r"(a) : "memory"); return v; }
__device__ __forceinline__ int ldsvol(uint32_t a) { int v; asm volatile("ld.volatile.shared.u32 %0, [%1];" : "=r"(v) : "r"(a) : "memory"); return v; }
__device__ __forceinline__ uint2 ldsvol64(uint32_t a) { uint2 v; asm volatile("{\n .reg .b64 d;\n ld.volatile.shared.b64 d, [%2];\n mov.b64 {%0,%1}, d;\n}" : "=r"(v.x), "=r"(v.y) : "r"(a) : "memory"); return v; }
__device__ __forceinline__ void stsvol64(uint32_t a, uint32_t x, uint32_t y) { asm volatile("{\n .reg .b64 d;\n mov.b64 d, {%1,%2};\n st.volatile.shared.b64 [%0], d;\n}" :: "r"(a), "r"(x), "r"(y) : "memory"); }
__device__ __forceinline__ void stsvol(uint32_t a, int v) { asm volatile("st.volatile.shared.u32 [%0], %1;" :: "r"(a), "r"(v) : "memory"); }
__device__ __forceinline__ void sts_hi16(uint32_t a, float v) { asm volatile("{\n .reg .b16 lo, hi;\n mov.b32 {lo, hi}, %1;\n st.shared.u16 [%0], hi;\n}" :: "r"(a), "r"(__float_as_uint(v)) : "memory"); }
__device__ __forceinline__ void sts16(uint32_t a, uint32_t v) { asm volatile("st.shared.u16 [%0], %1;" :: "r"(a), "r"(v) : "memory"); }
__device__ __forceinline__ void sts32(uint32_t a, uint32_t v) { asm volatile("st.shared.u32 [%0], %1;" :: "r"(a), "r"(v) : "memory"); }
__device__ __forceinline__ void stsf(uint32_t a, float v) { sts32(a, __float_as_uint(v)); }
__device__ __forceinline__ void sts64(uint32_t a, uint32_t x, uint32_t y) { asm volatile("st.shared.v2.u32 [%0], {%1,%2};" :: "r"(a), "r"(x), "r"(y) : "memory"); }

__device__ __forceinline__ void sts32_if(bool p, uint32_t a, uint32_t v) {
    asm volatile("{\n .reg .pred p;\n setp.ne.u32 p, %2, 0;\n @p st.shared.u32 [%0], %1;\n}" :: "r"(a), "r"(v), "r"((uint32_t)p) : "memory");
}
__device__ __forceinline__ void arrive_if(bool p, uint32_t bar) {
    asm volatile("{\n .reg .pred p;\n setp.ne.u32 p, %1, 0;\n @p mbarrier.arrive.shared::cta.b64 _, [%0];\n}" :: "r"(bar), "r"((uint32_t)p) : "memory");
}
__device__ __forceinline__ void keep(uint32_t& v) { asm volatile("" : "+r"(v)); }
__device__ __forceinline__ void keep(float& v) { asm volatile("" : "+f"(v)); }

__device__ __forceinline__ uint32_t ldp32(const char* p) { uint32_t v; asm volatile("ld.relaxed.gpu.global.u32 %0, [%1];" : "=r"(v) : "l"(p) : "memory"); return v; }
__device__ __forceinline__ uint2 ldp64(const char* p) {
    uint2 v; asm volatile("{\n .reg .b64 d;\n ld.relaxed.gpu.global.b64 d, [%2];\n mov.b64 {%0,%1}, d;\n}" : "=r"(v.x), "=r"(v.y) : "l"(p) : "memory"); return v;
}
__device__ __forceinline__ uint32_t tagw(float f, uint32_t par) { return (__float_as_uint(f) & ~1u) | par; }
__device__ __forceinline__ void stp32(char* p, float a, uint32_t par) { asm volatile("st.relaxed.gpu.global.u32 [%0], %1;" :: "l"(p), "r"(tagw(a, par)) : "memory"); }
__device__ __forceinline__ void stp64(char* p, float a, float b, uint32_t par) {
    asm volatile("{\n .reg .b64 d;\n mov.b64 d, {%1,%2};\n st.relaxed.gpu.global.b64 [%0], d;\n}" :: "l"(p), "r"(tagw(a, par)), "r"(tagw(b, par)) : "memory");
}
__device__ __forceinline__ void stp32_if(bool p, char* d, float a, uint32_t par) {
    asm volatile("{\n .reg .pred p;\n setp.ne.u32 p, %2, 0;\n @p st.relaxed.gpu.global.u32 [%0], %1;\n @p st.relaxed.gpu.global.u32 [%0+4096], %1;\n}" :: "l"(d), "r"(tagw(a, par)), "r"((uint32_t)p) : "memory");
}
__device__ __forceinline__ void stp32_if(bool p, char* d, char* e, float a, uint32_t par) {
    asm volatile("{\n .reg .pred p;\n setp.ne.u32 p, %2, 0;\n @p st.relaxed.gpu.global.u32 [%0], %1;\n @p st.relaxed.gpu.global.u32 [%3], %1;\n}" :: "l"(d), "r"(tagw(a, par)), "r"((uint32_t)p), "l"(e) : "memory");
}
__device__ __forceinline__ void stp64_if(bool p, char* d, char* e, uint32_t lo, uint32_t hi) {
    asm volatile("{\n .reg .pred p;\n .reg .b64 d;\n setp.ne.u32 p, %3, 0;\n mov.b64 d, {%1,%2};\n @p st.relaxed.gpu.global.b64 [%0], d;\n @p st.relaxed.gpu.global.b64 [%4], d;\n}" :: "l"(d), "r"(lo), "r"(hi), "r"((uint32_t)p), "l"(e) : "memory");
}
__device__ __forceinline__ uint32_t chk2(uint32_t a, uint32_t b, uint32_t par) { uint32_t r; asm("lop3.b32 %0, %1, %2, %3, 0x7E;" : "=r"(r) : "r"(a), "r"(b), "r"(par)); return r; }
__device__ __forceinline__ uint32_t or3(uint32_t a, uint32_t b, uint32_t c) { uint32_t r; asm("lop3.b32 %0, %1, %2, %3, 0xFE;" : "=r"(r) : "r"(a), "r"(b), "r"(c)); return r; }
__device__ __forceinline__ uint32_t chk8(const uint32_t (&v)[8], uint32_t par) { return or3(chk2(v[0], v[1], par), chk2(v[2], v[3], par), or3(chk2(v[4], v[5], par), chk2(v[6], v[7], par), 0)); }
__device__ __forceinline__ uint32_t chk8(const uint2 (&v)[8], uint32_t par) { return or3(chk2(v[0].x, v[1].x, par), chk2(v[2].x, v[3].x, par), or3(chk2(v[4].x, v[5].x, par), chk2(v[6].x, v[7].x, par), 0)); }
__device__ __forceinline__ uint32_t chk8y(const uint2 (&v)[8], uint32_t par) { return or3(chk2(v[0].y, v[1].y, par), chk2(v[2].y, v[3].y, par), or3(chk2(v[4].y, v[5].y, par), chk2(v[6].y, v[7].y, par), 0)); }
__device__ __forceinline__ uint32_t chk4(const uint2 (&v)[4], uint32_t par) { return or3(chk2(v[0].x, v[0].y, par), chk2(v[1].x, v[1].y, par), or3(chk2(v[2].x, v[2].y, par), chk2(v[3].x, v[3].y, par), 0)); }
__device__ __forceinline__ float asf(uint32_t v) { return __uint_as_float(v); }
__device__ __forceinline__ float sum8(const uint32_t (&v)[8]) { return ((asf(v[0]) + asf(v[1])) + (asf(v[2]) + asf(v[3]))) + ((asf(v[4]) + asf(v[5])) + (asf(v[6]) + asf(v[7]))); }
__device__ __forceinline__ float sum8x(const uint2 (&v)[8]) { return ((asf(v[0].x) + asf(v[1].x)) + (asf(v[2].x) + asf(v[3].x))) + ((asf(v[4].x) + asf(v[5].x)) + (asf(v[6].x) + asf(v[7].x))); }
__device__ __forceinline__ float sum8y(const uint2 (&v)[8]) { return ((asf(v[0].y) + asf(v[1].y)) + (asf(v[2].y) + asf(v[3].y))) + ((asf(v[4].y) + asf(v[5].y)) + (asf(v[6].y) + asf(v[7].y))); }

__device__ __forceinline__ uint32_t pack2(float lo, float hi) { uint32_t r; asm("cvt.rn.bf16x2.f32 %0, %1, %2;" : "=r"(r) : "f"(hi), "f"(lo)); return r; }
__device__ __forceinline__ float bfr(float x) { return __uint_as_float(pack2(0.0f, x)); }
__device__ __forceinline__ float ex2(float x) { float r; asm("ex2.approx.ftz.f32 %0, %1;" : "=f"(r) : "f"(x)); return r; }
__device__ __forceinline__ float rcp(float x) { float r; asm("rcp.approx.ftz.f32 %0, %1;" : "=f"(r) : "f"(x)); return r; }
__device__ __forceinline__ float sqrt_(float x) { float r; asm("sqrt.approx.ftz.f32 %0, %1;" : "=f"(r) : "f"(x)); return r; }
__device__ __forceinline__ float bf_lo(uint32_t v) { return __uint_as_float(v << 16); }
__device__ __forceinline__ float bf_hi(uint32_t v) { return __uint_as_float(v & 0xffff0000u); }
__device__ __forceinline__ float sel4(int k, float a, float b, float c, float d) { return (k & 2) ? ((k & 1) ? d : c) : ((k & 1) ? b : a); }
constexpr float LOG2E = 1.4426950408889634f;
constexpr uint32_t ONES = 0x3f803f80u;

__device__ __forceinline__ void ln_stats(float sum, float sq, float& mean, float& den) {
    const float m = sum * (1.0f / 640.0f);
    const float var = fmaxf(fmaf(sq, 1.0f / 640.0f, -m * m), 0.0f);
    mean = bfr(m);
    den = bfr(sqrt_(bfr(bfr(var) + 1e-5f)));
}
__device__ __forceinline__ float sigmoidf_(float x) { return rcp(1.0f + ex2(-x * LOG2E)); }

#define TSTAMP(k) do {} while (0)
#define TST(k) do {} while (0)

#define CSTAMP(k) do {} while (0)
template <int N> __device__ __forceinline__ uint32_t lag(uint32_t sb, uint32_t z = 0) {
#pragma unroll
    for (int k = 0; k < N; k++) z = ldsvol(sb + S_ZERO + z);
    return z;
}
__device__ __forceinline__ void warm_mma(uint32_t& a, uint32_t& b) {
    asm volatile("mma.sync.aligned.m16n8k8.row.col.f16.f16.f16.f16 {%0,%1}, {%0,%1}, {%0}, {%0,%1};" : "+r"(a), "+r"(b) :: "memory");
}
#define KWNS2 20
#define KWNS 200
template <class F>
__device__ __forceinline__ void gather16(const char* p, uint32_t par, int k, F use) {
    uint32_t v[8], u[8];
    int guard = 0;
    bool again;
    do {
#pragma unroll
        for (int s = 0; s < 8; s++) v[s] = ldp32(p + s * 512);
#pragma unroll
        for (int s = 0; s < 8; s++) u[s] = ldp32(p + HALF + s * 512);
        const uint32_t stale = use(sum8(v) + sum8(u), ((v[0] ^ par) & 1) * 8);
        again = __any_sync(~0u, (or3(chk8(v, par), chk8(u, par), stale) & 1) != 0);
    } while (again & (++guard < SPIN_LIMIT));
    SWEEPS(k, guard - 1);
}

struct Params {
    const __nv_bfloat16 *x, *k, *v, *wr, *wq;
    __nv_bfloat16* out;
};
struct Maps { CUtensorMap k, v, vu, wq, wo, wg, wu, wd; };

constexpr int KV_BATCH_KEYS = 32 * 4096;

__device__ __forceinline__ void tma2d(uint32_t dst, const CUtensorMap* m, int c0, int c1, uint32_t bar, uint32_t bytes, uint64_t pol) {
    asm volatile("{\n .reg .pred p;\n elect.sync _|p, 0xffffffff;\n"
                 " @p mbarrier.arrive.expect_tx.shared::cta.b64 _, [%2], %6;\n"
                 " @p cp.async.bulk.tensor.2d.shared::cluster.global.mbarrier::complete_tx::bytes.L2::cache_hint [%0], [%1, {%3, %4}], [%2], %5;\n}"
                 :: "r"(dst), "l"(m), "r"(bar), "r"(c0), "r"(c1), "l"(pol), "r"(bytes) : "memory");
}
__device__ __forceinline__ void scrap_copy(uint32_t dst, const char* src, uint32_t bar) {
    asm volatile("{\n .reg .pred p;\n elect.sync _|p, 0xffffffff;\n"
                 " @p mbarrier.arrive.expect_tx.shared::cta.b64 _, [%2], 12288;\n"
                 " @p cp.async.bulk.shared::cluster.global.mbarrier::complete_tx::bytes [%0], [%1], 4096, [%2];\n"
                 " @p cp.async.bulk.shared::cluster.global.mbarrier::complete_tx::bytes [%0], [%1+4096], 4096, [%2];\n"
                 " @p cp.async.bulk.shared::cluster.global.mbarrier::complete_tx::bytes [%0], [%1+8192], 4096, [%2];\n}"
                 :: "r"(dst), "l"(src), "r"(bar) : "memory");
}
__device__ __forceinline__ void prefetch_l2(const void* p, uint32_t bytes) {
    asm volatile("{\n .reg .pred p;\n elect.sync _|p, 0xffffffff;\n @p cp.async.bulk.prefetch.L2.global [%0], %1;\n}" :: "l"(p), "r"(bytes) : "memory");
}
__device__ __forceinline__ uint64_t pol_first() { uint64_t p; asm("createpolicy.fractional.L2::evict_first.b64 %0, 1.0;" : "=l"(p)); return p; }
__device__ __forceinline__ uint64_t pol_normal() { uint64_t p; asm("createpolicy.fractional.L2::evict_normal.b64 %0, 1.0;" : "=l"(p)); return p; }
__device__ __forceinline__ bool utest(uint32_t bar, uint32_t parity) { return __all_sync(~0u, mbar_test(bar, parity)); }
__device__ __forceinline__ void uwait(uint32_t bar, uint32_t parity) {
    int n = 0;
    while (!__all_sync(~0u, mbar_try(bar, parity)) && ++n < SPIN_LIMIT) {}
}
template <int A, int B, int CNT> __device__ __forceinline__ void init_bars(uint32_t sb) {
#pragma unroll 1
    for (int k = A; k < B; k++)
        asm volatile("{\n .reg .pred p;\n elect.sync _|p, 0xffffffff;\n @p mbarrier.init.shared::cta.b64 [%0], %1;\n}" :: "r"(sb + S_BAR + 8 * k), "n"(CNT) : "memory");
}
__device__ __forceinline__ int unit_key(uint32_t b, uint32_t u) {
    return (blockIdx.x >> 2) * 4096 + 3072 + (blockIdx.x & 3) * (16 * ILV) + b * KV_BATCH_KEYS + (u & ~(ILV - 1u)) * 64 + (u & (ILV - 1)) * 16;
}
__device__ __forceinline__ void load_tile(const CUtensorMap* m, uint32_t dst, uint32_t bar, uint32_t bytes, int key, uint64_t pol) { tma2d(dst, m, 0, 3 * key, bar, bytes, pol); }
__device__ __forceinline__ const char* unit_ptr(const Params& P, int n) { return (const char*)((n & 16) ? P.v : P.k) + (size_t)unit_key(n >> 5, n & 15) * 384; }
#define LSTAMP(k) do {} while (0)

__device__ __forceinline__ uint32_t k_place(uint32_t b, uint32_t s) { return s + 3 + 5 * (b & 1); }
__device__ __forceinline__ uint32_t v_place(uint32_t b, uint32_t s) { return s < 3 ? s : s + 8 - 8 * (b & 1); }
__device__ __forceinline__ void k_load(const Maps& M, uint32_t dst, uint32_t bar, int key8, uint64_t pol) {
    asm volatile("{\n .reg .pred p;\n elect.sync _|p, 0xffffffff;\n"
                 " @p mbarrier.arrive.expect_tx.shared::cta.b64 _, [%2], 6144;\n"
                 " @p cp.async.bulk.tensor.4d.shared::cluster.global.mbarrier::complete_tx::bytes.L2::cache_hint [%0], [%1, {0, 0, 0, %3}], [%2], %4;\n}"
                 :: "r"(dst), "l"(&M.k), "r"(bar), "r"(key8), "l"(pol) : "memory");
}
__device__ __forceinline__ int unit_key8(uint32_t n) { return unit_key(n >> 4, n & 15) >> 3; }
__device__ __forceinline__ void ring_load(const Maps& M, uint32_t sb, uint32_t b, uint32_t u, uint32_t pos) {
    if (u < 16) k_load(M, sb + pos * UNIT, sb + S_RING + 8 * pos, unit_key8(16 * b + u), pol_normal());
    else load_tile(&M.vu, sb + pos * UNIT, sb + S_FV + 4 * (pos & 6), UNIT, unit_key(b, pos), pol_first());
}
__device__ __forceinline__ uint32_t token(bool p, uint32_t a, uint32_t n) {
    uint32_t v;
    asm volatile("{\n .reg .pred p;\n setp.ne.u32 p, %2, 0;\n mov.u32 %0, 0;\n @p atom.shared.exch.b32 %0, [%1], %3;\n}" : "=r"(v) : "r"(a), "r"((uint32_t)p), "r"(n) : "memory");
    return v;
}
__device__ __forceinline__ void place_load(const Maps& M, uint32_t sb, uint32_t n) {
    k_load(M, sb + k_place(n >> 4, 0) * SLOT + (n & 15) * UNIT, sb + S_FK + 4 * (n & 14), unit_key8(n), pol_first());
}
__device__ __forceinline__ void v_load(const Maps& M, uint32_t sb, uint32_t b, uint32_t s) {
    load_tile(&M.v, sb + v_place(b, s) * SLOT, sb + S_FV + 8 * s, SLOT, unit_key(b, 2 * s), pol_first());
}

__device__ __forceinline__ void stream_warp(const Params& P, const Maps& M, uint32_t sb, uint32_t lane) {
    const uint64_t pol = pol_first();
    const int bid = blockIdx.x, g = bid >> 3, i = bid & 7;
    const uint32_t wf = sb + S_WFULL;
    uint32_t tn = __shfl_sync(~0u, gtime32(), 0) * 16;
    auto pace = [&](uint32_t dt) {
        int k = 0;
        uint32_t now;
        do now = __shfl_sync(~0u, gtime32(), 0) * 16; while ((int)(now - tn) < 0 && ++k < SPIN_LIMIT);
        if ((int)(now - tn) > SLACK0) tn = now - SLACK0;
        tn += dt;
    };
#pragma unroll
    for (int k = 0; k < 10; k++) {
        if (k < 2) {
            if (k == 0) init_bars<26, 27, 1>(sb); else init_bars<27, 37, 1>(sb);
            asm volatile("fence.mbarrier_init.release.cluster;" ::: "memory");
            if (k == 1) { asm volatile("bar.arrive 2, %0;" :: "n"(NTHR) : "memory"); asm volatile("bar.sync 3, 128;" ::: "memory"); }
        }
        if (k >= WIN_W) uwait(wf + 8 * (k - WIN_W), 0);
        pace(TAUW * 5 / 2 - (k == 0 || k == 2 ? LEADW : 0));
        if (k < 4) tma2d(sb + ST_WQ + 15360 * k, &M.wq, 384 * g + 192 * (k >> 1), 80 * i + 40 * (k & 1), wf + 8 * k, 15360, pol);
        else if (k < 6) tma2d(sb + ST_WG + 15360 * (k - 4), k == 4 ? &M.wg : &M.wu, 96 * g, 80 * i, wf + 8 * k, 15360, pol);
        else tma2d(sb + ST_WO + 15360 * (k - 6), &M.wo, 80 * i, 384 * g + 96 * (k - 6), wf + 8 * k, 15360, pol);
    }
#pragma unroll 1
    for (int n = 0; n < 16; n++) {
        if (n == 0 || n == 5 || n == 11) uwait(sb + S_RELW + (n == 0 ? 0 : n == 5 ? 8 : 16), 0);
        uwait(n < WIN_S ? wf + 8 * (10 - WIN_S + n) : sb + S_FV + 8 * ((n - WIN_S) ^ 8), 0);
        pace(2 * TAU0);
        if (n >= WIN_S && !utest(sb + S_FV + 8 * ((n - WIN_S + 1) ^ 8), 0)) tn += XB;
        if (n < 8) { place_load(M, sb, 2 * n); place_load(M, sb, 2 * n + 1); }
        else if (n < 11) { ring_load(M, sb, 0, 2 * n, 2 * n - 16); ring_load(M, sb, 0, 2 * n + 1, 2 * n - 15); }
        else v_load(M, sb, 0, n - 8);
        if (n == 7) { pace(TAUW * 5 / 2); tma2d(sb + S_WD, &M.wd, 80 * i, 96 * g, wf + 80, 15360, pol); }
    }
    int nd = 0;
    uint32_t q[4];
#pragma unroll
    for (int r = 0; r < 4; r++) q[r] = sb + S_FV + 8 * (7 - r);
    uint32_t td = tn;
    uint32_t pos = 2;
#pragma unroll 1
    for (int m = 16; m < 64; m++) {
        const int b = m >> 4, j = m & 15;
        const char* src = unit_ptr(P, 2 * m);
        const uint32_t tok = sb + S_TOK + (j < 3 ? 4 * pos : j < 11 ? 24 + 4 * pos : 16 + 4 * j) + 4 * lane;
        static_assert(WIN_U <= 12, "a ring position has at most one token of the timetable");
        int k = 0;
        while (true) {
            const uint2 c = lds64(sb + S_KF);
            if (__all_sync(~0u, mbar_test(q[WIN_S - 1] & ~1u, q[WIN_S - 1] & 1) & (min((int)c.x + 1, (int)c.y) >= 16 * b + min(2 * j + 2 - WIN_U, 16))) || ++k >= SPIN_LIMIT) break;
        }
        uint32_t now;
        while (true) {
            now = __shfl_sync(~0u, gtime32(), 0) * 16;
            if ((int)(now - td) >= 0 || ++k >= SPIN_LIMIT) break;
        }
        const uint32_t mine = __ballot_sync(~0u, token(lane < (j < 11 ? 2 : 1), tok, 2 * m + lane) == 2 * m + lane);
        {
            const uint2 c = lds64(sb + S_KF);
            if (!__all_sync(~0u, mbar_test(q[WIN_S - 2] & ~1u, q[WIN_S - 2] & 1) & (min((int)c.x + 1, (int)c.y) >= 16 * b + min(2 * j + 4 - WIN_U, 16)))) tn += XB;
        }
        q[3] = q[2]; q[2] = q[1]; q[1] = q[0]; q[0] = sb + S_QRDY;
        if (j < 11) {
            if (mine & 1) ring_load(M, sb, b, 2 * j, pos); else prefetch_l2(src, UNIT);
            if (mine & 2) ring_load(M, sb, b, 2 * j + 1, pos + 1); else prefetch_l2(src + UNIT, UNIT);
            if (j >= 8) q[0] = (sb + S_FV + 8 * (j - 8)) | (b & 1);
        } else if (mine) { v_load(M, sb, b, j - 8); q[0] = (sb + S_FV + 8 * (j - 8)) | (b & 1); }
        else if (j - 8 >= VPF) prefetch_l2(src, SLOT);
        else {
            scrap_copy(sb + S_DUMMY, src, sb + S_DBAR + 8 * (nd & 3));
            q[0] = (sb + S_DBAR + 8 * (nd & 3)) | ((nd >> 2) & 1);
            nd++;
        }
        pos = j == 15 ? 2 : pos == 4 ? 0 : pos + 2;
        if ((int)(now - tn) > SLACK) tn = now - SLACK;
        tn += 2 * TAU;
        td = (int)(tn - now) > 2 * TMIN ? tn : now + 2 * TMIN;
    }
#pragma unroll 1
    for (int m = max(nd - 4, 0); m < nd; m++) uwait(sb + S_DBAR + 8 * (m & 3), (m >> 2) & 1);
}

__host__ __device__ constexpr uint64_t bit_list(uint32_t m) { uint64_t r = 0; int n = 0; for (int k = 0; k < 12; k++) if ((m >> k) & 1) r |= (uint64_t)k << (4 * n++); return r; }
__device__ __forceinline__ float scaled(float s) { return bfr(bfr(s) * 0.07216878364870322f); }
__device__ __forceinline__ void probs(float s, uint32_t ps, uint32_t src, uint32_t ln) {
    const uint32_t q8 = ln >> 2, t4 = ln & 3;
    int key = __float_as_int(s);
    key ^= (key >> 31) & 0x7fffffff;
    key = __reduce_max_sync(~0u, key);
    key ^= (key >> 31) & 0x7fffffff;
    const float ml = __int_as_float(key) * LOG2E;
    sts16(ps + 64 * src + (q8 >> 1) * 16 + t4 * 4 + (q8 & 1) * 2, pack2(ex2(fmaf(s, LOG2E, -ml)), 0.f));
    stsf(ps + PS_MAX + 4 * src, ml);
}
template <int H> __device__ __forceinline__ uint32_t b_pos(uint32_t e) { const uint32_t h = e >= H, k = e - H * h; return h * 192 + (k & 6) * 24 + (k >> 3) * 4 + (k & 1) * 2; }
__device__ __forceinline__ uint32_t a_pos(uint32_t e) { const uint32_t h = e >= 40, k = e - 40 * h; return (k & 6) * 24 + (k >> 3) * 8 + h * 4 + (k & 1) * 2; }
__device__ __forceinline__ uint32_t q_pos(uint32_t d) { const uint32_t s = 3 * ((d >> 4) & 3) + (d >> 6); return s * 32 + (d & 6) * 4 + ((d >> 3) & 1) * 4 + (d & 1) * 2; }
__device__ __forceinline__ uint32_t k_off(uint32_t ln) { return (ln & 8) * 384 + (ln & 7) * 128 + (((ln & 7) ^ (ln >> 4)) << 4); }

#define HSTAMP(k) do {} while (0)
__device__ __forceinline__ char* xwindow() { return reinterpret_cast<char*>((reinterpret_cast<uintptr_t>(g_x) + (2u << 20) - 1) & ~(uintptr_t)((2u << 20) - 1)); }

struct XPtr {
    uint32_t lo, hi;
    __device__ __forceinline__ explicit XPtr(char* p) : lo((uint32_t)(uintptr_t)p), hi((uint32_t)((uintptr_t)p >> 32)) {}
    __device__ __forceinline__ XPtr(uint32_t l, uint32_t h) : lo(l), hi(h) {}
    __device__ __forceinline__ XPtr operator+(uint32_t o) const { return XPtr(lo + o, hi); }
    __device__ __forceinline__ operator char*() const { uint64_t p; asm("mov.b64 %0, {%1, %2};" : "=l"(p) : "r"(lo), "r"(hi)); return (char*)p; }
};

__device__ __forceinline__ char* side_word(uint32_t g, uint32_t i) { return xwindow() + pairG(1, 0, i) * 8192 + (g >> 3) * HALF + (g & 7) * 512 + 320; }

__device__ __forceinline__ uint32_t probe_side() {
    const uint32_t bid = blockIdx.x, g = bid >> 3, i = bid & 7, P = pairG(0, 0, i);
    char* p = xwindow() + P * 8192 + (g >> 3) * HALF + (g & 7) * 512 + 352;
    uint32_t best[2] = {~0u, ~0u};
#pragma unroll
    for (int k = 0; k < 4; k++) *reinterpret_cast<uint4*>(p + (k & 1) * 16 + (k >> 1) * COPY) = make_uint4(1, 1, 1, 1);
#pragma unroll 1
    for (int r = 0; r < 64; r++) {
        if (r >= 4 && !(r & 1) && min(best[0], best[1]) < 380 && max(best[0], best[1]) > min(best[0], best[1]) + 80) break;
        uint32_t c0, c1, v;
        asm volatile("mov.u32 %0, %clock;" : "=r"(c0) :: "memory");
        asm volatile("atom.relaxed.gpu.global.exch.b32 %0, [%1], 0;" : "=r"(v) : "l"(p + (r & 1) * COPY) : "memory");
        asm volatile("{\n .reg .pred q;\n setp.eq.u32 q, %1, 0x13579bdf;\n mov.u32 %0, 0;\n @!q mov.u32 %0, %clock;\n}" : "=r"(c1) : "r"(v) : "memory");
        if (r & 1) best[1] = min(best[1], c1 - c0); else best[0] = min(best[0], c1 - c0);
    }
    return 1 + ((best[1] < best[0]) ^ (__popc(P & PMASK) & 1));
}

template <int N>
__device__ __forceinline__ void hop_a(const char* src, uint32_t par, uint32_t dst, bool st, int k) {
    uint2 v[N][4];
    float e[4], rl;
    int guard = 0;
    bool again;
    do {
#pragma unroll
        for (int s = 0; s < 4 * N; s++) v[s / 4][s % 4] = ldp64(src + (s / 4) * 256 + (s % 4) * 1024);
        again = __any_sync(~0u, ((chk4(v[0], par) | chk4(v[N - 1], par)) & 1) != 0);
        const int M = max(max((int)v[0][0].x, (int)v[0][1].x), max((int)v[0][2].x, (int)v[0][3].x)) - 254;
#pragma unroll
        for (int s = 0; s < 4; s++) e[s] = __int_as_float(max((int)v[0][s].x - M, 0) << 22);
        rl = rcp(fmaf(e[0], asf(v[0][0].y), e[1] * asf(v[0][1].y)) + fmaf(e[2], asf(v[0][2].y), e[3] * asf(v[0][3].y)));
#pragma unroll
        for (int s = 0; s < 4; s++) e[s] = __shfl_sync(~0u, e[s], 24);
        keep(rl);
    } while (again & (++guard < SPIN_LIMIT));
    rl = __shfl_sync(~0u, rl, 24);
#pragma unroll
    for (int n = 0; n < N; n++) {
        const float o0 = fmaf(e[0], asf(v[n][0].x), e[1] * asf(v[n][1].x)) + fmaf(e[2], asf(v[n][2].x), e[3] * asf(v[n][3].x));
        const float o1 = fmaf(e[0], asf(v[n][0].y), e[1] * asf(v[n][1].y)) + fmaf(e[2], asf(v[n][2].y), e[3] * asf(v[n][3].y));
        sts32_if(st, dst + 192 * n, pack2(o0 * rl, o1 * rl));
    }
    SWEEPS(k, guard - 1);
    __syncwarp();
}

__device__ __forceinline__ void score_warp(const Maps& M, uint32_t sb, uint32_t h, uint32_t ln) {
    const uint32_t lane0 = ln;
    uwait(sb + S_QRDY, 0);
    const uint32_t q8 = ln >> 2;
    const uint32_t k0 = k_off(ln);
    uint32_t pos = h + 6, bar = sb + S_FK, par = 0, phases = 0;
    uint2 q = lds64(sb + S_QS + 8 * ln), qh = lds64(sb + S_QS + 8 * ln + 256);
    auto first_round = [&](uint32_t b, uint32_t ln) {
        uwait(sb + S_RELR, b & 1);
        const uint32_t u = h + 2 * ln, p = u < 4 ? u + 2 : u - 4;
        uint32_t todo = __ballot_sync(~0u, token(ln < 3, sb + S_TOK + 4 * p, 32 * b + 32 + u) == 32 * b + 32 + u);
#pragma unroll 1
        for (uint32_t r = h; todo; todo >>= 1, r += 2) if (todo & 1) ring_load(M, sb, b + 1, r, r < 4 ? r + 2 : r - 4);
    };
#pragma unroll 1
    for (uint32_t n = h; n < 64; n += 2) {
        HSTAMP(0);
        const uint32_t ua = sb + pos * UNIT;
        if (!__all_sync(~0u, mbar_try(bar, par))) uwait(bar, par);
        HSTAMP(1);
        float acc[2][4] = {};
        uint32_t mine = 0;
        const uint32_t id = n + (n & 48) + 6;
#pragma unroll
        for (int s = 0; s < 12; s++) {
            uint32_t kf[4];
            ldsm4(kf, (k0 ^ (32 * (s / 3))) + (ua + 1024 * (s % 3)));
            if (s == 11) {
                __syncwarp();
                mine = token(ln == 0 && n >= 16, sb + S_TOK + 24 + 4 * pos, id);
                stsvol(sb + S_KF + 4 * h, n + 1);
            }
            const bool m = q8 == (s & 7);
            mmaA(acc[s & 1], kf, m ? (s < 8 ? q.x : qh.x) : 0u, m ? (s < 8 ? q.y : qh.y) : 0u);
        }
        const uint32_t pos0 = pos;
        const bool last = (n & 14) == 14;
        pos = last ? h + 2 : n >= 16 && pos >= 4 ? h : pos + 2;
        bar = n >= 14 ? sb + S_RING + 8 * pos : bar + 8;
        par = n >= 14 ? (phases >> pos) & 1 : 0;
        phases ^= n >= 14 ? 1u << pos : 0;
        const float w0 = (acc[0][0] + acc[0][1]) + (acc[1][0] + acc[1][1]), w1 = (acc[0][2] + acc[0][3]) + (acc[1][2] + acc[1][3]);
        HSTAMP(2);
        if (__any_sync(~0u, mine == id)) ring_load(M, sb, n >> 4, (n & 15) + 6, pos0);
        HSTAMP(3);
        float s = ((ln & 1) ? w1 : w0) + __shfl_xor_sync(~0u, (ln & 1) ? w0 : w1, 1);
        s += __shfl_xor_sync(~0u, s, 2);
        sts_hi16(sb + S_SC + (((n & 12) >> 1) + h) * 64 + (n & 2) * 2 + (ln & 29) * 2, scaled(s));
        if (last) {
            __syncwarp();
            arrive_if(ln == 0, sb + S_SCO);
            const uint32_t b = n >> 4, ln = lane0 + lag<1>(sb);
            if (b > 0) {
                uwait(sb + S_RELK, (b - 1) & 1);
                if (h == 0) LSTAMP(64 + 2 * b);
                const uint32_t sl = 3 + h + 2 * ln, idv = 32 * b + 16 + 2 * sl;
                uint32_t todo = __ballot_sync(~0u, token(sl < 8, sb + S_TOK + 48 + 4 * sl, idv) == idv);
#pragma unroll 1
                for (uint32_t r = 3 + h; todo; todo >>= 1, r += 2) if (todo & 1) v_load(M, sb, b, r);
                const uint32_t g = blockIdx.x >> 3, pr = pairL(RA, 1, g), side = ldsvol(sb + S_SIDE);
                const char* src = xwindow() + pr * 8192 + ((side ^ 1 ^ __popc(pr & PMASK)) & 1) * COPY + h * HALF + 8 * min(ln, 24u);
                uwait(sb + S_RELV, (b - 1) & 1);
                __nanosleep(HOP1_NS);
#pragma unroll 1
                for (uint32_t r = 0; r < 4; r += 2) {
                    hop_a<2>(src + 256 * r, b & 1, sb + S_OS + 192 * (4 * h + r) + 96 + 4 * ln, ln < 24, 25);
                    if (r == 0 && b < 3) first_round(b, ln);
                }
                arrive_if(ln == 0, sb + S_OS1);
            } else first_round(0, ln);
            q = lds64(sb + S_QS + 24 * ((n + 2) & 48) + 8 * ln); qh = lds64(sb + S_QS + 24 * ((n + 2) & 48) + 8 * ln + 256);
        }
    }
}

__global__ void __launch_bounds__(NTHR, 1)
fused_kernel(const Params P, const __grid_constant__ Maps M) {
    extern __shared__ __align__(1024) unsigned char smem[];
    const uint32_t sb = smem_u32(smem);
    const int tid = threadIdx.x, bid = blockIdx.x;
    if (tid == 0) {
        asm volatile("prefetch.tensormap [%0];" :: "l"(&M.wq) : "memory");
        asm volatile("cp.async.bulk.prefetch.L2.global [%0], 12288;" :: "l"(P.wq + (80 * (bid & 7) + (bid >> 3)) * 6144) : "memory");
    }
    const int w = __shfl_sync(~0u, tid >> 5, 0), lane = tid & 31;

    if (w >= 8) {
        asm volatile("setmaxnreg.dec.sync.aligned.u32 " REG_LO ";");
        if (w == 8) {
            stream_warp(P, M, sb, lane);
        } else {
            if (w == 9) { init_bars<0, 3, 2>(sb); init_bars<3, 8, 1>(sb); init_bars<16, 22, 1>(sb); }
            else if (w == 10) { init_bars<8, 16, 2>(sb); init_bars<22, 26, 1>(sb); }
            else { init_bars<37, 38, 1>(sb); init_bars<38, 40, 8>(sb); init_bars<40, 41, 1>(sb); init_bars<41, 44, 8>(sb); init_bars<44, 46, 2>(sb); stsvol(sb + S_ZERO + 4 * lane, 0); if (lane < 16) stsvol(sb + S_LN + 4 * lane, 0); }
            asm volatile("fence.mbarrier_init.release.cluster;" ::: "memory");
            asm volatile("bar.arrive 3, 128;" ::: "memory");
            if (w == 11) asm volatile("bar.arrive 2, %0;" :: "n"(NTHR) : "memory");
            else {
                if (lane < 4) asm volatile("prefetch.tensormap [%0];" :: "l"(&M.k + lane + 4 * (w - 9)) : "memory");
                __syncwarp();
                asm volatile("bar.sync 2, %0;" :: "n"(NTHR) : "memory");
            }
            if (w < 11) score_warp(M, sb, w - 9, lane);
            else {
                uint32_t mine = 0;
                if (lane == 0) mine = probe_side();
                mine = __shfl_sync(~0u, mine, 0);
                if (lane < 8) stp32(side_word(bid >> 3, bid & 7) + 4 * lane, asf(mine & 2), 1);
                uint32_t a = 0, b = 0;
                int k = 0;
                while (!utest(sb + S_QRDY, 0) && ++k < SPIN_LIMIT) { warm_mma(a, b); __nanosleep(KWNS); }
                while (true) {
                    const uint32_t v = ldp32(side_word(bid >> 3, lane & 7));
                    const bool late = !__all_sync(~0u, v & 1);
                    if (!late || ++k >= SPIN_LIMIT) { stsvol(sb + S_SIDE, mine | (FORCE_BOTH || late || __any_sync(~0u, (v ^ mine) & 2) ? 4 : 0)); break; }
                    warm_mma(a, b); __nanosleep(KWNS);
                }
                while (ldsvol(sb + S_GATE) == 0 && ++k < SPIN_LIMIT) { warm_mma(a, b); __nanosleep(KWNS); }
                uint32_t rl = lane, rq = 0;
                auto reset = [&] {
                    if (rq < 128) *reinterpret_cast<uint4*>(reinterpret_cast<char*>(g_s) + (rl < 60 ? XS + bid * 7680 + 128 * rl : XS2 + bid * 768 + 128 * (rl - 60)) + rq) = make_uint4(0, 0, 0, 0);
                    rl += 32;
                    if (rl >= 66) { rl -= 66; rq += 16; }
                };
                reset(); reset();
                if (lane < 8) stp32(side_word(bid >> 3, bid & 7) + 4 * lane, 0.f, 0);
                const uint32_t side = (ldsvol(sb + S_SIDE) & 1) ^ 1, g = bid >> 3, i = bid & 7;
                const XPtr gx(xwindow());
                auto nearp = [&](uint32_t pr) { return gx.lo + pr * 8192 + ((side ^ __popc(pr & PMASK)) & 1) * COPY; };
                const uint32_t own = (i >> 2) * HALF + (i & 3) * 1024 + (lane & 7) * 128;
                const uint32_t cut = (lane & 7) == 7 ? 128 : 0;
                const uint32_t pAC = nearp(pairL(lane >> 4, (lane >> 3) & 1, g)) + own - (lane >> 4) * cut, pE = nearp(pairL(RE, (lane >> 3) & 1, g)) + own - cut;
                const uint32_t pG = nearp(pairG((lane >> 2) & 1, (lane >> 3) & 1, i)) + min(lane & 3, 2) * 128;
                uint32_t tr = 0, tk = 0, ph = 0, src = g + (lane >> 4), seen = 0, n = 16;
                bool go = false, first = true;
                while (n < 64 && ++k < SPIN_LIMIT) {
                    const uint32_t now = __shfl_sync(~0u, gtime32(), 0) * 16;
                    if (!go && utest((n & 15) < 6 ? sb + S_RELK : sb + S_RELV, ((n >> 4) & 1) ^ 1)) { go = true; if ((int)(now - tk) > 0 || !(n & 15)) tk = now; }
                    if (go && (int)(now - tk) >= 0) {
                        place_load(M, sb, (n & 16) ? n : (n & 48) | ((n + 10) & 15));
                        tk += KRE_TAU;
                        n++;
                        go = (n & 15) != 0 && (n & 15) != 6;
                        if (!(n & 15)) LSTAMP(63 + (n >> 3));
                    } else if (first || (int)(now - tr) >= 0) {
                        first = false;
                        tr = now + RFR_TAU;
                        b |= seen & a;
                        warm_mma(a, b);
                        seen = ldp32(XPtr(ph == 0 ? pAC : ph == 1 && lane < 16 ? pE : pG + (src & 8) * (HALF / 8) + (src & 7) * 512, gx.hi));
                        reset();
                        src += ph == 0 ? 0 : ph == 1 ? 2 : 1;
                        ph = ph == 2 ? 0 : ph + 1;
                    } else __nanosleep(KWNS2);
                }
                while (rq < 128) reset();
                __syncwarp();
                while (ldsvol(sb + S_GATE) < 6 && ++k < SPIN_LIMIT) { warm_mma(a, b); __nanosleep(KWNS); }
                if (a | b) stsvol(sb + S_GATE, 6);
            }
        }
        return;
    }
    asm volatile("setmaxnreg.inc.sync.aligned.u32 " REG_HI ";");

    const int g = bid >> 3, i = bid & 7;
    const int g8 = lane >> 2, t = lane & 3;
    char* const gs = reinterpret_cast<char*>(g_s);
    const XPtr gx(xwindow());

    W80 Wq[6], Wgu[3];
    uint32_t Wo[5][3][4];
    if (w < 4) {
        const uint32_t* xp = reinterpret_cast<const uint32_t*>(P.x + 640 * w);
        float sum = 0.f, sq = 0.f;
#pragma unroll
        for (int u = 0; u < 10; u++) { uint32_t v = xp[lane + 32 * u]; float a = bf_lo(v), b = bf_hi(v); sum += a + b; sq += a * a + b * b; }
#pragma unroll
        for (int o = 16; o > 0; o >>= 1) { sum += __shfl_xor_sync(~0u, sum, o); sq += __shfl_xor_sync(~0u, sq, o); }
        float mean, den; ln_stats(sum, sq, mean, den);
        if (lane < 20) {
            const uint2 v = reinterpret_cast<const uint2*>(P.x + 640 * w + 80 * i)[lane];
            sts64(sb + S_X0 + 160 * w + 8 * lane, v.x, v.y);
            sts32(sb + S_L0 + 384 * w + b_pos<40>(4 * lane), pack2(__fdiv_rn(bfr(bf_lo(v.x) - mean), den), __fdiv_rn(bfr(bf_hi(v.x) - mean), den)));
            sts32(sb + S_L0 + 384 * w + b_pos<40>(4 * lane + 2), pack2(__fdiv_rn(bfr(bf_lo(v.y) - mean), den), __fdiv_rn(bfr(bf_hi(v.y) - mean), den)));
        }
    } else if (w == 4) {
        const uint32_t* xp = reinterpret_cast<const uint32_t*>(P.wr);
        float sum = 0.f;
#pragma unroll
        for (int u = 0; u < 10; u++) { uint32_t v = xp[lane + 32 * u]; sum += bf_lo(v) + bf_hi(v); }
#pragma unroll
        for (int o = 16; o > 0; o >>= 1) sum += __shfl_xor_sync(~0u, sum, o);
        if (lane == 0) stsf(sb + S_SWR, sum);
        if (lane < 20) {
            const uint2 v = reinterpret_cast<const uint2*>(P.wr + 80 * i)[lane];
            sts32(sb + S_XA + 576 + a_pos(4 * lane), v.x); sts32(sb + S_XA + 576 + a_pos(4 * lane + 2), v.y);
            sts32(sb + S_XA + a_pos(4 * lane), ONES); sts32(sb + S_XA + a_pos(4 * lane + 2), ONES);
        }
    }
    asm volatile("bar.sync 2, %0;" :: "n"(NTHR) : "memory");
    auto frag = [](uint32_t (&a)[4], uint32_t p, int pitch) {
        const uint32_t r0 = lds32(p), r1 = lds32(p + pitch), r2 = lds32(p + 2 * pitch), r3 = lds32(p + 3 * pitch);
        a[0] = __byte_perm(r0, r1, 0x5410); a[1] = __byte_perm(r0, r1, 0x7632);
        a[2] = __byte_perm(r2, r3, 0x5410); a[3] = __byte_perm(r2, r3, 0x7632);
    };
    mbar_wait(sb + S_WFULL + 16 * (w >> 2), 0);
    mbar_wait(sb + S_WFULL + 16 * (w >> 2) + 8, 0);
    {
        const uint32_t p = sb + ST_WQ + (w >> 2) * 30720 + (2 * t) * 384 + (48 * (w & 3) + 2 * g8) * 2;
#pragma unroll
        for (int r = 0; r < 10; r++)
#pragma unroll
            for (int m = 0; m < 3; m++) {
                const uint32_t q = p + ((r & 1) * 40 + (r >> 1) * 8) * 384 + 32 * m, r0 = lds32(q), r1 = lds32(q + 384);
                (r < 8 ? Wq[2 * m].a[(r >> 2) & 1][r & 3] : Wq[2 * m].c[r & 1]) = __byte_perm(r0, r1, 0x5410);
                (r < 8 ? Wq[2 * m + 1].a[(r >> 2) & 1][r & 3] : Wq[2 * m + 1].c[r & 1]) = __byte_perm(r0, r1, 0x7632);
            }
    }
    __syncwarp();
    if (lane == 0) mbar_arrive(sb + S_RELW);
    TSTAMP(1);
    {
        char* d = gs + XS + bid * 7680 + (w >> 2) * 3840 + (48 * (w & 3) + 2 * g8) * 4;
        float acc[6][4] = {};
        mul80(acc, Wq, lds128(sb + S_L0 + 48 * lane), lds32(sb + S_L0 + 48 * lane + 16));
#pragma unroll
        for (int m = 0; m < 6; m += 2) stp64(d + t * 768 + 32 * m, acc[m][0] + acc[m][3], acc[m + 1][0] + acc[m + 1][3], 1);
        float sum[6][4] = {};
        mul80(sum, Wq, make_uint4(ONES, ONES, ONES, ONES), ONES);
        if (t == 0)
#pragma unroll
            for (int m = 0; m < 6; m += 2) stp64(d + 4 * 768 + 32 * m, sum[m][0] + sum[m][3], sum[m + 1][0] + sum[m + 1][3], 1);
    }
    mbar_wait(sb + S_WFULL + 32, 0);
    mbar_wait(sb + S_WFULL + 40, 0);
    const uint32_t oct = 3 * (w >> 1) + (w & 1), oct2 = 3 * (w >> 1) + 2;
    {
        const uint32_t p = sb + ST_WG + ((lane & 7) + 40 * ((lane >> 3) & 1) + 8 * (lane >> 4)) * 192;
#pragma unroll
        for (int T = 0; T < 3; T++) {
            const uint32_t q = p + (T < 2 ? T * 15360 + 16 * oct : (w & 1) * 15360 + 16 * oct2);
            ldsm4t(Wgu[T].a[0], q); ldsm4t(Wgu[T].a[1], q + 16 * 192); ldsm2t(Wgu[T].c, q + 32 * 192);
        }
        float sum[3][4] = {};
        mul80(sum, Wgu, make_uint4(ONES, ONES, ONES, ONES), ONES);
        if (t < 3) stp32(gs + XS2 + bid * 768 + (t < 2 ? 64 * oct + 4 * t : 64 * oct2 + 4 * (w & 1)) + 8 * g8,
                         sel4(t, sum[0][0] + sum[0][3], sum[1][0] + sum[1][3], sum[2][0] + sum[2][3], 0.f), 1);
    }
    __syncwarp();
    if (lane == 0) mbar_arrive(sb + S_RELW + 8);
    mbar_wait(sb + S_WFULL + 48 + 8 * (w >> 1), 0);
    {
        const uint32_t po = sb + ST_WO + (48 * w + 12 * t) * 160 + 4 * g8;
#pragma unroll
        for (int s = 0; s < 3; s++)
#pragma unroll
            for (int m = 0; m < 5; m++) frag(Wo[m][s], po + 4 * s * 160 + 32 * m, 160);
    }
    __syncwarp();
    if (lane == 0) mbar_arrive(sb + S_RELW + 16);
    if (tid < 192) {
        const char* srcS = gs + XS + g * 8 * 7680 + (i >> 2) * 3840 + tid * 4;
        uint32_t vs[5][8];
        int guard = 0;
        do {
#pragma unroll
            for (int b = 0; b < 5; b++)
#pragma unroll
                for (int s = 0; s < 8; s++) vs[b][s] = ldp32(srcS + b * 768 + s * 7680);
        } while (((or3(chk8(vs[0], 1), chk8(vs[1], 1), chk8(vs[2], 1)) | chk8(vs[3], 1) | chk8(vs[4], 1)) & 1) && ++guard < SPIN_LIMIT);
        const uint32_t qpos = sb + S_QS + q_pos(tid);
#pragma unroll
        for (int b = 0; b < 4; b++) {
            sts_hi16(qpos + 384 * b, bfr(sum8(vs[b])));
        }
        stsf(sb + S_CSQ + 4 * tid, sum8(vs[4]));
    }
    if (tid < 192) {
        uint32_t v[8];
        int guard = 0;
        do {
#pragma unroll
            for (int s = 0; s < 8; s++) v[s] = ldp32(gs + XS2 + (g * 8 + s) * 768 + tid * 4);
        } while ((chk8(v, 1) & 1) && ++guard < SPIN_LIMIT);
        stsf(sb + S_CSGU + 4 * tid, sum8(v));
    }
    __syncwarp();
    bar_main();
    arrive_if(tid == 0, sb + S_QRDY);
    TSTAMP(2);

    uint32_t side;
    { int k = 0; while ((side = ldsvol(sb + S_SIDE)) == 0 && ++k < SPIN_LIMIT) {} }
    const uint32_t both = __any_sync(~0u, side & 4) ? COPY : 0;
    uint32_t td = __shfl_sync(~0u, tid, lane);
    const uint32_t wp = __shfl_sync(~0u, tid >> 5, 0);
    const uint32_t cc = wp >= 3;
    auto uni = [](uint32_t v) { return __shfl_sync(~0u, v, 0); };
    auto pin = [&](uint32_t v) { return __shfl_sync(~0u, v, td); };
    auto nearp = [&](uint32_t P) { return gx.lo + P * 8192 + ((side ^ 1 ^ __popc(P & PMASK)) & 1) * COPY; };
    constexpr uint32_t COL = 32 * 8192;
    const uint32_t ownL = (i >> 2) * HALF + (i & 3) * 1024, ownG = gx.lo + (g >> 3) * HALF + (g & 7) * 512;
    const uint32_t uPubA = uni(ownL + nearp(pairL(RA, 0, g)) + (wp >> 1) * 256 + (wp & 1) * 96), uPolA = uni(nearp(pairL(RA, 0, g)) + (wp >> 2) * HALF + (wp & 3) * 256);
    const uint32_t uPubB = uni(ownG + pairG(0, cc, i) * 8192), uPolB = uni(nearp(pairG(0, cc, i)));
    const uint32_t uPubC = uni(ownL + nearp(pairL(RC, 0, g))), uPolC = uni(nearp(pairL(RC, wp < 6 ? cc : 0, g)));
    const uint32_t uPubD = uni(ownG + pairG(1, 0, i) * 8192 + (wp < 7 ? 32 * wp : 256)), uPolD = uni(nearp(pairG(1, cc, i)));
    const uint32_t uPubE = uni(ownL + nearp(pairL(RE, 0, g))), uPolE = uni(nearp(pairL(RE, i >> 2, g)));
    const uint32_t uOS = uni(sb + S_OS + 192 * wp);
    auto xp = [&](uint32_t lo) { return (char*)XPtr(lo, gx.hi); };
    {
        const uint4 z = make_uint4(0, 0, 0, 0);
        const uint32_t c = ((tid >> 6) & 1) * COL, cp = (tid >> 7) * both, k = (tid & 63) * 16;
        *reinterpret_cast<uint4*>(xp((ownL + nearp(pairL(RA, 0, g)) + c + k) ^ cp)) = z;
        if (k < 800) { *reinterpret_cast<uint4*>(xp((uPubC + c + k) ^ cp)) = z; *reinterpret_cast<uint4*>(xp((uPubE + c + k) ^ cp)) = z; }
        if ((tid & 31) < 20) *reinterpret_cast<uint4*>(xp(ownG + pairG((tid >> 5) & 1, 0, i) * 8192 + c + (tid >> 7) * COPY + (tid & 31) * 16)) = z;
    }
#define IDS() __syncwarp(); const uint32_t z0_ = lag<1>(sb), z_ = td + z0_; const uint32_t ln = z_ & 31, q8 = ln >> 2, t4 = z_ & 3, n96 = z_ - 96 * cc, n80 = min(n96, 79u); (void)q8; (void)t4; (void)n80; (void)ln

    auto vaddr = [&](uint32_t (&voff)[3]) {
        const uint32_t ln = td & 31;
        const uint32_t key3 = 3 * ((ln & 7) + 2 * (ln & 8) + ((ln >> 1) & 8));
#pragma unroll
        for (int T = 0; T < 3; T++) {
            const uint32_t u = 3 * wp + T, r = key3 + (u >> 3);
            voff[T] = r * 128 + (((u ^ r) & 7) << 4);
        }
    };
    auto values = [&](uint32_t (&vf)[8][3][4], float (&acc)[3][4], auto step, uint32_t ps, auto col, uint32_t par) {
        constexpr int CUT = col.value ? 8 : 6;
        const uint32_t ln = td & 31, q8 = ln >> 2, t4 = td & 3;
        uint4 p = lds128(ps + 16 * ln);
        float f0 = 0.f, f1 = 0.f, r3 = 0.f, o = 0.f;
        int M = 0;
#pragma unroll
        for (int s = 0; s < 8; s++) {
            if (s == 0 || s == CUT)
#pragma unroll
                for (int k = 0; k < 12; k++) acc[k / 4][k % 4] = 0.f;
            step(s);
            const bool m = s >= CUT || (q8 >> 1) == (s >> 1);
            const uint32_t b0 = m ? ((s & 1) ? p.z : p.x) : 0u, b1 = m ? ((s & 1) ? p.w : p.y) : 0u;
#pragma unroll
            for (int T = 0; T < 3; T++) mmaA(acc[T], vf[s][T], b0, b1);
            if (s == FSTEP) {
                const uint2 mp = lds64(ps + PS_MAX + 8 * t4);
                M = __reduce_max_sync(~0u, __float2int_ru(fmaxf(asf(mp.x), asf(mp.y))));
                f0 = ex2(asf(mp.x) - (float)M); f1 = ex2(asf(mp.y) - (float)M);
                float l[4] = {};
                mma16816(l, ONES, ONES, ONES, ONES, p.x, p.y); mma16816(l, ONES, ONES, ONES, ONES, p.z, p.w);
                r3 = fmaf(f0, l[0], f1 * l[1]);
            }
            if (s == CUT - 1) {
                if (CUT < 8) p = lds128(ps + 384 + 16 * (ln & 7));
                const float r0 = fmaf(f0, acc[0][0], f1 * acc[0][3]), r1 = fmaf(f0, acc[1][0], f1 * acc[1][3]), r2 = fmaf(f0, acc[2][0], f1 * acc[2][3]);
                const bool hi = t4 & 2, od = t4 & 1;
                const float u0 = (hi ? r2 : r0) + __shfl_xor_sync(~0u, hi ? r0 : r2, 2), u1 = (hi ? r3 : r1) + __shfl_xor_sync(~0u, hi ? r1 : r3, 2);
                o = (od ? u1 : u0) + __shfl_xor_sync(~0u, od ? u0 : u1, 1);
                if (ln == 3) o = __int_as_float(2 * M);
                if (CUT < 8) { f0 = __shfl_sync(~0u, f0, 3); f1 = __shfl_sync(~0u, f1, 3); }
            }
        }
        CSTAMP(25);
        const uint32_t pubA = uPubA + col.value * COL + 32 * t4 + 4 * q8;
        if (CUT < 8 && t4 < 3) o = fmaf(f0, sel4(t4, acc[0][0], acc[1][0], acc[2][0], acc[2][0]), fmaf(f1, sel4(t4, acc[0][3], acc[1][3], acc[2][3], acc[2][3]), o));
        stp32_if(t4 < 3 || ((wp & 1) && q8 < 2), xp(pubA ^ both), xp(pubA), o, par);
    };

    uint32_t left[36] = {};
#pragma unroll 1
    for (int ch = 0; ch < 5; ch++) {
        const uint32_t par0 = (ch + 1) & 1, par1 = ch & 1;
        uint32_t voff[3], vf[8][3][4];
        float acc_[3][4];
        if (ch < 4) {
            td = pin(td);
            vaddr(voff);
            mbar_wait(sb + S_SCO, par1);
            if (ch == 0) mbar_wait(sb + S_WFULL + 80, 0);
            TST(0);
            auto ldw = [&](int s) {
                mbar_wait(sb + S_FV + 8 * s, par1);
#pragma unroll
                for (int T = 0; T < 3; T++) ldsm4t(vf[s][T], voff[T] + (sb + v_place(ch, s) * SLOT));
            };
            probs(bf_lo(lds16(sb + S_SC + 2 * td)), sb + S_PS, wp, td & 31);
            ldw(0); ldw(1); ldw(2);
            bar_main();
            arrive_if(td == 0, sb + S_RELR);
            values(vf, acc_, [&](int s) {
                if (s >= 3) ldw(s);
            }, sb + S_PS, std::integral_constant<int, 0>(), par0);
            TST(1);
            CSTAMP(5);
            if (ch > 0) mbar_wait(sb + S_OS1, par0);
        } else {
#pragma unroll
            for (int s = 0; s < 36; s++) vf[s / 12][(s / 4) % 3][s & 3] = left[s];
        }
        const bool has0 = ch < 4, has1 = ch > 0;
        const bool actc = wp < 6 && (cc ? has1 : has0);
        const uint32_t parc = cc ? par1 : par0;
        const uint32_t pub0 = has0 ? par0 : 0;
        uint32_t rr, pubB;
        {
            IDS();
            const uint32_t c = ch == 4;
            const uint32_t osa = pin(uOS + 96 * c + 4 * ln), oa = pin(uOS + 48 * (q8 & 2) + 24 * t4), ra = pin(sb + S_RED + 640 * wp + 320 * (t4 & 1) + 8 * q8);
            rr = pin(sb + S_RED + 320 * cc + 4 * n80); pubB = pin(uPubB + 4 * n80);
            hop_a<1>(xp(uPolA + c * COL + 8 * min(ln, 24u) + lag<DELAY_L>(sb, z0_)), pub0, osa, ln < 24, 5 * ch);
            TST(2);
            CSTAMP(6);
            float acc[5][4] = {};
            const uint2 b0 = lds64(oa), b1 = lds64(oa + 8), b2 = lds64(oa + 16);
#pragma unroll
            for (int m = 0; m < 5; m++) mmaA(acc[m], Wo[m][0], b0.x, b0.y);
#pragma unroll
            for (int m = 0; m < 5; m++) mmaA(acc[m], Wo[m][1], b1.x, b1.y);
#pragma unroll
            for (int m = 0; m < 5; m++) mmaA(acc[m], Wo[m][2], b2.x, b2.y);
#pragma unroll
            for (int m = 0; m < 5; m++) { stsf(ra + 64 * m, acc[m][0]); stsf(ra + 64 * m + 4, acc[m][2]); }
        }
        CSTAMP(7);
        uint32_t xr, fl, pubC, pubC2;
        auto prepC = [&](uint32_t ln) {
            const uint32_t q8 = ln >> 2, t4 = ln & 3;
            xr = pin(sb + S_XB + 48 * (ln & 15));
            pubC = pin(uPubC + (t4 & 1) * COL + 192 * (wp >> 1) + 64 * (wp & 1) + 8 * q8);
            pubC2 = pin(uPubC + (t4 & 1) * COL + ((t4 & 2) ? 192 * (wp >> 1) + 128 + 4 * (wp & 1) + 8 * q8 : 768 + 2 * ((q8 + 1) & 6)));
            fl = pin(((t4 & 1) ? par1 : pub0) | (t4 >= 2 || (wp == 7 && q8 < 4 && q8 != 2 - t4) ? 2 : 0));
        };
        auto stats = [&](uint32_t xa, const uint4& b, uint32_t b4) {
            float a0[4] = {}, a1[4] = {}, a2[4] = {};
            const uint4 p0 = lds128(xa), p1 = lds128(xa + 16);
            const uint2 p2 = lds64(xa + 32);
            mmaV(a0, p0, b.x, b.y); mmaV(a1, p1, b.z, b.w); mma8(a2, p2.x, p2.y, b4);
            return ((a0[0] + a0[3]) + (a1[0] + a1[3])) + (a2[0] + a2[3]);
        };
        auto give_ln = [&](uint32_t src0, uint32_t par, uint32_t dst, uint32_t ln, float& mean, float& den, auto also) {
            const char* src = xp(src0 + 768 + (ln & 1) * HALF);
            float sx, sq;
            int guard = 0;
            bool again;
            do {
                uint2 st[4];
#pragma unroll
                for (int s = 0; s < 4; s++) st[s] = ldp64(src + s * 1024);
                again = __any_sync(~0u, ((chk4(st, par) | also()) & 1) != 0);
                sx = (asf(st[0].x) + asf(st[1].x)) + (asf(st[2].x) + asf(st[3].x)); sq = (asf(st[0].y) + asf(st[1].y)) + (asf(st[2].y) + asf(st[3].y));
                sx += __shfl_xor_sync(~0u, sx, 1); sq += __shfl_xor_sync(~0u, sq, 1);
            } while (again & (++guard < SPIN_LIMIT));
            ln_stats(sx, sq, mean, den);
            stsvol64(dst, __byte_perm(__float_as_uint(den), __float_as_uint(mean), 0x7632), (__float_as_uint(rcp(den)) & ~7u) | (ch + 1));
        };
        auto take_ln = [&](uint2& c, uint32_t a) { int k = 0; do c = ldsvol64(a); while (__any_sync(~0u, (c.y & 7) != ch + 1) & (++k < SPIN_LIMIT)); };
        {
            auto gate_up = [&](auto with_stats) {
                bar_main();
                TST(3);
                CSTAMP(11);
                const uint4 b = lds128(xr);
                uint32_t b4 = lds32(xr + 16);
                float acc[3][4] = {};
                if (with_stats.value) {
                    stp32_if(fl > 1 && !(td & 2), xp(pubC2 ^ both), xp(pubC2), stats(xr + (S_XA - S_XB), b, b4), fl & 1);
                    __syncwarp();
                    b4 = lds32(xr + 16);
                }
                mul80(acc, Wgu, b, b4);
                stp64_if(!(td & 2), xp(pubC ^ both), xp(pubC), tagw(acc[0][0] + acc[0][3], fl & 1), tagw(acc[1][0] + acc[1][3], fl & 1));
                stp32_if(td & 2, xp(pubC2 ^ both), xp(pubC2), acc[2][0] + acc[2][3], fl & 1);
            };
            if (wp == 7) {
                bar_main();
                IDS();
                prepC(ln);
                sts32(sb + S_ZERO + 4, or3(pubC, pubC2, fl));
                gate_up(std::true_type());
            } else {
                if (actc) {
                    bar_main();
                    CSTAMP(8);
                    uint32_t r[8];
#pragma unroll
                    for (int s = 0; s < 8; s++) r[s] = lds32(rr + 640 * s);
                    stp32_if(true, xp(pubB), sum8(r), parc);
                    CSTAMP(9);
                    IDS();
                    prepC(ln);
                    const uint32_t n4 = 4 * n80;
                    const uint32_t xas = pin(sb + S_XA + 192 + 192 * cc + a_pos(n80)), xbs = pin(sb + S_XB + 384 * cc + b_pos<40>(n80));
                    const float x0 = cc ? ldsf(sb + S_XCAR + n4) : bf_lo(lds16(sb + S_X0 + 160 * (ch & 3) + n4 / 2));
                    gather16(xp(uPolB + n4 + lag<DELAY_G>(sb, z0_)), parc, 5 * ch + 1, [&](float y, uint32_t) {
                        const uint32_t x = pack2(x0 + bfr(y), 0.f);
                        sts16(xbs, x);
                        sts16(xas, x);
                        return 0u;
                    });
                    CSTAMP(10);
                } else {
                    bar_main();
                    IDS();
                    prepC(ln);
                }
                gate_up(std::false_type());
            }
        }
        CSTAMP(12);
        float mean = 0.f, den = 1.f;
        {
            IDS();
            const uint32_t wh = pin((((ln & 7) + 48 * ((ln >> 3) & 1) + 8 * (ln >> 4)) * 160 + (wp < 7 ? 16 * wp : 128)) | ((384 * cc + b_pos<48>(n96)) << 16));
            const uint32_t pubD = pin(uPubD + (t4 & 1) * COL + 16 * (t4 & 2) + 4 * q8 + (fl & 1)), ha = xr + (S_HS - S_XB);
            auto down = [&](const uint32_t (&W)[3][4], const uint4& h0, const uint2& h1) {
                float a0[4] = {}, a1[4] = {}, a2[4] = {};
                mmaA(a0, W[0], h0.x, h0.y); mmaA(a1, W[1], h0.z, h0.w); mmaA(a2, W[2], h1.x, h1.y);
                return ((a0[0] + a0[3]) + (a1[0] + a1[3])) + (a2[0] + a2[3]);
            };
            if (wp < 6) {
                uint32_t Wd[3][4];
                auto ldd = [&](uint32_t z) {
#pragma unroll
                    for (int s = 0; s < 3; s++) ldsm4t(Wd[s], ((wh ^ z) & 0xffff) + (sb + S_WD + s * 2560));
                };
                ldd(0);
                if (actc) {
                    const char* srcv = xp(uPolC + lag<DELAY_C>(sb, z0_) + 8 * n96);
                    const uint2 cs = lds64(sb + S_CSGU + 8 * n96);
                    float gt, up;
                    int guard = 0;
                    while (true) {
                        uint2 v[8];
#pragma unroll
                        for (int s = 0; s < 8; s++) v[s] = ldp64(srcv + (s >> 2) * HALF + (s & 3) * 1024);
                        uint2 c = ldsvol64(sb + S_LN + 8 * cc + ((v[0].x ^ parc) & 1) * 32);
                        const bool stale = __any_sync(~0u, ((chk8(v, parc) | chk8y(v, parc)) & 1) != 0), late = __any_sync(~0u, (c.y & 7) != ch + 1);
                        const float pg = sum8x(v), pu = sum8y(v);
                        auto norm = [&] {
                            mean = bf_hi(c.x); den = bf_lo(c.x);
                            gt = bfr(fmaf(-mean, asf(cs.x), pg) * asf(c.y)); up = fmaf(-mean, asf(cs.y), pu) * asf(c.y);
                            keep(gt); keep(up);
                        };
                        norm();
                        if (!((stale | late) & (++guard < SPIN_LIMIT))) break;
                        if (!stale) { take_ln(c, sb + S_LN + 8 * cc); norm(); break; }
                    }
                    CSTAMP(13);
                    SWEEPS(5 * ch + 2, guard - 1);
                    const uint32_t h = pack2(bfr(gt * sigmoidf_(gt)) * bfr(up), 0.f);
                    sts16((wh >> 16) + (sb + S_HS), h);
                    CSTAMP(14);
                    if (ch == 3) CSTAMP(0);
                }
                bar_main();
                TST(4);
                CSTAMP(15);
                const uint4 h0 = lds128(ha);
                const uint2 h1 = lds64(ha + 16);
                stp32_if(!(td & 2), xp(pubD & ~1u), down(Wd, h0, h1), pubD & 1);
            } else {
                uint32_t v = 0;
                const uint32_t col = wp == 7 || !has0;
                const bool serve = wp == 6 || (has0 && has1);
                if (serve) {
                    const uint32_t par = col ? par1 : par0;
                    const char* src = xp(uPolC + col * COL + 776 + (td & 4) * (HALF / 4) + (td & 3) * 1024);
                    give_ln(uPolC + col * COL, par, sb + S_LN + 8 * col, td, mean, den, [&] { v = ldp32(src); return v ^ par; });
                }
                stsvol(sb + S_GATE, ch + 1);
                uint32_t Wd[2][3][4];
#pragma unroll
                for (int s = 0; s < 6; s++) ldsm4t(Wd[s / 3][s % 3], (wh & 0xffff) + (sb + S_WD + (s / 3) * 16 + (s % 3) * 2560));
                bar_main();
                const uint4 h0 = lds128(ha);
                const uint2 h1 = lds64(ha + 16);
                const float d0 = down(Wd[0], h0, h1), d1 = down(Wd[1], h0, h1);
                stp32_if(true, xp(pubD & ~1u), (td & 2) ? d1 : d0, pubD & 1);
                if (serve) {
                    float xw = asf(v);
                    xw += __shfl_xor_sync(~0u, xw, 1); xw += __shfl_xor_sync(~0u, xw, 2); xw += __shfl_xor_sync(~0u, xw, 4);
                    const float r = bfr(fmaf(-mean, ldsf(sb + S_SWR), xw) * rcp(den));
                    sts32(sb + S_STAT + 4 * col, __float_as_uint(bfr(sigmoidf_(r))) | (ch + 1));
                }
            }
        }
        CSTAMP(16);
        {
            IDS();
            const uint32_t pubE = pin(uPubE + (t4 < 3 ? (wp >> 2) * COL + 192 * (wp & 3) + 64 * t4 + 8 * q8 : (q8 >> 2) * COL + 768 + 4 * (q8 & 1)));
            xr = pin(sb + S_XB + 48 * (ln & 7));
            uint32_t x2 = 0;
            auto hop_d = [&](auto col) {
                const uint32_t xbs = pin(sb + S_XB + 384 * col.value + b_pos<40>(n80)), xas = col.value ? 0 : pin(sb + S_XA + 192 + a_pos(n80));
                const float x1 = bf_lo(lds16(xbs));
                const float lnx = __uint_as_float(pin(__float_as_uint(bfr(__fdiv_rn(bfr(x1 - mean), den)))));
                gather16(xp(uPolD + 4 * n80 + lag<DELAY_D>(sb, z0_)), col.value ? par1 : par0, 5 * ch + 3, [&](float y, uint32_t z) {
                    const uint32_t gate = ldsvol(sb + S_STAT + 4 * col.value + z);
                    x2 = pack2(x1 + bfr(lnx + bfr(bfr(y) * bf_hi(gate))), 0.f);
                    if (col.value) keep(x2); else { sts16(xbs, x2); sts16(xas, x2); }
                    return (uint32_t)((gate & 7) != ch + 1);
                });
                CSTAMP(17);
            };
            auto qproj = [&](auto with_stats) {
                bar_main();
                TST(5);
                CSTAMP(19);
                const uint32_t t4 = td & 3;
                const uint4 b = lds128(xr);
                uint32_t b4 = lds32(xr + 16);
                float acc[6][4] = {};
                if (with_stats.value) {
                    stp32_if((td & 11) == 3, xp(pubE ^ both), xp(pubE), stats(xr + (S_XA - S_XB), b, b4), par0);
                    __syncwarp();
                    b4 = lds32(xr + 16);
                }
                mul80(acc, Wq, b, b4);
                const float v0 = sel4(t4, acc[0][0] + acc[0][3], acc[2][0] + acc[2][3], acc[4][0] + acc[4][3], acc[4][0] + acc[4][3]);
                const float v1 = sel4(t4, acc[1][0] + acc[1][3], acc[3][0] + acc[3][3], acc[5][0] + acc[5][3], acc[5][0] + acc[5][3]);
                stp64_if(t4 < 3, xp(pubE ^ both), xp(pubE), tagw(v0, par0), tagw(v1, par0));
            };
            if (wp == 7) {
                if (!has0) break;
                qproj(std::true_type());
            } else {
                if (actc && !cc) hop_d(std::integral_constant<int, 0>());
                else {
                    if (actc && g == 0) {
                        const uint32_t po = pin(1280 * (ch - 1) + 160 * i + 2 * n80);
                        hop_d(std::integral_constant<int, 1>());
                        *reinterpret_cast<unsigned short*>(reinterpret_cast<char*>(P.out) + po) = (unsigned short)x2;
                    }
                    if (!has0) break;
                }
                qproj(std::false_type());
                sts32_if(td < 80, sb + S_XCAR + 4 * td, x2 << 16);
            }
        }
        CSTAMP(20);
        if (wp == 6) give_ln(uPolE, par0, sb + S_LN + 16, td, mean, den, [] { return 0u; });
        auto pass2 = [&](auto d0, auto d1, auto d2) {
            constexpr int D0 = d0.value, D1 = d1.value, D = D0 + D1 + d2.value;
            IDS();
            const uint32_t ua = sb + k_place(ch, wp & 6) * SLOT + (wp & 1) * UNIT, k0 = k_off(ln);
            uint32_t kf[12][2][4];
            auto ldk = [&](int s) { const uint32_t a = (k0 ^ (32 * (s / 3))) + (ua + 1024 * (s % 3)); ldsm4(kf[s][0], a); ldsm4(kf[s][1], a + SLOT); };
            auto ldv1 = [&](int k) { ldsm4t(vf[k / 3][k % 3], voff[k % 3] + (sb + v_place(ch, k / 3) * SLOT)); };
            auto ldv = [&](int s) { ldv1(3 * s); ldv1(3 * s + 1); ldv1(3 * s + 2); };
            constexpr uint32_t LATE = LAST_LATE;
            constexpr uint64_t EARLY_LIST = bit_list(~LATE), LATE_LIST = bit_list(LATE);
            auto early = [&](int k) {
                if (D1 == 0) ldk(k);
                else if (k < 3) { ldv1(9 + 2 * k); ldv1(10 + 2 * k); }
                else ldk((EARLY_LIST >> (4 * (k - 3))) & 15);
            };
            uint32_t v[8] = {}, qsa = 0;
            const char* srcv = xp(uPolE + lag<(D1 > 0 ? 0 : DELAY_E)>(sb, z0_) + 4 * td);
            auto look = [&] {
#pragma unroll
                for (int s = 0; s < 8; s++) v[s] = ldp32(srcv + (s >> 2) * HALF + (s & 3) * 1024);
            };
            if (D1 > 0) vaddr(voff);
            if (!(mbar_try(sb + S_FK + 8 * (wp & 6), par1) & mbar_try(sb + S_FK + 8 * (wp | 1), par1))) { mbar_wait(sb + S_FK + 8 * (wp & 6), par1); mbar_wait(sb + S_FK + 8 * (wp | 1), par1); }
#pragma unroll
            for (int s = 0; s < D0; s++) early(s);
            if (wp < 6) { look(); qsa = pin(sb + S_QS + 384 * ch + q_pos(z_)); }
#pragma unroll
            for (int s = D0; s < D0 + D1; s++) early(s);
            if (wp < 6) {
                const float cs = ldsf(sb + S_CSQ + 4 * td);
                int guard = 0;
                while (true) {
                    uint2 c = ldsvol64(sb + S_LN + 16 + ((v[0] ^ par0) & 1) * 32);
                    const bool stale = __any_sync(~0u, (chk8(v, par0) & 1) != 0), late = __any_sync(~0u, (c.y & 7) != ch + 1);
                    const float qs = sum8(v);
                    auto norm = [&] {
                        const uint32_t q = pack2(fmaf(-bf_hi(c.x), cs, qs) * asf(c.y), 0.f);
                        sts16(qsa, q);
                    };
                    norm();
                    if (!((stale | late) & (++guard < SPIN_LIMIT))) break;
                    if (!stale) { take_ln(c, sb + S_LN + 16); norm(); break; }
                    look();
                }
                SWEEPS(5 * ch + 4, guard - 1);
                CSTAMP(22);
            }
#pragma unroll
            for (int s = D0 + D1; s < D; s++) early(s);
            CSTAMP(21);
            bar_main();
            TST(6);
            CSTAMP(1);
            uint2 q = lds64(sb + S_QS + 384 * ch + 8 * ln);
            float acc[2][4] = {};
            constexpr int V0 = 13 - D, NV = D1 > 0 ? 2 : (2 * (D - 1)) / 3;
            static_assert(D1 == 0 || D - 3 + __builtin_popcount(LATE) == 12, "plan");
#pragma unroll
            for (int s = 0; s < 12; s++) {
                const bool m = q8 == (s & 7);
                const uint32_t b0 = m ? q.x : 0u, b1 = m ? q.y : 0u;
                if (s == 7) q = lds64(sb + S_QS + 384 * ch + 8 * ln + 256);
                mmaA(acc[0], kf[s][0], b0, b1);
                mmaA(acc[1], kf[s][1], b0, b1);
                if (D1 > 0) {
                    if (s >= 1 && s <= __builtin_popcount(LATE)) ldk((LATE_LIST >> (4 * (s - 1))) & 15);
                } else {
                    if (s >= 1 && s + D - 1 < 12) ldk(s + D - 1);
                    if (s >= 1 && s + D - 1 == 11) { __syncwarp(); arrive_if(ln == 0, sb + S_RELK); }
                    if (s == V0) vaddr(voff);
                    if (s >= V0 && 2 * (s - V0) < 3 * NV) ldv1(9 + 2 * (s - V0));
                    if (s >= V0 && 2 * (s - V0) + 1 < 3 * NV) ldv1(10 + 2 * (s - V0));
                }
            }
            CSTAMP(24);
            {
                const float v0 = acc[0][0] + acc[0][1], v1 = acc[0][2] + acc[0][3], v2 = acc[1][0] + acc[1][1], v3 = acc[1][2] + acc[1][3];
                const bool hi = t4 & 2, od = t4 & 1;
                const float u0 = (hi ? v2 : v0) + __shfl_xor_sync(~0u, hi ? v0 : v2, 2), u1 = (hi ? v3 : v1) + __shfl_xor_sync(~0u, hi ? v1 : v3, 2);
                const float s = (od ? u1 : u0) + __shfl_xor_sync(~0u, od ? u0 : u1, 1);
                CSTAMP(2);
                probs(scaled(s), sb + S_PS + PS_PASS, wp, ln);
                CSTAMP(3);
            }
            bar_main();
            TST(10);
            CSTAMP(4);
            if (D1 > 0) values(vf, acc_, [&](int s) { if (s < 3) ldv(s + 5); }, sb + S_PS + PS_PASS, std::integral_constant<int, 1>(), par0);
            else values(vf, acc_, [&](int s) { if (s >= (NV > 1 ? 2 : 1) && s + NV + (NV > 1 ? 1 : 2) < 8) ldv(s + NV + (NV > 1 ? 1 : 2)); }, sb + S_PS + PS_PASS, std::integral_constant<int, 1>(), par0);
            arrive_if(ln == 0, sb + S_RELV);
        };
        if (ch == 3) {
            pass2(std::integral_constant<int, LAST0>(), std::integral_constant<int, LAST1>(), std::integral_constant<int, LAST2>());
#pragma unroll
            for (int m = 0; m < 48; m++) Wq[m / 8].a[(m / 4) % 2][m % 4] = vf[3 + m / 12][(m / 4) % 3][m % 4];
#pragma unroll
            for (int m = 0; m < 12; m++) Wq[m / 2].c[m % 2] = vf[7][m / 4][m % 4];
#pragma unroll
            for (int m = 0; m < 36; m++) left[m] = m < 12 ? __float_as_uint(acc_[m / 4][m % 4]) : vf[m / 12][(m / 4) % 3][m % 4];
        } else {
            pass2(std::integral_constant<int, KPRE>(), std::integral_constant<int, 0>(), std::integral_constant<int, KPRE2>());
#pragma unroll
            for (int m = 0; m < 36; m++) left[m] = m < 12 ? __float_as_uint(acc_[m / 4][m % 4]) : vf[4 + m / 12][(m / 4) % 3][m % 4];
        }
        TST(11);
        CSTAMP(23);
    }
    sts32_if(td == 255, sb + S_GATE, 6);
    TSTAMP(3);
}

typedef CUresult (*EncodeFn)(CUtensorMap*, CUtensorMapDataType, cuuint32_t, void*, const cuuint64_t*, const cuuint64_t*, const cuuint32_t*,
                             const cuuint32_t*, CUtensorMapInterleave, CUtensorMapSwizzle, CUtensorMapL2promotion, CUtensorMapFloatOOBfill);

void make_map(EncodeFn enc, CUtensorMap* m, const void* base, uint64_t cols, uint64_t rows, uint32_t box_cols, uint32_t box_rows, bool swizzle) {
    cuuint64_t dims[2] = {cols, rows};
    cuuint64_t strides[1] = {cols * 2};
    cuuint32_t box[2] = {box_cols, box_rows};
    cuuint32_t es[2] = {1, 1};
    enc(m, CU_TENSOR_MAP_DATA_TYPE_BFLOAT16, 2, const_cast<void*>(base), dims, strides, box, es, CU_TENSOR_MAP_INTERLEAVE_NONE,
        swizzle ? CU_TENSOR_MAP_SWIZZLE_128B : CU_TENSOR_MAP_SWIZZLE_NONE, CU_TENSOR_MAP_L2_PROMOTION_NONE, CU_TENSOR_MAP_FLOAT_OOB_FILL_NONE);
}

}

extern "C" void kernel_launch(void* const* d_in, const int* in_sizes, int n_in, void* d_out, int out_size) {
    (void)in_sizes; (void)n_in; (void)out_size;
    static EncodeFn enc = nullptr;
    if (!enc) {
        void* f = nullptr;
        cudaDriverEntryPointQueryResult q;
        cudaGetDriverEntryPoint("cuTensorMapEncodeTiled", &f, cudaEnableDefault, &q);
        enc = (EncodeFn)f;
        cudaFuncSetAttribute(fused_kernel, cudaFuncAttributeMaxDynamicSharedMemorySize, SMEM_BYTES);
    }
    Params P;
    P.x = (const __nv_bfloat16*)d_in[0]; P.k = (const __nv_bfloat16*)d_in[1]; P.v = (const __nv_bfloat16*)d_in[2];
    P.wr = (const __nv_bfloat16*)d_in[6]; P.wq = (const __nv_bfloat16*)d_in[3];
    P.out = (__nv_bfloat16*)d_out;
    Maps M;
    {
        cuuint64_t dims[4] = {64, 8, 3, (cuuint64_t)KV_BATCH_KEYS / 2}, strides[3] = {384, 128, 3072};
        cuuint32_t box[4] = {64, 8, 3, 2}, es[4] = {1, 1, 1, 1};
        enc(&M.k, CU_TENSOR_MAP_DATA_TYPE_BFLOAT16, 4, d_in[1], dims, strides, box, es, CU_TENSOR_MAP_INTERLEAVE_NONE, CU_TENSOR_MAP_SWIZZLE_128B,
            CU_TENSOR_MAP_L2_PROMOTION_NONE, CU_TENSOR_MAP_FLOAT_OOB_FILL_NONE);
    }
    make_map(enc, &M.v, P.v, 64, (uint64_t)12 * KV_BATCH_KEYS, 64, 96, true);
    make_map(enc, &M.vu, P.v, 64, (uint64_t)12 * KV_BATCH_KEYS, 64, 48, true);
    make_map(enc, &M.wq, d_in[3], 6144, 640, 192, 40, false);
    make_map(enc, &M.wo, d_in[4], 640, 6144, 80, 96, false);
    make_map(enc, &M.wg, d_in[7], 1536, 640, 96, 80, false);
    make_map(enc, &M.wu, d_in[8], 1536, 640, 96, 80, false);
    make_map(enc, &M.wd, d_in[9], 640, 1536, 80, 96, false);
    fused_kernel<<<NCTA, NTHR, SMEM_BYTES, cudaStreamPerThread>>>(P, M);
}
```

```cpp
#include <cuda_runtime.h>
#include <cuda.h>
#include <cuda_bf16.h>
#include <stdint.h>
#include <type_traits>

namespace {

constexpr int NCTA = 128;
constexpr int NTHR = 384;
constexpr int UNIT = 6144;
constexpr int SLOT = 12288;
#define TAU 3880
#define TAUW 3700
#define TAU0 3780
#define ILV 4
#define XB 900
#define FORCE_BOTH 0
#define TMIN 2400
#define SLACK 6000
#define SLACK0 1000
#define LEADW 3500
#define WIN_W 3
#define WIN_S 4
#define WIN_U 10
#define VPF 4
#define KRE_TAU 2600
#define RFR_TAU 22400
#define HOP1_NS 200
#define KPRE 2
#define KPRE2 2
#define LAST0 4
#define LAST1 4
#define LAST2 2
#define LAST_LATE 0xaa8
#define FSTEP 4
#define DELAY_L 2
#define DELAY_G 2
#define DELAY_C 3
#define DELAY_D 0
#define DELAY_E 1
#define REG_LO "40"
#define REG_HI "232"
#define SPIN_LOG 17
constexpr int SPIN_LIMIT = 1 << SPIN_LOG;

__host__ __device__ constexpr uint32_t pairL(uint32_t region, uint32_t c, uint32_t g) { return (g & 1) | ((g >> 1) << 2) | (c << 5) | (region << 6); }
__host__ __device__ constexpr uint32_t pairG(uint32_t d, uint32_t c, uint32_t i) { return (i & 1) | ((i >> 1) << 2) | (d << 4) | (c << 5) | (3u << 6); }
constexpr uint32_t RA = 0, RC = 1, RE = 2, HALF = 16384, COPY = 4096, PMASK = 0x59;
constexpr uint32_t XS = 0;
constexpr uint32_t XS2 = XS + 128 * 7680;
constexpr uint32_t XSEND = XS2 + 128 * 768;
__device__ uint4 g_s[XSEND / 16];
__device__ uint4 g_x[(4u << 20) / 16];
#define SWEEPS(k, n) do {} while (0)

constexpr uint32_t S_WD = 16 * SLOT;
constexpr uint32_t S_DUMMY = S_WD + 15360;
constexpr uint32_t S_BAR = S_DUMMY + 4096;
constexpr uint32_t S_FV = S_BAR, S_FK = S_FV + 64, S_RING = S_FK + 64, S_DBAR = S_RING + 48, S_WFULL = S_DBAR + 32, S_QRDY = S_WFULL + 88;
constexpr uint32_t S_RELK = S_QRDY + 8, S_RELV = S_RELK + 8, S_RELR = S_RELV + 8, S_RELW = S_RELR + 8, S_SCO = S_RELW + 24;
constexpr uint32_t S_OS1 = S_SCO + 8;
constexpr uint32_t S_ZERO = S_OS1 + 8;
constexpr uint32_t S_KF = S_ZERO + 8;
constexpr uint32_t S_TOK = S_KF + 8;
constexpr uint32_t S_SIDE = S_TOK + 80, S_GATE = S_SIDE + 4;
constexpr uint32_t S_STAT = S_GATE + 12, S_SWR = S_STAT + 16;
constexpr uint32_t S_LN = S_STAT + 32;
constexpr uint32_t S_XCAR = S_LN + 64;
constexpr uint32_t S_CSQ = S_XCAR + 320;
constexpr uint32_t S_CSGU = S_CSQ + 768;
constexpr uint32_t S_RED = S_CSGU + 768;
constexpr uint32_t S_L0 = S_RED;
constexpr uint32_t S_OS = S_RED + 5120;
constexpr uint32_t S_PS = S_OS + 1536;
constexpr uint32_t PS_MAX = 512, PS_PASS = 544;
constexpr uint32_t S_QS = S_PS + 2 * PS_PASS;
constexpr uint32_t S_XB = S_QS + 1536;
constexpr uint32_t S_XA = S_XB + 768;
constexpr uint32_t S_HS = S_XA + 768;
constexpr uint32_t S_X0 = S_HS + 768;
constexpr uint32_t S_SC = S_X0 + 640;
constexpr uint32_t S_TM = S_SC + 512;
constexpr int SMEM_BYTES = S_TM + 256;
static_assert(SMEM_BYTES <= 232448 && S_STAT % 16 == 0 && S_RED % 16 == 0 && S_XB % 16 == 0 && S_HS % 16 == 0 && S_PS % 16 == 0 && S_QS % 16 == 0, "smem");
static_assert(S_SCO == S_BAR + 44 * 8 && S_RELK == S_BAR + 38 * 8, "barriers");
constexpr uint32_t ST_WQ = 3 * SLOT, ST_WG = 8 * SLOT, ST_WO = 11 * SLOT;

__device__ __forceinline__ uint32_t smem_u32(const void* p) { return (uint32_t)__cvta_generic_to_shared(p); }
__device__ __forceinline__ void mbar_arrive(uint32_t bar) { asm volatile("mbarrier.arrive.shared::cta.b64 _, [%0];" :: "r"(bar) : "memory"); }
__device__ __forceinline__ bool mbar_try(uint32_t bar, uint32_t parity) {
    uint32_t ok;
    asm volatile("{\n .reg .pred p;\n mbarrier.try_wait.parity.shared::cta.b64 p, [%1], %2;\n selp.u32 %0, 1, 0, p;\n}" : "=r"(ok) : "r"(bar), "r"(parity) : "memory");
    return ok != 0;
}
__device__ __forceinline__ bool mbar_test(uint32_t bar, uint32_t parity) {
    uint32_t ok;
    asm volatile("{\n .reg .pred p;\n mbarrier.test_wait.parity.shared::cta.b64 p, [%1], %2;\n selp.u32 %0, 1, 0, p;\n}" : "=r"(ok) : "r"(bar), "r"(parity) : "memory");
    return ok != 0;
}
__device__ __forceinline__ void mbar_wait(uint32_t bar, uint32_t parity) {
    int n = 0;
    while (!mbar_try(bar, parity) && ++n < SPIN_LIMIT) {}
}
__device__ __forceinline__ uint32_t gtime32() { uint32_t t; asm volatile("mov.u32 %0, %globaltimer_lo;" : "=r"(t)); return t; }
__device__ __forceinline__ void bar_main() { asm volatile("bar.sync 1, 256;" ::: "memory"); }

__device__ __forceinline__ void mma16816(float (&c)[4], uint32_t a0, uint32_t a1, uint32_t a2, uint32_t a3, uint32_t b0, uint32_t b1) {
    asm("mma.sync.aligned.m16n8k16.row.col.f32.bf16.bf16.f32 {%0,%1,%2,%3}, {%4,%5,%6,%7}, {%8,%9}, {%0,%1,%2,%3};"
        : "+f"(c[0]), "+f"(c[1]), "+f"(c[2]), "+f"(c[3]) : "r"(a0), "r"(a1), "r"(a2), "r"(a3), "r"(b0), "r"(b1));
}
__device__ __forceinline__ void mmaA(float (&c)[4], const uint32_t (&a)[4], uint32_t b0, uint32_t b1) { mma16816(c, a[0], a[1], a[2], a[3], b0, b1); }
__device__ __forceinline__ void mma8(float (&c)[4], uint32_t a0, uint32_t a1, uint32_t b0) {
    asm("mma.sync.aligned.m16n8k8.row.col.f32.bf16.bf16.f32 {%0,%1,%2,%3}, {%4,%5}, {%6}, {%0,%1,%2,%3};"
        : "+f"(c[0]), "+f"(c[1]), "+f"(c[2]), "+f"(c[3]) : "r"(a0), "r"(a1), "r"(b0));
}
struct W80 { uint32_t a[2][4], c[2]; };
template <int N> __device__ __forceinline__ void mul80(float (&acc)[N][4], const W80 (&W)[N], const uint4& b, uint32_t b4) {
#pragma unroll
    for (int m = 0; m < N; m++) mmaA(acc[m], W[m].a[0], b.x, b.y);
#pragma unroll
    for (int m = 0; m < N; m++) mmaA(acc[m], W[m].a[1], b.z, b.w);
#pragma unroll
    for (int m = 0; m < N; m++) mma8(acc[m], W[m].c[0], W[m].c[1], b4);
}
__device__ __forceinline__ void ldsm2t(uint32_t (&r)[2], uint32_t addr) {
    asm volatile("ldmatrix.sync.aligned.m8n8.x2.trans.shared.b16 {%0,%1}, [%2];" : "=r"(r[0]), "=r"(r[1]) : "r"(addr) : "memory");
}
__device__ __forceinline__ void mmaV(float (&c)[4], const uint4& a, uint32_t b0, uint32_t b1) { mma16816(c, a.x, a.y, a.z, a.w, b0, b1); }
__device__ __forceinline__ void ldsm4(uint32_t (&r)[4], uint32_t addr) {
    asm volatile("ldmatrix.sync.aligned.m8n8.x4.shared.b16 {%0,%1,%2,%3}, [%4];" : "=r"(r[0]), "=r"(r[1]), "=r"(r[2]), "=r"(r[3]) : "r"(addr) : "memory");
}
__device__ __forceinline__ void ldsm4t(uint32_t (&r)[4], uint32_t addr) {
    asm volatile("ldmatrix.sync.aligned.m8n8.x4.trans.shared.b16 {%0,%1,%2,%3}, [%4];" : "=r"(r[0]), "=r"(r[1]), "=r"(r[2]), "=r"(r[3]) : "r"(addr) : "memory");
}
__device__ __forceinline__ uint32_t lds16(uint32_t a) { uint16_t v; asm volatile("ld.shared.u16 %0, [%1];" : "=h"(v) : "r"(a) : "memory"); return v; }
__device__ __forceinline__ uint32_t lds32(uint32_t a) { uint32_t v; asm volatile("ld.shared.u32 %0, [%1];" : "=r"(v) : "r"(a) : "memory"); return v; }
__device__ __forceinline__ float ldsf(uint32_t a) { return __uint_as_float(lds32(a)); }
__device__ __forceinline__ uint2 lds64(uint32_t a) { uint2 v; asm volatile("ld.shared.v2.u32 {%0,%1}, [%2];" : "=r"(v.x), "=r"(v.y) : "r"(a) : "memory"); return v; }
__device__ __forceinline__ uint4 lds128(uint32_t a) { uint4 v; asm volatile("ld.shared.v4.u32 {%0,%1,%2,%3}, [%4];" : "=r"(v.x), "=r"(v.y), "=r"(v.z), "=r"(v.w) : "r"(a) : "memory"); return v; }
__device__ __forceinline__ int ldsvol(uint32_t a) { int v; asm volatile("ld.volatile.shared.u32 %0, [%1];" : "=r"(v) : "r"(a) : "memory"); return v; }
__device__ __forceinline__ uint2 ldsvol64(uint32_t a) { uint2 v; asm volatile("{\n .reg .b64 d;\n ld.volatile.shared.b64 d, [%2];\n mov.b64 {%0,%1}, d;\n}" : "=r"(v.x), "=r"(v.y) : "r"(a) : "memory"); return v; }
__device__ __forceinline__ void stsvol64(uint32_t a, uint32_t x, uint32_t y) { asm volatile("{\n .reg .b64 d;\n mov.b64 d, {%1,%2};\n st.volatile.shared.b64 [%0], d;\n}" :: "r"(a), "r"(x), "r"(y) : "memory"); }
__device__ __forceinline__ void stsvol(uint32_t a, int v) { asm volatile("st.volatile.shared.u32 [%0], %1;" :: "r"(a), "r"(v) : "memory"); }
__device__ __forceinline__ void sts_hi16(uint32_t a, float v) { asm volatile("{\n .reg .b16 lo, hi;\n mov.b32 {lo, hi}, %1;\n st.shared.u16 [%0], hi;\n}" :: "r"(a), "r"(__float_as_uint(v)) : "memory"); }
__device__ __forceinline__ void sts16(uint32_t a, uint32_t v) { asm volatile("st.shared.u16 [%0], %1;" :: "r"(a), "r"(v) : "memory"); }
__device__ __forceinline__ void sts32(uint32_t a, uint32_t v) { asm volatile("st.shared.u32 [%0], %1;" :: "r"(a), "r"(v) : "memory"); }
__device__ __forceinline__ void stsf(uint32_t a, float v) { sts32(a, __float_as_uint(v)); }
__device__ __forceinline__ void sts64(uint32_t a, uint32_t x, uint32_t y) { asm volatile("st.shared.v2.u32 [%0], {%1,%2};" :: "r"(a), "r"(x), "r"(y) : "memory"); }

__device__ __forceinline__ void sts32_if(bool p, uint32_t a, uint32_t v) {
    asm volatile("{\n .reg .pred p;\n setp.ne.u32 p, %2, 0;\n @p st.shared.u32 [%0], %1;\n}" :: "r"(a), "r"(v), "r"((uint32_t)p) : "memory");
}
__device__ __forceinline__ void arrive_if(bool p, uint32_t bar) {
    asm volatile("{\n .reg .pred p;\n setp.ne.u32 p, %1, 0;\n @p mbarrier.arrive.shared::cta.b64 _, [%0];\n}" :: "r"(bar), "r"((uint32_t)p) : "memory");
}
__device__ __forceinline__ void keep(uint32_t& v) { asm volatile("" : "+r"(v)); }
__device__ __forceinline__ void keep(float& v) { asm volatile("" : "+f"(v)); }

__device__ __forceinline__ uint32_t ldp32(const char* p) { uint32_t v; asm volatile("ld.relaxed.gpu.global.u32 %0, [%1];" : "=r"(v) : "l"(p) : "memory"); return v; }
__device__ __forceinline__ uint2 ldp64(const char* p) {
    uint2 v; asm volatile("{\n .reg .b64 d;\n ld.relaxed.gpu.global.b64 d, [%2];\n mov.b64 {%0,%1}, d;\n}" : "=r"(v.x), "=r"(v.y) : "l"(p) : "memory"); return v;
}
__device__ __forceinline__ uint32_t tagw(float f, uint32_t par) { return (__float_as_uint(f) & ~1u) | par; }
__device__ __forceinline__ void stp32(char* p, float a, uint32_t par) { asm volatile("st.relaxed.gpu.global.u32 [%0], %1;" :: "l"(p), "r"(tagw(a, par)) : "memory"); }
__device__ __forceinline__ void stp64(char* p, float a, float b, uint32_t par) {
    asm volatile("{\n .reg .b64 d;\n mov.b64 d, {%1,%2};\n st.relaxed.gpu.global.b64 [%0], d;\n}" :: "l"(p), "r"(tagw(a, par)), "r"(tagw(b, par)) : "memory");
}
__device__ __forceinline__ void stp32_if(bool p, char* d, float a, uint32_t par) {
    asm volatile("{\n .reg .pred p;\n setp.ne.u32 p, %2, 0;\n @p st.relaxed.gpu.global.u32 [%0], %1;\n @p st.relaxed.gpu.global.u32 [%0+4096], %1;\n}" :: "l"(d), "r"(tagw(a, par)), "r"((uint32_t)p) : "memory");
}
__device__ __forceinline__ void stp32_if(bool p, uint32_t both, char* d, char* e, float a, uint32_t par) {
    asm volatile("{\n .reg .pred p, q;\n setp.ne.u32 p, %2, 0;\n setp.ne.and.u32 q, %4, 0, p;\n @p st.relaxed.gpu.global.u32 [%3], %1;\n @q st.relaxed.gpu.global.u32 [%0], %1;\n}" :: "l"(d), "r"(tagw(a, par)), "r"((uint32_t)p), "l"(e), "r"(both) : "memory");
}
__device__ __forceinline__ void stp64_if(bool p, uint32_t both, char* d, char* e, uint32_t lo, uint32_t hi) {
    asm volatile("{\n .reg .pred p, q;\n .reg .b64 d;\n setp.ne.u32 p, %3, 0;\n setp.ne.and.u32 q, %5, 0, p;\n mov.b64 d, {%1,%2};\n @p st.relaxed.gpu.global.b64 [%4], d;\n @q st.relaxed.gpu.global.b64 [%0], d;\n}" :: "l"(d), "r"(lo), "r"(hi), "r"((uint32_t)p), "l"(e), "r"(both) : "memory");
}
__device__ __forceinline__ uint32_t chk2(uint32_t a, uint32_t b, uint32_t par) { uint32_t r; asm("lop3.b32 %0, %1, %2, %3, 0x7E;" : "=r"(r) : "r"(a), "r"(b), "r"(par)); return r; }
__device__ __forceinline__ uint32_t or3(uint32_t a, uint32_t b, uint32_t c) { uint32_t r; asm("lop3.b32 %0, %1, %2, %3, 0xFE;" : "=r"(r) : "r"(a), "r"(b), "r"(c)); return r; }
__device__ __forceinline__ uint32_t chk8(const uint32_t (&v)[8], uint32_t par) { return or3(chk2(v[0], v[1], par), chk2(v[2], v[3], par), or3(chk2(v[4], v[5], par), chk2(v[6], v[7], par), 0)); }
__device__ __forceinline__ uint32_t chk8(const uint2 (&v)[8], uint32_t par) { return or3(chk2(v[0].x, v[1].x, par), chk2(v[2].x, v[3].x, par), or3(chk2(v[4].x, v[5].x, par), chk2(v[6].x, v[7].x, par), 0)); }
__device__ __forceinline__ uint32_t chk8y(const uint2 (&v)[8], uint32_t par) { return or3(chk2(v[0].y, v[1].y, par), chk2(v[2].y, v[3].y, par), or3(chk2(v[4].y, v[5].y, par), chk2(v[6].y, v[7].y, par), 0)); }
__device__ __forceinline__ uint32_t chk4(const uint2 (&v)[4], uint32_t par) { return or3(chk2(v[0].x, v[0].y, par), chk2(v[1].x, v[1].y, par), or3(chk2(v[2].x, v[2].y, par), chk2(v[3].x, v[3].y, par), 0)); }
__device__ __forceinline__ float asf(uint32_t v) { return __uint_as_float(v); }
__device__ __forceinline__ float sum8(const uint32_t (&v)[8]) { return ((asf(v[0]) + asf(v[1])) + (asf(v[2]) + asf(v[3]))) + ((asf(v[4]) + asf(v[5])) + (asf(v[6]) + asf(v[7]))); }
__device__ __forceinline__ float sum8x(const uint2 (&v)[8]) { return ((asf(v[0].x) + asf(v[1].x)) + (asf(v[2].x) + asf(v[3].x))) + ((asf(v[4].x) + asf(v[5].x)) + (asf(v[6].x) + asf(v[7].x))); }
__device__ __forceinline__ float sum8y(const uint2 (&v)[8]) { return ((asf(v[0].y) + asf(v[1].y)) + (asf(v[2].y) + asf(v[3].y))) + ((asf(v[4].y) + asf(v[5].y)) + (asf(v[6].y) + asf(v[7].y))); }

__device__ __forceinline__ uint32_t pack2(float lo, float hi) { uint32_t r; asm("cvt.rn.bf16x2.f32 %0, %1, %2;" : "=r"(r) : "f"(hi), "f"(lo)); return r; }
__device__ __forceinline__ float bfr(float x) { return __uint_as_float(pack2(0.0f, x)); }
__device__ __forceinline__ float ex2(float x) { float r; asm("ex2.approx.ftz.f32 %0, %1;" : "=f"(r) : "f"(x)); return r; }
__device__ __forceinline__ float rcp(float x) { float r; asm("rcp.approx.ftz.f32 %0, %1;" : "=f"(r) : "f"(x)); return r; }
__device__ __forceinline__ float sqrt_(float x) { float r; asm("sqrt.approx.ftz.f32 %0, %1;" : "=f"(r) : "f"(x)); return r; }
__device__ __forceinline__ float bf_lo(uint32_t v) { return __uint_as_float(v << 16); }
__device__ __forceinline__ float bf_hi(uint32_t v) { return __uint_as_float(v & 0xffff0000u); }
__device__ __forceinline__ float sel4(int k, float a, float b, float c, float d) { return (k & 2) ? ((k & 1) ? d : c) : ((k & 1) ? b : a); }
constexpr float LOG2E = 1.4426950408889634f;
constexpr uint32_t ONES = 0x3f803f80u;

__device__ __forceinline__ void ln_stats(float sum, float sq, float& mean, float& den) {
    const float m = sum * (1.0f / 640.0f);
    const float var = fmaxf(fmaf(sq, 1.0f / 640.0f, -m * m), 0.0f);
    mean = bfr(m);
    den = bfr(sqrt_(bfr(bfr(var) + 1e-5f)));
}
__device__ __forceinline__ float sigmoidf_(float x) { return rcp(1.0f + ex2(-x * LOG2E)); }

#define TSTAMP(k) do {} while (0)
#define TST(k) do {} while (0)

#define CSTAMP(k) do {} while (0)
template <int N> __device__ __forceinline__ uint32_t lag(uint32_t sb, uint32_t z = 0) {
#pragma unroll
    for (int k = 0; k < N; k++) z = ldsvol(sb + S_ZERO + z);
    return z;
}
__device__ __forceinline__ void warm_mma(uint32_t& a, uint32_t& b) {
    asm volatile("mma.sync.aligned.m16n8k8.row.col.f16.f16.f16.f16 {%0,%1}, {%0,%1}, {%0}, {%0,%1};" : "+r"(a), "+r"(b) :: "memory");
}
#define KWNS2 20
#define KWNS 200
template <class F>
__device__ __forceinline__ void gather16(const char* p, uint32_t par, int k, F use) {
    uint32_t v[8], u[8];
    int guard = 0;
    bool again;
    do {
#pragma unroll
        for (int s = 0; s < 8; s++) v[s] = ldp32(p + s * 512);
#pragma unroll
        for (int s = 0; s < 8; s++) u[s] = ldp32(p + HALF + s * 512);
        const uint32_t stale = use(sum8(v) + sum8(u), ((v[0] ^ par) & 1) * 8);
        again = __any_sync(~0u, (or3(chk8(v, par), chk8(u, par), stale) & 1) != 0);
    } while (again & (++guard < SPIN_LIMIT));
    SWEEPS(k, guard - 1);
}

struct Params {
    const __nv_bfloat16 *x, *k, *v, *wr, *wq;
    __nv_bfloat16* out;
};
struct Maps { CUtensorMap k, v, vu, wq, wo, wg, wu, wd; };

constexpr int KV_BATCH_KEYS = 32 * 4096;

__device__ __forceinline__ void tma2d(uint32_t dst, const CUtensorMap* m, int c0, int c1, uint32_t bar, uint32_t bytes, uint64_t pol) {
    asm volatile("{\n .reg .pred p;\n elect.sync _|p, 0xffffffff;\n"
                 " @p mbarrier.arrive.expect_tx.shared::cta.b64 _, [%2], %6;\n"
                 " @p cp.async.bulk.tensor.2d.shared::cluster.global.mbarrier::complete_tx::bytes.L2::cache_hint [%0], [%1, {%3, %4}], [%2], %5;\n}"
                 :: "r"(dst), "l"(m), "r"(bar), "r"(c0), "r"(c1), "l"(pol), "r"(bytes) : "memory");
}
__device__ __forceinline__ void scrap_copy(uint32_t dst, const char* src, uint32_t bar) {
    asm volatile("{\n .reg .pred p;\n elect.sync _|p, 0xffffffff;\n"
                 " @p mbarrier.arrive.expect_tx.shared::cta.b64 _, [%2], 12288;\n"
                 " @p cp.async.bulk.shared::cluster.global.mbarrier::complete_tx::bytes [%0], [%1], 4096, [%2];\n"
                 " @p cp.async.bulk.shared::cluster.global.mbarrier::complete_tx::bytes [%0], [%1+4096], 4096, [%2];\n"
                 " @p cp.async.bulk.shared::cluster.global.mbarrier::complete_tx::bytes [%0], [%1+8192], 4096, [%2];\n}"
                 :: "r"(dst), "l"(src), "r"(bar) : "memory");
}
__device__ __forceinline__ void prefetch_l2(const void* p, uint32_t bytes) {
    asm volatile("{\n .reg .pred p;\n elect.sync _|p, 0xffffffff;\n @p cp.async.bulk.prefetch.L2.global [%0], %1;\n}" :: "l"(p), "r"(bytes) : "memory");
}
__device__ __forceinline__ uint64_t pol_first() { uint64_t p; asm("createpolicy.fractional.L2::evict_first.b64 %0, 1.0;" : "=l"(p)); return p; }
__device__ __forceinline__ uint64_t pol_normal() { uint64_t p; asm("createpolicy.fractional.L2::evict_normal.b64 %0, 1.0;" : "=l"(p)); return p; }
__device__ __forceinline__ bool utest(uint32_t bar, uint32_t parity) { return __all_sync(~0u, mbar_test(bar, parity)); }
__device__ __forceinline__ void uwait(uint32_t bar, uint32_t parity) {
    int n = 0;
    while (!__all_sync(~0u, mbar_try(bar, parity)) && ++n < SPIN_LIMIT) {}
}
template <int A, int B, int CNT> __device__ __forceinline__ void init_bars(uint32_t sb) {
#pragma unroll 1
    for (int k = A; k < B; k++)
        asm volatile("{\n .reg .pred p;\n elect.sync _|p, 0xffffffff;\n @p mbarrier.init.shared::cta.b64 [%0], %1;\n}" :: "r"(sb + S_BAR + 8 * k), "n"(CNT) : "memory");
}
__device__ __forceinline__ int unit_key(uint32_t b, uint32_t u) {
    return (blockIdx.x >> 2) * 4096 + 3072 + (blockIdx.x & 3) * (16 * ILV) + b * KV_BATCH_KEYS + (u & ~(ILV - 1u)) * 64 + (u & (ILV - 1)) * 16;
}
__device__ __forceinline__ void load_tile(const CUtensorMap* m, uint32_t dst, uint32_t bar, uint32_t bytes, int key, uint64_t pol) { tma2d(dst, m, 0, 3 * key, bar, bytes, pol); }
__device__ __forceinline__ const char* unit_ptr(const Params& P, int n) { return (const char*)((n & 16) ? P.v : P.k) + (size_t)unit_key(n >> 5, n & 15) * 384; }
#define LSTAMP(k) do {} while (0)

__device__ __forceinline__ uint32_t k_place(uint32_t b, uint32_t s) { return s + 3 + 5 * (b & 1); }
__device__ __forceinline__ uint32_t v_place(uint32_t b, uint32_t s) { return s < 3 ? s : s + 8 - 8 * (b & 1); }
__device__ __forceinline__ void k_load(const Maps& M, uint32_t dst, uint32_t bar, int key8, uint64_t pol) {
    asm volatile("{\n .reg .pred p;\n elect.sync _|p, 0xffffffff;\n"
                 " @p mbarrier.arrive.expect_tx.shared::cta.b64 _, [%2], 6144;\n"
                 " @p cp.async.bulk.tensor.4d.shared::cluster.global.mbarrier::complete_tx::bytes.L2::cache_hint [%0], [%1, {0, 0, 0, %3}], [%2], %4;\n}"
                 :: "r"(dst), "l"(&M.k), "r"(bar), "r"(key8), "l"(pol) : "memory");
}
__device__ __forceinline__ int unit_key8(uint32_t n) { return unit_key(n >> 4, n & 15) >> 3; }
__device__ __forceinline__ void ring_load(const Maps& M, uint32_t sb, uint32_t b, uint32_t u, uint32_t pos) {
    if (u < 16) k_load(M, sb + pos * UNIT, sb + S_RING + 8 * pos, unit_key8(16 * b + u), pol_normal());
    else load_tile(&M.vu, sb + pos * UNIT, sb + S_FV + 4 * (pos & 6), UNIT, unit_key(b, pos), pol_first());
}
__device__ __forceinline__ uint32_t token(bool p, uint32_t a, uint32_t n) {
    uint32_t v;
    asm volatile("{\n .reg .pred p;\n setp.ne.u32 p, %2, 0;\n mov.u32 %0, 0;\n @p atom.shared.exch.b32 %0, [%1], %3;\n}" : "=r"(v) : "r"(a), "r"((uint32_t)p), "r"(n) : "memory");
    return v;
}
__device__ __forceinline__ void place_load(const Maps& M, uint32_t sb, uint32_t n) {
    k_load(M, sb + k_place(n >> 4, 0) * SLOT + (n & 15) * UNIT, sb + S_FK + 4 * (n & 14), unit_key8(n), pol_first());
}
__device__ __forceinline__ void v_load(const Maps& M, uint32_t sb, uint32_t b, uint32_t s) {
    load_tile(&M.v, sb + v_place(b, s) * SLOT, sb + S_FV + 8 * s, SLOT, unit_key(b, 2 * s), pol_first());
}

__device__ __forceinline__ void stream_warp(const Params& P, const Maps& M, uint32_t sb, uint32_t lane) {
    const uint64_t pol = pol_first();
    const int bid = blockIdx.x, g = bid >> 3, i = bid & 7;
    const uint32_t wf = sb + S_WFULL;
    uint32_t tn = __shfl_sync(~0u, gtime32(), 0) * 16;
    auto pace = [&](uint32_t dt) {
        int k = 0;
        uint32_t now;
        do now = __shfl_sync(~0u, gtime32(), 0) * 16; while ((int)(now - tn) < 0 && ++k < SPIN_LIMIT);
        if ((int)(now - tn) > SLACK0) tn = now - SLACK0;
        tn += dt;
    };
#pragma unroll
    for (int k = 0; k < 10; k++) {
        if (k < 2) {
            if (k == 0) init_bars<26, 27, 1>(sb); else init_bars<27, 37, 1>(sb);
            asm volatile("fence.mbarrier_init.release.cluster;" ::: "memory");
            if (k == 1) { asm volatile("bar.arrive 2, %0;" :: "n"(NTHR) : "memory"); asm volatile("bar.sync 3, 128;" ::: "memory"); }
        }
        if (k >= WIN_W) uwait(wf + 8 * (k - WIN_W), 0);
        pace(TAUW * 5 / 2 - (k == 0 || k == 2 ? LEADW : 0));
        if (k < 4) tma2d(sb + ST_WQ + 15360 * k, &M.wq, 384 * g + 192 * (k >> 1), 80 * i + 40 * (k & 1), wf + 8 * k, 15360, pol);
        else if (k < 6) tma2d(sb + ST_WG + 15360 * (k - 4), k == 4 ? &M.wg : &M.wu, 96 * g, 80 * i, wf + 8 * k, 15360, pol);
        else tma2d(sb + ST_WO + 15360 * (k - 6), &M.wo, 80 * i, 384 * g + 96 * (k - 6), wf + 8 * k, 15360, pol);
    }
#pragma unroll 1
    for (int n = 0; n < 16; n++) {
        if (n == 0 || n == 5 || n == 11) uwait(sb + S_RELW + (n == 0 ? 0 : n == 5 ? 8 : 16), 0);
        uwait(n < WIN_S ? wf + 8 * (10 - WIN_S + n) : sb + S_FV + 8 * ((n - WIN_S) ^ 8), 0);
        pace(2 * TAU0);
        if (n >= WIN_S && !utest(sb + S_FV + 8 * ((n - WIN_S + 1) ^ 8), 0)) tn += XB;
        if (n < 8) { place_load(M, sb, 2 * n); place_load(M, sb, 2 * n + 1); }
        else if (n < 11) { ring_load(M, sb, 0, 2 * n, 2 * n - 16); ring_load(M, sb, 0, 2 * n + 1, 2 * n - 15); }
        else v_load(M, sb, 0, n - 8);
        if (n == 7) { pace(TAUW * 5 / 2); tma2d(sb + S_WD, &M.wd, 80 * i, 96 * g, wf + 80, 15360, pol); }
    }
    int nd = 0;
    uint32_t q[4];
#pragma unroll
    for (int r = 0; r < 4; r++) q[r] = sb + S_FV + 8 * (7 - r);
    uint32_t td = tn;
    uint32_t pos = 2;
#pragma unroll 1
    for (int m = 16; m < 64; m++) {
        const int b = m >> 4, j = m & 15;
        const char* src = unit_ptr(P, 2 * m);
        const uint32_t tok = sb + S_TOK + (j < 3 ? 4 * pos : j < 11 ? 24 + 4 * pos : 16 + 4 * j) + 4 * lane;
        static_assert(WIN_U <= 12, "a ring position has at most one token of the timetable");
        int k = 0;
        while (true) {
            const uint2 c = lds64(sb + S_KF);
            if (__all_sync(~0u, mbar_test(q[WIN_S - 1] & ~1u, q[WIN_S - 1] & 1) & (min((int)c.x + 1, (int)c.y) >= 16 * b + min(2 * j + 2 - WIN_U, 16))) || ++k >= SPIN_LIMIT) break;
        }
        uint32_t now;
        while (true) {
            now = __shfl_sync(~0u, gtime32(), 0) * 16;
            if ((int)(now - td) >= 0 || ++k >= SPIN_LIMIT) break;
        }
        const uint32_t mine = __ballot_sync(~0u, token(lane < (j < 11 ? 2 : 1), tok, 2 * m + lane) == 2 * m + lane);
        {
            const uint2 c = lds64(sb + S_KF);
            if (!__all_sync(~0u, mbar_test(q[WIN_S - 2] & ~1u, q[WIN_S - 2] & 1) & (min((int)c.x + 1, (int)c.y) >= 16 * b + min(2 * j + 4 - WIN_U, 16)))) tn += XB;
        }
        q[3] = q[2]; q[2] = q[1]; q[1] = q[0]; q[0] = sb + S_QRDY;
        if (j < 11) {
            if (mine & 1) ring_load(M, sb, b, 2 * j, pos); else prefetch_l2(src, UNIT);
            if (mine & 2) ring_load(M, sb, b, 2 * j + 1, pos + 1); else prefetch_l2(src + UNIT, UNIT);
            if (j >= 8) q[0] = (sb + S_FV + 8 * (j - 8)) | (b & 1);
        } else if (mine) { v_load(M, sb, b, j - 8); q[0] = (sb + S_FV + 8 * (j - 8)) | (b & 1); }
        else if (j - 8 >= VPF) prefetch_l2(src, SLOT);
        else {
            scrap_copy(sb + S_DUMMY, src, sb + S_DBAR + 8 * (nd & 3));
            q[0] = (sb + S_DBAR + 8 * (nd & 3)) | ((nd >> 2) & 1);
            nd++;
        }
        pos = j == 15 ? 2 : pos == 4 ? 0 : pos + 2;
        if ((int)(now - tn) > SLACK) tn = now - SLACK;
        tn += 2 * TAU;
        td = (int)(tn - now) > 2 * TMIN ? tn : now + 2 * TMIN;
    }
#pragma unroll 1
    for (int m = max(nd - 4, 0); m < nd; m++) uwait(sb + S_DBAR + 8 * (m & 3), (m >> 2) & 1);
}

__host__ __device__ constexpr uint64_t bit_list(uint32_t m) { uint64_t r = 0; int n = 0; for (int k = 0; k < 12; k++) if ((m >> k) & 1) r |= (uint64_t)k << (4 * n++); return r; }
__device__ __forceinline__ float scaled(float s) { return bfr(bfr(s) * 0.07216878364870322f); }
__device__ __forceinline__ void probs(float s, uint32_t ps, uint32_t src, uint32_t ln) {
    const uint32_t q8 = ln >> 2, t4 = ln & 3;
    int key = __float_as_int(s);
    key ^= (key >> 31) & 0x7fffffff;
    key = __reduce_max_sync(~0u, key);
    key ^= (key >> 31) & 0x7fffffff;
    const float ml = __int_as_float(key) * LOG2E;
    sts16(ps + 64 * src + (q8 >> 1) * 16 + t4 * 4 + (q8 & 1) * 2, pack2(ex2(fmaf(s, LOG2E, -ml)), 0.f));
    stsf(ps + PS_MAX + 4 * src, ml);
}
template <int H> __device__ __forceinline__ uint32_t b_pos(uint32_t e) { const uint32_t h = e >= H, k = e - H * h; return h * 192 + (k & 6) * 24 + (k >> 3) * 4 + (k & 1) * 2; }
__device__ __forceinline__ uint32_t a_pos(uint32_t e) { const uint32_t h = e >= 40, k = e - 40 * h; return (k & 6) * 24 + (k >> 3) * 8 + h * 4 + (k & 1) * 2; }
__device__ __forceinline__ uint32_t q_pos(uint32_t d) { const uint32_t s = 3 * ((d >> 4) & 3) + (d >> 6); return s * 32 + (d & 6) * 4 + ((d >> 3) & 1) * 4 + (d & 1) * 2; }
__device__ __forceinline__ uint32_t k_off(uint32_t ln) { return (ln & 8) * 384 + (ln & 7) * 128 + (((ln & 7) ^ (ln >> 4)) << 4); }

#define HSTAMP(k) do {} while (0)
__device__ __forceinline__ char* xwindow() { return reinterpret_cast<char*>((reinterpret_cast<uintptr_t>(g_x) + (2u << 20) - 1) & ~(uintptr_t)((2u << 20) - 1)); }

struct XPtr {
    uint32_t lo, hi;
    __device__ __forceinline__ explicit XPtr(char* p) : lo((uint32_t)(uintptr_t)p), hi((uint32_t)((uintptr_t)p >> 32)) {}
    __device__ __forceinline__ XPtr(uint32_t l, uint32_t h) : lo(l), hi(h) {}
    __device__ __forceinline__ XPtr operator+(uint32_t o) const { return XPtr(lo + o, hi); }
    __device__ __forceinline__ operator char*() const { uint64_t p; asm("mov.b64 %0, {%1, %2};" : "=l"(p) : "r"(lo), "r"(hi)); return (char*)p; }
};

__device__ __forceinline__ char* side_word(uint32_t g, uint32_t i) { return xwindow() + pairG(1, 0, i) * 8192 + (g >> 3) * HALF + (g & 7) * 512 + 320; }

__device__ __forceinline__ uint32_t probe_side() {
    const uint32_t bid = blockIdx.x, g = bid >> 3, i = bid & 7, P = pairG(0, 0, i);
    char* p = xwindow() + P * 8192 + (g >> 3) * HALF + (g & 7) * 512 + 352;
    uint32_t best[2] = {~0u, ~0u};
#pragma unroll
    for (int k = 0; k < 4; k++) *reinterpret_cast<uint4*>(p + (k & 1) * 16 + (k >> 1) * COPY) = make_uint4(1, 1, 1, 1);
#pragma unroll 1
    for (int r = 0; r < 64; r++) {
        if (r >= 4 && !(r & 1) && min(best[0], best[1]) < 380 && max(best[0], best[1]) > min(best[0], best[1]) + 80) break;
        uint32_t c0, c1, v;
        asm volatile("mov.u32 %0, %clock;" : "=r"(c0) :: "memory");
        asm volatile("atom.relaxed.gpu.global.exch.b32 %0, [%1], 0;" : "=r"(v) : "l"(p + (r & 1) * COPY) : "memory");
        asm volatile("{\n .reg .pred q;\n setp.eq.u32 q, %1, 0x13579bdf;\n mov.u32 %0, 0;\n @!q mov.u32 %0, %clock;\n}" : "=r"(c1) : "r"(v) : "memory");
        if (r & 1) best[1] = min(best[1], c1 - c0); else best[0] = min(best[0], c1 - c0);
    }
    return 1 + ((best[1] < best[0]) ^ (__popc(P & PMASK) & 1));
}

template <int N>
__device__ __forceinline__ void hop_a(const char* src, uint32_t par, uint32_t dst, bool st, int k) {
    uint2 v[N][4];
    float e[4], rl;
    int guard = 0;
    bool again;
    do {
#pragma unroll
        for (int s = 0; s < 4 * N; s++) v[s / 4][s % 4] = ldp64(src + (s / 4) * 256 + (s % 4) * 1024);
        again = __any_sync(~0u, ((chk4(v[0], par) | chk4(v[N - 1], par)) & 1) != 0);
        const int M = max(max((int)v[0][0].x, (int)v[0][1].x), max((int)v[0][2].x, (int)v[0][3].x)) - 254;
#pragma unroll
        for (int s = 0; s < 4; s++) e[s] = __int_as_float(max((int)v[0][s].x - M, 0) << 22);
        rl = rcp(fmaf(e[0], asf(v[0][0].y), e[1] * asf(v[0][1].y)) + fmaf(e[2], asf(v[0][2].y), e[3] * asf(v[0][3].y)));
#pragma unroll
        for (int s = 0; s < 4; s++) e[s] = __shfl_sync(~0u, e[s], 24);
        keep(rl);
    } while (again & (++guard < SPIN_LIMIT));
    rl = __shfl_sync(~0u, rl, 24);
#pragma unroll
    for (int n = 0; n < N; n++) {
        const float o0 = fmaf(e[0], asf(v[n][0].x), e[1] * asf(v[n][1].x)) + fmaf(e[2], asf(v[n][2].x), e[3] * asf(v[n][3].x));
        const float o1 = fmaf(e[0], asf(v[n][0].y), e[1] * asf(v[n][1].y)) + fmaf(e[2], asf(v[n][2].y), e[3] * asf(v[n][3].y));
        sts32_if(st, dst + 192 * n, pack2(o0 * rl, o1 * rl));
    }
    SWEEPS(k, guard - 1);
    __syncwarp();
}

__device__ __forceinline__ void score_warp(const Maps& M, uint32_t sb, uint32_t h, uint32_t ln) {
    const uint32_t lane0 = ln;
    uwait(sb + S_QRDY, 0);
    const uint32_t q8 = ln >> 2;
    const uint32_t k0 = k_off(ln);
    uint32_t pos = h + 6, bar = sb + S_FK, par = 0, phases = 0;
    uint2 q = lds64(sb + S_QS + 8 * ln), qh = lds64(sb + S_QS + 8 * ln + 256);
    auto first_round = [&](uint32_t b, uint32_t ln) {
        uwait(sb + S_RELR, b & 1);
        const uint32_t u = h + 2 * ln, p = u < 4 ? u + 2 : u - 4;
        uint32_t todo = __ballot_sync(~0u, token(ln < 3, sb + S_TOK + 4 * p, 32 * b + 32 + u) == 32 * b + 32 + u);
#pragma unroll 1
        for (uint32_t r = h; todo; todo >>= 1, r += 2) if (todo & 1) ring_load(M, sb, b + 1, r, r < 4 ? r + 2 : r - 4);
    };
#pragma unroll 1
    for (uint32_t n = h; n < 64; n += 2) {
        HSTAMP(0);
        const uint32_t ua = sb + pos * UNIT;
        if (!__all_sync(~0u, mbar_try(bar, par))) uwait(bar, par);
        HSTAMP(1);
        float acc[2][4] = {};
        uint32_t mine = 0;
        const uint32_t id = n + (n & 48) + 6;
#pragma unroll
        for (int s = 0; s < 12; s++) {
            uint32_t kf[4];
            ldsm4(kf, (k0 ^ (32 * (s / 3))) + (ua + 1024 * (s % 3)));
            if (s == 11) {
                __syncwarp();
                mine = token(ln == 0 && n >= 16, sb + S_TOK + 24 + 4 * pos, id);
                stsvol(sb + S_KF + 4 * h, n + 1);
            }
            const bool m = q8 == (s & 7);
            mmaA(acc[s & 1], kf, m ? (s < 8 ? q.x : qh.x) : 0u, m ? (s < 8 ? q.y : qh.y) : 0u);
        }
        const uint32_t pos0 = pos;
        const bool last = (n & 14) == 14;
        pos = last ? h + 2 : n >= 16 && pos >= 4 ? h : pos + 2;
        bar = n >= 14 ? sb + S_RING + 8 * pos : bar + 8;
        par = n >= 14 ? (phases >> pos) & 1 : 0;
        phases ^= n >= 14 ? 1u << pos : 0;
        const float w0 = (acc[0][0] + acc[0][1]) + (acc[1][0] + acc[1][1]), w1 = (acc[0][2] + acc[0][3]) + (acc[1][2] + acc[1][3]);
        HSTAMP(2);
        if (__any_sync(~0u, mine == id)) ring_load(M, sb, n >> 4, (n & 15) + 6, pos0);
        HSTAMP(3);
        float s = ((ln & 1) ? w1 : w0) + __shfl_xor_sync(~0u, (ln & 1) ? w0 : w1, 1);
        s += __shfl_xor_sync(~0u, s, 2);
        sts_hi16(sb + S_SC + (((n & 12) >> 1) + h) * 64 + (n & 2) * 2 + (ln & 29) * 2, scaled(s));
        if (last) {
            __syncwarp();
            arrive_if(ln == 0, sb + S_SCO);
            const uint32_t b = n >> 4, ln = lane0 + lag<1>(sb);
            if (b > 0) {
                uwait(sb + S_RELK, (b - 1) & 1);
                if (h == 0) LSTAMP(64 + 2 * b);
                const uint32_t sl = 3 + h + 2 * ln, idv = 32 * b + 16 + 2 * sl;
                uint32_t todo = __ballot_sync(~0u, token(sl < 8, sb + S_TOK + 48 + 4 * sl, idv) == idv);
#pragma unroll 1
                for (uint32_t r = 3 + h; todo; todo >>= 1, r += 2) if (todo & 1) v_load(M, sb, b, r);
                const uint32_t g = blockIdx.x >> 3, pr = pairL(RA, 1, g), side = ldsvol(sb + S_SIDE);
                const char* src = xwindow() + pr * 8192 + ((side ^ 1 ^ __popc(pr & PMASK)) & 1) * COPY + h * HALF + 8 * min(ln, 24u);
                uwait(sb + S_RELV, (b - 1) & 1);
                __nanosleep(HOP1_NS);
#pragma unroll 1
                for (uint32_t r = 0; r < 4; r += 2) {
                    hop_a<2>(src + 256 * r, b & 1, sb + S_OS + 192 * (4 * h + r) + 96 + 4 * ln, ln < 24, 25);
                    if (r == 0 && b < 3) first_round(b, ln);
                }
                arrive_if(ln == 0, sb + S_OS1);
            } else first_round(0, ln);
            q = lds64(sb + S_QS + 24 * ((n + 2) & 48) + 8 * ln); qh = lds64(sb + S_QS + 24 * ((n + 2) & 48) + 8 * ln + 256);
        }
    }
}

__global__ void __launch_bounds__(NTHR, 1)
fused_kernel(const Params P, const __grid_constant__ Maps M) {
    extern __shared__ __align__(1024) unsigned char smem[];
    const uint32_t sb = smem_u32(smem);
    const int tid = threadIdx.x, bid = blockIdx.x;
    if (tid == 0) {
        asm volatile("prefetch.tensormap [%0];" :: "l"(&M.wq) : "memory");
        asm volatile("cp.async.bulk.prefetch.L2.global [%0], 12288;" :: "l"(P.wq + (80 * (bid & 7) + (bid >> 3)) * 6144) : "memory");
    }
    const int w = __shfl_sync(~0u, tid >> 5, 0), lane = tid & 31;

    if (w >= 8) {
        asm volatile("setmaxnreg.dec.sync.aligned.u32 " REG_LO ";");
        if (w == 8) {
            stream_warp(P, M, sb, lane);
        } else {
            if (w == 9) { init_bars<0, 3, 2>(sb); init_bars<3, 8, 1>(sb); init_bars<16, 22, 1>(sb); }
            else if (w == 10) { init_bars<8, 16, 2>(sb); init_bars<22, 26, 1>(sb); }
            else { init_bars<37, 38, 1>(sb); init_bars<38, 40, 8>(sb); init_bars<40, 41, 1>(sb); init_bars<41, 44, 8>(sb); init_bars<44, 46, 2>(sb); stsvol(sb + S_ZERO + 4 * lane, 0); if (lane < 16) stsvol(sb + S_LN + 4 * lane, 0); }
            asm volatile("fence.mbarrier_init.release.cluster;" ::: "memory");
            asm volatile("bar.arrive 3, 128;" ::: "memory");
            if (w == 11) asm volatile("bar.arrive 2, %0;" :: "n"(NTHR) : "memory");
            else {
                if (lane < 4) asm volatile("prefetch.tensormap [%0];" :: "l"(&M.k + lane + 4 * (w - 9)) : "memory");
                __syncwarp();
                asm volatile("bar.sync 2, %0;" :: "n"(NTHR) : "memory");
            }
            if (w < 11) score_warp(M, sb, w - 9, lane);
            else {
                uint32_t mine = 0;
                if (lane == 0) mine = probe_side();
                mine = __shfl_sync(~0u, mine, 0);
                if (lane < 8) stp32(side_word(bid >> 3, bid & 7) + 4 * lane, asf(mine & 2), 1);
                uint32_t a = 0, b = 0;
                int k = 0;
                while (!utest(sb + S_QRDY, 0) && ++k < SPIN_LIMIT) { warm_mma(a, b); __nanosleep(KWNS); }
                while (true) {
                    const uint32_t v = ldp32(side_word(bid >> 3, lane & 7));
                    const bool late = !__all_sync(~0u, v & 1);
                    if (!late || ++k >= SPIN_LIMIT) { stsvol(sb + S_SIDE, mine | (FORCE_BOTH || late || __any_sync(~0u, (v ^ mine) & 2) ? 4 : 0)); break; }
                    warm_mma(a, b); __nanosleep(KWNS);
                }
                while (ldsvol(sb + S_GATE) == 0 && ++k < SPIN_LIMIT) { warm_mma(a, b); __nanosleep(KWNS); }
                uint32_t rl = lane, rq = 0;
                auto reset = [&] {
                    if (rq < 128) *reinterpret_cast<uint4*>(reinterpret_cast<char*>(g_s) + (rl < 60 ? XS + bid * 7680 + 128 * rl : XS2 + bid * 768 + 128 * (rl - 60)) + rq) = make_uint4(0, 0, 0, 0);
                    rl += 32;
                    if (rl >= 66) { rl -= 66; rq += 16; }
                };
                reset(); reset();
                if (lane < 8) stp32(side_word(bid >> 3, bid & 7) + 4 * lane, 0.f, 0);
                const uint32_t side = (ldsvol(sb + S_SIDE) & 1) ^ 1, g = bid >> 3, i = bid & 7;
                const XPtr gx(xwindow());
                auto nearp = [&](uint32_t pr) { return gx.lo + pr * 8192 + ((side ^ __popc(pr & PMASK)) & 1) * COPY; };
                const uint32_t own = (i >> 2) * HALF + (i & 3) * 1024 + (lane & 7) * 128;
                const uint32_t cut = (lane & 7) == 7 ? 128 : 0;
                const uint32_t pAC = nearp(pairL(lane >> 4, (lane >> 3) & 1, g)) + own - (lane >> 4) * cut, pE = nearp(pairL(RE, (lane >> 3) & 1, g)) + own - cut;
                const uint32_t pG = nearp(pairG((lane >> 2) & 1, (lane >> 3) & 1, i)) + min(lane & 3, 2) * 128;
                uint32_t tr = 0, tk = 0, ph = 0, src = g + (lane >> 4), seen = 0, n = 16;
                bool go = false, first = true;
                while (n < 64 && ++k < SPIN_LIMIT) {
                    const uint32_t now = __shfl_sync(~0u, gtime32(), 0) * 16;
                    if (!go && utest((n & 15) < 6 ? sb + S_RELK : sb + S_RELV, ((n >> 4) & 1) ^ 1)) { go = true; if ((int)(now - tk) > 0 || !(n & 15)) tk = now; }
                    if (go && (int)(now - tk) >= 0) {
                        place_load(M, sb, (n & 16) ? n : (n & 48) | ((n + 10) & 15));
                        tk += KRE_TAU;
                        n++;
                        go = (n & 15) != 0 && (n & 15) != 6;
                        if (!(n & 15)) LSTAMP(63 + (n >> 3));
                    } else if (first || (int)(now - tr) >= 0) {
                        first = false;
                        tr = now + RFR_TAU;
                        b |= seen & a;
                        warm_mma(a, b);
                        seen = ldp32(XPtr(ph == 0 ? pAC : ph == 1 && lane < 16 ? pE : pG + (src & 8) * (HALF / 8) + (src & 7) * 512, gx.hi));
                        reset();
                        src += ph == 0 ? 0 : ph == 1 ? 2 : 1;
                        ph = ph == 2 ? 0 : ph + 1;
                    } else __nanosleep(KWNS2);
                }
                while (rq < 128) reset();
                __syncwarp();
                while (ldsvol(sb + S_GATE) < 6 && ++k < SPIN_LIMIT) { warm_mma(a, b); __nanosleep(KWNS); }
                if (a | b) stsvol(sb + S_GATE, 6);
            }
        }
        return;
    }
    asm volatile("setmaxnreg.inc.sync.aligned.u32 " REG_HI ";");

    const int g = bid >> 3, i = bid & 7;
    const int g8 = lane >> 2, t = lane & 3;
    char* const gs = reinterpret_cast<char*>(g_s);
    const XPtr gx(xwindow());

    W80 Wq[6], Wgu[3];
    uint32_t Wo[5][3][4];
    if (w < 4) {
        const uint32_t* xp = reinterpret_cast<const uint32_t*>(P.x + 640 * w);
        float sum = 0.f, sq = 0.f;
#pragma unroll
        for (int u = 0; u < 10; u++) { uint32_t v = xp[lane + 32 * u]; float a = bf_lo(v), b = bf_hi(v); sum += a + b; sq += a * a + b * b; }
#pragma unroll
        for (int o = 16; o > 0; o >>= 1) { sum += __shfl_xor_sync(~0u, sum, o); sq += __shfl_xor_sync(~0u, sq, o); }
        float mean, den; ln_stats(sum, sq, mean, den);
        if (lane < 20) {
            const uint2 v = reinterpret_cast<const uint2*>(P.x + 640 * w + 80 * i)[lane];
            sts64(sb + S_X0 + 160 * w + 8 * lane, v.x, v.y);
            sts32(sb + S_L0 + 384 * w + b_pos<40>(4 * lane), pack2(__fdiv_rn(bfr(bf_lo(v.x) - mean), den), __fdiv_rn(bfr(bf_hi(v.x) - mean), den)));
            sts32(sb + S_L0 + 384 * w + b_pos<40>(4 * lane + 2), pack2(__fdiv_rn(bfr(bf_lo(v.y) - mean), den), __fdiv_rn(bfr(bf_hi(v.y) - mean), den)));
        }
    } else if (w == 4) {
        const uint32_t* xp = reinterpret_cast<const uint32_t*>(P.wr);
        float sum = 0.f;
#pragma unroll
        for (int u = 0; u < 10; u++) { uint32_t v = xp[lane + 32 * u]; sum += bf_lo(v) + bf_hi(v); }
#pragma unroll
        for (int o = 16; o > 0; o >>= 1) sum += __shfl_xor_sync(~0u, sum, o);
        if (lane == 0) stsf(sb + S_SWR, sum);
        if (lane < 20) {
            const uint2 v = reinterpret_cast<const uint2*>(P.wr + 80 * i)[lane];
            sts32(sb + S_XA + 576 + a_pos(4 * lane), v.x); sts32(sb + S_XA + 576 + a_pos(4 * lane + 2), v.y);
            sts32(sb + S_XA + a_pos(4 * lane), ONES); sts32(sb + S_XA + a_pos(4 * lane + 2), ONES);
        }
    }
    asm volatile("bar.sync 2, %0;" :: "n"(NTHR) : "memory");
    auto frag = [](uint32_t (&a)[4], uint32_t p, int pitch) {
        const uint32_t r0 = lds32(p), r1 = lds32(p + pitch), r2 = lds32(p + 2 * pitch), r3 = lds32(p + 3 * pitch);
        a[0] = __byte_perm(r0, r1, 0x5410); a[1] = __byte_perm(r0, r1, 0x7632);
        a[2] = __byte_perm(r2, r3, 0x5410); a[3] = __byte_perm(r2, r3, 0x7632);
    };
    mbar_wait(sb + S_WFULL + 16 * (w >> 2), 0);
    mbar_wait(sb + S_WFULL + 16 * (w >> 2) + 8, 0);
    {
        const uint32_t p = sb + ST_WQ + (w >> 2) * 30720 + (2 * t) * 384 + (48 * (w & 3) + 2 * g8) * 2;
#pragma unroll
        for (int r = 0; r < 10; r++)
#pragma unroll
            for (int m = 0; m < 3; m++) {
                const uint32_t q = p + ((r & 1) * 40 + (r >> 1) * 8) * 384 + 32 * m, r0 = lds32(q), r1 = lds32(q + 384);
                (r < 8 ? Wq[2 * m].a[(r >> 2) & 1][r & 3] : Wq[2 * m].c[r & 1]) = __byte_perm(r0, r1, 0x5410);
                (r < 8 ? Wq[2 * m + 1].a[(r >> 2) & 1][r & 3] : Wq[2 * m + 1].c[r & 1]) = __byte_perm(r0, r1, 0x7632);
            }
    }
    __syncwarp();
    if (lane == 0) mbar_arrive(sb + S_RELW);
    TSTAMP(1);
    {
        char* d = gs + XS + bid * 7680 + (w >> 2) * 3840 + (48 * (w & 3) + 2 * g8) * 4;
        float acc[6][4] = {};
        mul80(acc, Wq, lds128(sb + S_L0 + 48 * lane), lds32(sb + S_L0 + 48 * lane + 16));
#pragma unroll
        for (int m = 0; m < 6; m += 2) stp64(d + t * 768 + 32 * m, acc[m][0] + acc[m][3], acc[m + 1][0] + acc[m + 1][3], 1);
        float sum[6][4] = {};
        mul80(sum, Wq, make_uint4(ONES, ONES, ONES, ONES), ONES);
        if (t == 0)
#pragma unroll
            for (int m = 0; m < 6; m += 2) stp64(d + 4 * 768 + 32 * m, sum[m][0] + sum[m][3], sum[m + 1][0] + sum[m + 1][3], 1);
    }
    mbar_wait(sb + S_WFULL + 32, 0);
    mbar_wait(sb + S_WFULL + 40, 0);
    const uint32_t oct = 3 * (w >> 1) + (w & 1), oct2 = 3 * (w >> 1) + 2;
    {
        const uint32_t p = sb + ST_WG + ((lane & 7) + 40 * ((lane >> 3) & 1) + 8 * (lane >> 4)) * 192;
#pragma unroll
        for (int T = 0; T < 3; T++) {
            const uint32_t q = p + (T < 2 ? T * 15360 + 16 * oct : (w & 1) * 15360 + 16 * oct2);
            ldsm4t(Wgu[T].a[0], q); ldsm4t(Wgu[T].a[1], q + 16 * 192); ldsm2t(Wgu[T].c, q + 32 * 192);
        }
        float sum[3][4] = {};
        mul80(sum, Wgu, make_uint4(ONES, ONES, ONES, ONES), ONES);
        if (t < 3) stp32(gs + XS2 + bid * 768 + (t < 2 ? 64 * oct + 4 * t : 64 * oct2 + 4 * (w & 1)) + 8 * g8,
                         sel4(t, sum[0][0] + sum[0][3], sum[1][0] + sum[1][3], sum[2][0] + sum[2][3], 0.f), 1);
    }
    __syncwarp();
    if (lane == 0) mbar_arrive(sb + S_RELW + 8);
    mbar_wait(sb + S_WFULL + 48 + 8 * (w >> 1), 0);
    {
        const uint32_t po = sb + ST_WO + (48 * w + 12 * t) * 160 + 4 * g8;
#pragma unroll
        for (int s = 0; s < 3; s++)
#pragma unroll
            for (int m = 0; m < 5; m++) frag(Wo[m][s], po + 4 * s * 160 + 32 * m, 160);
    }
    __syncwarp();
    if (lane == 0) mbar_arrive(sb + S_RELW + 16);
    if (tid < 192) {
        const char* srcS = gs + XS + g * 8 * 7680 + (i >> 2) * 3840 + tid * 4;
        uint32_t vs[5][8];
        int guard = 0;
        do {
#pragma unroll
            for (int b = 0; b < 5; b++)
#pragma unroll
                for (int s = 0; s < 8; s++) vs[b][s] = ldp32(srcS + b * 768 + s * 7680);
        } while (((or3(chk8(vs[0], 1), chk8(vs[1], 1), chk8(vs[2], 1)) | chk8(vs[3], 1) | chk8(vs[4], 1)) & 1) && ++guard < SPIN_LIMIT);
        const uint32_t qpos = sb + S_QS + q_pos(tid);
#pragma unroll
        for (int b = 0; b < 4; b++) {
            sts_hi16(qpos + 384 * b, bfr(sum8(vs[b])));
        }
        stsf(sb + S_CSQ + 4 * tid, sum8(vs[4]));
    }
    if (tid < 192) {
        uint32_t v[8];
        int guard = 0;
        do {
#pragma unroll
            for (int s = 0; s < 8; s++) v[s] = ldp32(gs + XS2 + (g * 8 + s) * 768 + tid * 4);
        } while ((chk8(v, 1) & 1) && ++guard < SPIN_LIMIT);
        stsf(sb + S_CSGU + 4 * tid, sum8(v));
    }
    __syncwarp();
    bar_main();
    arrive_if(tid == 0, sb + S_QRDY);
    TSTAMP(2);

    uint32_t side;
    { int k = 0; while ((side = ldsvol(sb + S_SIDE)) == 0 && ++k < SPIN_LIMIT) {} }
    const uint32_t both = __any_sync(~0u, side & 4) ? COPY : 0;
    uint32_t td = __shfl_sync(~0u, tid, lane);
    const uint32_t wp = __shfl_sync(~0u, tid >> 5, 0);
    const uint32_t cc = wp >= 3;
    auto uni = [](uint32_t v) { return __shfl_sync(~0u, v, 0); };
    auto pin = [&](uint32_t v) { return __shfl_sync(~0u, v, td); };
    auto nearp = [&](uint32_t P) { return gx.lo + P * 8192 + ((side ^ 1 ^ __popc(P & PMASK)) & 1) * COPY; };
    constexpr uint32_t COL = 32 * 8192;
    const uint32_t ownL = (i >> 2) * HALF + (i & 3) * 1024, ownG = gx.lo + (g >> 3) * HALF + (g & 7) * 512;
    const uint32_t uPubA = uni(ownL + nearp(pairL(RA, 0, g)) + (wp >> 1) * 256 + (wp & 1) * 96), uPolA = uni(nearp(pairL(RA, 0, g)) + (wp >> 2) * HALF + (wp & 3) * 256);
    const uint32_t uPubB = uni(ownG + pairG(0, cc, i) * 8192), uPolB = uni(nearp(pairG(0, cc, i)));
    const uint32_t uPubC = uni(ownL + nearp(pairL(RC, 0, g))), uPolC = uni(nearp(pairL(RC, wp < 6 ? cc : 0, g)));
    const uint32_t uPubD = uni(ownG + pairG(1, 0, i) * 8192 + (wp < 7 ? 32 * wp : 256)), uPolD = uni(nearp(pairG(1, cc, i)));
    const uint32_t uPubE = uni(ownL + nearp(pairL(RE, 0, g))), uPolE = uni(nearp(pairL(RE, i >> 2, g)));
    const uint32_t uOS = uni(sb + S_OS + 192 * wp);
    auto xp = [&](uint32_t lo) { return (char*)XPtr(lo, gx.hi); };
    {
        const uint4 z = make_uint4(0, 0, 0, 0);
        const uint32_t c = ((tid >> 6) & 1) * COL, cp = (tid >> 7) * both, k = (tid & 63) * 16;
        *reinterpret_cast<uint4*>(xp((ownL + nearp(pairL(RA, 0, g)) + c + k) ^ cp)) = z;
        if (k < 800) { *reinterpret_cast<uint4*>(xp((uPubC + c + k) ^ cp)) = z; *reinterpret_cast<uint4*>(xp((uPubE + c + k) ^ cp)) = z; }
        if ((tid & 31) < 20) *reinterpret_cast<uint4*>(xp(ownG + pairG((tid >> 5) & 1, 0, i) * 8192 + c + (tid >> 7) * COPY + (tid & 31) * 16)) = z;
    }
#define IDS() __syncwarp(); const uint32_t z0_ = lag<1>(sb), z_ = td + z0_; const uint32_t ln = z_ & 31, q8 = ln >> 2, t4 = z_ & 3, n96 = z_ - 96 * cc, n80 = min(n96, 79u); (void)q8; (void)t4; (void)n80; (void)ln

    auto vaddr = [&](uint32_t (&voff)[3]) {
        const uint32_t ln = td & 31;
        const uint32_t key3 = 3 * ((ln & 7) + 2 * (ln & 8) + ((ln >> 1) & 8));
#pragma unroll
        for (int T = 0; T < 3; T++) {
            const uint32_t u = 3 * wp + T, r = key3 + (u >> 3);
            voff[T] = r * 128 + (((u ^ r) & 7) << 4);
        }
    };
    auto values = [&](uint32_t (&vf)[8][3][4], float (&acc)[3][4], auto step, uint32_t ps, auto col, uint32_t par) {
        constexpr int CUT = col.value ? 8 : 6;
        const uint32_t ln = td & 31, q8 = ln >> 2, t4 = td & 3;
        uint4 p = lds128(ps + 16 * ln);
        float f0 = 0.f, f1 = 0.f, r3 = 0.f, o = 0.f;
        int M = 0;
#pragma unroll
        for (int s = 0; s < 8; s++) {
            if (s == 0 || s == CUT)
#pragma unroll
                for (int k = 0; k < 12; k++) acc[k / 4][k % 4] = 0.f;
            step(s);
            const bool m = s >= CUT || (q8 >> 1) == (s >> 1);
            const uint32_t b0 = m ? ((s & 1) ? p.z : p.x) : 0u, b1 = m ? ((s & 1) ? p.w : p.y) : 0u;
#pragma unroll
            for (int T = 0; T < 3; T++) mmaA(acc[T], vf[s][T], b0, b1);
            if (s == FSTEP) {
                const uint2 mp = lds64(ps + PS_MAX + 8 * t4);
                M = __reduce_max_sync(~0u, __float2int_ru(fmaxf(asf(mp.x), asf(mp.y))));
                f0 = ex2(asf(mp.x) - (float)M); f1 = ex2(asf(mp.y) - (float)M);
                float l[4] = {};
                mma16816(l, ONES, ONES, ONES, ONES, p.x, p.y); mma16816(l, ONES, ONES, ONES, ONES, p.z, p.w);
                r3 = fmaf(f0, l[0], f1 * l[1]);
            }
            if (s == CUT - 1) {
                if (CUT < 8) p = lds128(ps + 384 + 16 * (ln & 7));
                const float r0 = fmaf(f0, acc[0][0], f1 * acc[0][3]), r1 = fmaf(f0, acc[1][0], f1 * acc[1][3]), r2 = fmaf(f0, acc[2][0], f1 * acc[2][3]);
                const bool hi = t4 & 2, od = t4 & 1;
                const float u0 = (hi ? r2 : r0) + __shfl_xor_sync(~0u, hi ? r0 : r2, 2), u1 = (hi ? r3 : r1) + __shfl_xor_sync(~0u, hi ? r1 : r3, 2);
                o = (od ? u1 : u0) + __shfl_xor_sync(~0u, od ? u0 : u1, 1);
                if (ln == 3) o = __int_as_float(2 * M);
                if (CUT < 8) { f0 = __shfl_sync(~0u, f0, 3); f1 = __shfl_sync(~0u, f1, 3); }
            }
        }
        CSTAMP(25);
        const uint32_t pubA = uPubA + col.value * COL + 32 * t4 + 4 * q8;
        if (CUT < 8 && t4 < 3) o = fmaf(f0, sel4(t4, acc[0][0], acc[1][0], acc[2][0], acc[2][0]), fmaf(f1, sel4(t4, acc[0][3], acc[1][3], acc[2][3], acc[2][3]), o));
        stp32_if(t4 < 3 || ((wp & 1) && q8 < 2), both, xp(pubA ^ COPY), xp(pubA), o, par);
    };

    uint32_t left[36] = {};
#pragma unroll 1
    for (int ch = 0; ch < 5; ch++) {
        const uint32_t par0 = (ch + 1) & 1, par1 = ch & 1;
        uint32_t voff[3], vf[8][3][4];
        float acc_[3][4];
        if (ch < 4) {
            td = pin(td);
            vaddr(voff);
            mbar_wait(sb + S_SCO, par1);
            if (ch == 0) mbar_wait(sb + S_WFULL + 80, 0);
            TST(0);
            auto ldw = [&](int s) {
                mbar_wait(sb + S_FV + 8 * s, par1);
#pragma unroll
                for (int T = 0; T < 3; T++) ldsm4t(vf[s][T], voff[T] + (sb + v_place(ch, s) * SLOT));
            };
            probs(bf_lo(lds16(sb + S_SC + 2 * td)), sb + S_PS, wp, td & 31);
            ldw(0); ldw(1); ldw(2);
            bar_main();
            arrive_if(td == 0, sb + S_RELR);
            values(vf, acc_, [&](int s) {
                if (s >= 3) ldw(s);
            }, sb + S_PS, std::integral_constant<int, 0>(), par0);
            TST(1);
            CSTAMP(5);
            if (ch > 0) mbar_wait(sb + S_OS1, par0);
        } else {
#pragma unroll
            for (int s = 0; s < 36; s++) vf[s / 12][(s / 4) % 3][s & 3] = left[s];
        }
        const bool has0 = ch < 4, has1 = ch > 0;
        const bool actc = wp < 6 && (cc ? has1 : has0);
        const uint32_t parc = cc ? par1 : par0;
        const uint32_t pub0 = has0 ? par0 : 0;
        uint32_t rr, pubB;
        {
            IDS();
            const uint32_t c = ch == 4;
            const uint32_t osa = pin(uOS + 96 * c + 4 * ln), oa = pin(uOS + 48 * (q8 & 2) + 24 * t4), ra = pin(sb + S_RED + 640 * wp + 320 * (t4 & 1) + 8 * q8);
            rr = pin(sb + S_RED + 320 * cc + 4 * n80); pubB = pin(uPubB + 4 * n80);
            hop_a<1>(xp(uPolA + c * COL + 8 * min(ln, 24u) + lag<DELAY_L>(sb, z0_)), pub0, osa, ln < 24, 5 * ch);
            TST(2);
            CSTAMP(6);
            float acc[5][4] = {};
            const uint2 b0 = lds64(oa), b1 = lds64(oa + 8), b2 = lds64(oa + 16);
#pragma unroll
            for (int m = 0; m < 5; m++) mmaA(acc[m], Wo[m][0], b0.x, b0.y);
#pragma unroll
            for (int m = 0; m < 5; m++) mmaA(acc[m], Wo[m][1], b1.x, b1.y);
#pragma unroll
            for (int m = 0; m < 5; m++) mmaA(acc[m], Wo[m][2], b2.x, b2.y);
#pragma unroll
            for (int m = 0; m < 5; m++) { stsf(ra + 64 * m, acc[m][0]); stsf(ra + 64 * m + 4, acc[m][2]); }
        }
        CSTAMP(7);
        uint32_t xr, fl, pubC, pubC2;
        auto prepC = [&](uint32_t ln) {
            const uint32_t q8 = ln >> 2, t4 = ln & 3;
            xr = pin(sb + S_XB + 48 * (ln & 15));
            pubC = pin(uPubC + (t4 & 1) * COL + 192 * (wp >> 1) + 64 * (wp & 1) + 8 * q8);
            pubC2 = pin(uPubC + (t4 & 1) * COL + ((t4 & 2) ? 192 * (wp >> 1) + 128 + 4 * (wp & 1) + 8 * q8 : 768 + 2 * ((q8 + 1) & 6)));
            fl = pin(((t4 & 1) ? par1 : pub0) | (t4 >= 2 || (wp == 7 && q8 < 4 && q8 != 2 - t4) ? 2 : 0));
        };
        auto stats = [&](uint32_t xa, const uint4& b, uint32_t b4) {
            float a0[4] = {}, a1[4] = {}, a2[4] = {};
            const uint4 p0 = lds128(xa), p1 = lds128(xa + 16);
            const uint2 p2 = lds64(xa + 32);
            mmaV(a0, p0, b.x, b.y); mmaV(a1, p1, b.z, b.w); mma8(a2, p2.x, p2.y, b4);
            return ((a0[0] + a0[3]) + (a1[0] + a1[3])) + (a2[0] + a2[3]);
        };
        auto give_ln = [&](uint32_t src0, uint32_t par, uint32_t dst, uint32_t ln, float& mean, float& den, auto also) {
            const char* src = xp(src0 + 768 + (ln & 1) * HALF);
            float sx, sq;
            int guard = 0;
            bool again;
            do {
                uint2 st[4];
#pragma unroll
                for (int s = 0; s < 4; s++) st[s] = ldp64(src + s * 1024);
                again = __any_sync(~0u, ((chk4(st, par) | also()) & 1) != 0);
                sx = (asf(st[0].x) + asf(st[1].x)) + (asf(st[2].x) + asf(st[3].x)); sq = (asf(st[0].y) + asf(st[1].y)) + (asf(st[2].y) + asf(st[3].y));
                sx += __shfl_xor_sync(~0u, sx, 1); sq += __shfl_xor_sync(~0u, sq, 1);
            } while (again & (++guard < SPIN_LIMIT));
            ln_stats(sx, sq, mean, den);
            stsvol64(dst, __byte_perm(__float_as_uint(den), __float_as_uint(mean), 0x7632), (__float_as_uint(rcp(den)) & ~7u) | (ch + 1));
        };
        auto take_ln = [&](uint2& c, uint32_t a) { int k = 0; do c = ldsvol64(a); while (__any_sync(~0u, (c.y & 7) != ch + 1) & (++k < SPIN_LIMIT)); };
        {
            auto gate_up = [&](auto with_stats) {
                bar_main();
                TST(3);
                CSTAMP(11);
                const uint4 b = lds128(xr);
                uint32_t b4 = lds32(xr + 16);
                float acc[3][4] = {};
                if (with_stats.value) {
                    stp32_if(fl > 1 && !(td & 2), both, xp(pubC2 ^ COPY), xp(pubC2), stats(xr + (S_XA - S_XB), b, b4), fl & 1);
                    __syncwarp();
                    b4 = lds32(xr + 16);
                }
                mul80(acc, Wgu, b, b4);
                stp64_if(!(td & 2), both, xp(pubC ^ COPY), xp(pubC), tagw(acc[0][0] + acc[0][3], fl & 1), tagw(acc[1][0] + acc[1][3], fl & 1));
                stp32_if(td & 2, both, xp(pubC2 ^ COPY), xp(pubC2), acc[2][0] + acc[2][3], fl & 1);
            };
            if (wp == 7) {
                bar_main();
                IDS();
                prepC(ln);
                sts32(sb + S_ZERO + 4, or3(pubC, pubC2, fl));
                gate_up(std::true_type());
            } else {
                if (actc) {
                    bar_main();
                    CSTAMP(8);
                    uint32_t r[8];
#pragma unroll
                    for (int s = 0; s < 8; s++) r[s] = lds32(rr + 640 * s);
                    stp32_if(true, xp(pubB), sum8(r), parc);
                    CSTAMP(9);
                    IDS();
                    prepC(ln);
                    const uint32_t n4 = 4 * n80;
                    const uint32_t xas = pin(sb + S_XA + 192 + 192 * cc + a_pos(n80)), xbs = pin(sb + S_XB + 384 * cc + b_pos<40>(n80));
                    const float x0 = cc ? ldsf(sb + S_XCAR + n4) : bf_lo(lds16(sb + S_X0 + 160 * (ch & 3) + n4 / 2));
                    gather16(xp(uPolB + n4 + lag<DELAY_G>(sb, z0_)), parc, 5 * ch + 1, [&](float y, uint32_t) {
                        const uint32_t x = pack2(x0 + bfr(y), 0.f);
                        sts16(xbs, x);
                        sts16(xas, x);
                        return 0u;
                    });
                    CSTAMP(10);
                } else {
                    bar_main();
                    IDS();
                    prepC(ln);
                }
                gate_up(std::false_type());
            }
        }
        CSTAMP(12);
        float mean = 0.f, den = 1.f;
        {
            IDS();
            const uint32_t wh = pin((((ln & 7) + 48 * ((ln >> 3) & 1) + 8 * (ln >> 4)) * 160 + (wp < 7 ? 16 * wp : 128)) | ((384 * cc + b_pos<48>(n96)) << 16));
            const uint32_t pubD = pin(uPubD + (t4 & 1) * COL + 16 * (t4 & 2) + 4 * q8 + (fl & 1)), ha = xr + (S_HS - S_XB);
            auto down = [&](const uint32_t (&W)[3][4], const uint4& h0, const uint2& h1) {
                float a0[4] = {}, a1[4] = {}, a2[4] = {};
                mmaA(a0, W[0], h0.x, h0.y); mmaA(a1, W[1], h0.z, h0.w); mmaA(a2, W[2], h1.x, h1.y);
                return ((a0[0] + a0[3]) + (a1[0] + a1[3])) + (a2[0] + a2[3]);
            };
            if (wp < 6) {
                uint32_t Wd[3][4];
                auto ldd = [&](uint32_t z) {
#pragma unroll
                    for (int s = 0; s < 3; s++) ldsm4t(Wd[s], ((wh ^ z) & 0xffff) + (sb + S_WD + s * 2560));
                };
                ldd(0);
                if (actc) {
                    const char* srcv = xp(uPolC + lag<DELAY_C>(sb, z0_) + 8 * n96);
                    const uint2 cs = lds64(sb + S_CSGU + 8 * n96);
                    float gt, up;
                    int guard = 0;
                    while (true) {
                        uint2 v[8];
#pragma unroll
                        for (int s = 0; s < 8; s++) v[s] = ldp64(srcv + (s >> 2) * HALF + (s & 3) * 1024);
                        uint2 c = ldsvol64(sb + S_LN + 8 * cc + ((v[0].x ^ parc) & 1) * 32);
                        const bool stale = __any_sync(~0u, ((chk8(v, parc) | chk8y(v, parc)) & 1) != 0), late = __any_sync(~0u, (c.y & 7) != ch + 1);
                        const float pg = sum8x(v), pu = sum8y(v);
                        auto norm = [&] {
                            mean = bf_hi(c.x); den = bf_lo(c.x);
                            gt = bfr(fmaf(-mean, asf(cs.x), pg) * asf(c.y)); up = fmaf(-mean, asf(cs.y), pu) * asf(c.y);
                            keep(gt); keep(up);
                        };
                        norm();
                        if (!((stale | late) & (++guard < SPIN_LIMIT))) break;
                        if (!stale) { take_ln(c, sb + S_LN + 8 * cc); norm(); break; }
                    }
                    CSTAMP(13);
                    SWEEPS(5 * ch + 2, guard - 1);
                    const uint32_t h = pack2(bfr(gt * sigmoidf_(gt)) * bfr(up), 0.f);
                    sts16((wh >> 16) + (sb + S_HS), h);
                    CSTAMP(14);
                    if (ch == 3) CSTAMP(0);
                }
                bar_main();
                TST(4);
                CSTAMP(15);
                const uint4 h0 = lds128(ha);
                const uint2 h1 = lds64(ha + 16);
                stp32_if(!(td & 2), xp(pubD & ~1u), down(Wd, h0, h1), pubD & 1);
            } else {
                uint32_t v = 0;
                const uint32_t col = wp == 7 || !has0;
                const bool serve = wp == 6 || (has0 && has1);
                if (serve) {
                    const uint32_t par = col ? par1 : par0;
                    const char* src = xp(uPolC + col * COL + 776 + (td & 4) * (HALF / 4) + (td & 3) * 1024);
                    give_ln(uPolC + col * COL, par, sb + S_LN + 8 * col, td, mean, den, [&] { v = ldp32(src); return v ^ par; });
                }
                stsvol(sb + S_GATE, ch + 1);
                uint32_t Wd[2][3][4];
#pragma unroll
                for (int s = 0; s < 6; s++) ldsm4t(Wd[s / 3][s % 3], (wh & 0xffff) + (sb + S_WD + (s / 3) * 16 + (s % 3) * 2560));
                bar_main();
                const uint4 h0 = lds128(ha);
                const uint2 h1 = lds64(ha + 16);
                const float d0 = down(Wd[0], h0, h1), d1 = down(Wd[1], h0, h1);
                stp32_if(true, xp(pubD & ~1u), (td & 2) ? d1 : d0, pubD & 1);
                if (serve) {
                    float xw = asf(v);
                    xw += __shfl_xor_sync(~0u, xw, 1); xw += __shfl_xor_sync(~0u, xw, 2); xw += __shfl_xor_sync(~0u, xw, 4);
                    const float r = bfr(fmaf(-mean, ldsf(sb + S_SWR), xw) * rcp(den));
                    sts32(sb + S_STAT + 4 * col, __float_as_uint(bfr(sigmoidf_(r))) | (ch + 1));
                }
            }
        }
        CSTAMP(16);
        {
            IDS();
            const uint32_t pubE = pin(uPubE + (t4 < 3 ? (wp >> 2) * COL + 192 * (wp & 3) + 64 * t4 + 8 * q8 : (q8 >> 2) * COL + 768 + 4 * (q8 & 1)));
            xr = pin(sb + S_XB + 48 * (ln & 7));
            uint32_t x2 = 0;
            auto hop_d = [&](auto col) {
                const uint32_t xbs = pin(sb + S_XB + 384 * col.value + b_pos<40>(n80)), xas = col.value ? 0 : pin(sb + S_XA + 192 + a_pos(n80));
                const float x1 = bf_lo(lds16(xbs));
                const float lnx = __uint_as_float(pin(__float_as_uint(bfr(__fdiv_rn(bfr(x1 - mean), den)))));
                gather16(xp(uPolD + 4 * n80 + lag<DELAY_D>(sb, z0_)), col.value ? par1 : par0, 5 * ch + 3, [&](float y, uint32_t z) {
                    const uint32_t gate = ldsvol(sb + S_STAT + 4 * col.value + z);
                    x2 = pack2(x1 + bfr(lnx + bfr(bfr(y) * bf_hi(gate))), 0.f);
                    if (col.value) keep(x2); else { sts16(xbs, x2); sts16(xas, x2); }
                    return (uint32_t)((gate & 7) != ch + 1);
                });
                CSTAMP(17);
            };
            auto qproj = [&](auto with_stats) {
                bar_main();
                TST(5);
                CSTAMP(19);
                const uint32_t t4 = td & 3;
                const uint4 b = lds128(xr);
                uint32_t b4 = lds32(xr + 16);
                float acc[6][4] = {};
                if (with_stats.value) {
                    stp32_if((td & 11) == 3, both, xp(pubE ^ COPY), xp(pubE), stats(xr + (S_XA - S_XB), b, b4), par0);
                    __syncwarp();
                    b4 = lds32(xr + 16);
                }
                mul80(acc, Wq, b, b4);
                const float v0 = sel4(t4, acc[0][0] + acc[0][3], acc[2][0] + acc[2][3], acc[4][0] + acc[4][3], acc[4][0] + acc[4][3]);
                const float v1 = sel4(t4, acc[1][0] + acc[1][3], acc[3][0] + acc[3][3], acc[5][0] + acc[5][3], acc[5][0] + acc[5][3]);
                stp64_if(t4 < 3, both, xp(pubE ^ COPY), xp(pubE), tagw(v0, par0), tagw(v1, par0));
            };
            if (wp == 7) {
                if (!has0) break;
                qproj(std::true_type());
            } else {
                if (actc && !cc) hop_d(std::integral_constant<int, 0>());
                else {
                    if (actc && g == 0) {
                        const uint32_t po = pin(1280 * (ch - 1) + 160 * i + 2 * n80);
                        hop_d(std::integral_constant<int, 1>());
                        *reinterpret_cast<unsigned short*>(reinterpret_cast<char*>(P.out) + po) = (unsigned short)x2;
                    }
                    if (!has0) break;
                }
                qproj(std::false_type());
                sts32_if(td < 80, sb + S_XCAR + 4 * td, x2 << 16);
            }
        }
        CSTAMP(20);
        if (wp == 6) give_ln(uPolE, par0, sb + S_LN + 16, td, mean, den, [] { return 0u; });
        auto pass2 = [&](auto d0, auto d1, auto d2) {
            constexpr int D0 = d0.value, D1 = d1.value, D = D0 + D1 + d2.value;
            IDS();
            const uint32_t ua = sb + k_place(ch, wp & 6) * SLOT + (wp & 1) * UNIT, k0 = k_off(ln);
            uint32_t kf[12][2][4];
            auto ldk = [&](int s) { const uint32_t a = (k0 ^ (32 * (s / 3))) + (ua + 1024 * (s % 3)); ldsm4(kf[s][0], a); ldsm4(kf[s][1], a + SLOT); };
            auto ldv1 = [&](int k) { ldsm4t(vf[k / 3][k % 3], voff[k % 3] + (sb + v_place(ch, k / 3) * SLOT)); };
            auto ldv = [&](int s) { ldv1(3 * s); ldv1(3 * s + 1); ldv1(3 * s + 2); };
            constexpr uint32_t LATE = LAST_LATE;
            constexpr uint64_t EARLY_LIST = bit_list(~LATE), LATE_LIST = bit_list(LATE);
            auto early = [&](int k) {
                if (D1 == 0) ldk(k);
                else if (k < 3) { ldv1(9 + 2 * k); ldv1(10 + 2 * k); }
                else ldk((EARLY_LIST >> (4 * (k - 3))) & 15);
            };
            uint32_t v[8] = {}, qsa = 0;
            const char* srcv = xp(uPolE + lag<(D1 > 0 ? 0 : DELAY_E)>(sb, z0_) + 4 * td);
            auto look = [&] {
#pragma unroll
                for (int s = 0; s < 8; s++) v[s] = ldp32(srcv + (s >> 2) * HALF + (s & 3) * 1024);
            };
            if (D1 > 0) vaddr(voff);
            if (!(mbar_try(sb + S_FK + 8 * (wp & 6), par1) & mbar_try(sb + S_FK + 8 * (wp | 1), par1))) { mbar_wait(sb + S_FK + 8 * (wp & 6), par1); mbar_wait(sb + S_FK + 8 * (wp | 1), par1); }
#pragma unroll
            for (int s = 0; s < D0; s++) early(s);
            if (wp < 6) { look(); qsa = pin(sb + S_QS + 384 * ch + q_pos(z_)); }
#pragma unroll
            for (int s = D0; s < D0 + D1; s++) early(s);
            if (wp < 6) {
                const float cs = ldsf(sb + S_CSQ + 4 * td);
                int guard = 0;
                while (true) {
                    uint2 c = ldsvol64(sb + S_LN + 16 + ((v[0] ^ par0) & 1) * 32);
                    const bool stale = __any_sync(~0u, (chk8(v, par0) & 1) != 0), late = __any_sync(~0u, (c.y & 7) != ch + 1);
                    const float qs = sum8(v);
                    auto norm = [&] {
                        const uint32_t q = pack2(fmaf(-bf_hi(c.x), cs, qs) * asf(c.y), 0.f);
                        sts16(qsa, q);
                    };
                    norm();
                    if (!((stale | late) & (++guard < SPIN_LIMIT))) break;
                    if (!stale) { take_ln(c, sb + S_LN + 16); norm(); break; }
                    look();
                }
                SWEEPS(5 * ch + 4, guard - 1);
                CSTAMP(22);
            }
#pragma unroll
            for (int s = D0 + D1; s < D; s++) early(s);
            CSTAMP(21);
            bar_main();
            TST(6);
            CSTAMP(1);
            uint2 q = lds64(sb + S_QS + 384 * ch + 8 * ln);
            float acc[2][4] = {};
            constexpr int V0 = 13 - D, NV = D1 > 0 ? 2 : (2 * (D - 1)) / 3;
            static_assert(D1 == 0 || D - 3 + __builtin_popcount(LATE) == 12, "plan");
#pragma unroll
            for (int s = 0; s < 12; s++) {
                const bool m = q8 == (s & 7);
                const uint32_t b0 = m ? q.x : 0u, b1 = m ? q.y : 0u;
                if (s == 7) q = lds64(sb + S_QS + 384 * ch + 8 * ln + 256);
                mmaA(acc[0], kf[s][0], b0, b1);
                mmaA(acc[1], kf[s][1], b0, b1);
                if (D1 > 0) {
                    if (s >= 1 && s <= __builtin_popcount(LATE)) ldk((LATE_LIST >> (4 * (s - 1))) & 15);
                } else {
                    if (s >= 1 && s + D - 1 < 12) ldk(s + D - 1);
                    if (s >= 1 && s + D - 1 == 11) { __syncwarp(); arrive_if(ln == 0, sb + S_RELK); }
                    if (s == V0) vaddr(voff);
                    if (s >= V0 && 2 * (s - V0) < 3 * NV) ldv1(9 + 2 * (s - V0));
                    if (s >= V0 && 2 * (s - V0) + 1 < 3 * NV) ldv1(10 + 2 * (s - V0));
                }
            }
            CSTAMP(24);
            {
                const float v0 = acc[0][0] + acc[0][1], v1 = acc[0][2] + acc[0][3], v2 = acc[1][0] + acc[1][1], v3 = acc[1][2] + acc[1][3];
                const bool hi = t4 & 2, od = t4 & 1;
                const float u0 = (hi ? v2 : v0) + __shfl_xor_sync(~0u, hi ? v0 : v2, 2), u1 = (hi ? v3 : v1) + __shfl_xor_sync(~0u, hi ? v1 : v3, 2);
                const float s = (od ? u1 : u0) + __shfl_xor_sync(~0u, od ? u0 : u1, 1);
                CSTAMP(2);
                probs(scaled(s), sb + S_PS + PS_PASS, wp, ln);
                CSTAMP(3);
            }
            bar_main();
            TST(10);
            CSTAMP(4);
            if (D1 > 0) values(vf, acc_, [&](int s) { if (s < 3) ldv(s + 5); }, sb + S_PS + PS_PASS, std::integral_constant<int, 1>(), par0);
            else values(vf, acc_, [&](int s) { if (s >= (NV > 1 ? 2 : 1) && s + NV + (NV > 1 ? 1 : 2) < 8) ldv(s + NV + (NV > 1 ? 1 : 2)); }, sb + S_PS + PS_PASS, std::integral_constant<int, 1>(), par0);
            arrive_if(ln == 0, sb + S_RELV);
        };
        if (ch == 3) {
            pass2(std::integral_constant<int, LAST0>(), std::integral_constant<int, LAST1>(), std::integral_constant<int, LAST2>());
#pragma unroll
            for (int m = 0; m < 48; m++) Wq[m / 8].a[(m / 4) % 2][m % 4] = vf[3 + m / 12][(m / 4) % 3][m % 4];
#pragma unroll
            for (int m = 0; m < 12; m++) Wq[m / 2].c[m % 2] = vf[7][m / 4][m % 4];
#pragma unroll
            for (int m = 0; m < 36; m++) left[m] = m < 12 ? __float_as_uint(acc_[m / 4][m % 4]) : vf[m / 12][(m / 4) % 3][m % 4];
        } else {
            pass2(std::integral_constant<int, KPRE>(), std::integral_constant<int, 0>(), std::integral_constant<int, KPRE2>());
#pragma unroll
            for (int m = 0; m < 36; m++) left[m] = m < 12 ? __float_as_uint(acc_[m / 4][m % 4]) : vf[4 + m / 12][(m / 4) % 3][m % 4];
        }
        TST(11);
        CSTAMP(23);
    }
    sts32_if(td == 255, sb + S_GATE, 6);
    TSTAMP(3);
}

typedef CUresult (*EncodeFn)(CUtensorMap*, CUtensorMapDataType, cuuint32_t, void*, const cuuint64_t*, const cuuint64_t*, const cuuint32_t*,
                             const cuuint32_t*, CUtensorMapInterleave, CUtensorMapSwizzle, CUtensorMapL2promotion, CUtensorMapFloatOOBfill);

void make_map(EncodeFn enc, CUtensorMap* m, const void* base, uint64_t cols, uint64_t rows, uint32_t box_cols, uint32_t box_rows, bool swizzle) {
    cuuint64_t dims[2] = {cols, rows};
    cuuint64_t strides[1] = {cols * 2};
    cuuint32_t box[2] = {box_cols, box_rows};
    cuuint32_t es[2] = {1, 1};
    enc(m, CU_TENSOR_MAP_DATA_TYPE_BFLOAT16, 2, const_cast<void*>(base), dims, strides, box, es, CU_TENSOR_MAP_INTERLEAVE_NONE,
        swizzle ? CU_TENSOR_MAP_SWIZZLE_128B : CU_TENSOR_MAP_SWIZZLE_NONE, CU_TENSOR_MAP_L2_PROMOTION_NONE, CU_TENSOR_MAP_FLOAT_OOB_FILL_NONE);
}

}

extern "C" void kernel_launch(void* const* d_in, const int* in_sizes, int n_in, void* d_out, int out_size) {
    (void)in_sizes; (void)n_in; (void)out_size;
    static EncodeFn enc = nullptr;
    if (!enc) {
        void* f = nullptr;
        cudaDriverEntryPointQueryResult q;
        cudaGetDriverEntryPoint("cuTensorMapEncodeTiled", &f, cudaEnableDefault, &q);
        enc = (EncodeFn)f;
        cudaFuncSetAttribute(fused_kernel, cudaFuncAttributeMaxDynamicSharedMemorySize, SMEM_BYTES);
    }
    Params P;
    P.x = (const __nv_bfloat16*)d_in[0]; P.k = (const __nv_bfloat16*)d_in[1]; P.v = (const __nv_bfloat16*)d_in[2];
    P.wr = (const __nv_bfloat16*)d_in[6]; P.wq = (const __nv_bfloat16*)d_in[3];
    P.out = (__nv_bfloat16*)d_out;
    Maps M;
    {
        cuuint64_t dims[4] = {64, 8, 3, (cuuint64_t)KV_BATCH_KEYS / 2}, strides[3] = {384, 128, 3072};
        cuuint32_t box[4] = {64, 8, 3, 2}, es[4] = {1, 1, 1, 1};
        enc(&M.k, CU_TENSOR_MAP_DATA_TYPE_BFLOAT16, 4, d_in[1], dims, strides, box, es, CU_TENSOR_MAP_INTERLEAVE_NONE, CU_TENSOR_MAP_SWIZZLE_128B,
            CU_TENSOR_MAP_L2_PROMOTION_NONE, CU_TENSOR_MAP_FLOAT_OOB_FILL_NONE);
    }
    make_map(enc, &M.v, P.v, 64, (uint64_t)12 * KV_BATCH_KEYS, 64, 96, true);
    make_map(enc, &M.vu, P.v, 64, (uint64_t)12 * KV_BATCH_KEYS, 64, 48, true);
    make_map(enc, &M.wq, d_in[3], 6144, 640, 192, 40, false);
    make_map(enc, &M.wo, d_in[4], 640, 6144, 80, 96, false);
    make_map(enc, &M.wg, d_in[7], 1536, 640, 96, 80, false);
    make_map(enc, &M.wu, d_in[8], 1536, 640, 96, 80, false);
    make_map(enc, &M.wd, d_in[9], 640, 1536, 80, 96, false);
    fused_kernel<<<NCTA, NTHR, SMEM_BYTES, cudaStreamPerThread>>>(P, M);
}
```

```cpp
#include <cuda_runtime.h>
#include <cuda.h>
#include <cuda_bf16.h>
#include <stdint.h>
#include <type_traits>

namespace {

constexpr int NCTA = 128;
constexpr int NTHR = 384;
constexpr int UNIT = 6144;
constexpr int SLOT = 12288;
#define TAU 3880
#define TAUW 3700
#define TAU0 3780
#define ILV 4
#define XB 900
#define FORCE_BOTH 0
#define TMIN 2400
#define SLACK 6000
#define SLACK0 1000
#define LEADW 3500
#define WIN_W 3
#define WIN_S 4
#define WIN_U 10
#define VPF 4
#define KRE_TAU 2600
#define RFR_TAU 22400
#define HOP1_NS 200
#define KPRE 2
#define KPRE2 2
#define LAST0 4
#define LAST1 4
#define LAST2 2
#define LAST_LATE 0xaa8
#define FSTEP 4
#define DELAY_L 2
#define DELAY_G 2
#define DELAY_C 3
#define DELAY_D 0
#define DELAY_E 1
#define REG_LO "40"
#define REG_HI "232"
#define SPIN_LOG 17
constexpr int SPIN_LIMIT = 1 << SPIN_LOG, SPIN_FAST = SPIN_LIMIT << 4;

__host__ __device__ constexpr uint32_t pairL(uint32_t region, uint32_t c, uint32_t g) { return (g & 1) | ((g >> 1) << 2) | (c << 5) | (region << 6); }
__host__ __device__ constexpr uint32_t pairG(uint32_t d, uint32_t c, uint32_t i) { return (i & 1) | ((i >> 1) << 2) | (d << 4) | (c << 5) | (3u << 6); }
constexpr uint32_t RA = 0, RC = 1, RE = 2, HALF = 16384, COPY = 4096, PMASK = 0x59;
constexpr uint32_t XS = 0;
constexpr uint32_t XS2 = XS + 128 * 7680;
constexpr uint32_t XSEND = XS2 + 128 * 768;
__device__ uint4 g_s[XSEND / 16];
__device__ uint4 g_x[(4u << 20) / 16];
#define SWEEPS(k, n) do {} while (0)

constexpr uint32_t S_WD = 16 * SLOT;
constexpr uint32_t S_DUMMY = S_WD + 15360;
constexpr uint32_t S_BAR = S_DUMMY + 4096;
constexpr uint32_t S_FV = S_BAR, S_FK = S_FV + 64, S_RING = S_FK + 64, S_DBAR = S_RING + 48, S_WFULL = S_DBAR + 32, S_QRDY = S_WFULL + 88;
constexpr uint32_t S_RELK = S_QRDY + 8, S_RELV = S_RELK + 8, S_RELR = S_RELV + 8, S_RELW = S_RELR + 8, S_SCO = S_RELW + 24;
constexpr uint32_t S_OS1 = S_SCO + 8;
constexpr uint32_t S_ZERO = S_OS1 + 8;
constexpr uint32_t S_KF = S_ZERO + 8;
constexpr uint32_t S_TOK = S_KF + 8;
constexpr uint32_t S_SIDE = S_TOK + 80, S_GATE = S_SIDE + 4;
constexpr uint32_t S_STAT = S_GATE + 12, S_SWR = S_STAT + 16;
constexpr uint32_t S_LN = S_STAT + 32;
constexpr uint32_t S_XCAR = S_LN + 64;
constexpr uint32_t S_CSQ = S_XCAR + 320;
constexpr uint32_t S_CSGU = S_CSQ + 768;
constexpr uint32_t S_RED = S_CSGU + 768;
constexpr uint32_t S_L0 = S_RED;
constexpr uint32_t S_OS = S_RED + 5120;
constexpr uint32_t S_PS = S_OS + 1536;
constexpr uint32_t PS_MAX = 512, PS_PASS = 544;
constexpr uint32_t S_QS = S_PS + 2 * PS_PASS;
constexpr uint32_t S_XB = S_QS + 1536;
constexpr uint32_t S_XA = S_XB + 768;
constexpr uint32_t S_HS = S_XA + 768;
constexpr uint32_t S_X0 = S_HS + 768;
constexpr uint32_t S_SC = S_X0 + 640;
constexpr uint32_t S_TM = S_SC + 512;
constexpr int SMEM_BYTES = S_TM + 256;
static_assert(SMEM_BYTES <= 232448 && S_STAT % 16 == 0 && S_RED % 16 == 0 && S_XB % 16 == 0 && S_HS % 16 == 0 && S_PS % 16 == 0 && S_QS % 16 == 0, "smem");
static_assert(S_SCO == S_BAR + 44 * 8 && S_RELK == S_BAR + 38 * 8, "barriers");
constexpr uint32_t ST_WQ = 3 * SLOT, ST_WG = 8 * SLOT, ST_WO = 11 * SLOT;

__device__ __forceinline__ uint32_t smem_u32(const void* p) { return (uint32_t)__cvta_generic_to_shared(p); }
__device__ __forceinline__ void mbar_arrive(uint32_t bar) { asm volatile("mbarrier.arrive.shared::cta.b64 _, [%0];" :: "r"(bar) : "memory"); }
__device__ __forceinline__ bool mbar_try(uint32_t bar, uint32_t parity) {
    uint32_t ok;
    asm volatile("{\n .reg .pred p;\n mbarrier.try_wait.parity.shared::cta.b64 p, [%1], %2;\n selp.u32 %0, 1, 0, p;\n}" : "=r"(ok) : "r"(bar), "r"(parity) : "memory");
    return ok != 0;
}
__device__ __forceinline__ bool mbar_test(uint32_t bar, uint32_t parity) {
    uint32_t ok;
    asm volatile("{\n .reg .pred p;\n mbarrier.test_wait.parity.shared::cta.b64 p, [%1], %2;\n selp.u32 %0, 1, 0, p;\n}" : "=r"(ok) : "r"(bar), "r"(parity) : "memory");
    return ok != 0;
}
__device__ __forceinline__ void mbar_wait(uint32_t bar, uint32_t parity) {
    int n = 0;
    while (!mbar_try(bar, parity) && ++n < SPIN_LIMIT) {}
}
__device__ __forceinline__ uint32_t gtime32() { uint32_t t; asm volatile("mov.u32 %0, %globaltimer_lo;" : "=r"(t)); return t; }
__device__ __forceinline__ void bar_main() { asm volatile("bar.sync 1, 256;" ::: "memory"); }

__device__ __forceinline__ void mma16816(float (&c)[4], uint32_t a0, uint32_t a1, uint32_t a2, uint32_t a3, uint32_t b0, uint32_t b1) {
    asm("mma.sync.aligned.m16n8k16.row.col.f32.bf16.bf16.f32 {%0,%1,%2,%3}, {%4,%5,%6,%7}, {%8,%9}, {%0,%1,%2,%3};"
        : "+f"(c[0]), "+f"(c[1]), "+f"(c[2]), "+f"(c[3]) : "r"(a0), "r"(a1), "r"(a2), "r"(a3), "r"(b0), "r"(b1));
}
__device__ __forceinline__ void mmaA(float (&c)[4], const uint32_t (&a)[4], uint32_t b0, uint32_t b1) { mma16816(c, a[0], a[1], a[2], a[3], b0, b1); }
__device__ __forceinline__ void mma8(float (&c)[4], uint32_t a0, uint32_t a1, uint32_t b0) {
    asm("mma.sync.aligned.m16n8k8.row.col.f32.bf16.bf16.f32 {%0,%1,%2,%3}, {%4,%5}, {%6}, {%0,%1,%2,%3};"
        : "+f"(c[0]), "+f"(c[1]), "+f"(c[2]), "+f"(c[3]) : "r"(a0), "r"(a1), "r"(b0));
}
struct W80 { uint32_t a[2][4], c[2]; };
template <int N> __device__ __forceinline__ void mul80(float (&acc)[N][4], const W80 (&W)[N], const uint4& b, uint32_t b4) {
#pragma unroll
    for (int m = 0; m < N; m++) mmaA(acc[m], W[m].a[0], b.x, b.y);
#pragma unroll
    for (int m = 0; m < N; m++) mmaA(acc[m], W[m].a[1], b.z, b.w);
#pragma unroll
    for (int m = 0; m < N; m++) mma8(acc[m], W[m].c[0], W[m].c[1], b4);
}
__device__ __forceinline__ void ldsm2t(uint32_t (&r)[2], uint32_t addr) {
    asm volatile("ldmatrix.sync.aligned.m8n8.x2.trans.shared.b16 {%0,%1}, [%2];" : "=r"(r[0]), "=r"(r[1]) : "r"(addr) : "memory");
}
__device__ __forceinline__ void mmaV(float (&c)[4], const uint4& a, uint32_t b0, uint32_t b1) { mma16816(c, a.x, a.y, a.z, a.w, b0, b1); }
__device__ __forceinline__ void ldsm4(uint32_t (&r)[4], uint32_t addr) {
    asm volatile("ldmatrix.sync.aligned.m8n8.x4.shared.b16 {%0,%1,%2,%3}, [%4];" : "=r"(r[0]), "=r"(r[1]), "=r"(r[2]), "=r"(r[3]) : "r"(addr) : "memory");
}
__device__ __forceinline__ void ldsm4t(uint32_t (&r)[4], uint32_t addr) {
    asm volatile("ldmatrix.sync.aligned.m8n8.x4.trans.shared.b16 {%0,%1,%2,%3}, [%4];" : "=r"(r[0]), "=r"(r[1]), "=r"(r[2]), "=r"(r[3]) : "r"(addr) : "memory");
}
__device__ __forceinline__ uint32_t lds16(uint32_t a) { uint16_t v; asm volatile("ld.shared.u16 %0, [%1];" : "=h"(v) : "r"(a) : "memory"); return v; }
__device__ __forceinline__ uint32_t lds32(uint32_t a) { uint32_t v; asm volatile("ld.shared.u32 %0, [%1];" : "=r"(v) : "r"(a) : "memory"); return v; }
__device__ __forceinline__ float ldsf(uint32_t a) { return __uint_as_float(lds32(a)); }
__device__ __forceinline__ uint2 lds64(uint32_t a) { uint2 v; asm volatile("ld.shared.v2.u32 {%0,%1}, [%2];" : "=r"(v.x), "=r"(v.y) : "r"(a) : "memory"); return v; }
__device__ __forceinline__ uint4 lds128(uint32_t a) { uint4 v; asm volatile("ld.shared.v4.u32 {%0,%1,%2,%3}, [%4];" : "=r"(v.x), "=r"(v.y), "=r"(v.z), "=r"(v.w) : "r"(a) : "memory"); return v; }
__device__ __forceinline__ int ldsvol(uint32_t a) { int v; asm volatile("ld.volatile.shared.u32 %0, [%1];" : "=r"(v) : "r"(a) : "memory"); return v; }
__device__ __forceinline__ uint2 ldsvol64(uint32_t a) { uint2 v; asm volatile("{\n .reg .b64 d;\n ld.volatile.shared.b64 d, [%2];\n mov.b64 {%0,%1}, d;\n}" : "=r"(v.x), "=r"(v.y) : "r"(a) : "memory"); return v; }
__device__ __forceinline__ void stsvol64(uint32_t a, uint32_t x, uint32_t y) { asm volatile("{\n .reg .b64 d;\n mov.b64 d, {%1,%2};\n st.volatile.shared.b64 [%0], d;\n}" :: "r"(a), "r"(x), "r"(y) : "memory"); }
__device__ __forceinline__ void stsvol(uint32_t a, int v) { asm volatile("st.volatile.shared.u32 [%0], %1;" :: "r"(a), "r"(v) : "memory"); }
__device__ __forceinline__ void sts_hi16(uint32_t a, float v) { asm volatile("{\n .reg .b16 lo, hi;\n mov.b32 {lo, hi}, %1;\n st.shared.u16 [%0], hi;\n}" :: "r"(a), "r"(__float_as_uint(v)) : "memory"); }
__device__ __forceinline__ void sts16(uint32_t a, uint32_t v) { asm volatile("st.shared.u16 [%0], %1;" :: "r"(a), "r"(v) : "memory"); }
__device__ __forceinline__ void sts32(uint32_t a, uint32_t v) { asm volatile("st.shared.u32 [%0], %1;" :: "r"(a), "r"(v) : "memory"); }
__device__ __forceinline__ void stsf(uint32_t a, float v) { sts32(a, __float_as_uint(v)); }
__device__ __forceinline__ void sts64(uint32_t a, uint32_t x, uint32_t y) { asm volatile("st.shared.v2.u32 [%0], {%1,%2};" :: "r"(a), "r"(x), "r"(y) : "memory"); }

__device__ __forceinline__ void sts32_if(bool p, uint32_t a, uint32_t v) {
    asm volatile("{\n .reg .pred p;\n setp.ne.u32 p, %2, 0;\n @p st.shared.u32 [%0], %1;\n}" :: "r"(a), "r"(v), "r"((uint32_t)p) : "memory");
}
__device__ __forceinline__ void arrive_if(bool p, uint32_t bar) {
    asm volatile("{\n .reg .pred p;\n setp.ne.u32 p, %1, 0;\n @p mbarrier.arrive.shared::cta.b64 _, [%0];\n}" :: "r"(bar), "r"((uint32_t)p) : "memory");
}
__device__ __forceinline__ void keep(uint32_t& v) { asm volatile("" : "+r"(v)); }
__device__ __forceinline__ void keep(float& v) { asm volatile("" : "+f"(v)); }

__device__ __forceinline__ uint32_t ldp32(const char* p) { uint32_t v; asm volatile("ld.relaxed.gpu.global.u32 %0, [%1];" : "=r"(v) : "l"(p) : "memory"); return v; }
__device__ __forceinline__ uint2 ldp64(const char* p) {
    uint2 v; asm volatile("{\n .reg .b64 d;\n ld.relaxed.gpu.global.b64 d, [%2];\n mov.b64 {%0,%1}, d;\n}" : "=r"(v.x), "=r"(v.y) : "l"(p) : "memory"); return v;
}
__device__ __forceinline__ uint32_t tagw(float f, uint32_t par) { return (__float_as_uint(f) & ~1u) | par; }
__device__ __forceinline__ void stp32(char* p, float a, uint32_t par) { asm volatile("st.relaxed.gpu.global.u32 [%0], %1;" :: "l"(p), "r"(tagw(a, par)) : "memory"); }
__device__ __forceinline__ void stp64(char* p, float a, float b, uint32_t par) {
    asm volatile("{\n .reg .b64 d;\n mov.b64 d, {%1,%2};\n st.relaxed.gpu.global.b64 [%0], d;\n}" :: "l"(p), "r"(tagw(a, par)), "r"(tagw(b, par)) : "memory");
}
__device__ __forceinline__ void stp32_if(bool p, char* d, float a, uint32_t par) {
    asm volatile("{\n .reg .pred p;\n setp.ne.u32 p, %2, 0;\n @p st.relaxed.gpu.global.u32 [%0], %1;\n @p st.relaxed.gpu.global.u32 [%0+4096], %1;\n}" :: "l"(d), "r"(tagw(a, par)), "r"((uint32_t)p) : "memory");
}
__device__ __forceinline__ void stp32_if(bool p, uint32_t both, char* d, char* e, float a, uint32_t par) {
    asm volatile("{\n .reg .pred p, q;\n setp.ne.u32 p, %2, 0;\n setp.ne.and.u32 q, %4, 0, p;\n @p st.relaxed.gpu.global.u32 [%3], %1;\n @q st.relaxed.gpu.global.u32 [%0], %1;\n}" :: "l"(d), "r"(tagw(a, par)), "r"((uint32_t)p), "l"(e), "r"(both) : "memory");
}
__device__ __forceinline__ void stp64_if(bool p, uint32_t both, char* d, char* e, uint32_t lo, uint32_t hi) {
    asm volatile("{\n .reg .pred p, q;\n .reg .b64 d;\n setp.ne.u32 p, %3, 0;\n setp.ne.and.u32 q, %5, 0, p;\n mov.b64 d, {%1,%2};\n @p st.relaxed.gpu.global.b64 [%4], d;\n @q st.relaxed.gpu.global.b64 [%0], d;\n}" :: "l"(d), "r"(lo), "r"(hi), "r"((uint32_t)p), "l"(e), "r"(both) : "memory");
}
__device__ __forceinline__ uint32_t chk2(uint32_t a, uint32_t b, uint32_t par) { uint32_t r; asm("lop3.b32 %0, %1, %2, %3, 0x7E;" : "=r"(r) : "r"(a), "r"(b), "r"(par)); return r; }
__device__ __forceinline__ uint32_t or3(uint32_t a, uint32_t b, uint32_t c) { uint32_t r; asm("lop3.b32 %0, %1, %2, %3, 0xFE;" : "=r"(r) : "r"(a), "r"(b), "r"(c)); return r; }
__device__ __forceinline__ uint32_t chk8(const uint32_t (&v)[8], uint32_t par) { return or3(chk2(v[0], v[1], par), chk2(v[2], v[3], par), or3(chk2(v[4], v[5], par), chk2(v[6], v[7], par), 0)); }
__device__ __forceinline__ uint32_t chk8(const uint2 (&v)[8], uint32_t par) { return or3(chk2(v[0].x, v[1].x, par), chk2(v[2].x, v[3].x, par), or3(chk2(v[4].x, v[5].x, par), chk2(v[6].x, v[7].x, par), 0)); }
__device__ __forceinline__ uint32_t chk8y(const uint2 (&v)[8], uint32_t par) { return or3(chk2(v[0].y, v[1].y, par), chk2(v[2].y, v[3].y, par), or3(chk2(v[4].y, v[5].y, par), chk2(v[6].y, v[7].y, par), 0)); }
__device__ __forceinline__ uint32_t chk4(const uint2 (&v)[4], uint32_t par) { return or3(chk2(v[0].x, v[0].y, par), chk2(v[1].x, v[1].y, par), or3(chk2(v[2].x, v[2].y, par), chk2(v[3].x, v[3].y, par), 0)); }
__device__ __forceinline__ float asf(uint32_t v) { return __uint_as_float(v); }
__device__ __forceinline__ float sum8(const uint32_t (&v)[8]) { return ((asf(v[0]) + asf(v[1])) + (asf(v[2]) + asf(v[3]))) + ((asf(v[4]) + asf(v[5])) + (asf(v[6]) + asf(v[7]))); }
__device__ __forceinline__ float sum8x(const uint2 (&v)[8]) { return ((asf(v[0].x) + asf(v[1].x)) + (asf(v[2].x) + asf(v[3].x))) + ((asf(v[4].x) + asf(v[5].x)) + (asf(v[6].x) + asf(v[7].x))); }
__device__ __forceinline__ float sum8y(const uint2 (&v)[8]) { return ((asf(v[0].y) + asf(v[1].y)) + (asf(v[2].y) + asf(v[3].y))) + ((asf(v[4].y) + asf(v[5].y)) + (asf(v[6].y) + asf(v[7].y))); }

__device__ __forceinline__ uint32_t pack2(float lo, float hi) { uint32_t r; asm("cvt.rn.bf16x2.f32 %0, %1, %2;" : "=r"(r) : "f"(hi), "f"(lo)); return r; }
__device__ __forceinline__ float bfr(float x) { return __uint_as_float(pack2(0.0f, x)); }
__device__ __forceinline__ float ex2(float x) { float r; asm("ex2.approx.ftz.f32 %0, %1;" : "=f"(r) : "f"(x)); return r; }
__device__ __forceinline__ float rcp(float x) { float r; asm("rcp.approx.ftz.f32 %0, %1;" : "=f"(r) : "f"(x)); return r; }
__device__ __forceinline__ float sqrt_(float x) { float r; asm("sqrt.approx.ftz.f32 %0, %1;" : "=f"(r) : "f"(x)); return r; }
__device__ __forceinline__ float bf_lo(uint32_t v) { return __uint_as_float(v << 16); }
__device__ __forceinline__ float bf_hi(uint32_t v) { return __uint_as_float(v & 0xffff0000u); }
__device__ __forceinline__ float sel4(int k, float a, float b, float c, float d) { return (k & 2) ? ((k & 1) ? d : c) : ((k & 1) ? b : a); }
constexpr float LOG2E = 1.4426950408889634f;
constexpr uint32_t ONES = 0x3f803f80u;

__device__ __forceinline__ void ln_stats(float sum, float sq, float& mean, float& den) {
    const float m = sum * (1.0f / 640.0f);
    const float var = fmaxf(fmaf(sq, 1.0f / 640.0f, -m * m), 0.0f);
    mean = bfr(m);
    den = bfr(sqrt_(bfr(bfr(var) + 1e-5f)));
}
__device__ __forceinline__ float sigmoidf_(float x) { return rcp(1.0f + ex2(-x * LOG2E)); }

#define TSTAMP(k) do {} while (0)
#define TST(k) do {} while (0)

#define CSTAMP(k) do {} while (0)
template <int N> __device__ __forceinline__ uint32_t lag(uint32_t sb, uint32_t z = 0) {
#pragma unroll
    for (int k = 0; k < N; k++) z = ldsvol(sb + S_ZERO + z);
    return z;
}
__device__ __forceinline__ void warm_mma(uint32_t& a, uint32_t& b) {
    asm volatile("mma.sync.aligned.m16n8k8.row.col.f16.f16.f16.f16 {%0,%1}, {%0,%1}, {%0}, {%0,%1};" : "+r"(a), "+r"(b) :: "memory");
}
#define KWNS2 20
#define KWNS 200
template <class F>
__device__ __forceinline__ void gather16(const char* p, uint32_t par, int k, F use) {
    uint32_t v[8], u[8];
    int guard = 0;
    bool again;
    do {
#pragma unroll
        for (int s = 0; s < 8; s++) v[s] = ldp32(p + s * 512);
#pragma unroll
        for (int s = 0; s < 8; s++) u[s] = ldp32(p + HALF + s * 512);
        const uint32_t stale = use(sum8(v) + sum8(u), ((v[0] ^ par) & 1) * 8);
        again = __any_sync(~0u, (or3(chk8(v, par), chk8(u, par), stale) & 1) != 0);
    } while (again & (++guard < SPIN_LIMIT));
    SWEEPS(k, guard - 1);
}

struct Params {
    const __nv_bfloat16 *x, *k, *v, *wr, *wq;
    __nv_bfloat16* out;
};
struct Maps { CUtensorMap k, v, vu, wq, wo, wg, wu, wd; };

constexpr int KV_BATCH_KEYS = 32 * 4096;

__device__ __forceinline__ void tma2d(uint32_t dst, const CUtensorMap* m, int c0, int c1, uint32_t bar, uint32_t bytes, uint64_t pol) {
    asm volatile("{\n .reg .pred p;\n elect.sync _|p, 0xffffffff;\n"
                 " @p mbarrier.arrive.expect_tx.shared::cta.b64 _, [%2], %6;\n"
                 " @p cp.async.bulk.tensor.2d.shared::cluster.global.mbarrier::complete_tx::bytes.L2::cache_hint [%0], [%1, {%3, %4}], [%2], %5;\n}"
                 :: "r"(dst), "l"(m), "r"(bar), "r"(c0), "r"(c1), "l"(pol), "r"(bytes) : "memory");
}
__device__ __forceinline__ void scrap_copy(uint32_t dst, const char* src, uint32_t bar) {
    asm volatile("{\n .reg .pred p;\n elect.sync _|p, 0xffffffff;\n"
                 " @p mbarrier.arrive.expect_tx.shared::cta.b64 _, [%2], 12288;\n"
                 " @p cp.async.bulk.shared::cluster.global.mbarrier::complete_tx::bytes [%0], [%1], 4096, [%2];\n"
                 " @p cp.async.bulk.shared::cluster.global.mbarrier::complete_tx::bytes [%0], [%1+4096], 4096, [%2];\n"
                 " @p cp.async.bulk.shared::cluster.global.mbarrier::complete_tx::bytes [%0], [%1+8192], 4096, [%2];\n}"
                 :: "r"(dst), "l"(src), "r"(bar) : "memory");
}
__device__ __forceinline__ void prefetch_l2(const void* p, uint32_t bytes) {
    asm volatile("{\n .reg .pred p;\n elect.sync _|p, 0xffffffff;\n @p cp.async.bulk.prefetch.L2.global [%0], %1;\n}" :: "l"(p), "r"(bytes) : "memory");
}
__device__ __forceinline__ uint64_t pol_first() { uint64_t p; asm("createpolicy.fractional.L2::evict_first.b64 %0, 1.0;" : "=l"(p)); return p; }
__device__ __forceinline__ uint64_t pol_normal() { uint64_t p; asm("createpolicy.fractional.L2::evict_normal.b64 %0, 1.0;" : "=l"(p)); return p; }
__device__ __forceinline__ bool utest(uint32_t bar, uint32_t parity) { return __all_sync(~0u, mbar_test(bar, parity)); }
__device__ __forceinline__ void uwait(uint32_t bar, uint32_t parity) {
    int n = 0;
    while (!__all_sync(~0u, mbar_try(bar, parity)) && ++n < SPIN_LIMIT) {}
}
template <int A, int B, int CNT> __device__ __forceinline__ void init_bars(uint32_t sb) {
#pragma unroll 1
    for (int k = A; k < B; k++)
        asm volatile("{\n .reg .pred p;\n elect.sync _|p, 0xffffffff;\n @p mbarrier.init.shared::cta.b64 [%0], %1;\n}" :: "r"(sb + S_BAR + 8 * k), "n"(CNT) : "memory");
}
__device__ __forceinline__ int unit_key(uint32_t b, uint32_t u) {
    return (blockIdx.x >> 2) * 4096 + 3072 + (blockIdx.x & 3) * (16 * ILV) + b * KV_BATCH_KEYS + (u & ~(ILV - 1u)) * 64 + (u & (ILV - 1)) * 16;
}
__device__ __forceinline__ void load_tile(const CUtensorMap* m, uint32_t dst, uint32_t bar, uint32_t bytes, int key, uint64_t pol) { tma2d(dst, m, 0, 3 * key, bar, bytes, pol); }
__device__ __forceinline__ const char* unit_ptr(const Params& P, int n) { return (const char*)((n & 16) ? P.v : P.k) + (size_t)unit_key(n >> 5, n & 15) * 384; }
#define LSTAMP(k) do {} while (0)

__device__ __forceinline__ uint32_t k_place(uint32_t b, uint32_t s) { return s + 3 + 5 * (b & 1); }
__device__ __forceinline__ uint32_t v_place(uint32_t b, uint32_t s) { return s < 3 ? s : s + 8 - 8 * (b & 1); }
__device__ __forceinline__ void k_load(const Maps& M, uint32_t dst, uint32_t bar, int key8, uint64_t pol) {
    asm volatile("{\n .reg .pred p;\n elect.sync _|p, 0xffffffff;\n"
                 " @p mbarrier.arrive.expect_tx.shared::cta.b64 _, [%2], 6144;\n"
                 " @p cp.async.bulk.tensor.4d.shared::cluster.global.mbarrier::complete_tx::bytes.L2::cache_hint [%0], [%1, {0, 0, 0, %3}], [%2], %4;\n}"
                 :: "r"(dst), "l"(&M.k), "r"(bar), "r"(key8), "l"(pol) : "memory");
}
__device__ __forceinline__ int unit_key8(uint32_t n) { return unit_key(n >> 4, n & 15) >> 3; }
__device__ __forceinline__ void ring_load(const Maps& M, uint32_t sb, uint32_t b, uint32_t u, uint32_t pos) {
    if (u < 16) k_load(M, sb + pos * UNIT, sb + S_RING + 8 * pos, unit_key8(16 * b + u), pol_normal());
    else load_tile(&M.vu, sb + pos * UNIT, sb + S_FV + 4 * (pos & 6), UNIT, unit_key(b, pos), pol_first());
}
__device__ __forceinline__ uint32_t token(bool p, uint32_t a, uint32_t n) {
    uint32_t v;
    asm volatile("{\n .reg .pred p;\n setp.ne.u32 p, %2, 0;\n mov.u32 %0, 0;\n @p atom.shared.exch.b32 %0, [%1], %3;\n}" : "=r"(v) : "r"(a), "r"((uint32_t)p), "r"(n) : "memory");
    return v;
}
__device__ __forceinline__ void place_load(const Maps& M, uint32_t sb, uint32_t n) {
    k_load(M, sb + k_place(n >> 4, 0) * SLOT + (n & 15) * UNIT, sb + S_FK + 4 * (n & 14), unit_key8(n), pol_first());
}
__device__ __forceinline__ void v_load(const Maps& M, uint32_t sb, uint32_t b, uint32_t s) {
    load_tile(&M.v, sb + v_place(b, s) * SLOT, sb + S_FV + 8 * s, SLOT, unit_key(b, 2 * s), pol_first());
}

__device__ __forceinline__ void stream_warp(const Params& P, const Maps& M, uint32_t sb, uint32_t lane) {
    const uint64_t pol = pol_first();
    const int bid = blockIdx.x, g = bid >> 3, i = bid & 7;
    const uint32_t wf = sb + S_WFULL;
    uint32_t tn = __shfl_sync(~0u, gtime32(), 0) * 16;
    auto pace = [&](uint32_t dt) {
        int k = 0;
        uint32_t now;
        do now = __shfl_sync(~0u, gtime32(), 0) * 16; while ((int)(now - tn) < 0 && ++k < SPIN_FAST);
        if ((int)(now - tn) > SLACK0) tn = now - SLACK0;
        tn += dt;
    };
#pragma unroll
    for (int k = 0; k < 10; k++) {
        if (k < 2) {
            if (k == 0) init_bars<26, 27, 1>(sb); else init_bars<27, 37, 1>(sb);
            asm volatile("fence.mbarrier_init.release.cluster;" ::: "memory");
            if (k == 1) { asm volatile("bar.arrive 2, %0;" :: "n"(NTHR) : "memory"); asm volatile("bar.sync 3, 128;" ::: "memory"); }
        }
        if (k >= WIN_W) uwait(wf + 8 * (k - WIN_W), 0);
        pace(TAUW * 5 / 2 - (k == 0 || k == 2 ? LEADW : 0));
        if (k < 4) tma2d(sb + ST_WQ + 15360 * k, &M.wq, 384 * g + 192 * (k >> 1), 80 * i + 40 * (k & 1), wf + 8 * k, 15360, pol);
        else if (k < 6) tma2d(sb + ST_WG + 15360 * (k - 4), k == 4 ? &M.wg : &M.wu, 96 * g, 80 * i, wf + 8 * k, 15360, pol);
        else tma2d(sb + ST_WO + 15360 * (k - 6), &M.wo, 80 * i, 384 * g + 96 * (k - 6), wf + 8 * k, 15360, pol);
    }
#pragma unroll 1
    for (int n = 0; n < 16; n++) {
        if (n == 0 || n == 5 || n == 11) uwait(sb + S_RELW + (n == 0 ? 0 : n == 5 ? 8 : 16), 0);
        uwait(n < WIN_S ? wf + 8 * (10 - WIN_S + n) : sb + S_FV + 8 * ((n - WIN_S) ^ 8), 0);
        pace(2 * TAU0);
        if (n >= WIN_S && !utest(sb + S_FV + 8 * ((n - WIN_S + 1) ^ 8), 0)) tn += XB;
        if (n < 8) { place_load(M, sb, 2 * n); place_load(M, sb, 2 * n + 1); }
        else if (n < 11) { ring_load(M, sb, 0, 2 * n, 2 * n - 16); ring_load(M, sb, 0, 2 * n + 1, 2 * n - 15); }
        else v_load(M, sb, 0, n - 8);
        if (n == 7) { pace(TAUW * 5 / 2); tma2d(sb + S_WD, &M.wd, 80 * i, 96 * g, wf + 80, 15360, pol); }
    }
    int nd = 0;
    uint32_t q[4];
#pragma unroll
    for (int r = 0; r < 4; r++) q[r] = sb + S_FV + 8 * (7 - r);
    uint32_t td = tn;
    uint32_t pos = 2;
#pragma unroll 1
    for (int m = 16; m < 64; m++) {
        const int b = m >> 4, j = m & 15;
        const char* src = unit_ptr(P, 2 * m);
        const uint32_t tok = sb + S_TOK + (j < 3 ? 4 * pos : j < 11 ? 24 + 4 * pos : 16 + 4 * j) + 4 * lane;
        static_assert(WIN_U <= 12, "a ring position has at most one token of the timetable");
        int k = 0;
        while (true) {
            const uint2 c = lds64(sb + S_KF);
            if (__all_sync(~0u, mbar_test(q[WIN_S - 1] & ~1u, q[WIN_S - 1] & 1) & (min((int)c.x + 1, (int)c.y) >= 16 * b + min(2 * j + 2 - WIN_U, 16))) || ++k >= SPIN_FAST) break;
        }
        uint32_t now;
        while (true) {
            now = __shfl_sync(~0u, gtime32(), 0) * 16;
            if ((int)(now - td) >= 0 || ++k >= SPIN_FAST) break;
        }
        const uint32_t mine = __ballot_sync(~0u, token(lane < (j < 11 ? 2 : 1), tok, 2 * m + lane) == 2 * m + lane);
        {
            const uint2 c = lds64(sb + S_KF);
            if (!__all_sync(~0u, mbar_test(q[WIN_S - 2] & ~1u, q[WIN_S - 2] & 1) & (min((int)c.x + 1, (int)c.y) >= 16 * b + min(2 * j + 4 - WIN_U, 16)))) tn += XB;
        }
        q[3] = q[2]; q[2] = q[1]; q[1] = q[0]; q[0] = sb + S_QRDY;
        if (j < 11) {
            if (mine & 1) ring_load(M, sb, b, 2 * j, pos); else prefetch_l2(src, UNIT);
            if (mine & 2) ring_load(M, sb, b, 2 * j + 1, pos + 1); else prefetch_l2(src + UNIT, UNIT);
            if (j >= 8) q[0] = (sb + S_FV + 8 * (j - 8)) | (b & 1);
        } else if (mine) { v_load(M, sb, b, j - 8); q[0] = (sb + S_FV + 8 * (j - 8)) | (b & 1); }
        else if (j - 8 >= VPF) prefetch_l2(src, SLOT);
        else {
            scrap_copy(sb + S_DUMMY, src, sb + S_DBAR + 8 * (nd & 3));
            q[0] = (sb + S_DBAR + 8 * (nd & 3)) | ((nd >> 2) & 1);
            nd++;
        }
        pos = j == 15 ? 2 : pos == 4 ? 0 : pos + 2;
        if ((int)(now - tn) > SLACK) tn = now - SLACK;
        tn += 2 * TAU;
        td = (int)(tn - now) > 2 * TMIN ? tn : now + 2 * TMIN;
    }
#pragma unroll 1
    for (int m = max(nd - 4, 0); m < nd; m++) uwait(sb + S_DBAR + 8 * (m & 3), (m >> 2) & 1);
}

__host__ __device__ constexpr uint64_t bit_list(uint32_t m) { uint64_t r = 0; int n = 0; for (int k = 0; k < 12; k++) if ((m >> k) & 1) r |= (uint64_t)k << (4 * n++); return r; }
__device__ __forceinline__ float scaled(float s) { return bfr(bfr(s) * 0.07216878364870322f); }
__device__ __forceinline__ void probs(float s, uint32_t ps, uint32_t src, uint32_t ln) {
    const uint32_t q8 = ln >> 2, t4 = ln & 3;
    int key = __float_as_int(s);
    key ^= (key >> 31) & 0x7fffffff;
    key = __reduce_max_sync(~0u, key);
    key ^= (key >> 31) & 0x7fffffff;
    const float ml = __int_as_float(key) * LOG2E;
    sts16(ps + 64 * src + (q8 >> 1) * 16 + t4 * 4 + (q8 & 1) * 2, pack2(ex2(fmaf(s, LOG2E, -ml)), 0.f));
    stsf(ps + PS_MAX + 4 * src, ml);
}
template <int H> __device__ __forceinline__ uint32_t b_pos(uint32_t e) { const uint32_t h = e >= H, k = e - H * h; return h * 192 + (k & 6) * 24 + (k >> 3) * 4 + (k & 1) * 2; }
__device__ __forceinline__ uint32_t a_pos(uint32_t e) { const uint32_t h = e >= 40, k = e - 40 * h; return (k & 6) * 24 + (k >> 3) * 8 + h * 4 + (k & 1) * 2; }
__device__ __forceinline__ uint32_t q_pos(uint32_t d) { const uint32_t s = 3 * ((d >> 4) & 3) + (d >> 6); return s * 32 + (d & 6) * 4 + ((d >> 3) & 1) * 4 + (d & 1) * 2; }
__device__ __forceinline__ uint32_t k_off(uint32_t ln) { return (ln & 8) * 384 + (ln & 7) * 128 + (((ln & 7) ^ (ln >> 4)) << 4); }

#define HSTAMP(k) do {} while (0)
__device__ __forceinline__ char* xwindow() { return reinterpret_cast<char*>((reinterpret_cast<uintptr_t>(g_x) + (2u << 20) - 1) & ~(uintptr_t)((2u << 20) - 1)); }

struct XPtr {
    uint32_t lo, hi;
    __device__ __forceinline__ explicit XPtr(char* p) : lo((uint32_t)(uintptr_t)p), hi((uint32_t)((uintptr_t)p >> 32)) {}
    __device__ __forceinline__ XPtr(uint32_t l, uint32_t h) : lo(l), hi(h) {}
    __device__ __forceinline__ XPtr operator+(uint32_t o) const { return XPtr(lo + o, hi); }
    __device__ __forceinline__ operator char*() const { uint64_t p; asm("mov.b64 %0, {%1, %2};" : "=l"(p) : "r"(lo), "r"(hi)); return (char*)p; }
};

__device__ __forceinline__ char* side_word(uint32_t g, uint32_t i) { return xwindow() + pairG(1, 0, i) * 8192 + (g >> 3) * HALF + (g & 7) * 512 + 320; }

__device__ __forceinline__ uint32_t probe_side() {
    const uint32_t bid = blockIdx.x, g = bid >> 3, i = bid & 7, P = pairG(0, 0, i);
    char* p = xwindow() + P * 8192 + (g >> 3) * HALF + (g & 7) * 512 + 352;
    uint32_t best[2] = {~0u, ~0u};
#pragma unroll
    for (int k = 0; k < 4; k++) *reinterpret_cast<uint4*>(p + (k & 1) * 16 + (k >> 1) * COPY) = make_uint4(1, 1, 1, 1);
#pragma unroll 1
    for (int r = 0; r < 64; r++) {
        if (r >= 4 && !(r & 1) && min(best[0], best[1]) < 380 && max(best[0], best[1]) > min(best[0], best[1]) + 80) break;
        uint32_t c0, c1, v;
        asm volatile("mov.u32 %0, %clock;" : "=r"(c0) :: "memory");
        asm volatile("atom.relaxed.gpu.global.exch.b32 %0, [%1], 0;" : "=r"(v) : "l"(p + (r & 1) * COPY) : "memory");
        asm volatile("{\n .reg .pred q;\n setp.eq.u32 q, %1, 0x13579bdf;\n mov.u32 %0, 0;\n @!q mov.u32 %0, %clock;\n}" : "=r"(c1) : "r"(v) : "memory");
        if (r & 1) best[1] = min(best[1], c1 - c0); else best[0] = min(best[0], c1 - c0);
    }
    return 1 + ((best[1] < best[0]) ^ (__popc(P & PMASK) & 1));
}

template <int N>
__device__ __forceinline__ void hop_a(const char* src, uint32_t par, uint32_t dst, bool st, int k) {
    uint2 v[N][4];
    float e[4], rl;
    int guard = 0;
    bool again;
    do {
#pragma unroll
        for (int s = 0; s < 4 * N; s++) v[s / 4][s % 4] = ldp64(src + (s / 4) * 256 + (s % 4) * 1024);
        again = __any_sync(~0u, ((chk4(v[0], par) | chk4(v[N - 1], par)) & 1) != 0);
        const uint32_t M = (uint32_t)max(max((int)v[0][0].x, (int)v[0][1].x), max((int)v[0][2].x, (int)v[0][3].x)) - 254;
#pragma unroll
        for (int s = 0; s < 4; s++) e[s] = asf((uint32_t)max((int)(v[0][s].x - M), 0) << 22);
        rl = rcp(fmaf(e[0], asf(v[0][0].y), e[1] * asf(v[0][1].y)) + fmaf(e[2], asf(v[0][2].y), e[3] * asf(v[0][3].y)));
#pragma unroll
        for (int s = 0; s < 4; s++) e[s] = __shfl_sync(~0u, e[s], 24);
        keep(rl);
    } while (again & (++guard < SPIN_LIMIT));
    rl = __shfl_sync(~0u, rl, 24);
#pragma unroll
    for (int n = 0; n < N; n++) {
        const float o0 = fmaf(e[0], asf(v[n][0].x), e[1] * asf(v[n][1].x)) + fmaf(e[2], asf(v[n][2].x), e[3] * asf(v[n][3].x));
        const float o1 = fmaf(e[0], asf(v[n][0].y), e[1] * asf(v[n][1].y)) + fmaf(e[2], asf(v[n][2].y), e[3] * asf(v[n][3].y));
        sts32_if(st, dst + 192 * n, pack2(o0 * rl, o1 * rl));
    }
    SWEEPS(k, guard - 1);
    __syncwarp();
}

__device__ __forceinline__ void score_warp(const Maps& M, uint32_t sb, uint32_t h, uint32_t ln) {
    const uint32_t lane0 = ln;
    uwait(sb + S_QRDY, 0);
    const uint32_t q8 = ln >> 2;
    const uint32_t k0 = k_off(ln);
    uint32_t pos = h + 6, bar = sb + S_FK, par = 0, phases = 0;
    uint2 q = lds64(sb + S_QS + 8 * ln), qh = lds64(sb + S_QS + 8 * ln + 256);
    auto first_round = [&](uint32_t b, uint32_t ln) {
        uwait(sb + S_RELR, b & 1);
        const uint32_t u = h + 2 * ln, p = u < 4 ? u + 2 : u - 4;
        uint32_t todo = __ballot_sync(~0u, token(ln < 3, sb + S_TOK + 4 * p, 32 * b + 32 + u) == 32 * b + 32 + u);
#pragma unroll 1
        for (uint32_t r = h; todo; todo >>= 1, r += 2) if (todo & 1) ring_load(M, sb, b + 1, r, r < 4 ? r + 2 : r - 4);
    };
#pragma unroll 1
    for (uint32_t n = h; n < 64; n += 2) {
        HSTAMP(0);
        const uint32_t ua = sb + pos * UNIT;
        if (!__all_sync(~0u, mbar_try(bar, par))) uwait(bar, par);
        HSTAMP(1);
        float acc[2][4] = {};
        uint32_t mine = 0;
        const uint32_t id = n + (n & 48) + 6;
#pragma unroll
        for (int s = 0; s < 12; s++) {
            uint32_t kf[4];
            ldsm4(kf, (k0 ^ (32 * (s / 3))) + (ua + 1024 * (s % 3)));
            if (s == 11) {
                __syncwarp();
                mine = token(ln == 0 && n >= 16, sb + S_TOK + 24 + 4 * pos, id);
                stsvol(sb + S_KF + 4 * h, n + 1);
            }
            const bool m = q8 == (s & 7);
            mmaA(acc[s & 1], kf, m ? (s < 8 ? q.x : qh.x) : 0u, m ? (s < 8 ? q.y : qh.y) : 0u);
        }
        const uint32_t pos0 = pos;
        const bool last = (n & 14) == 14;
        pos = last ? h + 2 : n >= 16 && pos >= 4 ? h : pos + 2;
        bar = n >= 14 ? sb + S_RING + 8 * pos : bar + 8;
        par = n >= 14 ? (phases >> pos) & 1 : 0;
        phases ^= n >= 14 ? 1u << pos : 0;
        const float w0 = (acc[0][0] + acc[0][1]) + (acc[1][0] + acc[1][1]), w1 = (acc[0][2] + acc[0][3]) + (acc[1][2] + acc[1][3]);
        HSTAMP(2);
        if (__any_sync(~0u, mine == id)) ring_load(M, sb, n >> 4, (n & 15) + 6, pos0);
        HSTAMP(3);
        float s = ((ln & 1) ? w1 : w0) + __shfl_xor_sync(~0u, (ln & 1) ? w0 : w1, 1);
        s += __shfl_xor_sync(~0u, s, 2);
        sts_hi16(sb + S_SC + (((n & 12) >> 1) + h) * 64 + (n & 2) * 2 + (ln & 29) * 2, scaled(s));
        if (last) {
            __syncwarp();
            arrive_if(ln == 0, sb + S_SCO);
            const uint32_t b = n >> 4, ln = lane0 + lag<1>(sb);
            if (b > 0) {
                uwait(sb + S_RELK, (b - 1) & 1);
                if (h == 0) LSTAMP(64 + 2 * b);
                const uint32_t sl = 3 + h + 2 * ln, idv = 32 * b + 16 + 2 * sl;
                uint32_t todo = __ballot_sync(~0u, token(sl < 8, sb + S_TOK + 48 + 4 * sl, idv) == idv);
#pragma unroll 1
                for (uint32_t r = 3 + h; todo; todo >>= 1, r += 2) if (todo & 1) v_load(M, sb, b, r);
                const uint32_t g = blockIdx.x >> 3, pr = pairL(RA, 1, g), side = ldsvol(sb + S_SIDE);
                const char* src = xwindow() + pr * 8192 + ((side ^ 1 ^ __popc(pr & PMASK)) & 1) * COPY + h * HALF + 8 * min(ln, 24u);
                uwait(sb + S_RELV, (b - 1) & 1);
                __nanosleep(HOP1_NS);
#pragma unroll 1
                for (uint32_t r = 0; r < 4; r += 2) {
                    hop_a<2>(src + 256 * r, b & 1, sb + S_OS + 192 * (4 * h + r) + 96 + 4 * ln, ln < 24, 25);
                    if (r == 0 && b < 3) first_round(b, ln);
                }
                arrive_if(ln == 0, sb + S_OS1);
            } else first_round(0, ln);
            q = lds64(sb + S_QS + 24 * ((n + 2) & 48) + 8 * ln); qh = lds64(sb + S_QS + 24 * ((n + 2) & 48) + 8 * ln + 256);
        }
    }
}

__global__ void __launch_bounds__(NTHR, 1)
fused_kernel(const Params P, const __grid_constant__ Maps M) {
    extern __shared__ __align__(1024) unsigned char smem[];
    const uint32_t sb = smem_u32(smem);
    const int tid = threadIdx.x, bid = blockIdx.x;
    if (tid == 0) {
        asm volatile("prefetch.tensormap [%0];" :: "l"(&M.wq) : "memory");
        asm volatile("cp.async.bulk.prefetch.L2.global [%0], 12288;" :: "l"(P.wq + (80 * (bid & 7) + (bid >> 3)) * 6144) : "memory");
    }
    const int w = __shfl_sync(~0u, tid >> 5, 0), lane = tid & 31;

    if (w >= 8) {
        asm volatile("setmaxnreg.dec.sync.aligned.u32 " REG_LO ";");
        if (w == 8) {
            stream_warp(P, M, sb, lane);
        } else {
            if (w == 9) { init_bars<0, 3, 2>(sb); init_bars<3, 8, 1>(sb); init_bars<16, 22, 1>(sb); }
            else if (w == 10) { init_bars<8, 16, 2>(sb); init_bars<22, 26, 1>(sb); }
            else { init_bars<37, 38, 1>(sb); init_bars<38, 40, 8>(sb); init_bars<40, 41, 1>(sb); init_bars<41, 44, 8>(sb); init_bars<44, 46, 2>(sb); stsvol(sb + S_ZERO + 4 * lane, 0); if (lane < 16) stsvol(sb + S_LN + 4 * lane, 0); }
            asm volatile("fence.mbarrier_init.release.cluster;" ::: "memory");
            asm volatile("bar.arrive 3, 128;" ::: "memory");
            if (w == 11) asm volatile("bar.arrive 2, %0;" :: "n"(NTHR) : "memory");
            else {
                if (lane < 4) asm volatile("prefetch.tensormap [%0];" :: "l"(&M.k + lane + 4 * (w - 9)) : "memory");
                __syncwarp();
                asm volatile("bar.sync 2, %0;" :: "n"(NTHR) : "memory");
            }
            if (w < 11) score_warp(M, sb, w - 9, lane);
            else {
                uint32_t mine = 0;
                if (lane == 0) mine = probe_side();
                mine = __shfl_sync(~0u, mine, 0);
                if (lane < 8) stp32(side_word(bid >> 3, bid & 7) + 4 * lane, asf(mine & 2), 1);
                uint32_t a = 0, b = 0;
                int k = 0;
                while (!utest(sb + S_QRDY, 0) && ++k < SPIN_FAST) { warm_mma(a, b); __nanosleep(KWNS); }
                while (true) {
                    const uint32_t v = ldp32(side_word(bid >> 3, lane & 7));
                    const bool late = !__all_sync(~0u, v & 1);
                    if (!late || ++k >= SPIN_FAST) { stsvol(sb + S_SIDE, mine | (FORCE_BOTH || late || __any_sync(~0u, (v ^ mine) & 2) ? 4 : 0)); break; }
                    warm_mma(a, b); __nanosleep(KWNS);
                }
                while (ldsvol(sb + S_GATE) == 0 && ++k < SPIN_FAST) { warm_mma(a, b); __nanosleep(KWNS); }
                uint32_t rl = lane, rq = 0;
                auto reset = [&] {
                    if (rq < 128) *reinterpret_cast<uint4*>(reinterpret_cast<char*>(g_s) + (rl < 60 ? XS + bid * 7680 + 128 * rl : XS2 + bid * 768 + 128 * (rl - 60)) + rq) = make_uint4(0, 0, 0, 0);
                    rl += 32;
                    if (rl >= 66) { rl -= 66; rq += 16; }
                };
                reset(); reset();
                if (lane < 8) stp32(side_word(bid >> 3, bid & 7) + 4 * lane, 0.f, 0);
                const uint32_t side = (ldsvol(sb + S_SIDE) & 1) ^ 1, g = bid >> 3, i = bid & 7;
                const XPtr gx(xwindow());
                auto nearp = [&](uint32_t pr) { return gx.lo + pr * 8192 + ((side ^ __popc(pr & PMASK)) & 1) * COPY; };
                const uint32_t own = (i >> 2) * HALF + (i & 3) * 1024 + (lane & 7) * 128;
                const uint32_t cut = (lane & 7) == 7 ? 128 : 0;
                const uint32_t pAC = nearp(pairL(lane >> 4, (lane >> 3) & 1, g)) + own - (lane >> 4) * cut, pE = nearp(pairL(RE, (lane >> 3) & 1, g)) + own - cut;
                const uint32_t pG = nearp(pairG((lane >> 2) & 1, (lane >> 3) & 1, i)) + min(lane & 3, 2) * 128;
                uint32_t tr = 0, tk = 0, ph = 0, src = g + (lane >> 4), seen = 0, n = 16;
                bool go = false, first = true;
                while (n < 64 && ++k < SPIN_FAST) {
                    const uint32_t now = __shfl_sync(~0u, gtime32(), 0) * 16;
                    if (!go && utest((n & 15) < 6 ? sb + S_RELK : sb + S_RELV, ((n >> 4) & 1) ^ 1)) { go = true; if ((int)(now - tk) > 0 || !(n & 15)) tk = now; }
                    if (go && (int)(now - tk) >= 0) {
                        place_load(M, sb, (n & 16) ? n : (n & 48) | ((n + 10) & 15));
                        tk += KRE_TAU;
                        n++;
                        go = (n & 15) != 0 && (n & 15) != 6;
                        if (!(n & 15)) LSTAMP(63 + (n >> 3));
                    } else if (first || (int)(now - tr) >= 0) {
                        first = false;
                        tr = now + RFR_TAU;
                        b |= seen & a;
                        warm_mma(a, b);
                        seen = ldp32(XPtr(ph == 0 ? pAC : ph == 1 && lane < 16 ? pE : pG + (src & 8) * (HALF / 8) + (src & 7) * 512, gx.hi));
                        reset();
                        src += ph == 0 ? 0 : ph == 1 ? 2 : 1;
                        ph = ph == 2 ? 0 : ph + 1;
                    } else __nanosleep(KWNS2);
                }
                while (rq < 128) reset();
                __syncwarp();
                while (ldsvol(sb + S_GATE) < 6 && ++k < SPIN_FAST) { warm_mma(a, b); __nanosleep(KWNS); }
                if (a | b) stsvol(sb + S_GATE, 6);
            }
        }
        return;
    }
    asm volatile("setmaxnreg.inc.sync.aligned.u32 " REG_HI ";");

    const int g = bid >> 3, i = bid & 7;
    const int g8 = lane >> 2, t = lane & 3;
    char* const gs = reinterpret_cast<char*>(g_s);
    const XPtr gx(xwindow());

    W80 Wq[6], Wgu[3];
    uint32_t Wo[5][3][4];
    if (w < 4) {
        const uint32_t* xp = reinterpret_cast<const uint32_t*>(P.x + 640 * w);
        float sum = 0.f, sq = 0.f;
#pragma unroll
        for (int u = 0; u < 10; u++) { uint32_t v = xp[lane + 32 * u]; float a = bf_lo(v), b = bf_hi(v); sum += a + b; sq += a * a + b * b; }
#pragma unroll
        for (int o = 16; o > 0; o >>= 1) { sum += __shfl_xor_sync(~0u, sum, o); sq += __shfl_xor_sync(~0u, sq, o); }
        float mean, den; ln_stats(sum, sq, mean, den);
        if (lane < 20) {
            const uint2 v = reinterpret_cast<const uint2*>(P.x + 640 * w + 80 * i)[lane];
            sts64(sb + S_X0 + 160 * w + 8 * lane, v.x, v.y);
            sts32(sb + S_L0 + 384 * w + b_pos<40>(4 * lane), pack2(__fdiv_rn(bfr(bf_lo(v.x) - mean), den), __fdiv_rn(bfr(bf_hi(v.x) - mean), den)));
            sts32(sb + S_L0 + 384 * w + b_pos<40>(4 * lane + 2), pack2(__fdiv_rn(bfr(bf_lo(v.y) - mean), den), __fdiv_rn(bfr(bf_hi(v.y) - mean), den)));
        }
    } else if (w == 4) {
        const uint32_t* xp = reinterpret_cast<const uint32_t*>(P.wr);
        float sum = 0.f;
#pragma unroll
        for (int u = 0; u < 10; u++) { uint32_t v = xp[lane + 32 * u]; sum += bf_lo(v) + bf_hi(v); }
#pragma unroll
        for (int o = 16; o > 0; o >>= 1) sum += __shfl_xor_sync(~0u, sum, o);
        if (lane == 0) stsf(sb + S_SWR, sum);
        if (lane < 20) {
            const uint2 v = reinterpret_cast<const uint2*>(P.wr + 80 * i)[lane];
            sts32(sb + S_XA + 576 + a_pos(4 * lane), v.x); sts32(sb + S_XA + 576 + a_pos(4 * lane + 2), v.y);
            sts32(sb + S_XA + a_pos(4 * lane), ONES); sts32(sb + S_XA + a_pos(4 * lane + 2), ONES);
        }
    }
    asm volatile("bar.sync 2, %0;" :: "n"(NTHR) : "memory");
    auto frag = [](uint32_t (&a)[4], uint32_t p, int pitch) {
        const uint32_t r0 = lds32(p), r1 = lds32(p + pitch), r2 = lds32(p + 2 * pitch), r3 = lds32(p + 3 * pitch);
        a[0] = __byte_perm(r0, r1, 0x5410); a[1] = __byte_perm(r0, r1, 0x7632);
        a[2] = __byte_perm(r2, r3, 0x5410); a[3] = __byte_perm(r2, r3, 0x7632);
    };
    mbar_wait(sb + S_WFULL + 16 * (w >> 2), 0);
    mbar_wait(sb + S_WFULL + 16 * (w >> 2) + 8, 0);
    {
        const uint32_t p = sb + ST_WQ + (w >> 2) * 30720 + (2 * t) * 384 + (48 * (w & 3) + 2 * g8) * 2;
#pragma unroll
        for (int r = 0; r < 10; r++)
#pragma unroll
            for (int m = 0; m < 3; m++) {
                const uint32_t q = p + ((r & 1) * 40 + (r >> 1) * 8) * 384 + 32 * m, r0 = lds32(q), r1 = lds32(q + 384);
                (r < 8 ? Wq[2 * m].a[(r >> 2) & 1][r & 3] : Wq[2 * m].c[r & 1]) = __byte_perm(r0, r1, 0x5410);
                (r < 8 ? Wq[2 * m + 1].a[(r >> 2) & 1][r & 3] : Wq[2 * m + 1].c[r & 1]) = __byte_perm(r0, r1, 0x7632);
            }
    }
    __syncwarp();
    if (lane == 0) mbar_arrive(sb + S_RELW);
    TSTAMP(1);
    {
        char* d = gs + XS + bid * 7680 + (w >> 2) * 3840 + (48 * (w & 3) + 2 * g8) * 4;
        float acc[6][4] = {};
        mul80(acc, Wq, lds128(sb + S_L0 + 48 * lane), lds32(sb + S_L0 + 48 * lane + 16));
#pragma unroll
        for (int m = 0; m < 6; m += 2) stp64(d + t * 768 + 32 * m, acc[m][0] + acc[m][3], acc[m + 1][0] + acc[m + 1][3], 1);
        float sum[6][4] = {};
        mul80(sum, Wq, make_uint4(ONES, ONES, ONES, ONES), ONES);
        if (t == 0)
#pragma unroll
            for (int m = 0; m < 6; m += 2) stp64(d + 4 * 768 + 32 * m, sum[m][0] + sum[m][3], sum[m + 1][0] + sum[m + 1][3], 1);
    }
    mbar_wait(sb + S_WFULL + 32, 0);
    mbar_wait(sb + S_WFULL + 40, 0);
    const uint32_t oct = 3 * (w >> 1) + (w & 1), oct2 = 3 * (w >> 1) + 2;
    {
        const uint32_t p = sb + ST_WG + ((lane & 7) + 40 * ((lane >> 3) & 1) + 8 * (lane >> 4)) * 192;
#pragma unroll
        for (int T = 0; T < 3; T++) {
            const uint32_t q = p + (T < 2 ? T * 15360 + 16 * oct : (w & 1) * 15360 + 16 * oct2);
            ldsm4t(Wgu[T].a[0], q); ldsm4t(Wgu[T].a[1], q + 16 * 192); ldsm2t(Wgu[T].c, q + 32 * 192);
        }
        float sum[3][4] = {};
        mul80(sum, Wgu, make_uint4(ONES, ONES, ONES, ONES), ONES);
        if (t < 3) stp32(gs + XS2 + bid * 768 + (t < 2 ? 64 * oct + 4 * t : 64 * oct2 + 4 * (w & 1)) + 8 * g8,
                         sel4(t, sum[0][0] + sum[0][3], sum[1][0] + sum[1][3], sum[2][0] + sum[2][3], 0.f), 1);
    }
    __syncwarp();
    if (lane == 0) mbar_arrive(sb + S_RELW + 8);
    mbar_wait(sb + S_WFULL + 48 + 8 * (w >> 1), 0);
    {
        const uint32_t po = sb + ST_WO + (48 * w + 12 * t) * 160 + 4 * g8;
#pragma unroll
        for (int s = 0; s < 3; s++)
#pragma unroll
            for (int m = 0; m < 5; m++) frag(Wo[m][s], po + 4 * s * 160 + 32 * m, 160);
    }
    __syncwarp();
    if (lane == 0) mbar_arrive(sb + S_RELW + 16);
    mbar_wait(sb + S_WFULL + 64, 0);
    if (tid < 192) {
        const char* srcS = gs + XS + g * 8 * 7680 + (i >> 2) * 3840 + tid * 4;
        uint32_t vs[5][8];
        int guard = 0;
        do {
#pragma unroll
            for (int b = 0; b < 5; b++)
#pragma unroll
                for (int s = 0; s < 8; s++) vs[b][s] = ldp32(srcS + b * 768 + s * 7680);
        } while (((or3(chk8(vs[0], 1), chk8(vs[1], 1), chk8(vs[2], 1)) | chk8(vs[3], 1) | chk8(vs[4], 1)) & 1) && ++guard < SPIN_LIMIT);
        const uint32_t qpos = sb + S_QS + q_pos(tid);
#pragma unroll
        for (int b = 0; b < 4; b++) {
            sts_hi16(qpos + 384 * b, bfr(sum8(vs[b])));
        }
        stsf(sb + S_CSQ + 4 * tid, sum8(vs[4]));
    }
    if (tid < 192) {
        uint32_t v[8];
        int guard = 0;
        do {
#pragma unroll
            for (int s = 0; s < 8; s++) v[s] = ldp32(gs + XS2 + (g * 8 + s) * 768 + tid * 4);
        } while ((chk8(v, 1) & 1) && ++guard < SPIN_LIMIT);
        stsf(sb + S_CSGU + 4 * tid, sum8(v));
    }
    __syncwarp();
    bar_main();
    arrive_if(tid == 0, sb + S_QRDY);
    TSTAMP(2);

    uint32_t side;
    { int k = 0; while ((side = ldsvol(sb + S_SIDE)) == 0 && ++k < SPIN_FAST) {} }
    const uint32_t both = __any_sync(~0u, side & 4) ? COPY : 0;
    uint32_t td = __shfl_sync(~0u, tid, lane);
    const uint32_t wp = __shfl_sync(~0u, tid >> 5, 0);
    const uint32_t cc = wp >= 3;
    auto uni = [](uint32_t v) { return __shfl_sync(~0u, v, 0); };
    auto pin = [&](uint32_t v) { return __shfl_sync(~0u, v, td); };
    auto nearp = [&](uint32_t P) { return gx.lo + P * 8192 + ((side ^ 1 ^ __popc(P & PMASK)) & 1) * COPY; };
    constexpr uint32_t COL = 32 * 8192;
    const uint32_t ownL = (i >> 2) * HALF + (i & 3) * 1024, ownG = gx.lo + (g >> 3) * HALF + (g & 7) * 512;
    const uint32_t uPubA = uni(ownL + nearp(pairL(RA, 0, g)) + (wp >> 1) * 256 + (wp & 1) * 96), uPolA = uni(nearp(pairL(RA, 0, g)) + (wp >> 2) * HALF + (wp & 3) * 256);
    const uint32_t uPubB = uni(ownG + pairG(0, cc, i) * 8192), uPolB = uni(nearp(pairG(0, cc, i)));
    const uint32_t uPubC = uni(ownL + nearp(pairL(RC, 0, g))), uPolC = uni(nearp(pairL(RC, wp < 6 ? cc : 0, g)));
    const uint32_t uPubD = uni(ownG + pairG(1, 0, i) * 8192 + (wp < 7 ? 32 * wp : 256)), uPolD = uni(nearp(pairG(1, cc, i)));
    const uint32_t uPubE = uni(ownL + nearp(pairL(RE, 0, g))), uPolE = uni(nearp(pairL(RE, i >> 2, g)));
    const uint32_t uOS = uni(sb + S_OS + 192 * wp);
    auto xp = [&](uint32_t lo) { return (char*)XPtr(lo, gx.hi); };
    {
        const uint4 z = make_uint4(0, 0, 0, 0);
        const uint32_t c = ((tid >> 6) & 1) * COL, cp = (tid >> 7) * both, k = (tid & 63) * 16;
        *reinterpret_cast<uint4*>(xp((ownL + nearp(pairL(RA, 0, g)) + c + k) ^ cp)) = z;
        if (k < 800) { *reinterpret_cast<uint4*>(xp((uPubC + c + k) ^ cp)) = z; *reinterpret_cast<uint4*>(xp((uPubE + c + k) ^ cp)) = z; }
        if ((tid & 31) < 20) *reinterpret_cast<uint4*>(xp(ownG + pairG((tid >> 5) & 1, 0, i) * 8192 + c + (tid >> 7) * COPY + (tid & 31) * 16)) = z;
    }
#define IDS() __syncwarp(); const uint32_t z0_ = lag<1>(sb), z_ = td + z0_; const uint32_t ln = z_ & 31, q8 = ln >> 2, t4 = z_ & 3, n96 = z_ - 96 * cc, n80 = min(n96, 79u); (void)q8; (void)t4; (void)n80; (void)ln

    auto vaddr = [&](uint32_t (&voff)[3]) {
        const uint32_t ln = td & 31;
        const uint32_t key3 = 3 * ((ln & 7) + 2 * (ln & 8) + ((ln >> 1) & 8));
#pragma unroll
        for (int T = 0; T < 3; T++) {
            const uint32_t u = 3 * wp + T, r = key3 + (u >> 3);
            voff[T] = r * 128 + (((u ^ r) & 7) << 4);
        }
    };
    auto values = [&](uint32_t (&vf)[8][3][4], float (&acc)[3][4], auto step, uint32_t ps, auto col, uint32_t par) {
        constexpr int CUT = col.value ? 8 : 6;
        const uint32_t ln = td & 31, q8 = ln >> 2, t4 = td & 3;
        uint4 p = lds128(ps + 16 * ln);
        float f0 = 0.f, f1 = 0.f, r3 = 0.f, o = 0.f;
        int M = 0;
#pragma unroll
        for (int s = 0; s < 8; s++) {
            if (s == 0 || s == CUT)
#pragma unroll
                for (int k = 0; k < 12; k++) acc[k / 4][k % 4] = 0.f;
            step(s);
            const bool m = s >= CUT || (q8 >> 1) == (s >> 1);
            const uint32_t b0 = m ? ((s & 1) ? p.z : p.x) : 0u, b1 = m ? ((s & 1) ? p.w : p.y) : 0u;
#pragma unroll
            for (int T = 0; T < 3; T++) mmaA(acc[T], vf[s][T], b0, b1);
            if (s == FSTEP) {
                const uint2 mp = lds64(ps + PS_MAX + 8 * t4);
                M = __reduce_max_sync(~0u, __float2int_ru(fmaxf(asf(mp.x), asf(mp.y))));
                f0 = ex2(asf(mp.x) - (float)M); f1 = ex2(asf(mp.y) - (float)M);
                float l[4] = {};
                mma16816(l, ONES, ONES, ONES, ONES, p.x, p.y); mma16816(l, ONES, ONES, ONES, ONES, p.z, p.w);
                r3 = fmaf(f0, l[0], f1 * l[1]);
            }
            if (s == CUT - 1) {
                if (CUT < 8) p = lds128(ps + 384 + 16 * (ln & 7));
                const float r0 = fmaf(f0, acc[0][0], f1 * acc[0][3]), r1 = fmaf(f0, acc[1][0], f1 * acc[1][3]), r2 = fmaf(f0, acc[2][0], f1 * acc[2][3]);
                const bool hi = t4 & 2, od = t4 & 1;
                const float u0 = (hi ? r2 : r0) + __shfl_xor_sync(~0u, hi ? r0 : r2, 2), u1 = (hi ? r3 : r1) + __shfl_xor_sync(~0u, hi ? r1 : r3, 2);
                o = (od ? u1 : u0) + __shfl_xor_sync(~0u, od ? u0 : u1, 1);
                if (ln == 3) o = asf(2 * (uint32_t)M);
                if (CUT < 8) { f0 = __shfl_sync(~0u, f0, 3); f1 = __shfl_sync(~0u, f1, 3); }
            }
        }
        CSTAMP(25);
        const uint32_t pubA = uPubA + col.value * COL + 32 * t4 + 4 * q8;
        if (CUT < 8 && t4 < 3) o = fmaf(f0, sel4(t4, acc[0][0], acc[1][0], acc[2][0], acc[2][0]), fmaf(f1, sel4(t4, acc[0][3], acc[1][3], acc[2][3], acc[2][3]), o));
        stp32_if(t4 < 3 || ((wp & 1) && q8 < 2), both, xp(pubA ^ COPY), xp(pubA), o, par);
    };

    uint32_t left[36] = {};
#pragma unroll 1
    for (int ch = 0; ch < 5; ch++) {
        const uint32_t par0 = (ch + 1) & 1, par1 = ch & 1;
        uint32_t voff[3], vf[8][3][4];
        float acc_[3][4];
        if (ch < 4) {
            td = pin(td);
            vaddr(voff);
            mbar_wait(sb + S_SCO, par1);
            if (ch == 0) mbar_wait(sb + S_WFULL + 80, 0);
            TST(0);
            auto ldw = [&](int s) {
                mbar_wait(sb + S_FV + 8 * s, par1);
#pragma unroll
                for (int T = 0; T < 3; T++) ldsm4t(vf[s][T], voff[T] + (sb + v_place(ch, s) * SLOT));
            };
            probs(bf_lo(lds16(sb + S_SC + 2 * td)), sb + S_PS, wp, td & 31);
            ldw(0); ldw(1); ldw(2);
            bar_main();
            arrive_if(td == 0, sb + S_RELR);
            values(vf, acc_, [&](int s) {
                if (s >= 3) ldw(s);
            }, sb + S_PS, std::integral_constant<int, 0>(), par0);
            TST(1);
            CSTAMP(5);
            if (ch > 0) mbar_wait(sb + S_OS1, par0);
        } else {
#pragma unroll
            for (int s = 0; s < 36; s++) vf[s / 12][(s / 4) % 3][s & 3] = left[s];
        }
        const bool has0 = ch < 4, has1 = ch > 0;
        const bool actc = wp < 6 && (cc ? has1 : has0);
        const uint32_t parc = cc ? par1 : par0;
        const uint32_t pub0 = has0 ? par0 : 0;
        uint32_t rr, pubB;
        {
            IDS();
            const uint32_t c = ch == 4;
            const uint32_t osa = pin(uOS + 96 * c + 4 * ln), oa = pin(uOS + 48 * (q8 & 2) + 24 * t4), ra = pin(sb + S_RED + 640 * wp + 320 * (t4 & 1) + 8 * q8);
            rr = pin(sb + S_RED + 320 * cc + 4 * n80); pubB = pin(uPubB + 4 * n80);
            hop_a<1>(xp(uPolA + c * COL + 8 * min(ln, 24u) + lag<DELAY_L>(sb, z0_)), pub0, osa, ln < 24, 5 * ch);
            TST(2);
            CSTAMP(6);
            float acc[5][4] = {};
            const uint2 b0 = lds64(oa), b1 = lds64(oa + 8), b2 = lds64(oa + 16);
#pragma unroll
            for (int m = 0; m < 5; m++) mmaA(acc[m], Wo[m][0], b0.x, b0.y);
#pragma unroll
            for (int m = 0; m < 5; m++) mmaA(acc[m], Wo[m][1], b1.x, b1.y);
#pragma unroll
            for (int m = 0; m < 5; m++) mmaA(acc[m], Wo[m][2], b2.x, b2.y);
#pragma unroll
            for (int m = 0; m < 5; m++) { stsf(ra + 64 * m, acc[m][0]); stsf(ra + 64 * m + 4, acc[m][2]); }
        }
        CSTAMP(7);
        uint32_t xr, fl, pubC, pubC2;
        auto prepC = [&](uint32_t ln) {
            const uint32_t q8 = ln >> 2, t4 = ln & 3;
            xr = pin(sb + S_XB + 48 * (ln & 15));
            pubC = pin(uPubC + (t4 & 1) * COL + 192 * (wp >> 1) + 64 * (wp & 1) + 8 * q8);
            pubC2 = pin(uPubC + (t4 & 1) * COL + ((t4 & 2) ? 192 * (wp >> 1) + 128 + 4 * (wp & 1) + 8 * q8 : 768 + 2 * ((q8 + 1) & 6)));
            fl = pin(((t4 & 1) ? par1 : pub0) | (t4 >= 2 || (wp == 7 && q8 < 4 && q8 != 2 - t4) ? 2 : 0));
        };
        auto stats = [&](uint32_t xa, const uint4& b, uint32_t b4) {
            float a0[4] = {}, a1[4] = {}, a2[4] = {};
            const uint4 p0 = lds128(xa), p1 = lds128(xa + 16);
            const uint2 p2 = lds64(xa + 32);
            mmaV(a0, p0, b.x, b.y); mmaV(a1, p1, b.z, b.w); mma8(a2, p2.x, p2.y, b4);
            return ((a0[0] + a0[3]) + (a1[0] + a1[3])) + (a2[0] + a2[3]);
        };
        auto give_ln = [&](uint32_t src0, uint32_t par, uint32_t dst, uint32_t ln, float& mean, float& den, auto also) {
            const char* src = xp(src0 + 768 + (ln & 1) * HALF);
            float sx, sq;
            int guard = 0;
            bool again;
            do {
                uint2 st[4];
#pragma unroll
                for (int s = 0; s < 4; s++) st[s] = ldp64(src + s * 1024);
                again = __any_sync(~0u, ((chk4(st, par) | also()) & 1) != 0);
                sx = (asf(st[0].x) + asf(st[1].x)) + (asf(st[2].x) + asf(st[3].x)); sq = (asf(st[0].y) + asf(st[1].y)) + (asf(st[2].y) + asf(st[3].y));
                sx += __shfl_xor_sync(~0u, sx, 1); sq += __shfl_xor_sync(~0u, sq, 1);
            } while (again & (++guard < SPIN_LIMIT));
            ln_stats(sx, sq, mean, den);
            stsvol64(dst, __byte_perm(__float_as_uint(den), __float_as_uint(mean), 0x7632), (__float_as_uint(rcp(den)) & ~7u) | (ch + 1));
        };
        auto take_ln = [&](uint2& c, uint32_t a) { int k = 0; do c = ldsvol64(a); while (__any_sync(~0u, (c.y & 7) != ch + 1) & (++k < SPIN_FAST)); };
        {
            auto gate_up = [&](auto with_stats) {
                bar_main();
                TST(3);
                CSTAMP(11);
                const uint4 b = lds128(xr);
                uint32_t b4 = lds32(xr + 16);
                float acc[3][4] = {};
                if (with_stats.value) {
                    stp32_if(fl > 1 && !(td & 2), both, xp(pubC2 ^ COPY), xp(pubC2), stats(xr + (S_XA - S_XB), b, b4), fl & 1);
                    __syncwarp();
                    b4 = lds32(xr + 16);
                }
                mul80(acc, Wgu, b, b4);
                stp64_if(!(td & 2), both, xp(pubC ^ COPY), xp(pubC), tagw(acc[0][0] + acc[0][3], fl & 1), tagw(acc[1][0] + acc[1][3], fl & 1));
                stp32_if(td & 2, both, xp(pubC2 ^ COPY), xp(pubC2), acc[2][0] + acc[2][3], fl & 1);
            };
            if (wp == 7) {
                bar_main();
                IDS();
                prepC(ln);
                sts32(sb + S_ZERO + 4, or3(pubC, pubC2, fl));
                gate_up(std::true_type());
            } else {
                if (actc) {
                    bar_main();
                    CSTAMP(8);
                    uint32_t r[8];
#pragma unroll
                    for (int s = 0; s < 8; s++) r[s] = lds32(rr + 640 * s);
                    stp32_if(true, xp(pubB), sum8(r), parc);
                    CSTAMP(9);
                    IDS();
                    prepC(ln);
                    const uint32_t n4 = 4 * n80;
                    const uint32_t xas = pin(sb + S_XA + 192 + 192 * cc + a_pos(n80)), xbs = pin(sb + S_XB + 384 * cc + b_pos<40>(n80));
                    const float x0 = cc ? ldsf(sb + S_XCAR + n4) : bf_lo(lds16(sb + S_X0 + 160 * (ch & 3) + n4 / 2));
                    gather16(xp(uPolB + n4 + lag<DELAY_G>(sb, z0_)), parc, 5 * ch + 1, [&](float y, uint32_t) {
                        const uint32_t x = pack2(x0 + bfr(y), 0.f);
                        sts16(xbs, x);
                        sts16(xas, x);
                        return 0u;
                    });
                    CSTAMP(10);
                } else {
                    bar_main();
                    IDS();
                    prepC(ln);
                }
                gate_up(std::false_type());
            }
        }
        CSTAMP(12);
        float mean = 0.f, den = 1.f;
        {
            IDS();
            const uint32_t wh = pin((((ln & 7) + 48 * ((ln >> 3) & 1) + 8 * (ln >> 4)) * 160 + (wp < 7 ? 16 * wp : 128)) | ((384 * cc + b_pos<48>(n96)) << 16));
            const uint32_t pubD = pin(uPubD + (t4 & 1) * COL + 16 * (t4 & 2) + 4 * q8 + (fl & 1)), ha = xr + (S_HS - S_XB);
            auto down = [&](const uint32_t (&W)[3][4], const uint4& h0, const uint2& h1) {
                float a0[4] = {}, a1[4] = {}, a2[4] = {};
                mmaA(a0, W[0], h0.x, h0.y); mmaA(a1, W[1], h0.z, h0.w); mmaA(a2, W[2], h1.x, h1.y);
                return ((a0[0] + a0[3]) + (a1[0] + a1[3])) + (a2[0] + a2[3]);
            };
            if (wp < 6) {
                uint32_t Wd[3][4];
                auto ldd = [&](uint32_t z) {
#pragma unroll
                    for (int s = 0; s < 3; s++) ldsm4t(Wd[s], ((wh ^ z) & 0xffff) + (sb + S_WD + s * 2560));
                };
                ldd(0);
                if (actc) {
                    const char* srcv = xp(uPolC + lag<DELAY_C>(sb, z0_) + 8 * n96);
                    const uint2 cs = lds64(sb + S_CSGU + 8 * n96);
                    float gt, up;
                    int guard = 0;
                    while (true) {
                        uint2 v[8];
#pragma unroll
                        for (int s = 0; s < 8; s++) v[s] = ldp64(srcv + (s >> 2) * HALF + (s & 3) * 1024);
                        uint2 c = ldsvol64(sb + S_LN + 8 * cc + ((v[0].x ^ parc) & 1) * 32);
                        const bool stale = __any_sync(~0u, ((chk8(v, parc) | chk8y(v, parc)) & 1) != 0), late = __any_sync(~0u, (c.y & 7) != ch + 1);
                        const float pg = sum8x(v), pu = sum8y(v);
                        auto norm = [&] {
                            mean = bf_hi(c.x); den = bf_lo(c.x);
                            gt = bfr(fmaf(-mean, asf(cs.x), pg) * asf(c.y)); up = fmaf(-mean, asf(cs.y), pu) * asf(c.y);
                            keep(gt); keep(up);
                        };
                        norm();
                        if (!((stale | late) & (++guard < SPIN_LIMIT))) break;
                        if (!stale) { take_ln(c, sb + S_LN + 8 * cc); norm(); break; }
                    }
                    CSTAMP(13);
                    SWEEPS(5 * ch + 2, guard - 1);
                    const uint32_t h = pack2(bfr(gt * sigmoidf_(gt)) * bfr(up), 0.f);
                    sts16((wh >> 16) + (sb + S_HS), h);
                    CSTAMP(14);
                    if (ch == 3) CSTAMP(0);
                }
                bar_main();
                TST(4);
                CSTAMP(15);
                const uint4 h0 = lds128(ha);
                const uint2 h1 = lds64(ha + 16);
                stp32_if(!(td & 2), xp(pubD & ~1u), down(Wd, h0, h1), pubD & 1);
            } else {
                uint32_t v = 0;
                const uint32_t col = wp == 7 || !has0;
                const bool serve = wp == 6 || (has0 && has1);
                if (serve) {
                    const uint32_t par = col ? par1 : par0;
                    const char* src = xp(uPolC + col * COL + 776 + (td & 4) * (HALF / 4) + (td & 3) * 1024);
                    give_ln(uPolC + col * COL, par, sb + S_LN + 8 * col, td, mean, den, [&] { v = ldp32(src); return v ^ par; });
                }
                stsvol(sb + S_GATE, ch + 1);
                uint32_t Wd[2][3][4];
#pragma unroll
                for (int s = 0; s < 6; s++) ldsm4t(Wd[s / 3][s % 3], (wh & 0xffff) + (sb + S_WD + (s / 3) * 16 + (s % 3) * 2560));
                bar_main();
                const uint4 h0 = lds128(ha);
                const uint2 h1 = lds64(ha + 16);
                const float d0 = down(Wd[0], h0, h1), d1 = down(Wd[1], h0, h1);
                stp32_if(true, xp(pubD & ~1u), (td & 2) ? d1 : d0, pubD & 1);
                if (serve) {
                    float xw = asf(v);
                    xw += __shfl_xor_sync(~0u, xw, 1); xw += __shfl_xor_sync(~0u, xw, 2); xw += __shfl_xor_sync(~0u, xw, 4);
                    const float r = bfr(fmaf(-mean, ldsf(sb + S_SWR), xw) * rcp(den));
                    sts32(sb + S_STAT + 4 * col, __float_as_uint(bfr(sigmoidf_(r))) | (ch + 1));
                }
            }
        }
        CSTAMP(16);
        {
            IDS();
            const uint32_t pubE = pin(uPubE + (t4 < 3 ? (wp >> 2) * COL + 192 * (wp & 3) + 64 * t4 + 8 * q8 : (q8 >> 2) * COL + 768 + 4 * (q8 & 1)));
            xr = pin(sb + S_XB + 48 * (ln & 7));
            uint32_t x2 = 0;
            auto hop_d = [&](auto col) {
                const uint32_t xbs = pin(sb + S_XB + 384 * col.value + b_pos<40>(n80)), xas = col.value ? 0 : pin(sb + S_XA + 192 + a_pos(n80));
                const float x1 = bf_lo(lds16(xbs));
                const float lnx = __uint_as_float(pin(__float_as_uint(bfr(__fdiv_rn(bfr(x1 - mean), den)))));
                gather16(xp(uPolD + 4 * n80 + lag<DELAY_D>(sb, z0_)), col.value ? par1 : par0, 5 * ch + 3, [&](float y, uint32_t z) {
                    const uint32_t gate = ldsvol(sb + S_STAT + 4 * col.value + z);
                    x2 = pack2(x1 + bfr(lnx + bfr(bfr(y) * bf_hi(gate))), 0.f);
                    if (col.value) keep(x2); else { sts16(xbs, x2); sts16(xas, x2); }
                    return (uint32_t)((gate & 7) != ch + 1);
                });
                CSTAMP(17);
            };
            auto qproj = [&](auto with_stats) {
                bar_main();
                TST(5);
                CSTAMP(19);
                const uint32_t t4 = td & 3;
                const uint4 b = lds128(xr);
                uint32_t b4 = lds32(xr + 16);
                float acc[6][4] = {};
                if (with_stats.value) {
                    stp32_if((td & 11) == 3, both, xp(pubE ^ COPY), xp(pubE), stats(xr + (S_XA - S_XB), b, b4), par0);
                    __syncwarp();
                    b4 = lds32(xr + 16);
                }
                mul80(acc, Wq, b, b4);
                const float v0 = sel4(t4, acc[0][0] + acc[0][3], acc[2][0] + acc[2][3], acc[4][0] + acc[4][3], acc[4][0] + acc[4][3]);
                const float v1 = sel4(t4, acc[1][0] + acc[1][3], acc[3][0] + acc[3][3], acc[5][0] + acc[5][3], acc[5][0] + acc[5][3]);
                stp64_if(t4 < 3, both, xp(pubE ^ COPY), xp(pubE), tagw(v0, par0), tagw(v1, par0));
            };
            if (wp == 7) {
                if (!has0) break;
                qproj(std::true_type());
            } else {
                if (actc && !cc) hop_d(std::integral_constant<int, 0>());
                else {
                    if (actc && g == 0) {
                        const uint32_t po = pin(1280 * (ch - 1) + 160 * i + 2 * n80);
                        hop_d(std::integral_constant<int, 1>());
                        *reinterpret_cast<unsigned short*>(reinterpret_cast<char*>(P.out) + po) = (unsigned short)x2;
                    }
                    if (!has0) break;
                }
                qproj(std::false_type());
                sts32_if(td < 80, sb + S_XCAR + 4 * td, x2 << 16);
            }
        }
        CSTAMP(20);
        if (wp == 6) give_ln(uPolE, par0, sb + S_LN + 16, td, mean, den, [] { return 0u; });
        auto pass2 = [&](auto d0, auto d1, auto d2) {
            constexpr int D0 = d0.value, D1 = d1.value, D = D0 + D1 + d2.value;
            IDS();
            const uint32_t ua = sb + k_place(ch, wp & 6) * SLOT + (wp & 1) * UNIT, k0 = k_off(ln);
            uint32_t kf[12][2][4];
            auto ldk = [&](int s) { const uint32_t a = (k0 ^ (32 * (s / 3))) + (ua + 1024 * (s % 3)); ldsm4(kf[s][0], a); ldsm4(kf[s][1], a + SLOT); };
            auto ldv1 = [&](int k) { ldsm4t(vf[k / 3][k % 3], voff[k % 3] + (sb + v_place(ch, k / 3) * SLOT)); };
            auto ldv = [&](int s) { ldv1(3 * s); ldv1(3 * s + 1); ldv1(3 * s + 2); };
            constexpr uint32_t LATE = LAST_LATE;
            constexpr uint64_t EARLY_LIST = bit_list(~LATE), LATE_LIST = bit_list(LATE);
            auto early = [&](int k) {
                if (D1 == 0) ldk(k);
                else if (k < 3) { ldv1(9 + 2 * k); ldv1(10 + 2 * k); }
                else ldk((EARLY_LIST >> (4 * (k - 3))) & 15);
            };
            uint32_t v[8] = {}, qsa = 0;
            const char* srcv = xp(uPolE + lag<(D1 > 0 ? 0 : DELAY_E)>(sb, z0_) + 4 * td);
            auto look = [&] {
#pragma unroll
                for (int s = 0; s < 8; s++) v[s] = ldp32(srcv + (s >> 2) * HALF + (s & 3) * 1024);
            };
            if (D1 > 0) vaddr(voff);
            if (!(mbar_try(sb + S_FK + 8 * (wp & 6), par1) & mbar_try(sb + S_FK + 8 * (wp | 1), par1))) { mbar_wait(sb + S_FK + 8 * (wp & 6), par1); mbar_wait(sb + S_FK + 8 * (wp | 1), par1); }
#pragma unroll
            for (int s = 0; s < D0; s++) early(s);
            if (wp < 6) { look(); qsa = pin(sb + S_QS + 384 * ch + q_pos(z_)); }
#pragma unroll
            for (int s = D0; s < D0 + D1; s++) early(s);
            if (wp < 6) {
                const float cs = ldsf(sb + S_CSQ + 4 * td);
                int guard = 0;
                while (true) {
                    uint2 c = ldsvol64(sb + S_LN + 16 + ((v[0] ^ par0) & 1) * 32);
                    const bool stale = __any_sync(~0u, (chk8(v, par0) & 1) != 0), late = __any_sync(~0u, (c.y & 7) != ch + 1);
                    const float qs = sum8(v);
                    auto norm = [&] {
                        const uint32_t q = pack2(fmaf(-bf_hi(c.x), cs, qs) * asf(c.y), 0.f);
                        sts16(qsa, q);
                    };
                    norm();
                    if (!((stale | late) & (++guard < SPIN_LIMIT))) break;
                    if (!stale) { take_ln(c, sb + S_LN + 16); norm(); break; }
                    look();
                }
                SWEEPS(5 * ch + 4, guard - 1);
                CSTAMP(22);
            }
#pragma unroll
            for (int s = D0 + D1; s < D; s++) early(s);
            CSTAMP(21);
            bar_main();
            TST(6);
            CSTAMP(1);
            uint2 q = lds64(sb + S_QS + 384 * ch + 8 * ln);
            float acc[2][4] = {};
            constexpr int V0 = 13 - D, NV = D1 > 0 ? 2 : (2 * (D - 1)) / 3;
            static_assert(D1 == 0 || D - 3 + __builtin_popcount(LATE) == 12, "plan");
#pragma unroll
            for (int s = 0; s < 12; s++) {
                const bool m = q8 == (s & 7);
                const uint32_t b0 = m ? q.x : 0u, b1 = m ? q.y : 0u;
                if (s == 7) q = lds64(sb + S_QS + 384 * ch + 8 * ln + 256);
                mmaA(acc[0], kf[s][0], b0, b1);
                mmaA(acc[1], kf[s][1], b0, b1);
                if (D1 > 0) {
                    if (s >= 1 && s <= __builtin_popcount(LATE)) ldk((LATE_LIST >> (4 * (s - 1))) & 15);
                } else {
                    if (s >= 1 && s + D - 1 < 12) ldk(s + D - 1);
                    if (s >= 1 && s + D - 1 == 11) { __syncwarp(); arrive_if(ln == 0, sb + S_RELK); }
                    if (s == V0) vaddr(voff);
                    if (s >= V0 && 2 * (s - V0) < 3 * NV) ldv1(9 + 2 * (s - V0));
                    if (s >= V0 && 2 * (s - V0) + 1 < 3 * NV) ldv1(10 + 2 * (s - V0));
                }
            }
            CSTAMP(24);
            {
                const float v0 = acc[0][0] + acc[0][1], v1 = acc[0][2] + acc[0][3], v2 = acc[1][0] + acc[1][1], v3 = acc[1][2] + acc[1][3];
                const bool hi = t4 & 2, od = t4 & 1;
                const float u0 = (hi ? v2 : v0) + __shfl_xor_sync(~0u, hi ? v0 : v2, 2), u1 = (hi ? v3 : v1) + __shfl_xor_sync(~0u, hi ? v1 : v3, 2);
                const float s = (od ? u1 : u0) + __shfl_xor_sync(~0u, od ? u0 : u1, 1);
                CSTAMP(2);
                probs(scaled(s), sb + S_PS + PS_PASS, wp, ln);
                CSTAMP(3);
            }
            bar_main();
            TST(10);
            CSTAMP(4);
            if (D1 > 0) values(vf, acc_, [&](int s) { if (s < 3) ldv(s + 5); }, sb + S_PS + PS_PASS, std::integral_constant<int, 1>(), par0);
            else values(vf, acc_, [&](int s) { if (s >= (NV > 1 ? 2 : 1) && s + NV + (NV > 1 ? 1 : 2) < 8) ldv(s + NV + (NV > 1 ? 1 : 2)); }, sb + S_PS + PS_PASS, std::integral_constant<int, 1>(), par0);
            arrive_if(ln == 0, sb + S_RELV);
        };
        if (ch == 3) {
            pass2(std::integral_constant<int, LAST0>(), std::integral_constant<int, LAST1>(), std::integral_constant<int, LAST2>());
#pragma unroll
            for (int m = 0; m < 48; m++) Wq[m / 8].a[(m / 4) % 2][m % 4] = vf[3 + m / 12][(m / 4) % 3][m % 4];
#pragma unroll
            for (int m = 0; m < 12; m++) Wq[m / 2].c[m % 2] = vf[7][m / 4][m % 4];
#pragma unroll
            for (int m = 0; m < 36; m++) left[m] = m < 12 ? __float_as_uint(acc_[m / 4][m % 4]) : vf[m / 12][(m / 4) % 3][m % 4];
        } else {
            pass2(std::integral_constant<int, KPRE>(), std::integral_constant<int, 0>(), std::integral_constant<int, KPRE2>());
#pragma unroll
            for (int m = 0; m < 36; m++) left[m] = m < 12 ? __float_as_uint(acc_[m / 4][m % 4]) : vf[4 + m / 12][(m / 4) % 3][m % 4];
        }
        TST(11);
        CSTAMP(23);
    }
    sts32_if(td == 255, sb + S_GATE, 6);
    TSTAMP(3);
}

typedef CUresult (*EncodeFn)(CUtensorMap*, CUtensorMapDataType, cuuint32_t, void*, const cuuint64_t*, const cuuint64_t*, const cuuint32_t*,
                             const cuuint32_t*, CUtensorMapInterleave, CUtensorMapSwizzle, CUtensorMapL2promotion, CUtensorMapFloatOOBfill);

void make_map(EncodeFn enc, CUtensorMap* m, const void* base, uint64_t cols, uint64_t rows, uint32_t box_cols, uint32_t box_rows, bool swizzle) {
    cuuint64_t dims[2] = {cols, rows};
    cuuint64_t strides[1] = {cols * 2};
    cuuint32_t box[2] = {box_cols, box_rows};
    cuuint32_t es[2] = {1, 1};
    enc(m, CU_TENSOR_MAP_DATA_TYPE_BFLOAT16, 2, const_cast<void*>(base), dims, strides, box, es, CU_TENSOR_MAP_INTERLEAVE_NONE,
        swizzle ? CU_TENSOR_MAP_SWIZZLE_128B : CU_TENSOR_MAP_SWIZZLE_NONE, CU_TENSOR_MAP_L2_PROMOTION_NONE, CU_TENSOR_MAP_FLOAT_OOB_FILL_NONE);
}

}

extern "C" void kernel_launch(void* const* d_in, const int* in_sizes, int n_in, void* d_out, int out_size) {
    (void)in_sizes; (void)n_in; (void)out_size;
    static EncodeFn enc = nullptr;
    if (!enc) {
        void* f = nullptr;
        cudaDriverEntryPointQueryResult q;
        cudaGetDriverEntryPoint("cuTensorMapEncodeTiled", &f, cudaEnableDefault, &q);
        enc = (EncodeFn)f;
        cudaFuncSetAttribute(fused_kernel, cudaFuncAttributeMaxDynamicSharedMemorySize, SMEM_BYTES);
    }
    Params P;
    P.x = (const __nv_bfloat16*)d_in[0]; P.k = (const __nv_bfloat16*)d_in[1]; P.v = (const __nv_bfloat16*)d_in[2];
    P.wr = (const __nv_bfloat16*)d_in[6]; P.wq = (const __nv_bfloat16*)d_in[3];
    P.out = (__nv_bfloat16*)d_out;
    Maps M;
    {
        cuuint64_t dims[4] = {64, 8, 3, (cuuint64_t)KV_BATCH_KEYS / 2}, strides[3] = {384, 128, 3072};
        cuuint32_t box[4] = {64, 8, 3, 2}, es[4] = {1, 1, 1, 1};
        enc(&M.k, CU_TENSOR_MAP_DATA_TYPE_BFLOAT16, 4, d_in[1], dims, strides, box, es, CU_TENSOR_MAP_INTERLEAVE_NONE, CU_TENSOR_MAP_SWIZZLE_128B,
            CU_TENSOR_MAP_L2_PROMOTION_NONE, CU_TENSOR_MAP_FLOAT_OOB_FILL_NONE);
    }
    make_map(enc, &M.v, P.v, 64, (uint64_t)12 * KV_BATCH_KEYS, 64, 96, true);
    make_map(enc, &M.vu, P.v, 64, (uint64_t)12 * KV_BATCH_KEYS, 64, 48, true);
    make_map(enc, &M.wq, d_in[3], 6144, 640, 192, 40, false);
    make_map(enc, &M.wo, d_in[4], 640, 6144, 80, 96, false);
    make_map(enc, &M.wg, d_in[7], 1536, 640, 96, 80, false);
    make_map(enc, &M.wu, d_in[8], 1536, 640, 96, 80, false);
    make_map(enc, &M.wd, d_in[9], 640, 1536, 80, 96, false);
    fused_kernel<<<NCTA, NTHR, SMEM_BYTES, cudaStreamPerThread>>>(P, M);
}
```

```cpp
#include <cuda_runtime.h>
#include <cuda.h>
#include <cuda_bf16.h>
#include <stdint.h>
#include <type_traits>

namespace {

constexpr int NCTA = 128;
constexpr int NTHR = 384;
constexpr int UNIT = 6144;
constexpr int SLOT = 12288;
#define TAU 3880
#define TAUW 3700
#define TAU0 3780
#define ILV 4
#define XB 900
#define FORCE_BOTH 0
#define TMIN 2400
#define SLACK 6000
#define SLACK0 1000
#define LEADW 3500
#define WIN_W 3
#define WIN_S 4
#define WIN_U 10
#define VPF 4
#define KRE_TAU 2600
#define RFR_TAU 22400
#define HOP1_NS 200
#define KPRE 2
#define KPRE2 2
#define LAST0 4
#define LAST1 4
#define LAST2 2
#define LAST_LATE 0xaa8
#define FSTEP 4
#define DELAY_L 2
#define DELAY_G 2
#define DELAY_C 3
#define DELAY_D 0
#define DELAY_E 1
#define REG_LO "40"
#define REG_HI "232"
#define SPIN_LOG 17
constexpr int SPIN_LIMIT = 1 << SPIN_LOG, SPIN_FAST = SPIN_LIMIT << 4;

__host__ __device__ constexpr uint32_t pairL(uint32_t region, uint32_t c, uint32_t g) { return (g & 1) | ((g >> 1) << 2) | (c << 5) | (region << 6); }
__host__ __device__ constexpr uint32_t pairG(uint32_t d, uint32_t c, uint32_t i) { return (i & 1) | ((i >> 1) << 2) | (d << 4) | (c << 5) | (3u << 6); }
constexpr uint32_t RA = 0, RC = 1, RE = 2, HALF = 16384, COPY = 4096, PMASK = 0x59;
constexpr uint32_t XS = 0;
constexpr uint32_t XS2 = XS + 128 * 7680;
constexpr uint32_t XSEND = XS2 + 128 * 768;
__device__ uint4 g_s[XSEND / 16];
__device__ uint4 g_x[(4u << 20) / 16];
#define SWEEPS(k, n) do {} while (0)

constexpr uint32_t S_WD = 16 * SLOT;
constexpr uint32_t S_DUMMY = S_WD + 15360;
constexpr uint32_t S_BAR = S_DUMMY + 4096;
constexpr uint32_t S_FV = S_BAR, S_FK = S_FV + 64, S_RING = S_FK + 64, S_DBAR = S_RING + 48, S_WFULL = S_DBAR + 32, S_QRDY = S_WFULL + 88;
constexpr uint32_t S_RELK = S_QRDY + 8, S_RELV = S_RELK + 8, S_RELR = S_RELV + 8, S_RELW = S_RELR + 8, S_SCO = S_RELW + 24;
constexpr uint32_t S_OS1 = S_SCO + 8;
constexpr uint32_t S_ZERO = S_OS1 + 8;
constexpr uint32_t S_KF = S_ZERO + 8;
constexpr uint32_t S_TOK = S_KF + 8;
constexpr uint32_t S_SIDE = S_TOK + 80, S_GATE = S_SIDE + 4;
constexpr uint32_t S_STAT = S_GATE + 12, S_SWR = S_STAT + 16;
constexpr uint32_t S_LN = S_STAT + 32;
constexpr uint32_t S_XCAR = S_LN + 64;
constexpr uint32_t S_CSQ = S_XCAR + 320;
constexpr uint32_t S_CSGU = S_CSQ + 768;
constexpr uint32_t S_RED = S_CSGU + 768;
constexpr uint32_t S_L0 = S_RED;
constexpr uint32_t S_OS = S_RED + 5120;
constexpr uint32_t S_PS = S_OS + 1536;
constexpr uint32_t PS_MAX = 512, PS_PASS = 544;
constexpr uint32_t S_QS = S_PS + 2 * PS_PASS;
constexpr uint32_t S_XB = S_QS + 1536;
constexpr uint32_t S_XA = S_XB + 768;
constexpr uint32_t S_HS = S_XA + 768;
constexpr uint32_t S_X0 = S_HS + 768;
constexpr uint32_t S_SC = S_X0 + 640;
constexpr uint32_t S_TM = S_SC + 512;
constexpr int SMEM_BYTES = S_TM + 256;
static_assert(SMEM_BYTES <= 232448 && S_STAT % 16 == 0 && S_RED % 16 == 0 && S_XB % 16 == 0 && S_HS % 16 == 0 && S_PS % 16 == 0 && S_QS % 16 == 0, "smem");
static_assert(S_SCO == S_BAR + 44 * 8 && S_RELK == S_BAR + 38 * 8, "barriers");
constexpr uint32_t ST_WQ = 3 * SLOT, ST_WG = 8 * SLOT, ST_WO = 11 * SLOT;

__device__ __forceinline__ uint32_t smem_u32(const void* p) { return (uint32_t)__cvta_generic_to_shared(p); }
__device__ __forceinline__ void mbar_arrive(uint32_t bar) { asm volatile("mbarrier.arrive.shared::cta.b64 _, [%0];" :: "r"(bar) : "memory"); }
__device__ __forceinline__ bool mbar_try(uint32_t bar, uint32_t parity) {
    uint32_t ok;
    asm volatile("{\n .reg .pred p;\n mbarrier.try_wait.parity.shared::cta.b64 p, [%1], %2;\n selp.u32 %0, 1, 0, p;\n}" : "=r"(ok) : "r"(bar), "r"(parity) : "memory");
    return ok != 0;
}
__device__ __forceinline__ bool mbar_test(uint32_t bar, uint32_t parity) {
    uint32_t ok;
    asm volatile("{\n .reg .pred p;\n mbarrier.test_wait.parity.shared::cta.b64 p, [%1], %2;\n selp.u32 %0, 1, 0, p;\n}" : "=r"(ok) : "r"(bar), "r"(parity) : "memory");
    return ok != 0;
}
__device__ __forceinline__ void mbar_wait(uint32_t bar, uint32_t parity) {
    int n = 0;
    while (!mbar_try(bar, parity) && ++n < SPIN_LIMIT) {}
}
__device__ __forceinline__ uint32_t gtime32() { uint32_t t; asm volatile("mov.u32 %0, %globaltimer_lo;" : "=r"(t)); return t; }
__device__ __forceinline__ void bar_main() { asm volatile("bar.sync 1, 256;" ::: "memory"); }

__device__ __forceinline__ void mma16816(float (&c)[4], uint32_t a0, uint32_t a1, uint32_t a2, uint32_t a3, uint32_t b0, uint32_t b1) {
    asm("mma.sync.aligned.m16n8k16.row.col.f32.bf16.bf16.f32 {%0,%1,%2,%3}, {%4,%5,%6,%7}, {%8,%9}, {%0,%1,%2,%3};"
        : "+f"(c[0]), "+f"(c[1]), "+f"(c[2]), "+f"(c[3]) : "r"(a0), "r"(a1), "r"(a2), "r"(a3), "r"(b0), "r"(b1));
}
__device__ __forceinline__ void mmaA(float (&c)[4], const uint32_t (&a)[4], uint32_t b0, uint32_t b1) { mma16816(c, a[0], a[1], a[2], a[3], b0, b1); }
__device__ __forceinline__ void mma8(float (&c)[4], uint32_t a0, uint32_t a1, uint32_t b0) {
    asm("mma.sync.aligned.m16n8k8.row.col.f32.bf16.bf16.f32 {%0,%1,%2,%3}, {%4,%5}, {%6}, {%0,%1,%2,%3};"
        : "+f"(c[0]), "+f"(c[1]), "+f"(c[2]), "+f"(c[3]) : "r"(a0), "r"(a1), "r"(b0));
}
struct W80 { uint32_t a[2][4], c[2]; };
template <int N> __device__ __forceinline__ void mul80(float (&acc)[N][4], const W80 (&W)[N], const uint4& b, uint32_t b4) {
#pragma unroll
    for (int m = 0; m < N; m++) mmaA(acc[m], W[m].a[0], b.x, b.y);
#pragma unroll
    for (int m = 0; m < N; m++) mmaA(acc[m], W[m].a[1], b.z, b.w);
#pragma unroll
    for (int m = 0; m < N; m++) mma8(acc[m], W[m].c[0], W[m].c[1], b4);
}
__device__ __forceinline__ void ldsm2t(uint32_t (&r)[2], uint32_t addr) {
    asm volatile("ldmatrix.sync.aligned.m8n8.x2.trans.shared.b16 {%0,%1}, [%2];" : "=r"(r[0]), "=r"(r[1]) : "r"(addr) : "memory");
}
__device__ __forceinline__ void mmaV(float (&c)[4], const uint4& a, uint32_t b0, uint32_t b1) { mma16816(c, a.x, a.y, a.z, a.w, b0, b1); }
__device__ __forceinline__ void ldsm4(uint32_t (&r)[4], uint32_t addr) {
    asm volatile("ldmatrix.sync.aligned.m8n8.x4.shared.b16 {%0,%1,%2,%3}, [%4];" : "=r"(r[0]), "=r"(r[1]), "=r"(r[2]), "=r"(r[3]) : "r"(addr) : "memory");
}
__device__ __forceinline__ void ldsm4t(uint32_t (&r)[4], uint32_t addr) {
    asm volatile("ldmatrix.sync.aligned.m8n8.x4.trans.shared.b16 {%0,%1,%2,%3}, [%4];" : "=r"(r[0]), "=r"(r[1]), "=r"(r[2]), "=r"(r[3]) : "r"(addr) : "memory");
}
__device__ __forceinline__ uint32_t lds16(uint32_t a) { uint16_t v; asm volatile("ld.shared.u16 %0, [%1];" : "=h"(v) : "r"(a) : "memory"); return v; }
__device__ __forceinline__ uint32_t lds32(uint32_t a) { uint32_t v; asm volatile("ld.shared.u32 %0, [%1];" : "=r"(v) : "r"(a) : "memory"); return v; }
__device__ __forceinline__ float ldsf(uint32_t a) { return __uint_as_float(lds32(a)); }
__device__ __forceinline__ uint2 lds64(uint32_t a) { uint2 v; asm volatile("ld.shared.v2.u32 {%0,%1}, [%2];" : "=r"(v.x), "=r"(v.y) : "r"(a) : "memory"); return v; }
__device__ __forceinline__ uint4 lds128(uint32_t a) { uint4 v; asm volatile("ld.shared.v4.u32 {%0,%1,%2,%3}, [%4];" : "=r"(v.x), "=r"(v.y), "=r"(v.z), "=r"(v.w) : "r"(a) : "memory"); return v; }
__device__ __forceinline__ int ldsvol(uint32_t a) { int v; asm volatile("ld.volatile.shared.u32 %0, [%1];" : "=r"(v) : "r"(a) : "memory"); return v; }
__device__ __forceinline__ uint2 ldsvol64(uint32_t a) { uint2 v; asm volatile("{\n .reg .b64 d;\n ld.volatile.shared.b64 d, [%2];\n mov.b64 {%0,%1}, d;\n}" : "=r"(v.x), "=r"(v.y) : "r"(a) : "memory"); return v; }
__device__ __forceinline__ void stsvol64(uint32_t a, uint32_t x, uint32_t y) { asm volatile("{\n .reg .b64 d;\n mov.b64 d, {%1,%2};\n st.volatile.shared.b64 [%0], d;\n}" :: "r"(a), "r"(x), "r"(y) : "memory"); }
__device__ __forceinline__ void stsvol(uint32_t a, int v) { asm volatile("st.volatile.shared.u32 [%0], %1;" :: "r"(a), "r"(v) : "memory"); }
__device__ __forceinline__ void sts_hi16(uint32_t a, float v) { asm volatile("{\n .reg .b16 lo, hi;\n mov.b32 {lo, hi}, %1;\n st.shared.u16 [%0], hi;\n}" :: "r"(a), "r"(__float_as_uint(v)) : "memory"); }
__device__ __forceinline__ void sts16(uint32_t a, uint32_t v) { asm volatile("st.shared.u16 [%0], %1;" :: "r"(a), "r"(v) : "memory"); }
__device__ __forceinline__ void sts32(uint32_t a, uint32_t v) { asm volatile("st.shared.u32 [%0], %1;" :: "r"(a), "r"(v) : "memory"); }
__device__ __forceinline__ void stsf(uint32_t a, float v) { sts32(a, __float_as_uint(v)); }
__device__ __forceinline__ void sts64(uint32_t a, uint32_t x, uint32_t y) { asm volatile("st.shared.v2.u32 [%0], {%1,%2};" :: "r"(a), "r"(x), "r"(y) : "memory"); }

__device__ __forceinline__ void sts32_if(bool p, uint32_t a, uint32_t v) {
    asm volatile("{\n .reg .pred p;\n setp.ne.u32 p, %2, 0;\n @p st.shared.u32 [%0], %1;\n}" :: "r"(a), "r"(v), "r"((uint32_t)p) : "memory");
}
__device__ __forceinline__ void arrive_if(bool p, uint32_t bar) {
    asm volatile("{\n .reg .pred p;\n setp.ne.u32 p, %1, 0;\n @p mbarrier.arrive.shared::cta.b64 _, [%0];\n}" :: "r"(bar), "r"((uint32_t)p) : "memory");
}
__device__ __forceinline__ void keep(uint32_t& v) { asm volatile("" : "+r"(v)); }
__device__ __forceinline__ void keep(float& v) { asm volatile("" : "+f"(v)); }

__device__ __forceinline__ uint32_t ldp32(const char* p) { uint32_t v; asm volatile("ld.relaxed.gpu.global.u32 %0, [%1];" : "=r"(v) : "l"(p) : "memory"); return v; }
__device__ __forceinline__ uint2 ldp64(const char* p) {
    uint2 v; asm volatile("{\n .reg .b64 d;\n ld.relaxed.gpu.global.b64 d, [%2];\n mov.b64 {%0,%1}, d;\n}" : "=r"(v.x), "=r"(v.y) : "l"(p) : "memory"); return v;
}
__device__ __forceinline__ uint32_t tagw(float f, uint32_t par) { return (__float_as_uint(f) & ~1u) | par; }
__device__ __forceinline__ void stp32(char* p, float a, uint32_t par) { asm volatile("st.relaxed.gpu.global.u32 [%0], %1;" :: "l"(p), "r"(tagw(a, par)) : "memory"); }
__device__ __forceinline__ void stp64(char* p, float a, float b, uint32_t par) {
    asm volatile("{\n .reg .b64 d;\n mov.b64 d, {%1,%2};\n st.relaxed.gpu.global.b64 [%0], d;\n}" :: "l"(p), "r"(tagw(a, par)), "r"(tagw(b, par)) : "memory");
}
__device__ __forceinline__ void stp32_if(bool p, char* d, float a, uint32_t par) {
    asm volatile("{\n .reg .pred p;\n setp.ne.u32 p, %2, 0;\n @p st.relaxed.gpu.global.u32 [%0], %1;\n @p st.relaxed.gpu.global.u32 [%0+4096], %1;\n}" :: "l"(d), "r"(tagw(a, par)), "r"((uint32_t)p) : "memory");
}
__device__ __forceinline__ void stp32_if(bool p, uint32_t both, char* d, char* e, float a, uint32_t par) {
    asm volatile("{\n .reg .pred p, q;\n setp.ne.u32 p, %2, 0;\n setp.ne.and.u32 q, %4, 0, p;\n @p st.relaxed.gpu.global.u32 [%3], %1;\n @q st.relaxed.gpu.global.u32 [%0], %1;\n}" :: "l"(d), "r"(tagw(a, par)), "r"((uint32_t)p), "l"(e), "r"(both) : "memory");
}
__device__ __forceinline__ void stp64_if(bool p, uint32_t both, char* d, char* e, uint32_t lo, uint32_t hi) {
    asm volatile("{\n .reg .pred p, q;\n .reg .b64 d;\n setp.ne.u32 p, %3, 0;\n setp.ne.and.u32 q, %5, 0, p;\n mov.b64 d, {%1,%2};\n @p st.relaxed.gpu.global.b64 [%4], d;\n @q st.relaxed.gpu.global.b64 [%0], d;\n}" :: "l"(d), "r"(lo), "r"(hi), "r"((uint32_t)p), "l"(e), "r"(both) : "memory");
}
__device__ __forceinline__ uint32_t chk2(uint32_t a, uint32_t b, uint32_t par) { uint32_t r; asm("lop3.b32 %0, %1, %2, %3, 0x7E;" : "=r"(r) : "r"(a), "r"(b), "r"(par)); return r; }
__device__ __forceinline__ uint32_t or3(uint32_t a, uint32_t b, uint32_t c) { uint32_t r; asm("lop3.b32 %0, %1, %2, %3, 0xFE;" : "=r"(r) : "r"(a), "r"(b), "r"(c)); return r; }
__device__ __forceinline__ uint32_t chk8(const uint32_t (&v)[8], uint32_t par) { return or3(chk2(v[0], v[1], par), chk2(v[2], v[3], par), or3(chk2(v[4], v[5], par), chk2(v[6], v[7], par), 0)); }
__device__ __forceinline__ uint32_t chk8(const uint2 (&v)[8], uint32_t par) { return or3(chk2(v[0].x, v[1].x, par), chk2(v[2].x, v[3].x, par), or3(chk2(v[4].x, v[5].x, par), chk2(v[6].x, v[7].x, par), 0)); }
__device__ __forceinline__ uint32_t chk8y(const uint2 (&v)[8], uint32_t par) { return or3(chk2(v[0].y, v[1].y, par), chk2(v[2].y, v[3].y, par), or3(chk2(v[4].y, v[5].y, par), chk2(v[6].y, v[7].y, par), 0)); }
__device__ __forceinline__ uint32_t chk4(const uint2 (&v)[4], uint32_t par) { return or3(chk2(v[0].x, v[0].y, par), chk2(v[1].x, v[1].y, par), or3(chk2(v[2].x, v[2].y, par), chk2(v[3].x, v[3].y, par), 0)); }
__device__ __forceinline__ float asf(uint32_t v) { return __uint_as_float(v); }
__device__ __forceinline__ float sum8(const uint32_t (&v)[8]) { return ((asf(v[0]) + asf(v[1])) + (asf(v[2]) + asf(v[3]))) + ((asf(v[4]) + asf(v[5])) + (asf(v[6]) + asf(v[7]))); }
__device__ __forceinline__ float sum8x(const uint2 (&v)[8]) { return ((asf(v[0].x) + asf(v[1].x)) + (asf(v[2].x) + asf(v[3].x))) + ((asf(v[4].x) + asf(v[5].x)) + (asf(v[6].x) + asf(v[7].x))); }
__device__ __forceinline__ float sum8y(const uint2 (&v)[8]) { return ((asf(v[0].y) + asf(v[1].y)) + (asf(v[2].y) + asf(v[3].y))) + ((asf(v[4].y) + asf(v[5].y)) + (asf(v[6].y) + asf(v[7].y))); }

__device__ __forceinline__ uint32_t pack2(float lo, float hi) { uint32_t r; asm("cvt.rn.bf16x2.f32 %0, %1, %2;" : "=r"(r) : "f"(hi), "f"(lo)); return r; }
__device__ __forceinline__ float bfr(float x) { return __uint_as_float(pack2(0.0f, x)); }
__device__ __forceinline__ float ex2(float x) { float r; asm("ex2.approx.ftz.f32 %0, %1;" : "=f"(r) : "f"(x)); return r; }
__device__ __forceinline__ float rcp(float x) { float r; asm("rcp.approx.ftz.f32 %0, %1;" : "=f"(r) : "f"(x)); return r; }
__device__ __forceinline__ float sqrt_(float x) { float r; asm("sqrt.approx.ftz.f32 %0, %1;" : "=f"(r) : "f"(x)); return r; }
__device__ __forceinline__ float bf_lo(uint32_t v) { return __uint_as_float(v << 16); }
__device__ __forceinline__ float bf_hi(uint32_t v) { return __uint_as_float(v & 0xffff0000u); }
__device__ __forceinline__ float sel4(int k, float a, float b, float c, float d) { return (k & 2) ? ((k & 1) ? d : c) : ((k & 1) ? b : a); }
constexpr float LOG2E = 1.4426950408889634f;
constexpr uint32_t ONES = 0x3f803f80u;

__device__ __forceinline__ void ln_stats(float sum, float sq, float& mean, float& den) {
    const float m = sum * (1.0f / 640.0f);
    const float var = fmaxf(fmaf(sq, 1.0f / 640.0f, -m * m), 0.0f);
    mean = bfr(m);
    den = bfr(sqrt_(bfr(bfr(var) + 1e-5f)));
}
__device__ __forceinline__ float sigmoidf_(float x) { return rcp(1.0f + ex2(-x * LOG2E)); }

#define TSTAMP(k) do {} while (0)
#define TST(k) do {} while (0)

#define CSTAMP(k) do {} while (0)
template <int N> __device__ __forceinline__ uint32_t lag(uint32_t sb, uint32_t z = 0) {
#pragma unroll
    for (int k = 0; k < N; k++) z = ldsvol(sb + S_ZERO + z);
    return z;
}
__device__ __forceinline__ void warm_mma(uint32_t& a, uint32_t& b) {
    asm volatile("mma.sync.aligned.m16n8k8.row.col.f16.f16.f16.f16 {%0,%1}, {%0,%1}, {%0}, {%0,%1};" : "+r"(a), "+r"(b) :: "memory");
}
#define KWNS2 20
#define KWNS 200
template <class F>
__device__ __forceinline__ void gather16(const char* p, uint32_t par, int k, F use) {
    uint32_t v[8], u[8];
    int guard = 0;
    bool again;
    do {
#pragma unroll
        for (int s = 0; s < 8; s++) v[s] = ldp32(p + s * 512);
#pragma unroll
        for (int s = 0; s < 8; s++) u[s] = ldp32(p + HALF + s * 512);
        const uint32_t stale = use(sum8(v) + sum8(u), ((v[0] ^ par) & 1) * 8);
        again = __any_sync(~0u, (or3(chk8(v, par), chk8(u, par), stale) & 1) != 0);
    } while (again & (++guard < SPIN_LIMIT));
    SWEEPS(k, guard - 1);
}

struct Params {
    const __nv_bfloat16 *x, *k, *v, *wr, *wq;
    __nv_bfloat16* out;
};
struct Maps { CUtensorMap k, v, vu, wq, wo, wg, wu, wd; };

constexpr int KV_BATCH_KEYS = 32 * 4096;

__device__ __forceinline__ void tma2d(uint32_t dst, const CUtensorMap* m, int c0, int c1, uint32_t bar, uint32_t bytes, uint64_t pol) {
    asm volatile("{\n .reg .pred p;\n elect.sync _|p, 0xffffffff;\n"
                 " @p mbarrier.arrive.expect_tx.shared::cta.b64 _, [%2], %6;\n"
                 " @p cp.async.bulk.tensor.2d.shared::cluster.global.mbarrier::complete_tx::bytes.L2::cache_hint [%0], [%1, {%3, %4}], [%2], %5;\n}"
                 :: "r"(dst), "l"(m), "r"(bar), "r"(c0), "r"(c1), "l"(pol), "r"(bytes) : "memory");
}
__device__ __forceinline__ void scrap_copy(uint32_t dst, const char* src, uint32_t bar) {
    asm volatile("{\n .reg .pred p;\n elect.sync _|p, 0xffffffff;\n"
                 " @p mbarrier.arrive.expect_tx.shared::cta.b64 _, [%2], 12288;\n"
                 " @p cp.async.bulk.shared::cluster.global.mbarrier::complete_tx::bytes [%0], [%1], 4096, [%2];\n"
                 " @p cp.async.bulk.shared::cluster.global.mbarrier::complete_tx::bytes [%0], [%1+4096], 4096, [%2];\n"
                 " @p cp.async.bulk.shared::cluster.global.mbarrier::complete_tx::bytes [%0], [%1+8192], 4096, [%2];\n}"
                 :: "r"(dst), "l"(src), "r"(bar) : "memory");
}
__device__ __forceinline__ void prefetch_l2(const void* p, uint32_t bytes) {
    asm volatile("{\n .reg .pred p;\n elect.sync _|p, 0xffffffff;\n @p cp.async.bulk.prefetch.L2.global [%0], %1;\n}" :: "l"(p), "r"(bytes) : "memory");
}
__device__ __forceinline__ uint64_t pol_first() { uint64_t p; asm("createpolicy.fractional.L2::evict_first.b64 %0, 1.0;" : "=l"(p)); return p; }
__device__ __forceinline__ uint64_t pol_normal() { uint64_t p; asm("createpolicy.fractional.L2::evict_normal.b64 %0, 1.0;" : "=l"(p)); return p; }
__device__ __forceinline__ bool utest(uint32_t bar, uint32_t parity) { return __all_sync(~0u, mbar_test(bar, parity)); }
__device__ __forceinline__ void uwait(uint32_t bar, uint32_t parity) {
    int n = 0;
    while (!__all_sync(~0u, mbar_try(bar, parity)) && ++n < SPIN_LIMIT) {}
}
template <int A, int B, int CNT> __device__ __forceinline__ void init_bars(uint32_t sb) {
#pragma unroll 1
    for (int k = A; k < B; k++)
        asm volatile("{\n .reg .pred p;\n elect.sync _|p, 0xffffffff;\n @p mbarrier.init.shared::cta.b64 [%0], %1;\n}" :: "r"(sb + S_BAR + 8 * k), "n"(CNT) : "memory");
}
__device__ __forceinline__ int unit_key(uint32_t b, uint32_t u) {
    return (blockIdx.x >> 2) * 4096 + 3072 + (blockIdx.x & 3) * (16 * ILV) + b * KV_BATCH_KEYS + (u & ~(ILV - 1u)) * 64 + (u & (ILV - 1)) * 16;
}
__device__ __forceinline__ void load_tile(const CUtensorMap* m, uint32_t dst, uint32_t bar, uint32_t bytes, int key, uint64_t pol) { tma2d(dst, m, 0, 3 * key, bar, bytes, pol); }
__device__ __forceinline__ const char* unit_ptr(const Params& P, int n) { return (const char*)((n & 16) ? P.v : P.k) + (size_t)unit_key(n >> 5, n & 15) * 384; }
#define LSTAMP(k) do {} while (0)

__device__ __forceinline__ uint32_t k_place(uint32_t b, uint32_t s) { return s + 3 + 5 * (b & 1); }
__device__ __forceinline__ uint32_t v_place(uint32_t b, uint32_t s) { return s < 3 ? s : s + 8 - 8 * (b & 1); }
__device__ __forceinline__ void k_load(const Maps& M, uint32_t dst, uint32_t bar, int key8, uint64_t pol) {
    asm volatile("{\n .reg .pred p;\n elect.sync _|p, 0xffffffff;\n"
                 " @p mbarrier.arrive.expect_tx.shared::cta.b64 _, [%2], 6144;\n"
                 " @p cp.async.bulk.tensor.4d.shared::cluster.global.mbarrier::complete_tx::bytes.L2::cache_hint [%0], [%1, {0, 0, 0, %3}], [%2], %4;\n}"
                 :: "r"(dst), "l"(&M.k), "r"(bar), "r"(key8), "l"(pol) : "memory");
}
__device__ __forceinline__ int unit_key8(uint32_t n) { return unit_key(n >> 4, n & 15) >> 3; }
__device__ __forceinline__ void ring_load(const Maps& M, uint32_t sb, uint32_t b, uint32_t u, uint32_t pos) {
    if (u < 16) k_load(M, sb + pos * UNIT, sb + S_RING + 8 * pos, unit_key8(16 * b + u), pol_normal());
    else load_tile(&M.vu, sb + pos * UNIT, sb + S_FV + 4 * (pos & 6), UNIT, unit_key(b, pos), pol_first());
}
__device__ __forceinline__ uint32_t token(bool p, uint32_t a, uint32_t n) {
    uint32_t v;
    asm volatile("{\n .reg .pred p;\n setp.ne.u32 p, %2, 0;\n mov.u32 %0, 0;\n @p atom.shared.exch.b32 %0, [%1], %3;\n}" : "=r"(v) : "r"(a), "r"((uint32_t)p), "r"(n) : "memory");
    return v;
}
__device__ __forceinline__ void place_load(const Maps& M, uint32_t sb, uint32_t n) {
    k_load(M, sb + k_place(n >> 4, 0) * SLOT + (n & 15) * UNIT, sb + S_FK + 4 * (n & 14), unit_key8(n), pol_first());
}
__device__ __forceinline__ void v_load(const Maps& M, uint32_t sb, uint32_t b, uint32_t s) {
    load_tile(&M.v, sb + v_place(b, s) * SLOT, sb + S_FV + 8 * s, SLOT, unit_key(b, 2 * s), pol_first());
}

__device__ __forceinline__ void stream_warp(const Params& P, const Maps& M, uint32_t sb, uint32_t lane) {
    const uint64_t pol = pol_first();
    const int bid = blockIdx.x, g = bid >> 3, i = bid & 7;
    const uint32_t wf = sb + S_WFULL;
    uint32_t tn = __shfl_sync(~0u, gtime32(), 0) * 16;
    int still = 0;
    auto until = [&](uint32_t t) {
        uint32_t now = __shfl_sync(~0u, gtime32(), 0) * 16;
        while ((int)(now - t) < 0 && still < 16) {
            const uint32_t last = now;
            now = __shfl_sync(~0u, gtime32(), 0) * 16;
            still = now == last ? still + 1 : 0;
        }
        return now;
    };
    auto pace = [&](uint32_t dt) {
        const uint32_t now = until(tn);
        if ((int)(now - tn) > SLACK0) tn = now - SLACK0;
        tn += dt;
    };
#pragma unroll
    for (int k = 0; k < 10; k++) {
        if (k < 2) {
            if (k == 0) init_bars<26, 27, 1>(sb); else init_bars<27, 37, 1>(sb);
            asm volatile("fence.mbarrier_init.release.cluster;" ::: "memory");
            if (k == 1) { asm volatile("bar.arrive 2, %0;" :: "n"(NTHR) : "memory"); asm volatile("bar.sync 3, 128;" ::: "memory"); }
        }
        if (k >= WIN_W) uwait(wf + 8 * (k - WIN_W), 0);
        pace(TAUW * 5 / 2 - (k == 0 || k == 2 ? LEADW : 0));
        if (k < 4) tma2d(sb + ST_WQ + 15360 * k, &M.wq, 384 * g + 192 * (k >> 1), 80 * i + 40 * (k & 1), wf + 8 * k, 15360, pol);
        else if (k < 6) tma2d(sb + ST_WG + 15360 * (k - 4), k == 4 ? &M.wg : &M.wu, 96 * g, 80 * i, wf + 8 * k, 15360, pol);
        else tma2d(sb + ST_WO + 15360 * (k - 6), &M.wo, 80 * i, 384 * g + 96 * (k - 6), wf + 8 * k, 15360, pol);
    }
#pragma unroll 1
    for (int n = 0; n < 16; n++) {
        if (n == 0 || n == 5 || n == 11) uwait(sb + S_RELW + (n == 0 ? 0 : n == 5 ? 8 : 16), 0);
        uwait(n < WIN_S ? wf + 8 * (10 - WIN_S + n) : sb + S_FV + 8 * ((n - WIN_S) ^ 8), 0);
        pace(2 * TAU0);
        if (n >= WIN_S && !utest(sb + S_FV + 8 * ((n - WIN_S + 1) ^ 8), 0)) tn += XB;
        if (n < 8) { place_load(M, sb, 2 * n); place_load(M, sb, 2 * n + 1); }
        else if (n < 11) { ring_load(M, sb, 0, 2 * n, 2 * n - 16); ring_load(M, sb, 0, 2 * n + 1, 2 * n - 15); }
        else v_load(M, sb, 0, n - 8);
        if (n == 7) { pace(TAUW * 5 / 2); tma2d(sb + S_WD, &M.wd, 80 * i, 96 * g, wf + 80, 15360, pol); }
    }
    int nd = 0;
    uint32_t q[4];
#pragma unroll
    for (int r = 0; r < 4; r++) q[r] = sb + S_FV + 8 * (7 - r);
    uint32_t td = tn;
    uint32_t pos = 2;
#pragma unroll 1
    for (int m = 16; m < 64; m++) {
        const int b = m >> 4, j = m & 15;
        const char* src = unit_ptr(P, 2 * m);
        const uint32_t tok = sb + S_TOK + (j < 3 ? 4 * pos : j < 11 ? 24 + 4 * pos : 16 + 4 * j) + 4 * lane;
        static_assert(WIN_U <= 12, "a ring position has at most one token of the timetable");
        int k = 0;
        while (true) {
            const uint2 c = lds64(sb + S_KF);
            if (__all_sync(~0u, mbar_test(q[WIN_S - 1] & ~1u, q[WIN_S - 1] & 1) & (min((int)c.x + 1, (int)c.y) >= 16 * b + min(2 * j + 2 - WIN_U, 16))) || ++k >= SPIN_FAST) break;
        }
        const uint32_t now = until(td);
        const uint32_t mine = __ballot_sync(~0u, token(lane < (j < 11 ? 2 : 1), tok, 2 * m + lane) == 2 * m + lane);
        {
            const uint2 c = lds64(sb + S_KF);
            if (!__all_sync(~0u, mbar_test(q[WIN_S - 2] & ~1u, q[WIN_S - 2] & 1) & (min((int)c.x + 1, (int)c.y) >= 16 * b + min(2 * j + 4 - WIN_U, 16)))) tn += XB;
        }
        q[3] = q[2]; q[2] = q[1]; q[1] = q[0]; q[0] = sb + S_QRDY;
        if (j < 11) {
            if (mine & 1) ring_load(M, sb, b, 2 * j, pos); else prefetch_l2(src, UNIT);
            if (mine & 2) ring_load(M, sb, b, 2 * j + 1, pos + 1); else prefetch_l2(src + UNIT, UNIT);
            if (j >= 8) q[0] = (sb + S_FV + 8 * (j - 8)) | (b & 1);
        } else if (mine) { v_load(M, sb, b, j - 8); q[0] = (sb + S_FV + 8 * (j - 8)) | (b & 1); }
        else if (j - 8 >= VPF) prefetch_l2(src, SLOT);
        else {
            scrap_copy(sb + S_DUMMY, src, sb + S_DBAR + 8 * (nd & 3));
            q[0] = (sb + S_DBAR + 8 * (nd & 3)) | ((nd >> 2) & 1);
            nd++;
        }
        pos = j == 15 ? 2 : pos == 4 ? 0 : pos + 2;
        if ((int)(now - tn) > SLACK) tn = now - SLACK;
        tn += 2 * TAU;
        td = (int)(tn - now) > 2 * TMIN ? tn : now + 2 * TMIN;
    }
#pragma unroll 1
    for (int m = max(nd - 4, 0); m < nd; m++) uwait(sb + S_DBAR + 8 * (m & 3), (m >> 2) & 1);
}

__host__ __device__ constexpr uint64_t bit_list(uint32_t m) { uint64_t r = 0; int n = 0; for (int k = 0; k < 12; k++) if ((m >> k) & 1) r |= (uint64_t)k << (4 * n++); return r; }
__device__ __forceinline__ float scaled(float s) { return bfr(bfr(s) * 0.07216878364870322f); }
__device__ __forceinline__ void probs(float s, uint32_t ps, uint32_t src, uint32_t ln) {
    const uint32_t q8 = ln >> 2, t4 = ln & 3;
    int key = __float_as_int(s);
    key ^= (key >> 31) & 0x7fffffff;
    key = __reduce_max_sync(~0u, key);
    key ^= (key >> 31) & 0x7fffffff;
    const float ml = __int_as_float(key) * LOG2E;
    sts16(ps + 64 * src + (q8 >> 1) * 16 + t4 * 4 + (q8 & 1) * 2, pack2(ex2(fmaf(s, LOG2E, -ml)), 0.f));
    stsf(ps + PS_MAX + 4 * src, ml);
}
template <int H> __device__ __forceinline__ uint32_t b_pos(uint32_t e) { const uint32_t h = e >= H, k = e - H * h; return h * 192 + (k & 6) * 24 + (k >> 3) * 4 + (k & 1) * 2; }
__device__ __forceinline__ uint32_t a_pos(uint32_t e) { const uint32_t h = e >= 40, k = e - 40 * h; return (k & 6) * 24 + (k >> 3) * 8 + h * 4 + (k & 1) * 2; }
__device__ __forceinline__ uint32_t q_pos(uint32_t d) { const uint32_t s = 3 * ((d >> 4) & 3) + (d >> 6); return s * 32 + (d & 6) * 4 + ((d >> 3) & 1) * 4 + (d & 1) * 2; }
__device__ __forceinline__ uint32_t k_off(uint32_t ln) { return (ln & 8) * 384 + (ln & 7) * 128 + (((ln & 7) ^ (ln >> 4)) << 4); }

#define HSTAMP(k) do {} while (0)
__device__ __forceinline__ char* xwindow() { return reinterpret_cast<char*>((reinterpret_cast<uintptr_t>(g_x) + (2u << 20) - 1) & ~(uintptr_t)((2u << 20) - 1)); }

struct XPtr {
    uint32_t lo, hi;
    __device__ __forceinline__ explicit XPtr(char* p) : lo((uint32_t)(uintptr_t)p), hi((uint32_t)((uintptr_t)p >> 32)) {}
    __device__ __forceinline__ XPtr(uint32_t l, uint32_t h) : lo(l), hi(h) {}
    __device__ __forceinline__ XPtr operator+(uint32_t o) const { return XPtr(lo + o, hi); }
    __device__ __forceinline__ operator char*() const { uint64_t p; asm("mov.b64 %0, {%1, %2};" : "=l"(p) : "r"(lo), "r"(hi)); return (char*)p; }
};

__device__ __forceinline__ char* side_word(uint32_t g, uint32_t i) { return xwindow() + pairG(1, 0, i) * 8192 + (g >> 3) * HALF + (g & 7) * 512 + 320; }

__device__ __forceinline__ uint32_t probe_side() {
    const uint32_t bid = blockIdx.x, g = bid >> 3, i = bid & 7, P = pairG(0, 0, i);
    char* p = xwindow() + P * 8192 + (g >> 3) * HALF + (g & 7) * 512 + 352;
    uint32_t best[2] = {~0u, ~0u};
#pragma unroll
    for (int k = 0; k < 4; k++) *reinterpret_cast<uint4*>(p + (k & 1) * 16 + (k >> 1) * COPY) = make_uint4(1, 1, 1, 1);
#pragma unroll 1
    for (int r = 0; r < 64; r++) {
        if (r >= 4 && !(r & 1) && min(best[0], best[1]) < 380 && max(best[0], best[1]) > min(best[0], best[1]) + 80) break;
        uint32_t c0, c1, v;
        asm volatile("mov.u32 %0, %clock;" : "=r"(c0) :: "memory");
        asm volatile("atom.relaxed.gpu.global.exch.b32 %0, [%1], 0;" : "=r"(v) : "l"(p + (r & 1) * COPY) : "memory");
        asm volatile("{\n .reg .pred q;\n setp.eq.u32 q, %1, 0x13579bdf;\n mov.u32 %0, 0;\n @!q mov.u32 %0, %clock;\n}" : "=r"(c1) : "r"(v) : "memory");
        if (r & 1) best[1] = min(best[1], c1 - c0); else best[0] = min(best[0], c1 - c0);
    }
    return 1 + ((best[1] < best[0]) ^ (__popc(P & PMASK) & 1));
}

template <int N>
__device__ __forceinline__ void hop_a(const char* src, uint32_t par, uint32_t dst, bool st, int k) {
    uint2 v[N][4];
    float e[4], rl;
    int guard = 0;
    bool again;
    do {
#pragma unroll
        for (int s = 0; s < 4 * N; s++) v[s / 4][s % 4] = ldp64(src + (s / 4) * 256 + (s % 4) * 1024);
        again = __any_sync(~0u, ((chk4(v[0], par) | chk4(v[N - 1], par)) & 1) != 0);
        const uint32_t M = (uint32_t)max(max((int)v[0][0].x, (int)v[0][1].x), max((int)v[0][2].x, (int)v[0][3].x)) - 254;
#pragma unroll
        for (int s = 0; s < 4; s++) e[s] = asf((uint32_t)max((int)(v[0][s].x - M), 0) << 22);
        rl = rcp(fmaf(e[0], asf(v[0][0].y), e[1] * asf(v[0][1].y)) + fmaf(e[2], asf(v[0][2].y), e[3] * asf(v[0][3].y)));
#pragma unroll
        for (int s = 0; s < 4; s++) e[s] = __shfl_sync(~0u, e[s], 24);
        keep(rl);
    } while (again & (++guard < SPIN_LIMIT));
    rl = __shfl_sync(~0u, rl, 24);
#pragma unroll
    for (int n = 0; n < N; n++) {
        const float o0 = fmaf(e[0], asf(v[n][0].x), e[1] * asf(v[n][1].x)) + fmaf(e[2], asf(v[n][2].x), e[3] * asf(v[n][3].x));
        const float o1 = fmaf(e[0], asf(v[n][0].y), e[1] * asf(v[n][1].y)) + fmaf(e[2], asf(v[n][2].y), e[3] * asf(v[n][3].y));
        sts32_if(st, dst + 192 * n, pack2(o0 * rl, o1 * rl));
    }
    SWEEPS(k, guard - 1);
    __syncwarp();
}

__device__ __forceinline__ void score_warp(const Maps& M, uint32_t sb, uint32_t h, uint32_t ln) {
    const uint32_t lane0 = ln;
    uwait(sb + S_QRDY, 0);
    const uint32_t q8 = ln >> 2;
    const uint32_t k0 = k_off(ln);
    uint32_t pos = h + 6, bar = sb + S_FK, par = 0, phases = 0;
    uint2 q = lds64(sb + S_QS + 8 * ln), qh = lds64(sb + S_QS + 8 * ln + 256);
    auto first_round = [&](uint32_t b, uint32_t ln) {
        uwait(sb + S_RELR, b & 1);
        const uint32_t u = h + 2 * ln, p = u < 4 ? u + 2 : u - 4;
        uint32_t todo = __ballot_sync(~0u, token(ln < 3, sb + S_TOK + 4 * p, 32 * b + 32 + u) == 32 * b + 32 + u);
#pragma unroll 1
        for (uint32_t r = h; todo; todo >>= 1, r += 2) if (todo & 1) ring_load(M, sb, b + 1, r, r < 4 ? r + 2 : r - 4);
    };
#pragma unroll 1
    for (uint32_t n = h; n < 64; n += 2) {
        HSTAMP(0);
        const uint32_t ua = sb + pos * UNIT;
        if (!__all_sync(~0u, mbar_try(bar, par))) uwait(bar, par);
        HSTAMP(1);
        float acc[2][4] = {};
        uint32_t mine = 0;
        const uint32_t id = n + (n & 48) + 6;
#pragma unroll
        for (int s = 0; s < 12; s++) {
            uint32_t kf[4];
            ldsm4(kf, (k0 ^ (32 * (s / 3))) + (ua + 1024 * (s % 3)));
            if (s == 11) {
                __syncwarp();
                mine = token(ln == 0 && n >= 16, sb + S_TOK + 24 + 4 * pos, id);
                stsvol(sb + S_KF + 4 * h, n + 1);
            }
            const bool m = q8 == (s & 7);
            mmaA(acc[s & 1], kf, m ? (s < 8 ? q.x : qh.x) : 0u, m ? (s < 8 ? q.y : qh.y) : 0u);
        }
        const uint32_t pos0 = pos;
        const bool last = (n & 14) == 14;
        pos = last ? h + 2 : n >= 16 && pos >= 4 ? h : pos + 2;
        bar = n >= 14 ? sb + S_RING + 8 * pos : bar + 8;
        par = n >= 14 ? (phases >> pos) & 1 : 0;
        phases ^= n >= 14 ? 1u << pos : 0;
        const float w0 = (acc[0][0] + acc[0][1]) + (acc[1][0] + acc[1][1]), w1 = (acc[0][2] + acc[0][3]) + (acc[1][2] + acc[1][3]);
        HSTAMP(2);
        if (__any_sync(~0u, mine == id)) ring_load(M, sb, n >> 4, (n & 15) + 6, pos0);
        HSTAMP(3);
        float s = ((ln & 1) ? w1 : w0) + __shfl_xor_sync(~0u, (ln & 1) ? w0 : w1, 1);
        s += __shfl_xor_sync(~0u, s, 2);
        sts_hi16(sb + S_SC + (((n & 12) >> 1) + h) * 64 + (n & 2) * 2 + (ln & 29) * 2, scaled(s));
        if (last) {
            __syncwarp();
            arrive_if(ln == 0, sb + S_SCO);
            const uint32_t b = n >> 4, ln = lane0 + lag<1>(sb);
            if (b > 0) {
                uwait(sb + S_RELK, (b - 1) & 1);
                if (h == 0) LSTAMP(64 + 2 * b);
                const uint32_t sl = 3 + h + 2 * ln, idv = 32 * b + 16 + 2 * sl;
                uint32_t todo = __ballot_sync(~0u, token(sl < 8, sb + S_TOK + 48 + 4 * sl, idv) == idv);
#pragma unroll 1
                for (uint32_t r = 3 + h; todo; todo >>= 1, r += 2) if (todo & 1) v_load(M, sb, b, r);
                const uint32_t g = blockIdx.x >> 3, pr = pairL(RA, 1, g), side = ldsvol(sb + S_SIDE);
                const char* src = xwindow() + pr * 8192 + ((side ^ 1 ^ __popc(pr & PMASK)) & 1) * COPY + h * HALF + 8 * min(ln, 24u);
                uwait(sb + S_RELV, (b - 1) & 1);
                __nanosleep(HOP1_NS);
#pragma unroll 1
                for (uint32_t r = 0; r < 4; r += 2) {
                    hop_a<2>(src + 256 * r, b & 1, sb + S_OS + 192 * (4 * h + r) + 96 + 4 * ln, ln < 24, 25);
                    if (r == 0 && b < 3) first_round(b, ln);
                }
                arrive_if(ln == 0, sb + S_OS1);
            } else first_round(0, ln);
            q = lds64(sb + S_QS + 24 * ((n + 2) & 48) + 8 * ln); qh = lds64(sb + S_QS + 24 * ((n + 2) & 48) + 8 * ln + 256);
        }
    }
}

__global__ void __launch_bounds__(NTHR, 1)
fused_kernel(const Params P, const __grid_constant__ Maps M) {
    extern __shared__ __align__(1024) unsigned char smem[];
    const uint32_t sb = smem_u32(smem);
    const int tid = threadIdx.x, bid = blockIdx.x;
    if (tid == 0) {
        asm volatile("prefetch.tensormap [%0];" :: "l"(&M.wq) : "memory");
        asm volatile("cp.async.bulk.prefetch.L2.global [%0], 12288;" :: "l"(P.wq + (80 * (bid & 7) + (bid >> 3)) * 6144) : "memory");
    }
    const int w = __shfl_sync(~0u, tid >> 5, 0), lane = tid & 31;

    if (w >= 8) {
        asm volatile("setmaxnreg.dec.sync.aligned.u32 " REG_LO ";");
        if (w == 8) {
            stream_warp(P, M, sb, lane);
        } else {
            if (w == 9) { init_bars<0, 3, 2>(sb); init_bars<3, 8, 1>(sb); init_bars<16, 22, 1>(sb); }
            else if (w == 10) { init_bars<8, 16, 2>(sb); init_bars<22, 26, 1>(sb); }
            else { init_bars<37, 38, 1>(sb); init_bars<38, 40, 8>(sb); init_bars<40, 41, 1>(sb); init_bars<41, 44, 8>(sb); init_bars<44, 46, 2>(sb); stsvol(sb + S_ZERO + 4 * lane, 0); if (lane < 16) stsvol(sb + S_LN + 4 * lane, 0); }
            asm volatile("fence.mbarrier_init.release.cluster;" ::: "memory");
            asm volatile("bar.arrive 3, 128;" ::: "memory");
            if (w == 11) asm volatile("bar.arrive 2, %0;" :: "n"(NTHR) : "memory");
            else {
                if (lane < 4) asm volatile("prefetch.tensormap [%0];" :: "l"(&M.k + lane + 4 * (w - 9)) : "memory");
                __syncwarp();
                asm volatile("bar.sync 2, %0;" :: "n"(NTHR) : "memory");
            }
            if (w < 11) score_warp(M, sb, w - 9, lane);
            else {
                uint32_t mine = 0;
                if (lane == 0) mine = probe_side();
                mine = __shfl_sync(~0u, mine, 0);
                if (lane < 8) stp32(side_word(bid >> 3, bid & 7) + 4 * lane, asf(mine & 2), 1);
                uint32_t a = 0, b = 0;
                int k = 0;
                while (!utest(sb + S_QRDY, 0) && ++k < SPIN_FAST) { warm_mma(a, b); __nanosleep(KWNS); }
                while (true) {
                    const uint32_t v = ldp32(side_word(bid >> 3, lane & 7));
                    const bool late = !__all_sync(~0u, v & 1);
                    if (!late || ++k >= SPIN_FAST) { stsvol(sb + S_SIDE, mine | (FORCE_BOTH || late || __any_sync(~0u, (v ^ mine) & 2) ? 4 : 0)); break; }
                    warm_mma(a, b); __nanosleep(KWNS);
                }
                while (ldsvol(sb + S_GATE) == 0 && ++k < SPIN_FAST) { warm_mma(a, b); __nanosleep(KWNS); }
                uint32_t rl = lane, rq = 0;
                auto reset = [&] {
                    if (rq < 128) *reinterpret_cast<uint4*>(reinterpret_cast<char*>(g_s) + (rl < 60 ? XS + bid * 7680 + 128 * rl : XS2 + bid * 768 + 128 * (rl - 60)) + rq) = make_uint4(0, 0, 0, 0);
                    rl += 32;
                    if (rl >= 66) { rl -= 66; rq += 16; }
                };
                reset(); reset();
                if (lane < 8) stp32(side_word(bid >> 3, bid & 7) + 4 * lane, 0.f, 0);
                const uint32_t side = (ldsvol(sb + S_SIDE) & 1) ^ 1, g = bid >> 3, i = bid & 7;
                const XPtr gx(xwindow());
                auto nearp = [&](uint32_t pr) { return gx.lo + pr * 8192 + ((side ^ __popc(pr & PMASK)) & 1) * COPY; };
                const uint32_t own = (i >> 2) * HALF + (i & 3) * 1024 + (lane & 7) * 128;
                const uint32_t cut = (lane & 7) == 7 ? 128 : 0;
                const uint32_t pAC = nearp(pairL(lane >> 4, (lane >> 3) & 1, g)) + own - (lane >> 4) * cut, pE = nearp(pairL(RE, (lane >> 3) & 1, g)) + own - cut;
                const uint32_t pG = nearp(pairG((lane >> 2) & 1, (lane >> 3) & 1, i)) + min(lane & 3, 2) * 128;
                uint32_t tr = 0, tk = 0, ph = 0, src = g + (lane >> 4), seen = 0, n = 16;
                bool go = false, first = true;
                while (n < 64 && ++k < SPIN_FAST) {
                    const uint32_t now = __shfl_sync(~0u, gtime32(), 0) * 16;
                    if (!go && utest((n & 15) < 6 ? sb + S_RELK : sb + S_RELV, ((n >> 4) & 1) ^ 1)) { go = true; if ((int)(now - tk) > 0 || !(n & 15)) tk = now; }
                    if (go && (int)(now - tk) >= 0) {
                        place_load(M, sb, (n & 16) ? n : (n & 48) | ((n + 10) & 15));
                        tk += KRE_TAU;
                        n++;
                        go = (n & 15) != 0 && (n & 15) != 6;
                        if (!(n & 15)) LSTAMP(63 + (n >> 3));
                    } else if (first || (int)(now - tr) >= 0) {
                        first = false;
                        tr = now + RFR_TAU;
                        b |= seen & a;
                        warm_mma(a, b);
                        seen = ldp32(XPtr(ph == 0 ? pAC : ph == 1 && lane < 16 ? pE : pG + (src & 8) * (HALF / 8) + (src & 7) * 512, gx.hi));
                        reset();
                        src += ph == 0 ? 0 : ph == 1 ? 2 : 1;
                        ph = ph == 2 ? 0 : ph + 1;
                    } else __nanosleep(KWNS2);
                }
                while (rq < 128) reset();
                __syncwarp();
                while (ldsvol(sb + S_GATE) < 6 && ++k < SPIN_FAST) { warm_mma(a, b); __nanosleep(KWNS); }
                if (a | b) stsvol(sb + S_GATE, 6);
            }
        }
        return;
    }
    asm volatile("setmaxnreg.inc.sync.aligned.u32 " REG_HI ";");

    const int g = bid >> 3, i = bid & 7;
    const int g8 = lane >> 2, t = lane & 3;
    char* const gs = reinterpret_cast<char*>(g_s);
    const XPtr gx(xwindow());

    W80 Wq[6], Wgu[3];
    uint32_t Wo[5][3][4];
    if (w < 4) {
        const uint32_t* xp = reinterpret_cast<const uint32_t*>(P.x + 640 * w);
        float sum = 0.f, sq = 0.f;
#pragma unroll
        for (int u = 0; u < 10; u++) { uint32_t v = xp[lane + 32 * u]; float a = bf_lo(v), b = bf_hi(v); sum += a + b; sq += a * a + b * b; }
#pragma unroll
        for (int o = 16; o > 0; o >>= 1) { sum += __shfl_xor_sync(~0u, sum, o); sq += __shfl_xor_sync(~0u, sq, o); }
        float mean, den; ln_stats(sum, sq, mean, den);
        if (lane < 20) {
            const uint2 v = reinterpret_cast<const uint2*>(P.x + 640 * w + 80 * i)[lane];
            sts64(sb + S_X0 + 160 * w + 8 * lane, v.x, v.y);
            sts32(sb + S_L0 + 384 * w + b_pos<40>(4 * lane), pack2(__fdiv_rn(bfr(bf_lo(v.x) - mean), den), __fdiv_rn(bfr(bf_hi(v.x) - mean), den)));
            sts32(sb + S_L0 + 384 * w + b_pos<40>(4 * lane + 2), pack2(__fdiv_rn(bfr(bf_lo(v.y) - mean), den), __fdiv_rn(bfr(bf_hi(v.y) - mean), den)));
        }
    } else if (w == 4) {
        const uint32_t* xp = reinterpret_cast<const uint32_t*>(P.wr);
        float sum = 0.f;
#pragma unroll
        for (int u = 0; u < 10; u++) { uint32_t v = xp[lane + 32 * u]; sum += bf_lo(v) + bf_hi(v); }
#pragma unroll
        for (int o = 16; o > 0; o >>= 1) sum += __shfl_xor_sync(~0u, sum, o);
        if (lane == 0) stsf(sb + S_SWR, sum);
        if (lane < 20) {
            const uint2 v = reinterpret_cast<const uint2*>(P.wr + 80 * i)[lane];
            sts32(sb + S_XA + 576 + a_pos(4 * lane), v.x); sts32(sb + S_XA + 576 + a_pos(4 * lane + 2), v.y);
            sts32(sb + S_XA + a_pos(4 * lane), ONES); sts32(sb + S_XA + a_pos(4 * lane + 2), ONES);
        }
    }
    asm volatile("bar.sync 2, %0;" :: "n"(NTHR) : "memory");
    auto frag = [](uint32_t (&a)[4], uint32_t p, int pitch) {
        const uint32_t r0 = lds32(p), r1 = lds32(p + pitch), r2 = lds32(p + 2 * pitch), r3 = lds32(p + 3 * pitch);
        a[0] = __byte_perm(r0, r1, 0x5410); a[1] = __byte_perm(r0, r1, 0x7632);
        a[2] = __byte_perm(r2, r3, 0x5410); a[3] = __byte_perm(r2, r3, 0x7632);
    };
    mbar_wait(sb + S_WFULL + 16 * (w >> 2), 0);
    mbar_wait(sb + S_WFULL + 16 * (w >> 2) + 8, 0);
    {
        const uint32_t p = sb + ST_WQ + (w >> 2) * 30720 + (2 * t) * 384 + (48 * (w & 3) + 2 * g8) * 2;
#pragma unroll
        for (int r = 0; r < 10; r++)
#pragma unroll
            for (int m = 0; m < 3; m++) {
                const uint32_t q = p + ((r & 1) * 40 + (r >> 1) * 8) * 384 + 32 * m, r0 = lds32(q), r1 = lds32(q + 384);
                (r < 8 ? Wq[2 * m].a[(r >> 2) & 1][r & 3] : Wq[2 * m].c[r & 1]) = __byte_perm(r0, r1, 0x5410);
                (r < 8 ? Wq[2 * m + 1].a[(r >> 2) & 1][r & 3] : Wq[2 * m + 1].c[r & 1]) = __byte_perm(r0, r1, 0x7632);
            }
    }
    __syncwarp();
    if (lane == 0) mbar_arrive(sb + S_RELW);
    TSTAMP(1);
    {
        char* d = gs + XS + bid * 7680 + (w >> 2) * 3840 + (48 * (w & 3) + 2 * g8) * 4;
        float acc[6][4] = {};
        mul80(acc, Wq, lds128(sb + S_L0 + 48 * lane), lds32(sb + S_L0 + 48 * lane + 16));
#pragma unroll
        for (int m = 0; m < 6; m += 2) stp64(d + t * 768 + 32 * m, acc[m][0] + acc[m][3], acc[m + 1][0] + acc[m + 1][3], 1);
        float sum[6][4] = {};
        mul80(sum, Wq, make_uint4(ONES, ONES, ONES, ONES), ONES);
        if (t == 0)
#pragma unroll
            for (int m = 0; m < 6; m += 2) stp64(d + 4 * 768 + 32 * m, sum[m][0] + sum[m][3], sum[m + 1][0] + sum[m + 1][3], 1);
    }
    mbar_wait(sb + S_WFULL + 32, 0);
    mbar_wait(sb + S_WFULL + 40, 0);
    const uint32_t oct = 3 * (w >> 1) + (w & 1), oct2 = 3 * (w >> 1) + 2;
    {
        const uint32_t p = sb + ST_WG + ((lane & 7) + 40 * ((lane >> 3) & 1) + 8 * (lane >> 4)) * 192;
#pragma unroll
        for (int T = 0; T < 3; T++) {
            const uint32_t q = p + (T < 2 ? T * 15360 + 16 * oct : (w & 1) * 15360 + 16 * oct2);
            ldsm4t(Wgu[T].a[0], q); ldsm4t(Wgu[T].a[1], q + 16 * 192); ldsm2t(Wgu[T].c, q + 32 * 192);
        }
        float sum[3][4] = {};
        mul80(sum, Wgu, make_uint4(ONES, ONES, ONES, ONES), ONES);
        if (t < 3) stp32(gs + XS2 + bid * 768 + (t < 2 ? 64 * oct + 4 * t : 64 * oct2 + 4 * (w & 1)) + 8 * g8,
                         sel4(t, sum[0][0] + sum[0][3], sum[1][0] + sum[1][3], sum[2][0] + sum[2][3], 0.f), 1);
    }
    __syncwarp();
    if (lane == 0) mbar_arrive(sb + S_RELW + 8);
    mbar_wait(sb + S_WFULL + 48 + 8 * (w >> 1), 0);
    {
        const uint32_t po = sb + ST_WO + (48 * w + 12 * t) * 160 + 4 * g8;
#pragma unroll
        for (int s = 0; s < 3; s++)
#pragma unroll
            for (int m = 0; m < 5; m++) frag(Wo[m][s], po + 4 * s * 160 + 32 * m, 160);
    }
    __syncwarp();
    if (lane == 0) mbar_arrive(sb + S_RELW + 16);
    mbar_wait(sb + S_WFULL + 64, 0);
    if (tid < 192) {
        const char* srcS = gs + XS + g * 8 * 7680 + (i >> 2) * 3840 + tid * 4;
        uint32_t vs[5][8];
        int guard = 0;
        do {
#pragma unroll
            for (int b = 0; b < 5; b++)
#pragma unroll
                for (int s = 0; s < 8; s++) vs[b][s] = ldp32(srcS + b * 768 + s * 7680);
        } while (((or3(chk8(vs[0], 1), chk8(vs[1], 1), chk8(vs[2], 1)) | chk8(vs[3], 1) | chk8(vs[4], 1)) & 1) && ++guard < SPIN_LIMIT);
        const uint32_t qpos = sb + S_QS + q_pos(tid);
#pragma unroll
        for (int b = 0; b < 4; b++) {
            sts_hi16(qpos + 384 * b, bfr(sum8(vs[b])));
        }
        stsf(sb + S_CSQ + 4 * tid, sum8(vs[4]));
    }
    if (tid < 192) {
        uint32_t v[8];
        int guard = 0;
        do {
#pragma unroll
            for (int s = 0; s < 8; s++) v[s] = ldp32(gs + XS2 + (g * 8 + s) * 768 + tid * 4);
        } while ((chk8(v, 1) & 1) && ++guard < SPIN_LIMIT);
        stsf(sb + S_CSGU + 4 * tid, sum8(v));
    }
    __syncwarp();
    bar_main();
    arrive_if(tid == 0, sb + S_QRDY);
    TSTAMP(2);

    uint32_t side;
    { int k = 0; while ((side = ldsvol(sb + S_SIDE)) == 0 && ++k < SPIN_FAST) {} }
    const uint32_t both = __any_sync(~0u, side & 4) ? COPY : 0;
    uint32_t td = __shfl_sync(~0u, tid, lane);
    const uint32_t wp = __shfl_sync(~0u, tid >> 5, 0);
    const uint32_t cc = wp >= 3;
    auto uni = [](uint32_t v) { return __shfl_sync(~0u, v, 0); };
    auto pin = [&](uint32_t v) { return __shfl_sync(~0u, v, td); };
    auto nearp = [&](uint32_t P) { return gx.lo + P * 8192 + ((side ^ 1 ^ __popc(P & PMASK)) & 1) * COPY; };
    constexpr uint32_t COL = 32 * 8192;
    const uint32_t ownL = (i >> 2) * HALF + (i & 3) * 1024, ownG = gx.lo + (g >> 3) * HALF + (g & 7) * 512;
    const uint32_t uPubA = uni(ownL + nearp(pairL(RA, 0, g)) + (wp >> 1) * 256 + (wp & 1) * 96), uPolA = uni(nearp(pairL(RA, 0, g)) + (wp >> 2) * HALF + (wp & 3) * 256);
    const uint32_t uPubB = uni(ownG + pairG(0, cc, i) * 8192), uPolB = uni(nearp(pairG(0, cc, i)));
    const uint32_t uPubC = uni(ownL + nearp(pairL(RC, 0, g))), uPolC = uni(nearp(pairL(RC, wp < 6 ? cc : 0, g)));
    const uint32_t uPubD = uni(ownG + pairG(1, 0, i) * 8192 + (wp < 7 ? 32 * wp : 256)), uPolD = uni(nearp(pairG(1, cc, i)));
    const uint32_t uPubE = uni(ownL + nearp(pairL(RE, 0, g))), uPolE = uni(nearp(pairL(RE, i >> 2, g)));
    const uint32_t uOS = uni(sb + S_OS + 192 * wp);
    auto xp = [&](uint32_t lo) { return (char*)XPtr(lo, gx.hi); };
    {
        const uint4 z = make_uint4(0, 0, 0, 0);
        const uint32_t c = ((tid >> 6) & 1) * COL, cp = (tid >> 7) * both, k = (tid & 63) * 16;
        *reinterpret_cast<uint4*>(xp((ownL + nearp(pairL(RA, 0, g)) + c + k) ^ cp)) = z;
        if (k < 800) { *reinterpret_cast<uint4*>(xp((uPubC + c + k) ^ cp)) = z; *reinterpret_cast<uint4*>(xp((uPubE + c + k) ^ cp)) = z; }
        if ((tid & 31) < 20) *reinterpret_cast<uint4*>(xp(ownG + pairG((tid >> 5) & 1, 0, i) * 8192 + c + (tid >> 7) * COPY + (tid & 31) * 16)) = z;
    }
#define IDS() __syncwarp(); const uint32_t z0_ = lag<1>(sb), z_ = td + z0_; const uint32_t ln = z_ & 31, q8 = ln >> 2, t4 = z_ & 3, n96 = z_ - 96 * cc, n80 = min(n96, 79u); (void)q8; (void)t4; (void)n80; (void)ln

    auto vaddr = [&](uint32_t (&voff)[3]) {
        const uint32_t ln = td & 31;
        const uint32_t key3 = 3 * ((ln & 7) + 2 * (ln & 8) + ((ln >> 1) & 8));
#pragma unroll
        for (int T = 0; T < 3; T++) {
            const uint32_t u = 3 * wp + T, r = key3 + (u >> 3);
            voff[T] = r * 128 + (((u ^ r) & 7) << 4);
        }
    };
    auto values = [&](uint32_t (&vf)[8][3][4], float (&acc)[3][4], auto step, uint32_t ps, auto col, uint32_t par) {
        constexpr int CUT = col.value ? 8 : 6;
        const uint32_t ln = td & 31, q8 = ln >> 2, t4 = td & 3;
        uint4 p = lds128(ps + 16 * ln);
        float f0 = 0.f, f1 = 0.f, r3 = 0.f, o = 0.f;
        int M = 0;
#pragma unroll
        for (int s = 0; s < 8; s++) {
            if (s == 0 || s == CUT)
#pragma unroll
                for (int k = 0; k < 12; k++) acc[k / 4][k % 4] = 0.f;
            step(s);
            const bool m = s >= CUT || (q8 >> 1) == (s >> 1);
            const uint32_t b0 = m ? ((s & 1) ? p.z : p.x) : 0u, b1 = m ? ((s & 1) ? p.w : p.y) : 0u;
#pragma unroll
            for (int T = 0; T < 3; T++) mmaA(acc[T], vf[s][T], b0, b1);
            if (s == FSTEP) {
                const uint2 mp = lds64(ps + PS_MAX + 8 * t4);
                M = __reduce_max_sync(~0u, __float2int_ru(fmaxf(asf(mp.x), asf(mp.y))));
                f0 = ex2(asf(mp.x) - (float)M); f1 = ex2(asf(mp.y) - (float)M);
                float l[4] = {};
                mma16816(l, ONES, ONES, ONES, ONES, p.x, p.y); mma16816(l, ONES, ONES, ONES, ONES, p.z, p.w);
                r3 = fmaf(f0, l[0], f1 * l[1]);
            }
            if (s == CUT - 1) {
                if (CUT < 8) p = lds128(ps + 384 + 16 * (ln & 7));
                const float r0 = fmaf(f0, acc[0][0], f1 * acc[0][3]), r1 = fmaf(f0, acc[1][0], f1 * acc[1][3]), r2 = fmaf(f0, acc[2][0], f1 * acc[2][3]);
                const bool hi = t4 & 2, od = t4 & 1;
                const float u0 = (hi ? r2 : r0) + __shfl_xor_sync(~0u, hi ? r0 : r2, 2), u1 = (hi ? r3 : r1) + __shfl_xor_sync(~0u, hi ? r1 : r3, 2);
                o = (od ? u1 : u0) + __shfl_xor_sync(~0u, od ? u0 : u1, 1);
                if (ln == 3) o = asf(2 * (uint32_t)M);
                if (CUT < 8) { f0 = __shfl_sync(~0u, f0, 3); f1 = __shfl_sync(~0u, f1, 3); }
            }
        }
        CSTAMP(25);
        const uint32_t pubA = uPubA + col.value * COL + 32 * t4 + 4 * q8;
        if (CUT < 8 && t4 < 3) o = fmaf(f0, sel4(t4, acc[0][0], acc[1][0], acc[2][0], acc[2][0]), fmaf(f1, sel4(t4, acc[0][3], acc[1][3], acc[2][3], acc[2][3]), o));
        stp32_if(t4 < 3 || ((wp & 1) && q8 < 2), both, xp(pubA ^ COPY), xp(pubA), o, par);
    };

    uint32_t left[36] = {};
#pragma unroll 1
    for (int ch = 0; ch < 5; ch++) {
        const uint32_t par0 = (ch + 1) & 1, par1 = ch & 1;
        uint32_t voff[3], vf[8][3][4];
        float acc_[3][4];
        if (ch < 4) {
            td = pin(td);
            vaddr(voff);
            mbar_wait(sb + S_SCO, par1);
            if (ch == 0) mbar_wait(sb + S_WFULL + 80, 0);
            TST(0);
            auto ldw = [&](int s) {
                mbar_wait(sb + S_FV + 8 * s, par1);
#pragma unroll
                for (int T = 0; T < 3; T++) ldsm4t(vf[s][T], voff[T] + (sb + v_place(ch, s) * SLOT));
            };
            probs(bf_lo(lds16(sb + S_SC + 2 * td)), sb + S_PS, wp, td & 31);
            ldw(0); ldw(1); ldw(2);
            bar_main();
            arrive_if(td == 0, sb + S_RELR);
            values(vf, acc_, [&](int s) {
                if (s >= 3) ldw(s);
            }, sb + S_PS, std::integral_constant<int, 0>(), par0);
            TST(1);
            CSTAMP(5);
            if (ch > 0) mbar_wait(sb + S_OS1, par0);
        } else {
#pragma unroll
            for (int s = 0; s < 36; s++) vf[s / 12][(s / 4) % 3][s & 3] = left[s];
        }
        const bool has0 = ch < 4, has1 = ch > 0;
        const bool actc = wp < 6 && (cc ? has1 : has0);
        const uint32_t parc = cc ? par1 : par0;
        const uint32_t pub0 = has0 ? par0 : 0;
        uint32_t rr, pubB;
        {
            IDS();
            const uint32_t c = ch == 4;
            const uint32_t osa = pin(uOS + 96 * c + 4 * ln), oa = pin(uOS + 48 * (q8 & 2) + 24 * t4), ra = pin(sb + S_RED + 640 * wp + 320 * (t4 & 1) + 8 * q8);
            rr = pin(sb + S_RED + 320 * cc + 4 * n80); pubB = pin(uPubB + 4 * n80);
            hop_a<1>(xp(uPolA + c * COL + 8 * min(ln, 24u) + lag<DELAY_L>(sb, z0_)), pub0, osa, ln < 24, 5 * ch);
            TST(2);
            CSTAMP(6);
            float acc[5][4] = {};
            const uint2 b0 = lds64(oa), b1 = lds64(oa + 8), b2 = lds64(oa + 16);
#pragma unroll
            for (int m = 0; m < 5; m++) mmaA(acc[m], Wo[m][0], b0.x, b0.y);
#pragma unroll
            for (int m = 0; m < 5; m++) mmaA(acc[m], Wo[m][1], b1.x, b1.y);
#pragma unroll
            for (int m = 0; m < 5; m++) mmaA(acc[m], Wo[m][2], b2.x, b2.y);
#pragma unroll
            for (int m = 0; m < 5; m++) { stsf(ra + 64 * m, acc[m][0]); stsf(ra + 64 * m + 4, acc[m][2]); }
        }
        CSTAMP(7);
        uint32_t xr, fl, pubC, pubC2;
        auto prepC = [&](uint32_t ln) {
            const uint32_t q8 = ln >> 2, t4 = ln & 3;
            xr = pin(sb + S_XB + 48 * (ln & 15));
            pubC = pin(uPubC + (t4 & 1) * COL + 192 * (wp >> 1) + 64 * (wp & 1) + 8 * q8);
            pubC2 = pin(uPubC + (t4 & 1) * COL + ((t4 & 2) ? 192 * (wp >> 1) + 128 + 4 * (wp & 1) + 8 * q8 : 768 + 2 * ((q8 + 1) & 6)));
            fl = pin(((t4 & 1) ? par1 : pub0) | (t4 >= 2 || (wp == 7 && q8 < 4 && q8 != 2 - t4) ? 2 : 0));
        };
        auto stats = [&](uint32_t xa, const uint4& b, uint32_t b4) {
            float a0[4] = {}, a1[4] = {}, a2[4] = {};
            const uint4 p0 = lds128(xa), p1 = lds128(xa + 16);
            const uint2 p2 = lds64(xa + 32);
            mmaV(a0, p0, b.x, b.y); mmaV(a1, p1, b.z, b.w); mma8(a2, p2.x, p2.y, b4);
            return ((a0[0] + a0[3]) + (a1[0] + a1[3])) + (a2[0] + a2[3]);
        };
        auto give_ln = [&](uint32_t src0, uint32_t par, uint32_t dst, uint32_t ln, float& mean, float& den, auto also) {
            const char* src = xp(src0 + 768 + (ln & 1) * HALF);
            float sx, sq;
            int guard = 0;
            bool again;
            do {
                uint2 st[4];
#pragma unroll
                for (int s = 0; s < 4; s++) st[s] = ldp64(src + s * 1024);
                again = __any_sync(~0u, ((chk4(st, par) | also()) & 1) != 0);
                sx = (asf(st[0].x) + asf(st[1].x)) + (asf(st[2].x) + asf(st[3].x)); sq = (asf(st[0].y) + asf(st[1].y)) + (asf(st[2].y) + asf(st[3].y));
                sx += __shfl_xor_sync(~0u, sx, 1); sq += __shfl_xor_sync(~0u, sq, 1);
            } while (again & (++guard < SPIN_LIMIT));
            ln_stats(sx, sq, mean, den);
            stsvol64(dst, __byte_perm(__float_as_uint(den), __float_as_uint(mean), 0x7632), (__float_as_uint(rcp(den)) & ~7u) | (ch + 1));
        };
        auto take_ln = [&](uint2& c, uint32_t a) { int k = 0; do c = ldsvol64(a); while (__any_sync(~0u, (c.y & 7) != ch + 1) & (++k < SPIN_FAST)); };
        {
            auto gate_up = [&](auto with_stats) {
                bar_main();
                TST(3);
                CSTAMP(11);
                const uint4 b = lds128(xr);
                uint32_t b4 = lds32(xr + 16);
                float acc[3][4] = {};
                if (with_stats.value) {
                    stp32_if(fl > 1 && !(td & 2), both, xp(pubC2 ^ COPY), xp(pubC2), stats(xr + (S_XA - S_XB), b, b4), fl & 1);
                    __syncwarp();
                    b4 = lds32(xr + 16);
                }
                mul80(acc, Wgu, b, b4);
                stp64_if(!(td & 2), both, xp(pubC ^ COPY), xp(pubC), tagw(acc[0][0] + acc[0][3], fl & 1), tagw(acc[1][0] + acc[1][3], fl & 1));
                stp32_if(td & 2, both, xp(pubC2 ^ COPY), xp(pubC2), acc[2][0] + acc[2][3], fl & 1);
            };
            if (wp == 7) {
                bar_main();
                IDS();
                prepC(ln);
                sts32(sb + S_ZERO + 4, or3(pubC, pubC2, fl));
                gate_up(std::true_type());
            } else {
                if (actc) {
                    bar_main();
                    CSTAMP(8);
                    uint32_t r[8];
#pragma unroll
                    for (int s = 0; s < 8; s++) r[s] = lds32(rr + 640 * s);
                    stp32_if(true, xp(pubB), sum8(r), parc);
                    CSTAMP(9);
                    IDS();
                    prepC(ln);
                    const uint32_t n4 = 4 * n80;
                    const uint32_t xas = pin(sb + S_XA + 192 + 192 * cc + a_pos(n80)), xbs = pin(sb + S_XB + 384 * cc + b_pos<40>(n80));
                    const float x0 = cc ? ldsf(sb + S_XCAR + n4) : bf_lo(lds16(sb + S_X0 + 160 * (ch & 3) + n4 / 2));
                    gather16(xp(uPolB + n4 + lag<DELAY_G>(sb, z0_)), parc, 5 * ch + 1, [&](float y, uint32_t) {
                        const uint32_t x = pack2(x0 + bfr(y), 0.f);
                        sts16(xbs, x);
                        sts16(xas, x);
                        return 0u;
                    });
                    CSTAMP(10);
                } else {
                    bar_main();
                    IDS();
                    prepC(ln);
                }
                gate_up(std::false_type());
            }
        }
        CSTAMP(12);
        float mean = 0.f, den = 1.f;
        {
            IDS();
            const uint32_t wh = pin((((ln & 7) + 48 * ((ln >> 3) & 1) + 8 * (ln >> 4)) * 160 + (wp < 7 ? 16 * wp : 128)) | ((384 * cc + b_pos<48>(n96)) << 16));
            const uint32_t pubD = pin(uPubD + (t4 & 1) * COL + 16 * (t4 & 2) + 4 * q8 + (fl & 1)), ha = xr + (S_HS - S_XB);
            auto down = [&](const uint32_t (&W)[3][4], const uint4& h0, const uint2& h1) {
                float a0[4] = {}, a1[4] = {}, a2[4] = {};
                mmaA(a0, W[0], h0.x, h0.y); mmaA(a1, W[1], h0.z, h0.w); mmaA(a2, W[2], h1.x, h1.y);
                return ((a0[0] + a0[3]) + (a1[0] + a1[3])) + (a2[0] + a2[3]);
            };
            if (wp < 6) {
                uint32_t Wd[3][4];
                auto ldd = [&](uint32_t z) {
#pragma unroll
                    for (int s = 0; s < 3; s++) ldsm4t(Wd[s], ((wh ^ z) & 0xffff) + (sb + S_WD + s * 2560));
                };
                ldd(0);
                if (actc) {
                    const char* srcv = xp(uPolC + lag<DELAY_C>(sb, z0_) + 8 * n96);
                    const uint2 cs = lds64(sb + S_CSGU + 8 * n96);
                    float gt, up;
                    int guard = 0;
                    while (true) {
                        uint2 v[8];
#pragma unroll
                        for (int s = 0; s < 8; s++) v[s] = ldp64(srcv + (s >> 2) * HALF + (s & 3) * 1024);
                        uint2 c = ldsvol64(sb + S_LN + 8 * cc + ((v[0].x ^ parc) & 1) * 32);
                        const bool stale = __any_sync(~0u, ((chk8(v, parc) | chk8y(v, parc)) & 1) != 0), late = __any_sync(~0u, (c.y & 7) != ch + 1);
                        const float pg = sum8x(v), pu = sum8y(v);
                        auto norm = [&] {
                            mean = bf_hi(c.x); den = bf_lo(c.x);
                            gt = bfr(fmaf(-mean, asf(cs.x), pg) * asf(c.y)); up = fmaf(-mean, asf(cs.y), pu) * asf(c.y);
                            keep(gt); keep(up);
                        };
                        norm();
                        if (!((stale | late) & (++guard < SPIN_LIMIT))) break;
                        if (!stale) { take_ln(c, sb + S_LN + 8 * cc); norm(); break; }
                    }
                    CSTAMP(13);
                    SWEEPS(5 * ch + 2, guard - 1);
                    const uint32_t h = pack2(bfr(gt * sigmoidf_(gt)) * bfr(up), 0.f);
                    sts16((wh >> 16) + (sb + S_HS), h);
                    CSTAMP(14);
                    if (ch == 3) CSTAMP(0);
                }
                bar_main();
                TST(4);
                CSTAMP(15);
                const uint4 h0 = lds128(ha);
                const uint2 h1 = lds64(ha + 16);
                stp32_if(!(td & 2), xp(pubD & ~1u), down(Wd, h0, h1), pubD & 1);
            } else {
                uint32_t v = 0;
                const uint32_t col = wp == 7 || !has0;
                const bool serve = wp == 6 || (has0 && has1);
                if (serve) {
                    const uint32_t par = col ? par1 : par0;
                    const char* src = xp(uPolC + col * COL + 776 + (td & 4) * (HALF / 4) + (td & 3) * 1024);
                    give_ln(uPolC + col * COL, par, sb + S_LN + 8 * col, td, mean, den, [&] { v = ldp32(src); return v ^ par; });
                }
                stsvol(sb + S_GATE, ch + 1);
                uint32_t Wd[2][3][4];
#pragma unroll
                for (int s = 0; s < 6; s++) ldsm4t(Wd[s / 3][s % 3], (wh & 0xffff) + (sb + S_WD + (s / 3) * 16 + (s % 3) * 2560));
                bar_main();
                const uint4 h0 = lds128(ha);
                const uint2 h1 = lds64(ha + 16);
                const float d0 = down(Wd[0], h0, h1), d1 = down(Wd[1], h0, h1);
                stp32_if(true, xp(pubD & ~1u), (td & 2) ? d1 : d0, pubD & 1);
                if (serve) {
                    float xw = asf(v);
                    xw += __shfl_xor_sync(~0u, xw, 1); xw += __shfl_xor_sync(~0u, xw, 2); xw += __shfl_xor_sync(~0u, xw, 4);
                    const float r = bfr(fmaf(-mean, ldsf(sb + S_SWR), xw) * rcp(den));
                    sts32(sb + S_STAT + 4 * col, __float_as_uint(bfr(sigmoidf_(r))) | (ch + 1));
                }
            }
        }
        CSTAMP(16);
        {
            IDS();
            const uint32_t pubE = pin(uPubE + (t4 < 3 ? (wp >> 2) * COL + 192 * (wp & 3) + 64 * t4 + 8 * q8 : (q8 >> 2) * COL + 768 + 4 * (q8 & 1)));
            xr = pin(sb + S_XB + 48 * (ln & 7));
            uint32_t x2 = 0;
            auto hop_d = [&](auto col) {
                const uint32_t xbs = pin(sb + S_XB + 384 * col.value + b_pos<40>(n80)), xas = col.value ? 0 : pin(sb + S_XA + 192 + a_pos(n80));
                const float x1 = bf_lo(lds16(xbs));
                const float lnx = __uint_as_float(pin(__float_as_uint(bfr(__fdiv_rn(bfr(x1 - mean), den)))));
                gather16(xp(uPolD + 4 * n80 + lag<DELAY_D>(sb, z0_)), col.value ? par1 : par0, 5 * ch + 3, [&](float y, uint32_t z) {
                    const uint32_t gate = ldsvol(sb + S_STAT + 4 * col.value + z);
                    x2 = pack2(x1 + bfr(lnx + bfr(bfr(y) * bf_hi(gate))), 0.f);
                    if (col.value) keep(x2); else { sts16(xbs, x2); sts16(xas, x2); }
                    return (uint32_t)((gate & 7) != ch + 1);
                });
                CSTAMP(17);
            };
            auto qproj = [&](auto with_stats) {
                bar_main();
                TST(5);
                CSTAMP(19);
                const uint32_t t4 = td & 3;
                const uint4 b = lds128(xr);
                uint32_t b4 = lds32(xr + 16);
                float acc[6][4] = {};
                if (with_stats.value) {
                    stp32_if((td & 11) == 3, both, xp(pubE ^ COPY), xp(pubE), stats(xr + (S_XA - S_XB), b, b4), par0);
                    __syncwarp();
                    b4 = lds32(xr + 16);
                }
                mul80(acc, Wq, b, b4);
                const float v0 = sel4(t4, acc[0][0] + acc[0][3], acc[2][0] + acc[2][3], acc[4][0] + acc[4][3], acc[4][0] + acc[4][3]);
                const float v1 = sel4(t4, acc[1][0] + acc[1][3], acc[3][0] + acc[3][3], acc[5][0] + acc[5][3], acc[5][0] + acc[5][3]);
                stp64_if(t4 < 3, both, xp(pubE ^ COPY), xp(pubE), tagw(v0, par0), tagw(v1, par0));
            };
            if (wp == 7) {
                if (!has0) break;
                qproj(std::true_type());
            } else {
                if (actc && !cc) hop_d(std::integral_constant<int, 0>());
                else {
                    if (actc && g == 0) {
                        const uint32_t po = pin(1280 * (ch - 1) + 160 * i + 2 * n80);
                        hop_d(std::integral_constant<int, 1>());
                        *reinterpret_cast<unsigned short*>(reinterpret_cast<char*>(P.out) + po) = (unsigned short)x2;
                    }
                    if (!has0) break;
                }
                qproj(std::false_type());
                sts32_if(td < 80, sb + S_XCAR + 4 * td, x2 << 16);
            }
        }
        CSTAMP(20);
        if (wp == 6) give_ln(uPolE, par0, sb + S_LN + 16, td, mean, den, [] { return 0u; });
        auto pass2 = [&](auto d0, auto d1, auto d2) {
            constexpr int D0 = d0.value, D1 = d1.value, D = D0 + D1 + d2.value;
            IDS();
            const uint32_t ua = sb + k_place(ch, wp & 6) * SLOT + (wp & 1) * UNIT, k0 = k_off(ln);
            uint32_t kf[12][2][4];
            auto ldk = [&](int s) { const uint32_t a = (k0 ^ (32 * (s / 3))) + (ua + 1024 * (s % 3)); ldsm4(kf[s][0], a); ldsm4(kf[s][1], a + SLOT); };
            auto ldv1 = [&](int k) { ldsm4t(vf[k / 3][k % 3], voff[k % 3] + (sb + v_place(ch, k / 3) * SLOT)); };
            auto ldv = [&](int s) { ldv1(3 * s); ldv1(3 * s + 1); ldv1(3 * s + 2); };
            constexpr uint32_t LATE = LAST_LATE;
            constexpr uint64_t EARLY_LIST = bit_list(~LATE), LATE_LIST = bit_list(LATE);
            auto early = [&](int k) {
                if (D1 == 0) ldk(k);
                else if (k < 3) { ldv1(9 + 2 * k); ldv1(10 + 2 * k); }
                else ldk((EARLY_LIST >> (4 * (k - 3))) & 15);
            };
            uint32_t v[8] = {}, qsa = 0;
            const char* srcv = xp(uPolE + lag<(D1 > 0 ? 0 : DELAY_E)>(sb, z0_) + 4 * td);
            auto look = [&] {
#pragma unroll
                for (int s = 0; s < 8; s++) v[s] = ldp32(srcv + (s >> 2) * HALF + (s & 3) * 1024);
            };
            if (D1 > 0) vaddr(voff);
            if (!(mbar_try(sb + S_FK + 8 * (wp & 6), par1) & mbar_try(sb + S_FK + 8 * (wp | 1), par1))) { mbar_wait(sb + S_FK + 8 * (wp & 6), par1); mbar_wait(sb + S_FK + 8 * (wp | 1), par1); }
#pragma unroll
            for (int s = 0; s < D0; s++) early(s);
            if (wp < 6) { look(); qsa = pin(sb + S_QS + 384 * ch + q_pos(z_)); }
#pragma unroll
            for (int s = D0; s < D0 + D1; s++) early(s);
            if (wp < 6) {
                const float cs = ldsf(sb + S_CSQ + 4 * td);
                int guard = 0;
                while (true) {
                    uint2 c = ldsvol64(sb + S_LN + 16 + ((v[0] ^ par0) & 1) * 32);
                    const bool stale = __any_sync(~0u, (chk8(v, par0) & 1) != 0), late = __any_sync(~0u, (c.y & 7) != ch + 1);
                    const float qs = sum8(v);
                    auto norm = [&] {
                        const uint32_t q = pack2(fmaf(-bf_hi(c.x), cs, qs) * asf(c.y), 0.f);
                        sts16(qsa, q);
                    };
                    norm();
                    if (!((stale | late) & (++guard < SPIN_LIMIT))) break;
                    if (!stale) { take_ln(c, sb + S_LN + 16); norm(); break; }
                    look();
                }
                SWEEPS(5 * ch + 4, guard - 1);
                CSTAMP(22);
            }
#pragma unroll
            for (int s = D0 + D1; s < D; s++) early(s);
            CSTAMP(21);
            bar_main();
            TST(6);
            CSTAMP(1);
            uint2 q = lds64(sb + S_QS + 384 * ch + 8 * ln);
            float acc[2][4] = {};
            constexpr int V0 = 13 - D, NV = D1 > 0 ? 2 : (2 * (D - 1)) / 3;
            static_assert(D1 == 0 || D - 3 + __builtin_popcount(LATE) == 12, "plan");
#pragma unroll
            for (int s = 0; s < 12; s++) {
                const bool m = q8 == (s & 7);
                const uint32_t b0 = m ? q.x : 0u, b1 = m ? q.y : 0u;
                if (s == 7) q = lds64(sb + S_QS + 384 * ch + 8 * ln + 256);
                mmaA(acc[0], kf[s][0], b0, b1);
                mmaA(acc[1], kf[s][1], b0, b1);
                if (D1 > 0) {
                    if (s >= 1 && s <= __builtin_popcount(LATE)) ldk((LATE_LIST >> (4 * (s - 1))) & 15);
                } else {
                    if (s >= 1 && s + D - 1 < 12) ldk(s + D - 1);
                    if (s >= 1 && s + D - 1 == 11) { __syncwarp(); arrive_if(ln == 0, sb + S_RELK); }
                    if (s == V0) vaddr(voff);
                    if (s >= V0 && 2 * (s - V0) < 3 * NV) ldv1(9 + 2 * (s - V0));
                    if (s >= V0 && 2 * (s - V0) + 1 < 3 * NV) ldv1(10 + 2 * (s - V0));
                }
            }
            CSTAMP(24);
            {
                const float v0 = acc[0][0] + acc[0][1], v1 = acc[0][2] + acc[0][3], v2 = acc[1][0] + acc[1][1], v3 = acc[1][2] + acc[1][3];
                const bool hi = t4 & 2, od = t4 & 1;
                const float u0 = (hi ? v2 : v0) + __shfl_xor_sync(~0u, hi ? v0 : v2, 2), u1 = (hi ? v3 : v1) + __shfl_xor_sync(~0u, hi ? v1 : v3, 2);
                const float s = (od ? u1 : u0) + __shfl_xor_sync(~0u, od ? u0 : u1, 1);
                CSTAMP(2);
                probs(scaled(s), sb + S_PS + PS_PASS, wp, ln);
                CSTAMP(3);
            }
            bar_main();
            TST(10);
            CSTAMP(4);
            if (D1 > 0) values(vf, acc_, [&](int s) { if (s < 3) ldv(s + 5); }, sb + S_PS + PS_PASS, std::integral_constant<int, 1>(), par0);
            else values(vf, acc_, [&](int s) { if (s >= (NV > 1 ? 2 : 1) && s + NV + (NV > 1 ? 1 : 2) < 8) ldv(s + NV + (NV > 1 ? 1 : 2)); }, sb + S_PS + PS_PASS, std::integral_constant<int, 1>(), par0);
            arrive_if(ln == 0, sb + S_RELV);
        };
        if (ch == 3) {
            pass2(std::integral_constant<int, LAST0>(), std::integral_constant<int, LAST1>(), std::integral_constant<int, LAST2>());
#pragma unroll
            for (int m = 0; m < 48; m++) Wq[m / 8].a[(m / 4) % 2][m % 4] = vf[3 + m / 12][(m / 4) % 3][m % 4];
#pragma unroll
            for (int m = 0; m < 12; m++) Wq[m / 2].c[m % 2] = vf[7][m / 4][m % 4];
#pragma unroll
            for (int m = 0; m < 36; m++) left[m] = m < 12 ? __float_as_uint(acc_[m / 4][m % 4]) : vf[m / 12][(m / 4) % 3][m % 4];
        } else {
            pass2(std::integral_constant<int, KPRE>(), std::integral_constant<int, 0>(), std::integral_constant<int, KPRE2>());
#pragma unroll
            for (int m = 0; m < 36; m++) left[m] = m < 12 ? __float_as_uint(acc_[m / 4][m % 4]) : vf[4 + m / 12][(m / 4) % 3][m % 4];
        }
        TST(11);
        CSTAMP(23);
    }
    sts32_if(td == 255, sb + S_GATE, 6);
    TSTAMP(3);
}

typedef CUresult (*EncodeFn)(CUtensorMap*, CUtensorMapDataType, cuuint32_t, void*, const cuuint64_t*, const cuuint64_t*, const cuuint32_t*,
                             const cuuint32_t*, CUtensorMapInterleave, CUtensorMapSwizzle, CUtensorMapL2promotion, CUtensorMapFloatOOBfill);

void make_map(EncodeFn enc, CUtensorMap* m, const void* base, uint64_t cols, uint64_t rows, uint32_t box_cols, uint32_t box_rows, bool swizzle) {
    cuuint64_t dims[2] = {cols, rows};
    cuuint64_t strides[1] = {cols * 2};
    cuuint32_t box[2] = {box_cols, box_rows};
    cuuint32_t es[2] = {1, 1};
    enc(m, CU_TENSOR_MAP_DATA_TYPE_BFLOAT16, 2, const_cast<void*>(base), dims, strides, box, es, CU_TENSOR_MAP_INTERLEAVE_NONE,
        swizzle ? CU_TENSOR_MAP_SWIZZLE_128B : CU_TENSOR_MAP_SWIZZLE_NONE, CU_TENSOR_MAP_L2_PROMOTION_NONE, CU_TENSOR_MAP_FLOAT_OOB_FILL_NONE);
}

}

extern "C" void kernel_launch(void* const* d_in, const int* in_sizes, int n_in, void* d_out, int out_size) {
    (void)in_sizes; (void)n_in; (void)out_size;
    static EncodeFn enc = nullptr;
    if (!enc) {
        void* f = nullptr;
        cudaDriverEntryPointQueryResult q;
        cudaGetDriverEntryPoint("cuTensorMapEncodeTiled", &f, cudaEnableDefault, &q);
        enc = (EncodeFn)f;
        cudaFuncSetAttribute(fused_kernel, cudaFuncAttributeMaxDynamicSharedMemorySize, SMEM_BYTES);
    }
    Params P;
    P.x = (const __nv_bfloat16*)d_in[0]; P.k = (const __nv_bfloat16*)d_in[1]; P.v = (const __nv_bfloat16*)d_in[2];
    P.wr = (const __nv_bfloat16*)d_in[6]; P.wq = (const __nv_bfloat16*)d_in[3];
    P.out = (__nv_bfloat16*)d_out;
    Maps M;
    {
        cuuint64_t dims[4] = {64, 8, 3, (cuuint64_t)KV_BATCH_KEYS / 2}, strides[3] = {384, 128, 3072};
        cuuint32_t box[4] = {64, 8, 3, 2}, es[4] = {1, 1, 1, 1};
        enc(&M.k, CU_TENSOR_MAP_DATA_TYPE_BFLOAT16, 4, d_in[1], dims, strides, box, es, CU_TENSOR_MAP_INTERLEAVE_NONE, CU_TENSOR_MAP_SWIZZLE_128B,
            CU_TENSOR_MAP_L2_PROMOTION_NONE, CU_TENSOR_MAP_FLOAT_OOB_FILL_NONE);
    }
    make_map(enc, &M.v, P.v, 64, (uint64_t)12 * KV_BATCH_KEYS, 64, 96, true);
    make_map(enc, &M.vu, P.v, 64, (uint64_t)12 * KV_BATCH_KEYS, 64, 48, true);
    make_map(enc, &M.wq, d_in[3], 6144, 640, 192, 40, false);
    make_map(enc, &M.wo, d_in[4], 640, 6144, 80, 96, false);
    make_map(enc, &M.wg, d_in[7], 1536, 640, 96, 80, false);
    make_map(enc, &M.wu, d_in[8], 1536, 640, 96, 80, false);
    make_map(enc, &M.wd, d_in[9], 640, 1536, 80, 96, false);
    fused_kernel<<<NCTA, NTHR, SMEM_BYTES, cudaStreamPerThread>>>(P, M);
}
```

```cpp
#include <cuda_runtime.h>
#include <cuda.h>
#include <cuda_bf16.h>
#include <stdint.h>
#include <type_traits>

namespace {

constexpr int NCTA = 128;
constexpr int NTHR = 384;
constexpr int UNIT = 6144;
constexpr int SLOT = 12288;
#define TAU 3880
#define TAUW 3700
#define TAU0 3780
#define ILV 4
#define XB 900
#define FORCE_BOTH 0
#define TMIN 2400
#define SLACK 6000
#define SLACK0 1000
#define LEADW 3500
#define WIN_W 3
#define WIN_S 4
#define WIN_U 10
#define VPF 4
#define KRE_TAU 2600
#define RFR_TAU 22400
#define HOP1_NS 200
#define KPRE 2
#define KPRE2 2
#define LAST0 4
#define LAST1 4
#define LAST2 2
#define LAST_LATE 0xaa8
#define FSTEP 4
#define DELAY_L 1
#define DELAY_G 2
#define DELAY_C 0
#define DELAY_D 4
#define DELAY_E 3
#define REG_LO "40"
#define REG_HI "232"
#define SPIN_LOG 17
constexpr int SPIN_LIMIT = 1 << SPIN_LOG, SPIN_FAST = SPIN_LIMIT << 4;

__host__ __device__ constexpr uint32_t pairL(uint32_t region, uint32_t c, uint32_t g) { return (g & 1) | ((g >> 1) << 2) | (c << 5) | (region << 6); }
__host__ __device__ constexpr uint32_t pairG(uint32_t d, uint32_t c, uint32_t i) { return (i & 1) | ((i >> 1) << 2) | (d << 4) | (c << 5) | (3u << 6); }
constexpr uint32_t RA = 0, RC = 1, RE = 2, HALF = 16384, COPY = 4096, PMASK = 0x59;
constexpr uint32_t XS = 0;
constexpr uint32_t XS2 = XS + 128 * 7680;
constexpr uint32_t XSEND = XS2 + 128 * 768;
__device__ uint4 g_s[XSEND / 16];
__device__ uint4 g_x[(4u << 20) / 16];
#define SWEEPS(k, n) do {} while (0)

constexpr uint32_t S_WD = 16 * SLOT;
constexpr uint32_t S_DUMMY = S_WD + 15360;
constexpr uint32_t S_BAR = S_DUMMY + 4096;
constexpr uint32_t S_FV = S_BAR, S_FK = S_FV + 64, S_RING = S_FK + 64, S_DBAR = S_RING + 48, S_WFULL = S_DBAR + 32, S_QRDY = S_WFULL + 88;
constexpr uint32_t S_RELK = S_QRDY + 8, S_RELV = S_RELK + 8, S_RELR = S_RELV + 8, S_RELW = S_RELR + 8, S_SCO = S_RELW + 24;
constexpr uint32_t S_OS1 = S_SCO + 8;
constexpr uint32_t S_ZERO = S_OS1 + 8;
constexpr uint32_t S_KF = S_ZERO + 8;
constexpr uint32_t S_TOK = S_KF + 8;
constexpr uint32_t S_SIDE = S_TOK + 80, S_GATE = S_SIDE + 4;
constexpr uint32_t S_STAT = S_GATE + 12, S_SWR = S_STAT + 16;
constexpr uint32_t S_LN = S_STAT + 32;
constexpr uint32_t S_XCAR = S_LN + 64;
constexpr uint32_t S_CSQ = S_XCAR + 320;
constexpr uint32_t S_CSGU = S_CSQ + 768;
constexpr uint32_t S_RED = S_CSGU + 768;
constexpr uint32_t S_L0 = S_RED;
constexpr uint32_t S_OS = S_RED + 5120;
constexpr uint32_t S_PS = S_OS + 1536;
constexpr uint32_t PS_MAX = 512, PS_PASS = 544;
constexpr uint32_t S_QS = S_PS + 2 * PS_PASS;
constexpr uint32_t S_XB = S_QS + 1536;
constexpr uint32_t S_XA = S_XB + 768;
constexpr uint32_t S_HS = S_XA + 768;
constexpr uint32_t S_X0 = S_HS + 768;
constexpr uint32_t S_SC = S_X0 + 640;
constexpr uint32_t S_TM = S_SC + 512;
constexpr int SMEM_BYTES = S_TM + 256;
static_assert(SMEM_BYTES <= 232448 && S_STAT % 16 == 0 && S_RED % 16 == 0 && S_XB % 16 == 0 && S_HS % 16 == 0 && S_PS % 16 == 0 && S_QS % 16 == 0, "smem");
static_assert(S_SCO == S_BAR + 44 * 8 && S_RELK == S_BAR + 38 * 8, "barriers");
constexpr uint32_t ST_WQ = 3 * SLOT, ST_WG = 8 * SLOT, ST_WO = 11 * SLOT;

__device__ __forceinline__ uint32_t smem_u32(const void* p) { return (uint32_t)__cvta_generic_to_shared(p); }
__device__ __forceinline__ void mbar_arrive(uint32_t bar) { asm volatile("mbarrier.arrive.shared::cta.b64 _, [%0];" :: "r"(bar) : "memory"); }
__device__ __forceinline__ bool mbar_try(uint32_t bar, uint32_t parity) {
    uint32_t ok;
    asm volatile("{\n .reg .pred p;\n mbarrier.try_wait.parity.shared::cta.b64 p, [%1], %2;\n selp.u32 %0, 1, 0, p;\n}" : "=r"(ok) : "r"(bar), "r"(parity) : "memory");
    return ok != 0;
}
__device__ __forceinline__ bool mbar_test(uint32_t bar, uint32_t parity) {
    uint32_t ok;
    asm volatile("{\n .reg .pred p;\n mbarrier.test_wait.parity.shared::cta.b64 p, [%1], %2;\n selp.u32 %0, 1, 0, p;\n}" : "=r"(ok) : "r"(bar), "r"(parity) : "memory");
    return ok != 0;
}
__device__ __forceinline__ void mbar_wait(uint32_t bar, uint32_t parity) {
    int n = 0;
    while (!mbar_try(bar, parity) && ++n < SPIN_LIMIT) {}
}
__device__ __forceinline__ uint32_t gtime32() { uint32_t t; asm volatile("mov.u32 %0, %globaltimer_lo;" : "=r"(t)); return t; }
__device__ __forceinline__ void bar_main() { asm volatile("bar.sync 1, 256;" ::: "memory"); }

__device__ __forceinline__ void mma16816(float (&c)[4], uint32_t a0, uint32_t a1, uint32_t a2, uint32_t a3, uint32_t b0, uint32_t b1) {
    asm("mma.sync.aligned.m16n8k16.row.col.f32.bf16.bf16.f32 {%0,%1,%2,%3}, {%4,%5,%6,%7}, {%8,%9}, {%0,%1,%2,%3};"
        : "+f"(c[0]), "+f"(c[1]), "+f"(c[2]), "+f"(c[3]) : "r"(a0), "r"(a1), "r"(a2), "r"(a3), "r"(b0), "r"(b1));
}
__device__ __forceinline__ void mmaA(float (&c)[4], const uint32_t (&a)[4], uint32_t b0, uint32_t b1) { mma16816(c, a[0], a[1], a[2], a[3], b0, b1); }
__device__ __forceinline__ void mma8(float (&c)[4], uint32_t a0, uint32_t a1, uint32_t b0) {
    asm("mma.sync.aligned.m16n8k8.row.col.f32.bf16.bf16.f32 {%0,%1,%2,%3}, {%4,%5}, {%6}, {%0,%1,%2,%3};"
        : "+f"(c[0]), "+f"(c[1]), "+f"(c[2]), "+f"(c[3]) : "r"(a0), "r"(a1), "r"(b0));
}
struct W80 { uint32_t a[2][4], c[2]; };
template <int N> __device__ __forceinline__ void mul80(float (&acc)[N][4], const W80 (&W)[N], const uint4& b, uint32_t b4) {
#pragma unroll
    for (int m = 0; m < N; m++) mmaA(acc[m], W[m].a[0], b.x, b.y);
#pragma unroll
    for (int m = 0; m < N; m++) mmaA(acc[m], W[m].a[1], b.z, b.w);
#pragma unroll
    for (int m = 0; m < N; m++) mma8(acc[m], W[m].c[0], W[m].c[1], b4);
}
__device__ __forceinline__ void ldsm2t(uint32_t (&r)[2], uint32_t addr) {
    asm volatile("ldmatrix.sync.aligned.m8n8.x2.trans.shared.b16 {%0,%1}, [%2];" : "=r"(r[0]), "=r"(r[1]) : "r"(addr) : "memory");
}
__device__ __forceinline__ void mmaV(float (&c)[4], const uint4& a, uint32_t b0, uint32_t b1) { mma16816(c, a.x, a.y, a.z, a.w, b0, b1); }
__device__ __forceinline__ void ldsm4(uint32_t (&r)[4], uint32_t addr) {
    asm volatile("ldmatrix.sync.aligned.m8n8.x4.shared.b16 {%0,%1,%2,%3}, [%4];" : "=r"(r[0]), "=r"(r[1]), "=r"(r[2]), "=r"(r[3]) : "r"(addr) : "memory");
}
__device__ __forceinline__ void ldsm4t(uint32_t (&r)[4], uint32_t addr) {
    asm volatile("ldmatrix.sync.aligned.m8n8.x4.trans.shared.b16 {%0,%1,%2,%3}, [%4];" : "=r"(r[0]), "=r"(r[1]), "=r"(r[2]), "=r"(r[3]) : "r"(addr) : "memory");
}
__device__ __forceinline__ uint32_t lds16(uint32_t a) { uint16_t v; asm volatile("ld.shared.u16 %0, [%1];" : "=h"(v) : "r"(a) : "memory"); return v; }
__device__ __forceinline__ uint32_t lds32(uint32_t a) { uint32_t v; asm volatile("ld.shared.u32 %0, [%1];" : "=r"(v) : "r"(a) : "memory"); return v; }
__device__ __forceinline__ float ldsf(uint32_t a) { return __uint_as_float(lds32(a)); }
__device__ __forceinline__ uint2 lds64(uint32_t a) { uint2 v; asm volatile("ld.shared.v2.u32 {%0,%1}, [%2];" : "=r"(v.x), "=r"(v.y) : "r"(a) : "memory"); return v; }
__device__ __forceinline__ uint4 lds128(uint32_t a) { uint4 v; asm volatile("ld.shared.v4.u32 {%0,%1,%2,%3}, [%4];" : "=r"(v.x), "=r"(v.y), "=r"(v.z), "=r"(v.w) : "r"(a) : "memory"); return v; }
__device__ __forceinline__ int ldsvol(uint32_t a) { int v; asm volatile("ld.volatile.shared.u32 %0, [%1];" : "=r"(v) : "r"(a) : "memory"); return v; }
__device__ __forceinline__ uint2 ldsvol64(uint32_t a) { uint2 v; asm volatile("{\n .reg .b64 d;\n ld.volatile.shared.b64 d, [%2];\n mov.b64 {%0,%1}, d;\n}" : "=r"(v.x), "=r"(v.y) : "r"(a) : "memory"); return v; }
__device__ __forceinline__ void stsvol64(uint32_t a, uint32_t x, uint32_t y) { asm volatile("{\n .reg .b64 d;\n mov.b64 d, {%1,%2};\n st.volatile.shared.b64 [%0], d;\n}" :: "r"(a), "r"(x), "r"(y) : "memory"); }
__device__ __forceinline__ void stsvol(uint32_t a, int v) { asm volatile("st.volatile.shared.u32 [%0], %1;" :: "r"(a), "r"(v) : "memory"); }
__device__ __forceinline__ void sts_hi16(uint32_t a, float v) { asm volatile("{\n .reg .b16 lo, hi;\n mov.b32 {lo, hi}, %1;\n st.shared.u16 [%0], hi;\n}" :: "r"(a), "r"(__float_as_uint(v)) : "memory"); }
__device__ __forceinline__ void sts16(uint32_t a, uint32_t v) { asm volatile("st.shared.u16 [%0], %1;" :: "r"(a), "r"(v) : "memory"); }
__device__ __forceinline__ void sts32(uint32_t a, uint32_t v) { asm volatile("st.shared.u32 [%0], %1;" :: "r"(a), "r"(v) : "memory"); }
__device__ __forceinline__ void stsf(uint32_t a, float v) { sts32(a, __float_as_uint(v)); }
__device__ __forceinline__ void sts64(uint32_t a, uint32_t x, uint32_t y) { asm volatile("st.shared.v2.u32 [%0], {%1,%2};" :: "r"(a), "r"(x), "r"(y) : "memory"); }

__device__ __forceinline__ void sts32_if(bool p, uint32_t a, uint32_t v) {
    asm volatile("{\n .reg .pred p;\n setp.ne.u32 p, %2, 0;\n @p st.shared.u32 [%0], %1;\n}" :: "r"(a), "r"(v), "r"((uint32_t)p) : "memory");
}
__device__ __forceinline__ void arrive_if(bool p, uint32_t bar) {
    asm volatile("{\n .reg .pred p;\n setp.ne.u32 p, %1, 0;\n @p mbarrier.arrive.shared::cta.b64 _, [%0];\n}" :: "r"(bar), "r"((uint32_t)p) : "memory");
}
__device__ __forceinline__ void keep(uint32_t& v) { asm volatile("" : "+r"(v)); }
__device__ __forceinline__ void keep(float& v) { asm volatile("" : "+f"(v)); }

__device__ __forceinline__ uint32_t ldp32(const char* p) { uint32_t v; asm volatile("ld.relaxed.gpu.global.u32 %0, [%1];" : "=r"(v) : "l"(p) : "memory"); return v; }
__device__ __forceinline__ uint2 ldp64(const char* p) {
    uint2 v; asm volatile("{\n .reg .b64 d;\n ld.relaxed.gpu.global.b64 d, [%2];\n mov.b64 {%0,%1}, d;\n}" : "=r"(v.x), "=r"(v.y) : "l"(p) : "memory"); return v;
}
__device__ __forceinline__ uint32_t tagw(float f, uint32_t par) { return (__float_as_uint(f) & ~31u) | par; }
__device__ __forceinline__ void stp32(char* p, float a, uint32_t par) { asm volatile("st.relaxed.gpu.global.u32 [%0], %1;" :: "l"(p), "r"(tagw(a, par)) : "memory"); }
__device__ __forceinline__ void stp64(char* p, float a, float b, uint32_t par) {
    asm volatile("{\n .reg .b64 d;\n mov.b64 d, {%1,%2};\n st.relaxed.gpu.global.b64 [%0], d;\n}" :: "l"(p), "r"(tagw(a, par)), "r"(tagw(b, par)) : "memory");
}
__device__ __forceinline__ void stp32_if(bool p, char* d, float a, uint32_t par) {
    asm volatile("{\n .reg .pred p;\n setp.ne.u32 p, %2, 0;\n @p st.relaxed.gpu.global.u32 [%0], %1;\n @p st.relaxed.gpu.global.u32 [%0+4096], %1;\n}" :: "l"(d), "r"(tagw(a, par)), "r"((uint32_t)p) : "memory");
}
__device__ __forceinline__ void stp32_if(bool p, uint32_t both, char* d, char* e, float a, uint32_t par) {
    asm volatile("{\n .reg .pred p, q;\n setp.ne.u32 p, %2, 0;\n setp.ne.and.u32 q, %4, 0, p;\n @p st.relaxed.gpu.global.u32 [%3], %1;\n @q st.relaxed.gpu.global.u32 [%0], %1;\n}" :: "l"(d), "r"(tagw(a, par)), "r"((uint32_t)p), "l"(e), "r"(both) : "memory");
}
__device__ __forceinline__ void stp64_if(bool p, uint32_t both, char* d, char* e, uint32_t lo, uint32_t hi) {
    asm volatile("{\n .reg .pred p, q;\n .reg .b64 d;\n setp.ne.u32 p, %3, 0;\n setp.ne.and.u32 q, %5, 0, p;\n mov.b64 d, {%1,%2};\n @p st.relaxed.gpu.global.b64 [%4], d;\n @q st.relaxed.gpu.global.b64 [%0], d;\n}" :: "l"(d), "r"(lo), "r"(hi), "r"((uint32_t)p), "l"(e), "r"(both) : "memory");
}
__device__ __forceinline__ uint32_t add3(uint32_t a, uint32_t b, uint32_t c) { uint32_t r; asm("{\n .reg .u32 t;\n add.u32 t, %1, %2;\n add.u32 %0, t, %3;\n}" : "=r"(r) : "r"(a), "r"(b), "r"(c)); return r; }
__device__ __forceinline__ uint32_t cnt8(const uint32_t (&v)[8], uint32_t c) { return add3(add3(v[0], v[1], c), add3(v[2], v[3], v[4]), add3(v[5], v[6], v[7])); }
__device__ __forceinline__ uint32_t cnt8(const uint2 (&v)[4], uint32_t c) { return add3(add3(v[0].x, v[0].y, c), add3(v[1].x, v[1].y, v[2].x), add3(v[2].y, v[3].x, v[3].y)); }
__device__ __forceinline__ uint32_t cnt16(const uint2 (&v)[8], uint32_t c) {
    return add3(add3(add3(v[0].x, v[0].y, c), add3(v[1].x, v[1].y, v[2].x), add3(v[2].y, v[3].x, v[3].y)), add3(add3(v[4].x, v[4].y, v[5].x), v[5].y, v[6].x), add3(v[6].y, v[7].x, v[7].y));
}
__device__ __forceinline__ uint32_t cnt16(const uint32_t (&v)[8], const uint32_t (&u)[8], uint32_t c) { return add3(cnt8(v, c), add3(add3(u[0], u[1], u[2]), u[3], u[4]), add3(u[5], u[6], u[7])); }
__device__ __forceinline__ float asf(uint32_t v) { return __uint_as_float(v); }
__device__ __forceinline__ float sum8(const uint32_t (&v)[8]) { return ((asf(v[0]) + asf(v[1])) + (asf(v[2]) + asf(v[3]))) + ((asf(v[4]) + asf(v[5])) + (asf(v[6]) + asf(v[7]))); }
__device__ __forceinline__ float sum8x(const uint2 (&v)[8]) { return ((asf(v[0].x) + asf(v[1].x)) + (asf(v[2].x) + asf(v[3].x))) + ((asf(v[4].x) + asf(v[5].x)) + (asf(v[6].x) + asf(v[7].x))); }
__device__ __forceinline__ float sum8y(const uint2 (&v)[8]) { return ((asf(v[0].y) + asf(v[1].y)) + (asf(v[2].y) + asf(v[3].y))) + ((asf(v[4].y) + asf(v[5].y)) + (asf(v[6].y) + asf(v[7].y))); }

__device__ __forceinline__ uint32_t pack2(float lo, float hi) { uint32_t r; asm("cvt.rn.bf16x2.f32 %0, %1, %2;" : "=r"(r) : "f"(hi), "f"(lo)); return r; }
__device__ __forceinline__ float bfr(float x) { return __uint_as_float(pack2(0.0f, x)); }
__device__ __forceinline__ float ex2(float x) { float r; asm("ex2.approx.ftz.f32 %0, %1;" : "=f"(r) : "f"(x)); return r; }
__device__ __forceinline__ float rcp(float x) { float r; asm("rcp.approx.ftz.f32 %0, %1;" : "=f"(r) : "f"(x)); return r; }
__device__ __forceinline__ float sqrt_(float x) { float r; asm("sqrt.approx.ftz.f32 %0, %1;" : "=f"(r) : "f"(x)); return r; }
__device__ __forceinline__ float bf_lo(uint32_t v) { return __uint_as_float(v << 16); }
__device__ __forceinline__ float bf_hi(uint32_t v) { return __uint_as_float(v & 0xffff0000u); }
__device__ __forceinline__ float sel4(int k, float a, float b, float c, float d) { return (k & 2) ? ((k & 1) ? d : c) : ((k & 1) ? b : a); }
constexpr float LOG2E = 1.4426950408889634f;
constexpr uint32_t ONES = 0x3f803f80u;

__device__ __forceinline__ void ln_stats(float sum, float sq, float& mean, float& den) {
    const float m = sum * (1.0f / 640.0f);
    const float var = fmaxf(fmaf(sq, 1.0f / 640.0f, -m * m), 0.0f);
    mean = bfr(m);
    den = bfr(sqrt_(bfr(bfr(var) + 1e-5f)));
}
__device__ __forceinline__ float sigmoidf_(float x) { return rcp(1.0f + ex2(-x * LOG2E)); }

#define TSTAMP(k) do {} while (0)
#define TST(k) do {} while (0)

#define CSTAMP(k) do {} while (0)
template <int N> __device__ __forceinline__ uint32_t lag(uint32_t sb, uint32_t z = 0) {
#pragma unroll
    for (int k = 0; k < N; k++) z = ldsvol(sb + S_ZERO + z);
    return z;
}
__device__ __forceinline__ void warm_mma(uint32_t& a, uint32_t& b) {
    asm volatile("mma.sync.aligned.m16n8k8.row.col.f16.f16.f16.f16 {%0,%1}, {%0,%1}, {%0}, {%0,%1};" : "+r"(a), "+r"(b) :: "memory");
}
#define KWNS2 20
#define KWNS 200
template <class F>
__device__ __forceinline__ void gather16(const char* p, uint32_t par, int k, F use) {
    uint32_t v[8], u[8];
    int guard = 0;
    bool again;
    do {
#pragma unroll
        for (int s = 0; s < 8; s++) v[s] = ldp32(p + s * 512);
#pragma unroll
        for (int s = 0; s < 8; s++) u[s] = ldp32(p + HALF + s * 512);
        const uint32_t stale = use(sum8(v) + sum8(u), ((v[0] ^ par) & 1) * 8);
        again = __any_sync(~0u, ((cnt16(v, u, 16 * par) | stale) & 31) != 0);
    } while (again & (++guard < SPIN_LIMIT));
    SWEEPS(k, guard - 1);
}

struct Params {
    const __nv_bfloat16 *x, *k, *v, *wr, *wq;
    __nv_bfloat16* out;
};
struct Maps { CUtensorMap k, v, vu, wq, wo, wg, wu, wd; };

constexpr int KV_BATCH_KEYS = 32 * 4096;

__device__ __forceinline__ void tma2d(uint32_t dst, const CUtensorMap* m, int c0, int c1, uint32_t bar, uint32_t bytes, uint64_t pol) {
    asm volatile("{\n .reg .pred p;\n elect.sync _|p, 0xffffffff;\n"
                 " @p mbarrier.arrive.expect_tx.shared::cta.b64 _, [%2], %6;\n"
                 " @p cp.async.bulk.tensor.2d.shared::cluster.global.mbarrier::complete_tx::bytes.L2::cache_hint [%0], [%1, {%3, %4}], [%2], %5;\n}"
                 :: "r"(dst), "l"(m), "r"(bar), "r"(c0), "r"(c1), "l"(pol), "r"(bytes) : "memory");
}
__device__ __forceinline__ void scrap_copy(uint32_t dst, const char* src, uint32_t bar) {
    asm volatile("{\n .reg .pred p;\n elect.sync _|p, 0xffffffff;\n"
                 " @p mbarrier.arrive.expect_tx.shared::cta.b64 _, [%2], 12288;\n"
                 " @p cp.async.bulk.shared::cluster.global.mbarrier::complete_tx::bytes [%0], [%1], 4096, [%2];\n"
                 " @p cp.async.bulk.shared::cluster.global.mbarrier::complete_tx::bytes [%0], [%1+4096], 4096, [%2];\n"
                 " @p cp.async.bulk.shared::cluster.global.mbarrier::complete_tx::bytes [%0], [%1+8192], 4096, [%2];\n}"
                 :: "r"(dst), "l"(src), "r"(bar) : "memory");
}
__device__ __forceinline__ void prefetch_l2(const void* p, uint32_t bytes) {
    asm volatile("{\n .reg .pred p;\n elect.sync _|p, 0xffffffff;\n @p cp.async.bulk.prefetch.L2.global [%0], %1;\n}" :: "l"(p), "r"(bytes) : "memory");
}
__device__ __forceinline__ uint64_t pol_first() { uint64_t p; asm("createpolicy.fractional.L2::evict_first.b64 %0, 1.0;" : "=l"(p)); return p; }
__device__ __forceinline__ uint64_t pol_normal() { uint64_t p; asm("createpolicy.fractional.L2::evict_normal.b64 %0, 1.0;" : "=l"(p)); return p; }
__device__ __forceinline__ bool utest(uint32_t bar, uint32_t parity) { return __all_sync(~0u, mbar_test(bar, parity)); }
__device__ __forceinline__ void uwait(uint32_t bar, uint32_t parity) {
    int n = 0;
    while (!__all_sync(~0u, mbar_try(bar, parity)) && ++n < SPIN_LIMIT) {}
}
template <int A, int B, int CNT> __device__ __forceinline__ void init_bars(uint32_t sb) {
#pragma unroll 1
    for (int k = A; k < B; k++)
        asm volatile("{\n .reg .pred p;\n elect.sync _|p, 0xffffffff;\n @p mbarrier.init.shared::cta.b64 [%0], %1;\n}" :: "r"(sb + S_BAR + 8 * k), "n"(CNT) : "memory");
}
__device__ __forceinline__ int unit_key(uint32_t b, uint32_t u) {
    return (blockIdx.x >> 2) * 4096 + 3072 + (blockIdx.x & 3) * (16 * ILV) + b * KV_BATCH_KEYS + (u & ~(ILV - 1u)) * 64 + (u & (ILV - 1)) * 16;
}
__device__ __forceinline__ void load_tile(const CUtensorMap* m, uint32_t dst, uint32_t bar, uint32_t bytes, int key, uint64_t pol) { tma2d(dst, m, 0, 3 * key, bar, bytes, pol); }
__device__ __forceinline__ const char* unit_ptr(const Params& P, int n) { return (const char*)((n & 16) ? P.v : P.k) + (size_t)unit_key(n >> 5, n & 15) * 384; }
#define LSTAMP(k) do {} while (0)

__device__ __forceinline__ uint32_t k_place(uint32_t b, uint32_t s) { return s + 3 + 5 * (b & 1); }
__device__ __forceinline__ uint32_t v_place(uint32_t b, uint32_t s) { return s < 3 ? s : s + 8 - 8 * (b & 1); }
__device__ __forceinline__ void k_load(const Maps& M, uint32_t dst, uint32_t bar, int key8, uint64_t pol) {
    asm volatile("{\n .reg .pred p;\n elect.sync _|p, 0xffffffff;\n"
                 " @p mbarrier.arrive.expect_tx.shared::cta.b64 _, [%2], 6144;\n"
                 " @p cp.async.bulk.tensor.4d.shared::cluster.global.mbarrier::complete_tx::bytes.L2::cache_hint [%0], [%1, {0, 0, 0, %3}], [%2], %4;\n}"
                 :: "r"(dst), "l"(&M.k), "r"(bar), "r"(key8), "l"(pol) : "memory");
}
__device__ __forceinline__ int unit_key8(uint32_t n) { return unit_key(n >> 4, n & 15) >> 3; }
__device__ __forceinline__ void ring_load(const Maps& M, uint32_t sb, uint32_t b, uint32_t u, uint32_t pos) {
    if (u < 16) k_load(M, sb + pos * UNIT, sb + S_RING + 8 * pos, unit_key8(16 * b + u), pol_normal());
    else load_tile(&M.vu, sb + pos * UNIT, sb + S_FV + 4 * (pos & 6), UNIT, unit_key(b, pos), pol_first());
}
__device__ __forceinline__ uint32_t token(bool p, uint32_t a, uint32_t n) {
    uint32_t v;
    asm volatile("{\n .reg .pred p;\n setp.ne.u32 p, %2, 0;\n mov.u32 %0, 0;\n @p atom.shared.exch.b32 %0, [%1], %3;\n}" : "=r"(v) : "r"(a), "r"((uint32_t)p), "r"(n) : "memory");
    return v;
}
__device__ __forceinline__ void place_load(const Maps& M, uint32_t sb, uint32_t n) {
    k_load(M, sb + k_place(n >> 4, 0) * SLOT + (n & 15) * UNIT, sb + S_FK + 4 * (n & 14), unit_key8(n), pol_first());
}
__device__ __forceinline__ void v_load(const Maps& M, uint32_t sb, uint32_t b, uint32_t s) {
    load_tile(&M.v, sb + v_place(b, s) * SLOT, sb + S_FV + 8 * s, SLOT, unit_key(b, 2 * s), pol_first());
}

__device__ __forceinline__ void stream_warp(const Params& P, const Maps& M, uint32_t sb, uint32_t lane) {
    const uint64_t pol = pol_first();
    const int bid = blockIdx.x, g = bid >> 3, i = bid & 7;
    const uint32_t wf = sb + S_WFULL;
    uint32_t tn = __shfl_sync(~0u, gtime32(), 0) * 16;
    int still = 0;
    auto until = [&](uint32_t t) {
        uint32_t now = __shfl_sync(~0u, gtime32(), 0) * 16;
        while ((int)(now - t) < 0 && still < 16) {
            const uint32_t last = now;
            now = __shfl_sync(~0u, gtime32(), 0) * 16;
            still = now == last ? still + 1 : 0;
        }
        return now;
    };
    auto pace = [&](uint32_t dt) {
        const uint32_t now = until(tn);
        if ((int)(now - tn) > SLACK0) tn = now - SLACK0;
        tn += dt;
    };
#pragma unroll
    for (int k = 0; k < 10; k++) {
        if (k < 2) {
            if (k == 0) init_bars<26, 27, 1>(sb); else init_bars<27, 37, 1>(sb);
            asm volatile("fence.mbarrier_init.release.cluster;" ::: "memory");
            if (k == 1) { asm volatile("bar.arrive 2, %0;" :: "n"(NTHR) : "memory"); asm volatile("bar.sync 3, 128;" ::: "memory"); }
        }
        if (k >= WIN_W) uwait(wf + 8 * (k - WIN_W), 0);
        pace(TAUW * 5 / 2 - (k == 0 || k == 2 ? LEADW : 0));
        if (k < 4) tma2d(sb + ST_WQ + 15360 * k, &M.wq, 384 * g + 192 * (k >> 1), 80 * i + 40 * (k & 1), wf + 8 * k, 15360, pol);
        else if (k < 6) tma2d(sb + ST_WG + 15360 * (k - 4), k == 4 ? &M.wg : &M.wu, 96 * g, 80 * i, wf + 8 * k, 15360, pol);
        else tma2d(sb + ST_WO + 15360 * (k - 6), &M.wo, 80 * i, 384 * g + 96 * (k - 6), wf + 8 * k, 15360, pol);
    }
#pragma unroll 1
    for (int n = 0; n < 16; n++) {
        if (n == 0 || n == 5 || n == 11) uwait(sb + S_RELW + (n == 0 ? 0 : n == 5 ? 8 : 16), 0);
        uwait(n < WIN_S ? wf + 8 * (10 - WIN_S + n) : sb + S_FV + 8 * ((n - WIN_S) ^ 8), 0);
        pace(2 * TAU0);
        if (n >= WIN_S && !utest(sb + S_FV + 8 * ((n - WIN_S + 1) ^ 8), 0)) tn += XB;
        if (n < 8) { place_load(M, sb, 2 * n); place_load(M, sb, 2 * n + 1); }
        else if (n < 11) { ring_load(M, sb, 0, 2 * n, 2 * n - 16); ring_load(M, sb, 0, 2 * n + 1, 2 * n - 15); }
        else v_load(M, sb, 0, n - 8);
        if (n == 7) { pace(TAUW * 5 / 2); tma2d(sb + S_WD, &M.wd, 80 * i, 96 * g, wf + 80, 15360, pol); }
    }
    int nd = 0;
    uint32_t q[4];
#pragma unroll
    for (int r = 0; r < 4; r++) q[r] = sb + S_FV + 8 * (7 - r);
    uint32_t td = tn;
    uint32_t pos = 2;
#pragma unroll 1
    for (int m = 16; m < 64; m++) {
        const int b = m >> 4, j = m & 15;
        const char* src = unit_ptr(P, 2 * m);
        const uint32_t tok = sb + S_TOK + (j < 3 ? 4 * pos : j < 11 ? 24 + 4 * pos : 16 + 4 * j) + 4 * lane;
        static_assert(WIN_U <= 12, "a ring position has at most one token of the timetable");
        int k = 0;
        while (true) {
            const uint2 c = lds64(sb + S_KF);
            if (__all_sync(~0u, mbar_test(q[WIN_S - 1] & ~1u, q[WIN_S - 1] & 1) & (min((int)c.x + 1, (int)c.y) >= 16 * b + min(2 * j + 2 - WIN_U, 16))) || ++k >= SPIN_FAST) break;
        }
        const uint32_t now = until(td);
        const uint32_t mine = __ballot_sync(~0u, token(lane < (j < 11 ? 2 : 1), tok, 2 * m + lane) == 2 * m + lane);
        {
            const uint2 c = lds64(sb + S_KF);
            if (!__all_sync(~0u, mbar_test(q[WIN_S - 2] & ~1u, q[WIN_S - 2] & 1) & (min((int)c.x + 1, (int)c.y) >= 16 * b + min(2 * j + 4 - WIN_U, 16)))) tn += XB;
        }
        q[3] = q[2]; q[2] = q[1]; q[1] = q[0]; q[0] = sb + S_QRDY;
        if (j < 11) {
            if (mine & 1) ring_load(M, sb, b, 2 * j, pos); else prefetch_l2(src, UNIT);
            if (mine & 2) ring_load(M, sb, b, 2 * j + 1, pos + 1); else prefetch_l2(src + UNIT, UNIT);
            if (j >= 8) q[0] = (sb + S_FV + 8 * (j - 8)) | (b & 1);
        } else if (mine) { v_load(M, sb, b, j - 8); q[0] = (sb + S_FV + 8 * (j - 8)) | (b & 1); }
        else if (j - 8 >= VPF) prefetch_l2(src, SLOT);
        else {
            scrap_copy(sb + S_DUMMY, src, sb + S_DBAR + 8 * (nd & 3));
            q[0] = (sb + S_DBAR + 8 * (nd & 3)) | ((nd >> 2) & 1);
            nd++;
        }
        pos = j == 15 ? 2 : pos == 4 ? 0 : pos + 2;
        if ((int)(now - tn) > SLACK) tn = now - SLACK;
        tn += 2 * TAU;
        td = (int)(tn - now) > 2 * TMIN ? tn : now + 2 * TMIN;
    }
#pragma unroll 1
    for (int m = max(nd - 4, 0); m < nd; m++) uwait(sb + S_DBAR + 8 * (m & 3), (m >> 2) & 1);
}

__host__ __device__ constexpr uint64_t bit_list(uint32_t m) { uint64_t r = 0; int n = 0; for (int k = 0; k < 12; k++) if ((m >> k) & 1) r |= (uint64_t)k << (4 * n++); return r; }
__device__ __forceinline__ float scaled(float s) { return bfr(bfr(s) * 0.07216878364870322f); }
__device__ __forceinline__ void probs(float s, uint32_t ps, uint32_t src, uint32_t ln) {
    const uint32_t q8 = ln >> 2, t4 = ln & 3;
    int key = __float_as_int(s);
    key ^= (key >> 31) & 0x7fffffff;
    key = __reduce_max_sync(~0u, key);
    key ^= (key >> 31) & 0x7fffffff;
    const float ml = __int_as_float(key) * LOG2E;
    sts16(ps + 64 * src + (q8 >> 1) * 16 + t4 * 4 + (q8 & 1) * 2, pack2(ex2(fmaf(s, LOG2E, -ml)), 0.f));
    stsf(ps + PS_MAX + 4 * src, ml);
}
template <int H> __device__ __forceinline__ uint32_t b_pos(uint32_t e) { const uint32_t h = e >= H, k = e - H * h; return h * 192 + (k & 6) * 24 + (k >> 3) * 4 + (k & 1) * 2; }
__device__ __forceinline__ uint32_t a_pos(uint32_t e) { const uint32_t h = e >= 40, k = e - 40 * h; return (k & 6) * 24 + (k >> 3) * 8 + h * 4 + (k & 1) * 2; }
__device__ __forceinline__ uint32_t q_pos(uint32_t d) { const uint32_t s = 3 * ((d >> 4) & 3) + (d >> 6); return s * 32 + (d & 6) * 4 + ((d >> 3) & 1) * 4 + (d & 1) * 2; }
__device__ __forceinline__ uint32_t k_off(uint32_t ln) { return (ln & 8) * 384 + (ln & 7) * 128 + (((ln & 7) ^ (ln >> 4)) << 4); }

#define HSTAMP(k) do {} while (0)
__device__ __forceinline__ char* xwindow() { return reinterpret_cast<char*>((reinterpret_cast<uintptr_t>(g_x) + (2u << 20) - 1) & ~(uintptr_t)((2u << 20) - 1)); }

struct XPtr {
    uint32_t lo, hi;
    __device__ __forceinline__ explicit XPtr(char* p) : lo((uint32_t)(uintptr_t)p), hi((uint32_t)((uintptr_t)p >> 32)) {}
    __device__ __forceinline__ XPtr(uint32_t l, uint32_t h) : lo(l), hi(h) {}
    __device__ __forceinline__ XPtr operator+(uint32_t o) const { return XPtr(lo + o, hi); }
    __device__ __forceinline__ operator char*() const { uint64_t p; asm("mov.b64 %0, {%1, %2};" : "=l"(p) : "r"(lo), "r"(hi)); return (char*)p; }
};

__device__ __forceinline__ char* side_word(uint32_t g, uint32_t i) { return xwindow() + pairG(1, 0, i) * 8192 + (g >> 3) * HALF + (g & 7) * 512 + 320; }

__device__ __forceinline__ uint32_t probe_side() {
    const uint32_t bid = blockIdx.x, g = bid >> 3, i = bid & 7, P = pairG(0, 0, i);
    char* p = xwindow() + P * 8192 + (g >> 3) * HALF + (g & 7) * 512 + 352;
    uint32_t best[2] = {~0u, ~0u};
#pragma unroll
    for (int k = 0; k < 4; k++) *reinterpret_cast<uint4*>(p + (k & 1) * 16 + (k >> 1) * COPY) = make_uint4(1, 1, 1, 1);
#pragma unroll 1
    for (int r = 0; r < 64; r++) {
        if (r >= 4 && !(r & 1) && min(best[0], best[1]) < 380 && max(best[0], best[1]) > min(best[0], best[1]) + 80) break;
        uint32_t c0, c1, v;
        asm volatile("mov.u32 %0, %clock;" : "=r"(c0) :: "memory");
        asm volatile("atom.relaxed.gpu.global.exch.b32 %0, [%1], 0;" : "=r"(v) : "l"(p + (r & 1) * COPY) : "memory");
        asm volatile("{\n .reg .pred q;\n setp.eq.u32 q, %1, 0x13579bdf;\n mov.u32 %0, 0;\n @!q mov.u32 %0, %clock;\n}" : "=r"(c1) : "r"(v) : "memory");
        if (r & 1) best[1] = min(best[1], c1 - c0); else best[0] = min(best[0], c1 - c0);
    }
    return 1 + ((best[1] < best[0]) ^ (__popc(P & PMASK) & 1));
}

template <int N>
__device__ __forceinline__ void hop_a(const char* src, uint32_t par, uint32_t dst, bool st, int k) {
    uint2 v[N][4];
    float e[4], rl;
    int guard = 0;
    bool again;
    do {
#pragma unroll
        for (int s = 0; s < 4 * N; s++) v[s / 4][s % 4] = ldp64(src + (s / 4) * 256 + (s % 4) * 1024);
        again = __any_sync(~0u, ((N == 1 ? cnt8(v[0], 24 * par) : cnt8(v[N - 1], cnt8(v[0], 16 * par))) & 31) != 0);
        const uint32_t M = (uint32_t)max(max((int)v[0][0].x, (int)v[0][1].x), max((int)v[0][2].x, (int)v[0][3].x)) - 127 * 32;
#pragma unroll
        for (int s = 0; s < 4; s++) e[s] = asf((uint32_t)max((int)(v[0][s].x - M), 0) << 18);
        rl = rcp(fmaf(e[0], asf(v[0][0].y), e[1] * asf(v[0][1].y)) + fmaf(e[2], asf(v[0][2].y), e[3] * asf(v[0][3].y)));
#pragma unroll
        for (int s = 0; s < 4; s++) e[s] = __shfl_sync(~0u, e[s], 24);
        keep(rl);
    } while (again & (++guard < SPIN_LIMIT));
    rl = __shfl_sync(~0u, rl, 24);
#pragma unroll
    for (int n = 0; n < N; n++) {
        const float o0 = fmaf(e[0], asf(v[n][0].x), e[1] * asf(v[n][1].x)) + fmaf(e[2], asf(v[n][2].x), e[3] * asf(v[n][3].x));
        const float o1 = fmaf(e[0], asf(v[n][0].y), e[1] * asf(v[n][1].y)) + fmaf(e[2], asf(v[n][2].y), e[3] * asf(v[n][3].y));
        sts32_if(st, dst + 192 * n, pack2(o0 * rl, o1 * rl));
    }
    SWEEPS(k, guard - 1);
    __syncwarp();
}

__device__ __forceinline__ void score_warp(const Maps& M, uint32_t sb, uint32_t h, uint32_t ln) {
    const uint32_t lane0 = ln;
    uwait(sb + S_QRDY, 0);
    const uint32_t q8 = ln >> 2;
    const uint32_t k0 = k_off(ln);
    uint32_t pos = h + 6, bar = sb + S_FK, par = 0, phases = 0;
    uint2 q = lds64(sb + S_QS + 8 * ln), qh = lds64(sb + S_QS + 8 * ln + 256);
    auto first_round = [&](uint32_t b, uint32_t ln) {
        uwait(sb + S_RELR, b & 1);
        const uint32_t u = h + 2 * ln, p = u < 4 ? u + 2 : u - 4;
        uint32_t todo = __ballot_sync(~0u, token(ln < 3, sb + S_TOK + 4 * p, 32 * b + 32 + u) == 32 * b + 32 + u);
#pragma unroll 1
        for (uint32_t r = h; todo; todo >>= 1, r += 2) if (todo & 1) ring_load(M, sb, b + 1, r, r < 4 ? r + 2 : r - 4);
    };
#pragma unroll 1
    for (uint32_t n = h; n < 64; n += 2) {
        HSTAMP(0);
        const uint32_t ua = sb + pos * UNIT;
        if (!__all_sync(~0u, mbar_try(bar, par))) uwait(bar, par);
        HSTAMP(1);
        float acc[2][4] = {};
        uint32_t mine = 0;
        const uint32_t id = n + (n & 48) + 6;
#pragma unroll
        for (int s = 0; s < 12; s++) {
            uint32_t kf[4];
            ldsm4(kf, (k0 ^ (32 * (s / 3))) + (ua + 1024 * (s % 3)));
            if (s == 11) {
                __syncwarp();
                mine = token(ln == 0 && n >= 16, sb + S_TOK + 24 + 4 * pos, id);
                stsvol(sb + S_KF + 4 * h, n + 1);
            }
            const bool m = q8 == (s & 7);
            mmaA(acc[s & 1], kf, m ? (s < 8 ? q.x : qh.x) : 0u, m ? (s < 8 ? q.y : qh.y) : 0u);
        }
        const uint32_t pos0 = pos;
        const bool last = (n & 14) == 14;
        pos = last ? h + 2 : n >= 16 && pos >= 4 ? h : pos + 2;
        bar = n >= 14 ? sb + S_RING + 8 * pos : bar + 8;
        par = n >= 14 ? (phases >> pos) & 1 : 0;
        phases ^= n >= 14 ? 1u << pos : 0;
        const float w0 = (acc[0][0] + acc[0][1]) + (acc[1][0] + acc[1][1]), w1 = (acc[0][2] + acc[0][3]) + (acc[1][2] + acc[1][3]);
        HSTAMP(2);
        if (__any_sync(~0u, mine == id)) ring_load(M, sb, n >> 4, (n & 15) + 6, pos0);
        HSTAMP(3);
        float s = ((ln & 1) ? w1 : w0) + __shfl_xor_sync(~0u, (ln & 1) ? w0 : w1, 1);
        s += __shfl_xor_sync(~0u, s, 2);
        sts_hi16(sb + S_SC + (((n & 12) >> 1) + h) * 64 + (n & 2) * 2 + (ln & 29) * 2, scaled(s));
        if (last) {
            __syncwarp();
            arrive_if(ln == 0, sb + S_SCO);
            const uint32_t b = n >> 4, ln = lane0 + lag<1>(sb);
            if (b > 0) {
                uwait(sb + S_RELK, (b - 1) & 1);
                if (h == 0) LSTAMP(64 + 2 * b);
                const uint32_t sl = 3 + h + 2 * ln, idv = 32 * b + 16 + 2 * sl;
                uint32_t todo = __ballot_sync(~0u, token(sl < 8, sb + S_TOK + 48 + 4 * sl, idv) == idv);
#pragma unroll 1
                for (uint32_t r = 3 + h; todo; todo >>= 1, r += 2) if (todo & 1) v_load(M, sb, b, r);
                const uint32_t g = blockIdx.x >> 3, pr = pairL(RA, 1, g), side = ldsvol(sb + S_SIDE);
                const char* src = xwindow() + pr * 8192 + ((side ^ 1 ^ __popc(pr & PMASK)) & 1) * COPY + h * HALF + 8 * min(ln, 24u);
                uwait(sb + S_RELV, (b - 1) & 1);
                __nanosleep(HOP1_NS);
#pragma unroll 1
                for (uint32_t r = 0; r < 4; r += 2) {
                    hop_a<2>(src + 256 * r, b & 1, sb + S_OS + 192 * (4 * h + r) + 96 + 4 * ln, ln < 24, 25);
                    if (r == 0 && b < 3) first_round(b, ln);
                }
                arrive_if(ln == 0, sb + S_OS1);
            } else first_round(0, ln);
            q = lds64(sb + S_QS + 24 * ((n + 2) & 48) + 8 * ln); qh = lds64(sb + S_QS + 24 * ((n + 2) & 48) + 8 * ln + 256);
        }
    }
}

__global__ void __launch_bounds__(NTHR, 1)
fused_kernel(const Params P, const __grid_constant__ Maps M) {
    extern __shared__ __align__(1024) unsigned char smem[];
    const uint32_t sb = smem_u32(smem);
    const int tid = threadIdx.x, bid = blockIdx.x;
    if (tid == 0) {
        asm volatile("prefetch.tensormap [%0];" :: "l"(&M.wq) : "memory");
        asm volatile("cp.async.bulk.prefetch.L2.global [%0], 12288;" :: "l"(P.wq + (80 * (bid & 7) + (bid >> 3)) * 6144) : "memory");
    }
    const int w = __shfl_sync(~0u, tid >> 5, 0), lane = tid & 31;

    if (w >= 8) {
        asm volatile("setmaxnreg.dec.sync.aligned.u32 " REG_LO ";");
        if (w == 8) {
            stream_warp(P, M, sb, lane);
        } else {
            if (w == 9) { init_bars<0, 3, 2>(sb); init_bars<3, 8, 1>(sb); init_bars<16, 22, 1>(sb); }
            else if (w == 10) { init_bars<8, 16, 2>(sb); init_bars<22, 26, 1>(sb); }
            else { init_bars<37, 38, 1>(sb); init_bars<38, 40, 8>(sb); init_bars<40, 41, 1>(sb); init_bars<41, 44, 8>(sb); init_bars<44, 46, 2>(sb); stsvol(sb + S_ZERO + 4 * lane, 0); if (lane < 16) stsvol(sb + S_LN + 4 * lane, 0); }
            asm volatile("fence.mbarrier_init.release.cluster;" ::: "memory");
            asm volatile("bar.arrive 3, 128;" ::: "memory");
            if (w == 11) asm volatile("bar.arrive 2, %0;" :: "n"(NTHR) : "memory");
            else {
                if (lane < 4) asm volatile("prefetch.tensormap [%0];" :: "l"(&M.k + lane + 4 * (w - 9)) : "memory");
                __syncwarp();
                asm volatile("bar.sync 2, %0;" :: "n"(NTHR) : "memory");
            }
            if (w < 11) score_warp(M, sb, w - 9, lane);
            else {
                uint32_t mine = 0;
                if (lane == 0) mine = probe_side();
                mine = __shfl_sync(~0u, mine, 0);
                if (lane < 8) stp32(side_word(bid >> 3, bid & 7) + 4 * lane, asf(mine << 5), 1);
                uint32_t a = 0, b = 0;
                int k = 0;
                while (!utest(sb + S_QRDY, 0) && ++k < SPIN_FAST) { warm_mma(a, b); __nanosleep(KWNS); }
                while (true) {
                    const uint32_t v = ldp32(side_word(bid >> 3, lane & 7));
                    const bool late = !__all_sync(~0u, v & 1);
                    if (!late || ++k >= SPIN_FAST) { stsvol(sb + S_SIDE, mine | (FORCE_BOTH || late || __any_sync(~0u, (v >> 5) != mine) ? 4 : 0)); break; }
                    warm_mma(a, b); __nanosleep(KWNS);
                }
                while (ldsvol(sb + S_GATE) == 0 && ++k < SPIN_FAST) { warm_mma(a, b); __nanosleep(KWNS); }
                uint32_t rl = lane, rq = 0;
                auto reset = [&] {
                    if (rq < 128) *reinterpret_cast<uint4*>(reinterpret_cast<char*>(g_s) + (rl < 60 ? XS + bid * 7680 + 128 * rl : XS2 + bid * 768 + 128 * (rl - 60)) + rq) = make_uint4(0, 0, 0, 0);
                    rl += 32;
                    if (rl >= 66) { rl -= 66; rq += 16; }
                };
                reset(); reset();
                if (lane < 8) stp32(side_word(bid >> 3, bid & 7) + 4 * lane, 0.f, 0);
                const uint32_t side = (ldsvol(sb + S_SIDE) & 1) ^ 1, g = bid >> 3, i = bid & 7;
                const XPtr gx(xwindow());
                auto nearp = [&](uint32_t pr) { return gx.lo + pr * 8192 + ((side ^ __popc(pr & PMASK)) & 1) * COPY; };
                const uint32_t own = (i >> 2) * HALF + (i & 3) * 1024 + (lane & 7) * 128;
                const uint32_t cut = (lane & 7) == 7 ? 128 : 0;
                const uint32_t pAC = nearp(pairL(lane >> 4, (lane >> 3) & 1, g)) + own - (lane >> 4) * cut, pE = nearp(pairL(RE, (lane >> 3) & 1, g)) + own - cut;
                const uint32_t pG = nearp(pairG((lane >> 2) & 1, (lane >> 3) & 1, i)) + min(lane & 3, 2) * 128;
                uint32_t tr = 0, tk = 0, ph = 0, src = g + (lane >> 4), seen = 0, n = 16;
                bool go = false, first = true;
                while (n < 64 && ++k < SPIN_FAST) {
                    const uint32_t now = __shfl_sync(~0u, gtime32(), 0) * 16;
                    if (!go && utest((n & 15) < 6 ? sb + S_RELK : sb + S_RELV, ((n >> 4) & 1) ^ 1)) { go = true; if ((int)(now - tk) > 0 || !(n & 15)) tk = now; }
                    if (go && (int)(now - tk) >= 0) {
                        place_load(M, sb, (n & 16) ? n : (n & 48) | ((n + 10) & 15));
                        tk += KRE_TAU;
                        n++;
                        go = (n & 15) != 0 && (n & 15) != 6;
                        if (!(n & 15)) LSTAMP(63 + (n >> 3));
                    } else if (first || (int)(now - tr) >= 0) {
                        first = false;
                        tr = now + RFR_TAU;
                        b |= seen & a;
                        warm_mma(a, b);
                        seen = ldp32(XPtr(ph == 0 ? pAC : ph == 1 && lane < 16 ? pE : pG + (src & 8) * (HALF / 8) + (src & 7) * 512, gx.hi));
                        reset();
                        src += ph == 0 ? 0 : ph == 1 ? 2 : 1;
                        ph = ph == 2 ? 0 : ph + 1;
                    } else __nanosleep(KWNS2);
                }
                while (rq < 128) reset();
                __syncwarp();
                while (ldsvol(sb + S_GATE) < 6 && ++k < SPIN_FAST) { warm_mma(a, b); __nanosleep(KWNS); }
                if (a | b) stsvol(sb + S_GATE, 6);
            }
        }
        return;
    }
    asm volatile("setmaxnreg.inc.sync.aligned.u32 " REG_HI ";");

    const int g = bid >> 3, i = bid & 7;
    const int g8 = lane >> 2, t = lane & 3;
    char* const gs = reinterpret_cast<char*>(g_s);
    const XPtr gx(xwindow());

    W80 Wq[6], Wgu[3];
    uint32_t Wo[5][3][4];
    if (w < 4) {
        const uint32_t* xp = reinterpret_cast<const uint32_t*>(P.x + 640 * w);
        float sum = 0.f, sq = 0.f;
#pragma unroll
        for (int u = 0; u < 10; u++) { uint32_t v = xp[lane + 32 * u]; float a = bf_lo(v), b = bf_hi(v); sum += a + b; sq += a * a + b * b; }
#pragma unroll
        for (int o = 16; o > 0; o >>= 1) { sum += __shfl_xor_sync(~0u, sum, o); sq += __shfl_xor_sync(~0u, sq, o); }
        float mean, den; ln_stats(sum, sq, mean, den);
        if (lane < 20) {
            const uint2 v = reinterpret_cast<const uint2*>(P.x + 640 * w + 80 * i)[lane];
            sts64(sb + S_X0 + 160 * w + 8 * lane, v.x, v.y);
            sts32(sb + S_L0 + 384 * w + b_pos<40>(4 * lane), pack2(__fdiv_rn(bfr(bf_lo(v.x) - mean), den), __fdiv_rn(bfr(bf_hi(v.x) - mean), den)));
            sts32(sb + S_L0 + 384 * w + b_pos<40>(4 * lane + 2), pack2(__fdiv_rn(bfr(bf_lo(v.y) - mean), den), __fdiv_rn(bfr(bf_hi(v.y) - mean), den)));
        }
    } else if (w == 4) {
        const uint32_t* xp = reinterpret_cast<const uint32_t*>(P.wr);
        float sum = 0.f;
#pragma unroll
        for (int u = 0; u < 10; u++) { uint32_t v = xp[lane + 32 * u]; sum += bf_lo(v) + bf_hi(v); }
#pragma unroll
        for (int o = 16; o > 0; o >>= 1) sum += __shfl_xor_sync(~0u, sum, o);
        if (lane == 0) stsf(sb + S_SWR, sum);
        if (lane < 20) {
            const uint2 v = reinterpret_cast<const uint2*>(P.wr + 80 * i)[lane];
            sts32(sb + S_XA + 576 + a_pos(4 * lane), v.x); sts32(sb + S_XA + 576 + a_pos(4 * lane + 2), v.y);
            sts32(sb + S_XA + a_pos(4 * lane), ONES); sts32(sb + S_XA + a_pos(4 * lane + 2), ONES);
        }
    }
    asm volatile("bar.sync 2, %0;" :: "n"(NTHR) : "memory");
    auto frag = [](uint32_t (&a)[4], uint32_t p, int pitch) {
        const uint32_t r0 = lds32(p), r1 = lds32(p + pitch), r2 = lds32(p + 2 * pitch), r3 = lds32(p + 3 * pitch);
        a[0] = __byte_perm(r0, r1, 0x5410); a[1] = __byte_perm(r0, r1, 0x7632);
        a[2] = __byte_perm(r2, r3, 0x5410); a[3] = __byte_perm(r2, r3, 0x7632);
    };
    mbar_wait(sb + S_WFULL + 16 * (w >> 2), 0);
    mbar_wait(sb + S_WFULL + 16 * (w >> 2) + 8, 0);
    {
        const uint32_t p = sb + ST_WQ + (w >> 2) * 30720 + (2 * t) * 384 + (48 * (w & 3) + 2 * g8) * 2;
#pragma unroll
        for (int r = 0; r < 10; r++)
#pragma unroll
            for (int m = 0; m < 3; m++) {
                const uint32_t q = p + ((r & 1) * 40 + (r >> 1) * 8) * 384 + 32 * m, r0 = lds32(q), r1 = lds32(q + 384);
                (r < 8 ? Wq[2 * m].a[(r >> 2) & 1][r & 3] : Wq[2 * m].c[r & 1]) = __byte_perm(r0, r1, 0x5410);
                (r < 8 ? Wq[2 * m + 1].a[(r >> 2) & 1][r & 3] : Wq[2 * m + 1].c[r & 1]) = __byte_perm(r0, r1, 0x7632);
            }
    }
    __syncwarp();
    if (lane == 0) mbar_arrive(sb + S_RELW);
    TSTAMP(1);
    {
        char* d = gs + XS + bid * 7680 + (w >> 2) * 3840 + (48 * (w & 3) + 2 * g8) * 4;
        float acc[6][4] = {};
        mul80(acc, Wq, lds128(sb + S_L0 + 48 * lane), lds32(sb + S_L0 + 48 * lane + 16));
#pragma unroll
        for (int m = 0; m < 6; m += 2) stp64(d + t * 768 + 32 * m, acc[m][0] + acc[m][3], acc[m + 1][0] + acc[m + 1][3], 1);
        float sum[6][4] = {};
        mul80(sum, Wq, make_uint4(ONES, ONES, ONES, ONES), ONES);
        if (t == 0)
#pragma unroll
            for (int m = 0; m < 6; m += 2) stp64(d + 4 * 768 + 32 * m, sum[m][0] + sum[m][3], sum[m + 1][0] + sum[m + 1][3], 1);
    }
    mbar_wait(sb + S_WFULL + 32, 0);
    mbar_wait(sb + S_WFULL + 40, 0);
    const uint32_t oct = 3 * (w >> 1) + (w & 1), oct2 = 3 * (w >> 1) + 2;
    {
        const uint32_t p = sb + ST_WG + ((lane & 7) + 40 * ((lane >> 3) & 1) + 8 * (lane >> 4)) * 192;
#pragma unroll
        for (int T = 0; T < 3; T++) {
            const uint32_t q = p + (T < 2 ? T * 15360 + 16 * oct : (w & 1) * 15360 + 16 * oct2);
            ldsm4t(Wgu[T].a[0], q); ldsm4t(Wgu[T].a[1], q + 16 * 192); ldsm2t(Wgu[T].c, q + 32 * 192);
        }
        float sum[3][4] = {};
        mul80(sum, Wgu, make_uint4(ONES, ONES, ONES, ONES), ONES);
        if (t < 3) stp32(gs + XS2 + bid * 768 + (t < 2 ? 64 * oct + 4 * t : 64 * oct2 + 4 * (w & 1)) + 8 * g8,
                         sel4(t, sum[0][0] + sum[0][3], sum[1][0] + sum[1][3], sum[2][0] + sum[2][3], 0.f), 1);
    }
    __syncwarp();
    if (lane == 0) mbar_arrive(sb + S_RELW + 8);
    mbar_wait(sb + S_WFULL + 48 + 8 * (w >> 1), 0);
    {
        const uint32_t po = sb + ST_WO + (48 * w + 12 * t) * 160 + 4 * g8;
#pragma unroll
        for (int s = 0; s < 3; s++)
#pragma unroll
            for (int m = 0; m < 5; m++) frag(Wo[m][s], po + 4 * s * 160 + 32 * m, 160);
    }
    __syncwarp();
    if (lane == 0) mbar_arrive(sb + S_RELW + 16);
    mbar_wait(sb + S_WFULL + 64, 0);
    if (tid < 192) {
        const char* srcS = gs + XS + g * 8 * 7680 + (i >> 2) * 3840 + tid * 4;
        uint32_t vs[5][8];
        int guard = 0;
        do {
#pragma unroll
            for (int b = 0; b < 5; b++)
#pragma unroll
                for (int s = 0; s < 8; s++) vs[b][s] = ldp32(srcS + b * 768 + s * 7680);
        } while (((cnt16(vs[0], vs[1], 16) | cnt16(vs[2], vs[3], 16) | cnt8(vs[4], 24)) & 31) && ++guard < SPIN_LIMIT);
        const uint32_t qpos = sb + S_QS + q_pos(tid);
#pragma unroll
        for (int b = 0; b < 4; b++) {
            sts_hi16(qpos + 384 * b, bfr(sum8(vs[b])));
        }
        stsf(sb + S_CSQ + 4 * tid, sum8(vs[4]));
    }
    if (tid < 192) {
        uint32_t v[8];
        int guard = 0;
        do {
#pragma unroll
            for (int s = 0; s < 8; s++) v[s] = ldp32(gs + XS2 + (g * 8 + s) * 768 + tid * 4);
        } while ((cnt8(v, 24) & 31) && ++guard < SPIN_LIMIT);
        stsf(sb + S_CSGU + 4 * tid, sum8(v));
    }
    __syncwarp();
    bar_main();
    arrive_if(tid == 0, sb + S_QRDY);
    TSTAMP(2);

    uint32_t side;
    { int k = 0; while ((side = ldsvol(sb + S_SIDE)) == 0 && ++k < SPIN_FAST) {} }
    const uint32_t both = __any_sync(~0u, side & 4) ? COPY : 0;
    uint32_t td = __shfl_sync(~0u, tid, lane);
    const uint32_t wp = __shfl_sync(~0u, tid >> 5, 0);
    const uint32_t cc = wp >= 3;
    auto uni = [](uint32_t v) { return __shfl_sync(~0u, v, 0); };
    auto pin = [&](uint32_t v) { return __shfl_sync(~0u, v, td); };
    auto nearp = [&](uint32_t P) { return gx.lo + P * 8192 + ((side ^ 1 ^ __popc(P & PMASK)) & 1) * COPY; };
    constexpr uint32_t COL = 32 * 8192;
    const uint32_t ownL = (i >> 2) * HALF + (i & 3) * 1024, ownG = gx.lo + (g >> 3) * HALF + (g & 7) * 512;
    const uint32_t uPubA = uni(ownL + nearp(pairL(RA, 0, g)) + (wp >> 1) * 256 + (wp & 1) * 96), uPolA = uni(nearp(pairL(RA, 0, g)) + (wp >> 2) * HALF + (wp & 3) * 256);
    const uint32_t uPubB = uni(ownG + pairG(0, cc, i) * 8192), uPolB = uni(nearp(pairG(0, cc, i)));
    const uint32_t uPubC = uni(ownL + nearp(pairL(RC, 0, g))), uPolC = uni(nearp(pairL(RC, wp < 6 ? cc : 0, g)));
    const uint32_t uPubD = uni(ownG + pairG(1, 0, i) * 8192 + (wp < 7 ? 32 * wp : 256)), uPolD = uni(nearp(pairG(1, cc, i)));
    const uint32_t uPubE = uni(ownL + nearp(pairL(RE, 0, g))), uPolE = uni(nearp(pairL(RE, i >> 2, g)));
    const uint32_t uOS = uni(sb + S_OS + 192 * wp);
    auto xp = [&](uint32_t lo) { return (char*)XPtr(lo, gx.hi); };
    {
        const uint4 z = make_uint4(0, 0, 0, 0);
        const uint32_t c = ((tid >> 6) & 1) * COL, cp = (tid >> 7) * both, k = (tid & 63) * 16;
        *reinterpret_cast<uint4*>(xp((ownL + nearp(pairL(RA, 0, g)) + c + k) ^ cp)) = z;
        if (k < 800) { *reinterpret_cast<uint4*>(xp((uPubC + c + k) ^ cp)) = z; *reinterpret_cast<uint4*>(xp((uPubE + c + k) ^ cp)) = z; }
        if ((tid & 31) < 20) *reinterpret_cast<uint4*>(xp(ownG + pairG((tid >> 5) & 1, 0, i) * 8192 + c + (tid >> 7) * COPY + (tid & 31) * 16)) = z;
    }
#define IDS() __syncwarp(); const uint32_t z0_ = lag<1>(sb), z_ = td + z0_; const uint32_t ln = z_ & 31, q8 = ln >> 2, t4 = z_ & 3, n96 = z_ - 96 * cc, n80 = min(n96, 79u); (void)q8; (void)t4; (void)n80; (void)ln

    auto vaddr = [&](uint32_t (&voff)[3]) {
        const uint32_t ln = td & 31;
        const uint32_t key3 = 3 * ((ln & 7) + 2 * (ln & 8) + ((ln >> 1) & 8));
#pragma unroll
        for (int T = 0; T < 3; T++) {
            const uint32_t u = 3 * wp + T, r = key3 + (u >> 3);
            voff[T] = r * 128 + (((u ^ r) & 7) << 4);
        }
    };
    auto values = [&](uint32_t (&vf)[8][3][4], float (&acc)[3][4], auto step, uint32_t ps, auto col, uint32_t par) {
        constexpr int CUT = col.value ? 8 : 6;
        const uint32_t ln = td & 31, q8 = ln >> 2, t4 = td & 3;
        uint4 p = lds128(ps + 16 * ln);
        float f0 = 0.f, f1 = 0.f, r3 = 0.f, o = 0.f;
        int M = 0;
#pragma unroll
        for (int s = 0; s < 8; s++) {
            if (s == 0 || s == CUT)
#pragma unroll
                for (int k = 0; k < 12; k++) acc[k / 4][k % 4] = 0.f;
            step(s);
            const bool m = s >= CUT || (q8 >> 1) == (s >> 1);
            const uint32_t b0 = m ? ((s & 1) ? p.z : p.x) : 0u, b1 = m ? ((s & 1) ? p.w : p.y) : 0u;
#pragma unroll
            for (int T = 0; T < 3; T++) mmaA(acc[T], vf[s][T], b0, b1);
            if (s == FSTEP) {
                const uint2 mp = lds64(ps + PS_MAX + 8 * t4);
                M = __reduce_max_sync(~0u, __float2int_ru(fmaxf(asf(mp.x), asf(mp.y))));
                f0 = ex2(asf(mp.x) - (float)M); f1 = ex2(asf(mp.y) - (float)M);
                float l[4] = {};
                mma16816(l, ONES, ONES, ONES, ONES, p.x, p.y); mma16816(l, ONES, ONES, ONES, ONES, p.z, p.w);
                r3 = fmaf(f0, l[0], f1 * l[1]);
            }
            if (s == CUT - 1) {
                if (CUT < 8) p = lds128(ps + 384 + 16 * (ln & 7));
                const float r0 = fmaf(f0, acc[0][0], f1 * acc[0][3]), r1 = fmaf(f0, acc[1][0], f1 * acc[1][3]), r2 = fmaf(f0, acc[2][0], f1 * acc[2][3]);
                const bool hi = t4 & 2, od = t4 & 1;
                const float u0 = (hi ? r2 : r0) + __shfl_xor_sync(~0u, hi ? r0 : r2, 2), u1 = (hi ? r3 : r1) + __shfl_xor_sync(~0u, hi ? r1 : r3, 2);
                o = (od ? u1 : u0) + __shfl_xor_sync(~0u, od ? u0 : u1, 1);
                if (ln == 3) o = asf(32 * (uint32_t)M);
                if (CUT < 8) { f0 = __shfl_sync(~0u, f0, 3); f1 = __shfl_sync(~0u, f1, 3); }
            }
        }
        CSTAMP(25);
        const uint32_t pubA = uPubA + col.value * COL + 32 * t4 + 4 * q8;
        if (CUT < 8 && t4 < 3) o = fmaf(f0, sel4(t4, acc[0][0], acc[1][0], acc[2][0], acc[2][0]), fmaf(f1, sel4(t4, acc[0][3], acc[1][3], acc[2][3], acc[2][3]), o));
        stp32_if(t4 < 3 || ((wp & 1) && q8 < 2), both, xp(pubA ^ COPY), xp(pubA), o, par);
    };

    uint32_t left[36] = {};
#pragma unroll 1
    for (int ch = 0; ch < 5; ch++) {
        const uint32_t par0 = (ch + 1) & 1, par1 = ch & 1;
        uint32_t voff[3], vf[8][3][4];
        float acc_[3][4];
        if (ch < 4) {
            td = pin(td);
            vaddr(voff);
            mbar_wait(sb + S_SCO, par1);
            if (ch == 0) mbar_wait(sb + S_WFULL + 80, 0);
            TST(0);
            auto ldw = [&](int s) {
                mbar_wait(sb + S_FV + 8 * s, par1);
#pragma unroll
                for (int T = 0; T < 3; T++) ldsm4t(vf[s][T], voff[T] + (sb + v_place(ch, s) * SLOT));
            };
            probs(bf_lo(lds16(sb + S_SC + 2 * td)), sb + S_PS, wp, td & 31);
            ldw(0); ldw(1); ldw(2);
            bar_main();
            arrive_if(td == 0, sb + S_RELR);
            values(vf, acc_, [&](int s) {
                if (s >= 3) ldw(s);
            }, sb + S_PS, std::integral_constant<int, 0>(), par0);
            TST(1);
            CSTAMP(5);
            if (ch > 0) mbar_wait(sb + S_OS1, par0);
        } else {
#pragma unroll
            for (int s = 0; s < 36; s++) vf[s / 12][(s / 4) % 3][s & 3] = left[s];
        }
        const bool has0 = ch < 4, has1 = ch > 0;
        const bool actc = wp < 6 && (cc ? has1 : has0);
        const uint32_t parc = cc ? par1 : par0;
        const uint32_t pub0 = has0 ? par0 : 0;
        uint32_t rr, pubB;
        {
            IDS();
            const uint32_t c = ch == 4;
            const uint32_t osa = pin(uOS + 96 * c + 4 * ln), oa = pin(uOS + 48 * (q8 & 2) + 24 * t4), ra = pin(sb + S_RED + 640 * wp + 320 * (t4 & 1) + 8 * q8);
            rr = pin(sb + S_RED + 320 * cc + 4 * n80); pubB = pin(uPubB + 4 * n80);
            hop_a<1>(xp(uPolA + c * COL + 8 * min(ln, 24u) + lag<DELAY_L>(sb, z0_)), pub0, osa, ln < 24, 5 * ch);
            TST(2);
            CSTAMP(6);
            float acc[5][4] = {};
            const uint2 b0 = lds64(oa), b1 = lds64(oa + 8), b2 = lds64(oa + 16);
#pragma unroll
            for (int m = 0; m < 5; m++) mmaA(acc[m], Wo[m][0], b0.x, b0.y);
#pragma unroll
            for (int m = 0; m < 5; m++) mmaA(acc[m], Wo[m][1], b1.x, b1.y);
#pragma unroll
            for (int m = 0; m < 5; m++) mmaA(acc[m], Wo[m][2], b2.x, b2.y);
#pragma unroll
            for (int m = 0; m < 5; m++) { stsf(ra + 64 * m, acc[m][0]); stsf(ra + 64 * m + 4, acc[m][2]); }
        }
        CSTAMP(7);
        uint32_t xr, fl, pubC, pubC2;
        auto prepC = [&](uint32_t ln) {
            const uint32_t q8 = ln >> 2, t4 = ln & 3;
            xr = pin(sb + S_XB + 48 * (ln & 15));
            pubC = pin(uPubC + (t4 & 1) * COL + 192 * (wp >> 1) + 64 * (wp & 1) + 8 * q8);
            pubC2 = pin(uPubC + (t4 & 1) * COL + ((t4 & 2) ? 192 * (wp >> 1) + 128 + 4 * (wp & 1) + 8 * q8 : 768 + 2 * ((q8 + 1) & 6)));
            fl = pin(((t4 & 1) ? par1 : pub0) | (t4 >= 2 || (wp == 7 && q8 < 4 && q8 != 2 - t4) ? 2 : 0));
        };
        auto stats = [&](uint32_t xa, const uint4& b, uint32_t b4) {
            float a0[4] = {}, a1[4] = {}, a2[4] = {};
            const uint4 p0 = lds128(xa), p1 = lds128(xa + 16);
            const uint2 p2 = lds64(xa + 32);
            mmaV(a0, p0, b.x, b.y); mmaV(a1, p1, b.z, b.w); mma8(a2, p2.x, p2.y, b4);
            return ((a0[0] + a0[3]) + (a1[0] + a1[3])) + (a2[0] + a2[3]);
        };
        auto give_ln = [&](uint32_t src0, uint32_t par, uint32_t dst, uint32_t ln, float& mean, float& den, auto also) {
            const char* src = xp(src0 + 768 + (ln & 1) * HALF);
            float sx, sq;
            int guard = 0;
            bool again;
            do {
                uint2 st[4];
#pragma unroll
                for (int s = 0; s < 4; s++) st[s] = ldp64(src + s * 1024);
                again = __any_sync(~0u, ((cnt8(st, 24 * par) | also()) & 31) != 0);
                sx = (asf(st[0].x) + asf(st[1].x)) + (asf(st[2].x) + asf(st[3].x)); sq = (asf(st[0].y) + asf(st[1].y)) + (asf(st[2].y) + asf(st[3].y));
                sx += __shfl_xor_sync(~0u, sx, 1); sq += __shfl_xor_sync(~0u, sq, 1);
            } while (again & (++guard < SPIN_LIMIT));
            ln_stats(sx, sq, mean, den);
            stsvol64(dst, __byte_perm(__float_as_uint(den), __float_as_uint(mean), 0x7632), (__float_as_uint(rcp(den)) & ~7u) | (ch + 1));
        };
        auto take_ln = [&](uint2& c, uint32_t a) { int k = 0; do c = ldsvol64(a); while (__any_sync(~0u, (c.y & 7) != ch + 1) & (++k < SPIN_FAST)); };
        {
            auto gate_up = [&](auto with_stats) {
                bar_main();
                TST(3);
                CSTAMP(11);
                const uint4 b = lds128(xr);
                uint32_t b4 = lds32(xr + 16);
                float acc[3][4] = {};
                if (with_stats.value) {
                    stp32_if(fl > 1 && !(td & 2), both, xp(pubC2 ^ COPY), xp(pubC2), stats(xr + (S_XA - S_XB), b, b4), fl & 1);
                    __syncwarp();
                    b4 = lds32(xr + 16);
                }
                mul80(acc, Wgu, b, b4);
                stp64_if(!(td & 2), both, xp(pubC ^ COPY), xp(pubC), tagw(acc[0][0] + acc[0][3], fl & 1), tagw(acc[1][0] + acc[1][3], fl & 1));
                stp32_if(td & 2, both, xp(pubC2 ^ COPY), xp(pubC2), acc[2][0] + acc[2][3], fl & 1);
            };
            if (wp == 7) {
                bar_main();
                IDS();
                prepC(ln);
                sts32(sb + S_ZERO + 4, add3(pubC, pubC2, fl));
                gate_up(std::true_type());
            } else {
                if (actc) {
                    bar_main();
                    CSTAMP(8);
                    uint32_t r[8];
#pragma unroll
                    for (int s = 0; s < 8; s++) r[s] = lds32(rr + 640 * s);
                    stp32_if(true, xp(pubB), sum8(r), parc);
                    CSTAMP(9);
                    IDS();
                    prepC(ln);
                    const uint32_t n4 = 4 * n80;
                    const uint32_t xas = pin(sb + S_XA + 192 + 192 * cc + a_pos(n80)), xbs = pin(sb + S_XB + 384 * cc + b_pos<40>(n80));
                    const float x0 = cc ? ldsf(sb + S_XCAR + n4) : bf_lo(lds16(sb + S_X0 + 160 * (ch & 3) + n4 / 2));
                    gather16(xp(uPolB + n4 + lag<DELAY_G>(sb, z0_)), parc, 5 * ch + 1, [&](float y, uint32_t) {
                        const uint32_t x = pack2(x0 + bfr(y), 0.f);
                        sts16(xbs, x);
                        sts16(xas, x);
                        return 0u;
                    });
                    CSTAMP(10);
                } else {
                    bar_main();
                    IDS();
                    prepC(ln);
                }
                gate_up(std::false_type());
            }
        }
        CSTAMP(12);
        float mean = 0.f, den = 1.f;
        {
            IDS();
            const uint32_t wh = pin((((ln & 7) + 48 * ((ln >> 3) & 1) + 8 * (ln >> 4)) * 160 + (wp < 7 ? 16 * wp : 128)) | ((384 * cc + b_pos<48>(n96)) << 16));
            const uint32_t pubD = pin(uPubD + (t4 & 1) * COL + 16 * (t4 & 2) + 4 * q8 + (fl & 1)), ha = xr + (S_HS - S_XB);
            auto down = [&](const uint32_t (&W)[3][4], const uint4& h0, const uint2& h1) {
                float a0[4] = {}, a1[4] = {}, a2[4] = {};
                mmaA(a0, W[0], h0.x, h0.y); mmaA(a1, W[1], h0.z, h0.w); mmaA(a2, W[2], h1.x, h1.y);
                return ((a0[0] + a0[3]) + (a1[0] + a1[3])) + (a2[0] + a2[3]);
            };
            if (wp < 6) {
                uint32_t Wd[3][4];
                auto ldd = [&](uint32_t z) {
#pragma unroll
                    for (int s = 0; s < 3; s++) ldsm4t(Wd[s], ((wh ^ z) & 0xffff) + (sb + S_WD + s * 2560));
                };
                ldd(0);
                if (actc) {
                    const char* srcv = xp(uPolC + lag<DELAY_C>(sb, z0_) + 8 * n96);
                    const uint2 cs = lds64(sb + S_CSGU + 8 * n96);
                    float gt, up;
                    int guard = 0;
                    while (true) {
                        uint2 v[8];
#pragma unroll
                        for (int s = 0; s < 8; s++) v[s] = ldp64(srcv + (s >> 2) * HALF + (s & 3) * 1024);
                        uint2 c = ldsvol64(sb + S_LN + 8 * cc + ((v[7].x ^ parc) & 1) * 32);
                        const bool stale = __any_sync(~0u, (cnt16(v, 16 * parc) & 31) != 0), late = __any_sync(~0u, (c.y & 7) != ch + 1);
                        const float pg = sum8x(v), pu = sum8y(v);
                        auto norm = [&] {
                            mean = bf_hi(c.x); den = bf_lo(c.x);
                            gt = bfr(fmaf(-mean, asf(cs.x), pg) * asf(c.y)); up = fmaf(-mean, asf(cs.y), pu) * asf(c.y);
                            keep(gt); keep(up);
                        };
                        norm();
                        if (!((stale | late) & (++guard < SPIN_LIMIT))) break;
                        if (!stale) { take_ln(c, sb + S_LN + 8 * cc); norm(); break; }
                    }
                    CSTAMP(13);
                    SWEEPS(5 * ch + 2, guard - 1);
                    const uint32_t h = pack2(bfr(gt * sigmoidf_(gt)) * bfr(up), 0.f);
                    sts16((wh >> 16) + (sb + S_HS), h);
                    CSTAMP(14);
                    if (ch == 3) CSTAMP(0);
                }
                bar_main();
                TST(4);
                CSTAMP(15);
                const uint4 h0 = lds128(ha);
                const uint2 h1 = lds64(ha + 16);
                stp32_if(!(td & 2), xp(pubD & ~1u), down(Wd, h0, h1), pubD & 1);
            } else {
                uint32_t v = 0;
                const uint32_t col = wp == 7 || !has0;
                const bool serve = wp == 6 || (has0 && has1);
                if (serve) {
                    const uint32_t par = col ? par1 : par0;
                    const char* src = xp(uPolC + col * COL + 776 + (td & 4) * (HALF / 4) + (td & 3) * 1024);
                    give_ln(uPolC + col * COL, par, sb + S_LN + 8 * col, td, mean, den, [&] { v = ldp32(src); return v ^ par; });
                }
                stsvol(sb + S_GATE, ch + 1);
                uint32_t Wd[2][3][4];
#pragma unroll
                for (int s = 0; s < 6; s++) ldsm4t(Wd[s / 3][s % 3], (wh & 0xffff) + (sb + S_WD + (s / 3) * 16 + (s % 3) * 2560));
                bar_main();
                const uint4 h0 = lds128(ha);
                const uint2 h1 = lds64(ha + 16);
                const float d0 = down(Wd[0], h0, h1), d1 = down(Wd[1], h0, h1);
                stp32_if(true, xp(pubD & ~1u), (td & 2) ? d1 : d0, pubD & 1);
                if (serve) {
                    float xw = asf(v);
                    xw += __shfl_xor_sync(~0u, xw, 1); xw += __shfl_xor_sync(~0u, xw, 2); xw += __shfl_xor_sync(~0u, xw, 4);
                    const float r = bfr(fmaf(-mean, ldsf(sb + S_SWR), xw) * rcp(den));
                    sts32(sb + S_STAT + 4 * col, __float_as_uint(bfr(sigmoidf_(r))) | (ch + 1));
                }
            }
        }
        CSTAMP(16);
        {
            IDS();
            const uint32_t pubE = pin(uPubE + (t4 < 3 ? (wp >> 2) * COL + 192 * (wp & 3) + 64 * t4 + 8 * q8 : (q8 >> 2) * COL + 768 + 4 * (q8 & 1)));
            xr = pin(sb + S_XB + 48 * (ln & 7));
            uint32_t x2 = 0;
            auto hop_d = [&](auto col) {
                const uint32_t xbs = pin(sb + S_XB + 384 * col.value + b_pos<40>(n80)), xas = col.value ? 0 : pin(sb + S_XA + 192 + a_pos(n80));
                const float x1 = bf_lo(lds16(xbs));
                const float lnx = __uint_as_float(pin(__float_as_uint(bfr(__fdiv_rn(bfr(x1 - mean), den)))));
                gather16(xp(uPolD + 4 * n80 + lag<DELAY_D>(sb, z0_)), col.value ? par1 : par0, 5 * ch + 3, [&](float y, uint32_t z) {
                    const uint32_t gate = ldsvol(sb + S_STAT + 4 * col.value + z);
                    x2 = pack2(x1 + bfr(lnx + bfr(bfr(y) * bf_hi(gate))), 0.f);
                    if (col.value) keep(x2); else { sts16(xbs, x2); sts16(xas, x2); }
                    return (uint32_t)((gate & 7) != ch + 1);
                });
                CSTAMP(17);
            };
            auto qproj = [&](auto with_stats) {
                bar_main();
                TST(5);
                CSTAMP(19);
                const uint32_t t4 = td & 3;
                const uint4 b = lds128(xr);
                uint32_t b4 = lds32(xr + 16);
                float acc[6][4] = {};
                if (with_stats.value) {
                    stp32_if((td & 11) == 3, both, xp(pubE ^ COPY), xp(pubE), stats(xr + (S_XA - S_XB), b, b4), par0);
                    __syncwarp();
                    b4 = lds32(xr + 16);
                }
                mul80(acc, Wq, b, b4);
                const float v0 = sel4(t4, acc[0][0] + acc[0][3], acc[2][0] + acc[2][3], acc[4][0] + acc[4][3], acc[4][0] + acc[4][3]);
                const float v1 = sel4(t4, acc[1][0] + acc[1][3], acc[3][0] + acc[3][3], acc[5][0] + acc[5][3], acc[5][0] + acc[5][3]);
                stp64_if(t4 < 3, both, xp(pubE ^ COPY), xp(pubE), tagw(v0, par0), tagw(v1, par0));
            };
            if (wp == 7) {
                if (!has0) break;
                qproj(std::true_type());
            } else {
                if (actc && !cc) hop_d(std::integral_constant<int, 0>());
                else {
                    if (actc && g == 0) {
                        const uint32_t po = pin(1280 * (ch - 1) + 160 * i + 2 * n80);
                        hop_d(std::integral_constant<int, 1>());
                        *reinterpret_cast<unsigned short*>(reinterpret_cast<char*>(P.out) + po) = (unsigned short)x2;
                    }
                    if (!has0) break;
                }
                qproj(std::false_type());
                sts32_if(td < 80, sb + S_XCAR + 4 * td, x2 << 16);
            }
        }
        CSTAMP(20);
        if (wp == 6) give_ln(uPolE, par0, sb + S_LN + 16, td, mean, den, [] { return 0u; });
        auto pass2 = [&](auto d0, auto d1, auto d2) {
            constexpr int D0 = d0.value, D1 = d1.value, D = D0 + D1 + d2.value;
            IDS();
            const uint32_t ua = sb + k_place(ch, wp & 6) * SLOT + (wp & 1) * UNIT, k0 = k_off(ln);
            uint32_t kf[12][2][4];
            auto ldk = [&](int s) { const uint32_t a = (k0 ^ (32 * (s / 3))) + (ua + 1024 * (s % 3)); ldsm4(kf[s][0], a); ldsm4(kf[s][1], a + SLOT); };
            auto ldv1 = [&](int k) { ldsm4t(vf[k / 3][k % 3], voff[k % 3] + (sb + v_place(ch, k / 3) * SLOT)); };
            auto ldv = [&](int s) { ldv1(3 * s); ldv1(3 * s + 1); ldv1(3 * s + 2); };
            constexpr uint32_t LATE = LAST_LATE;
            constexpr uint64_t EARLY_LIST = bit_list(~LATE), LATE_LIST = bit_list(LATE);
            auto early = [&](int k) {
                if (D1 == 0) ldk(k);
                else if (k < 3) { ldv1(9 + 2 * k); ldv1(10 + 2 * k); }
                else ldk((EARLY_LIST >> (4 * (k - 3))) & 15);
            };
            uint32_t v[8] = {}, qsa = 0;
            const char* srcv = xp(uPolE + lag<(D1 > 0 ? 0 : DELAY_E)>(sb, z0_) + 4 * td);
            auto look = [&] {
#pragma unroll
                for (int s = 0; s < 8; s++) v[s] = ldp32(srcv + (s >> 2) * HALF + (s & 3) * 1024);
            };
            if (D1 > 0) vaddr(voff);
            if (!(mbar_try(sb + S_FK + 8 * (wp & 6), par1) & mbar_try(sb + S_FK + 8 * (wp | 1), par1))) { mbar_wait(sb + S_FK + 8 * (wp & 6), par1); mbar_wait(sb + S_FK + 8 * (wp | 1), par1); }
#pragma unroll
            for (int s = 0; s < D0; s++) early(s);
            if (wp < 6) { look(); qsa = pin(sb + S_QS + 384 * ch + q_pos(z_)); }
#pragma unroll
            for (int s = D0; s < D0 + D1; s++) early(s);
            if (wp < 6) {
                const float cs = ldsf(sb + S_CSQ + 4 * td);
                int guard = 0;
                while (true) {
                    uint2 c = ldsvol64(sb + S_LN + 16 + ((v[0] ^ par0) & 1) * 32);
                    const bool stale = __any_sync(~0u, (cnt8(v, 24 * par0) & 31) != 0), late = __any_sync(~0u, (c.y & 7) != ch + 1);
                    const float qs = sum8(v);
                    auto norm = [&] {
                        const uint32_t q = pack2(fmaf(-bf_hi(c.x), cs, qs) * asf(c.y), 0.f);
                        sts16(qsa, q);
                    };
                    norm();
                    if (!((stale | late) & (++guard < SPIN_LIMIT))) break;
                    if (!stale) { take_ln(c, sb + S_LN + 16); norm(); break; }
                    look();
                }
                SWEEPS(5 * ch + 4, guard - 1);
                CSTAMP(22);
            }
#pragma unroll
            for (int s = D0 + D1; s < D; s++) early(s);
            CSTAMP(21);
            bar_main();
            TST(6);
            CSTAMP(1);
            uint2 q = lds64(sb + S_QS + 384 * ch + 8 * ln);
            float acc[2][4] = {};
            constexpr int V0 = 13 - D, NV = D1 > 0 ? 2 : (2 * (D - 1)) / 3;
            static_assert(D1 == 0 || D - 3 + __builtin_popcount(LATE) == 12, "plan");
#pragma unroll
            for (int s = 0; s < 12; s++) {
                const bool m = q8 == (s & 7);
                const uint32_t b0 = m ? q.x : 0u, b1 = m ? q.y : 0u;
                if (s == 7) q = lds64(sb + S_QS + 384 * ch + 8 * ln + 256);
                mmaA(acc[0], kf[s][0], b0, b1);
                mmaA(acc[1], kf[s][1], b0, b1);
                if (D1 > 0) {
                    if (s >= 1 && s <= __builtin_popcount(LATE)) ldk((LATE_LIST >> (4 * (s - 1))) & 15);
                } else {
                    if (s >= 1 && s + D - 1 < 12) ldk(s + D - 1);
                    if (s >= 1 && s + D - 1 == 11) { __syncwarp(); arrive_if(ln == 0, sb + S_RELK); }
                    if (s == V0) vaddr(voff);
                    if (s >= V0 && 2 * (s - V0) < 3 * NV) ldv1(9 + 2 * (s - V0));
                    if (s >= V0 && 2 * (s - V0) + 1 < 3 * NV) ldv1(10 + 2 * (s - V0));
                }
            }
            CSTAMP(24);
            {
                const float v0 = acc[0][0] + acc[0][1], v1 = acc[0][2] + acc[0][3], v2 = acc[1][0] + acc[1][1], v3 = acc[1][2] + acc[1][3];
                const bool hi = t4 & 2, od = t4 & 1;
                const float u0 = (hi ? v2 : v0) + __shfl_xor_sync(~0u, hi ? v0 : v2, 2), u1 = (hi ? v3 : v1) + __shfl_xor_sync(~0u, hi ? v1 : v3, 2);
                const float s = (od ? u1 : u0) + __shfl_xor_sync(~0u, od ? u0 : u1, 1);
                CSTAMP(2);
                probs(scaled(s), sb + S_PS + PS_PASS, wp, ln);
                CSTAMP(3);
            }
            bar_main();
            TST(10);
            CSTAMP(4);
            if (D1 > 0) values(vf, acc_, [&](int s) { if (s < 3) ldv(s + 5); }, sb + S_PS + PS_PASS, std::integral_constant<int, 1>(), par0);
            else values(vf, acc_, [&](int s) { if (s >= (NV > 1 ? 2 : 1) && s + NV + (NV > 1 ? 1 : 2) < 8) ldv(s + NV + (NV > 1 ? 1 : 2)); }, sb + S_PS + PS_PASS, std::integral_constant<int, 1>(), par0);
            arrive_if(ln == 0, sb + S_RELV);
        };
        if (ch == 3) {
            pass2(std::integral_constant<int, LAST0>(), std::integral_constant<int, LAST1>(), std::integral_constant<int, LAST2>());
#pragma unroll
            for (int m = 0; m < 48; m++) Wq[m / 8].a[(m / 4) % 2][m % 4] = vf[3 + m / 12][(m / 4) % 3][m % 4];
#pragma unroll
            for (int m = 0; m < 12; m++) Wq[m / 2].c[m % 2] = vf[7][m / 4][m % 4];
#pragma unroll
            for (int m = 0; m < 36; m++) left[m] = m < 12 ? __float_as_uint(acc_[m / 4][m % 4]) : vf[m / 12][(m / 4) % 3][m % 4];
        } else {
            pass2(std::integral_constant<int, KPRE>(), std::integral_constant<int, 0>(), std::integral_constant<int, KPRE2>());
#pragma unroll
            for (int m = 0; m < 36; m++) left[m] = m < 12 ? __float_as_uint(acc_[m / 4][m % 4]) : vf[4 + m / 12][(m / 4) % 3][m % 4];
        }
        TST(11);
        CSTAMP(23);
    }
    sts32_if(td == 255, sb + S_GATE, 6);
    TSTAMP(3);
}

typedef CUresult (*EncodeFn)(CUtensorMap*, CUtensorMapDataType, cuuint32_t, void*, const cuuint64_t*, const cuuint64_t*, const cuuint32_t*,
                             const cuuint32_t*, CUtensorMapInterleave, CUtensorMapSwizzle, CUtensorMapL2promotion, CUtensorMapFloatOOBfill);

void make_map(EncodeFn enc, CUtensorMap* m, const void* base, uint64_t cols, uint64_t rows, uint32_t box_cols, uint32_t box_rows, bool swizzle) {
    cuuint64_t dims[2] = {cols, rows};
    cuuint64_t strides[1] = {cols * 2};
    cuuint32_t box[2] = {box_cols, box_rows};
    cuuint32_t es[2] = {1, 1};
    enc(m, CU_TENSOR_MAP_DATA_TYPE_BFLOAT16, 2, const_cast<void*>(base), dims, strides, box, es, CU_TENSOR_MAP_INTERLEAVE_NONE,
        swizzle ? CU_TENSOR_MAP_SWIZZLE_128B : CU_TENSOR_MAP_SWIZZLE_NONE, CU_TENSOR_MAP_L2_PROMOTION_NONE, CU_TENSOR_MAP_FLOAT_OOB_FILL_NONE);
}

}

extern "C" void kernel_launch(void* const* d_in, const int* in_sizes, int n_in, void* d_out, int out_size) {
    (void)in_sizes; (void)n_in; (void)out_size;
    static EncodeFn enc = nullptr;
    if (!enc) {
        void* f = nullptr;
        cudaDriverEntryPointQueryResult q;
        cudaGetDriverEntryPoint("cuTensorMapEncodeTiled", &f, cudaEnableDefault, &q);
        enc = (EncodeFn)f;
        cudaFuncSetAttribute(fused_kernel, cudaFuncAttributeMaxDynamicSharedMemorySize, SMEM_BYTES);
    }
    Params P;
    P.x = (const __nv_bfloat16*)d_in[0]; P.k = (const __nv_bfloat16*)d_in[1]; P.v = (const __nv_bfloat16*)d_in[2];
    P.wr = (const __nv_bfloat16*)d_in[6]; P.wq = (const __nv_bfloat16*)d_in[3];
    P.out = (__nv_bfloat16*)d_out;
    Maps M;
    {
        cuuint64_t dims[4] = {64, 8, 3, (cuuint64_t)KV_BATCH_KEYS / 2}, strides[3] = {384, 128, 3072};
        cuuint32_t box[4] = {64, 8, 3, 2}, es[4] = {1, 1, 1, 1};
        enc(&M.k, CU_TENSOR_MAP_DATA_TYPE_BFLOAT16, 4, d_in[1], dims, strides, box, es, CU_TENSOR_MAP_INTERLEAVE_NONE, CU_TENSOR_MAP_SWIZZLE_128B,
            CU_TENSOR_MAP_L2_PROMOTION_NONE, CU_TENSOR_MAP_FLOAT_OOB_FILL_NONE);
    }
    make_map(enc, &M.v, P.v, 64, (uint64_t)12 * KV_BATCH_KEYS, 64, 96, true);
    make_map(enc, &M.vu, P.v, 64, (uint64_t)12 * KV_BATCH_KEYS, 64, 48, true);
    make_map(enc, &M.wq, d_in[3], 6144, 640, 192, 40, false);
    make_map(enc, &M.wo, d_in[4], 640, 6144, 80, 96, false);
    make_map(enc, &M.wg, d_in[7], 1536, 640, 96, 80, false);
    make_map(enc, &M.wu, d_in[8], 1536, 640, 96, 80, false);
    make_map(enc, &M.wd, d_in[9], 640, 1536, 80, 96, false);
    fused_kernel<<<NCTA, NTHR, SMEM_BYTES, cudaStreamPerThread>>>(P, M);
}
```

```cpp
#include <cuda_runtime.h>
#include <cuda.h>
#include <cuda_bf16.h>
#include <stdint.h>
#include <type_traits>

namespace {

constexpr int NCTA = 128;
constexpr int NTHR = 384;
constexpr int UNIT = 6144;
constexpr int SLOT = 12288;
#define TAU 3880
#define TAUW 3700
#define TAU0 3780
#define ILV 4
#define XB 900
#define FORCE_BOTH 0
#define TMIN 2400
#define SLACK 6000
#define SLACK0 1000
#define LEADW 3500
#define WIN_W 3
#define WIN_S 4
#define WIN_U 10
#define VPF 4
#define KRE_TAU 2600
#define RFR_TAU 22400
#define HOP1_NS 200
#define KPRE 2
#define KPRE2 2
#define LAST0 3
#define LAST1 5
#define LAST2 2
#define LAST_LATE 0xaa8
#define FSTEP 4
#define DELAY_L 0
#define DELAY_G 2
#define DELAY_C 2
#define DELAY_D 4
#define DELAY_E 3
#define REG_LO "40"
#define REG_HI "232"
#define SPIN_LOG 17
constexpr int SPIN_LIMIT = 1 << SPIN_LOG, SPIN_FAST = SPIN_LIMIT << 4;

__host__ __device__ constexpr uint32_t pairL(uint32_t region, uint32_t c, uint32_t g) { return (g & 1) | ((g >> 1) << 2) | (c << 5) | (region << 6); }
__host__ __device__ constexpr uint32_t pairG(uint32_t d, uint32_t c, uint32_t i) { return (i & 1) | ((i >> 1) << 2) | (d << 4) | (c << 5) | (3u << 6); }
constexpr uint32_t RA = 0, RC = 1, RE = 2, HALF = 16384, COPY = 4096, PMASK = 0x59;
constexpr uint32_t XS = 0;
constexpr uint32_t XS2 = XS + 128 * 7680;
constexpr uint32_t XSEND = XS2 + 128 * 768;
__device__ uint4 g_s[XSEND / 16];
__device__ uint4 g_x[(4u << 20) / 16];
#define SWEEPS(k, n) do {} while (0)

constexpr uint32_t S_WD = 16 * SLOT;
constexpr uint32_t S_DUMMY = S_WD + 15360;
constexpr uint32_t S_BAR = S_DUMMY + 4096;
constexpr uint32_t S_FV = S_BAR, S_FK = S_FV + 64, S_RING = S_FK + 64, S_DBAR = S_RING + 48, S_WFULL = S_DBAR + 32, S_QRDY = S_WFULL + 88;
constexpr uint32_t S_RELK = S_QRDY + 8, S_RELV = S_RELK + 8, S_RELR = S_RELV + 8, S_RELW = S_RELR + 8, S_SCO = S_RELW + 24;
constexpr uint32_t S_OS1 = S_SCO + 8;
constexpr uint32_t S_ZERO = S_OS1 + 8;
constexpr uint32_t S_KF = S_ZERO + 8;
constexpr uint32_t S_TOK = S_KF + 8;
constexpr uint32_t S_SIDE = S_TOK + 80, S_GATE = S_SIDE + 4;
constexpr uint32_t S_STAT = S_GATE + 12, S_SWR = S_STAT + 16;
constexpr uint32_t S_LN = S_STAT + 32;
constexpr uint32_t S_XCAR = S_LN + 64;
constexpr uint32_t S_CSQ = S_XCAR + 320;
constexpr uint32_t S_CSGU = S_CSQ + 768;
constexpr uint32_t S_RED = S_CSGU + 768;
constexpr uint32_t S_L0 = S_RED;
constexpr uint32_t S_OS = S_RED + 5120;
constexpr uint32_t S_PS = S_OS + 1536;
constexpr uint32_t PS_MAX = 512, PS_PASS = 544;
constexpr uint32_t S_QS = S_PS + 2 * PS_PASS;
constexpr uint32_t S_XB = S_QS + 1536;
constexpr uint32_t S_XA = S_XB + 768;
constexpr uint32_t S_HS = S_XA + 768;
constexpr uint32_t S_X0 = S_HS + 768;
constexpr uint32_t S_SC = S_X0 + 640;
constexpr uint32_t S_TM = S_SC + 512;
constexpr int SMEM_BYTES = S_TM + 256;
static_assert(SMEM_BYTES <= 232448 && S_STAT % 16 == 0 && S_RED % 16 == 0 && S_XB % 16 == 0 && S_HS % 16 == 0 && S_PS % 16 == 0 && S_QS % 16 == 0, "smem");
static_assert(S_SCO == S_BAR + 44 * 8 && S_RELK == S_BAR + 38 * 8, "barriers");
constexpr uint32_t ST_WQ = 3 * SLOT, ST_WG = 8 * SLOT, ST_WO = 11 * SLOT;

__device__ __forceinline__ uint32_t smem_u32(const void* p) { return (uint32_t)__cvta_generic_to_shared(p); }
__device__ __forceinline__ void mbar_arrive(uint32_t bar) { asm volatile("mbarrier.arrive.shared::cta.b64 _, [%0];" :: "r"(bar) : "memory"); }
__device__ __forceinline__ bool mbar_try(uint32_t bar, uint32_t parity) {
    uint32_t ok;
    asm volatile("{\n .reg .pred p;\n mbarrier.try_wait.parity.shared::cta.b64 p, [%1], %2;\n selp.u32 %0, 1, 0, p;\n}" : "=r"(ok) : "r"(bar), "r"(parity) : "memory");
    return ok != 0;
}
__device__ __forceinline__ bool mbar_test(uint32_t bar, uint32_t parity) {
    uint32_t ok;
    asm volatile("{\n .reg .pred p;\n mbarrier.test_wait.parity.shared::cta.b64 p, [%1], %2;\n selp.u32 %0, 1, 0, p;\n}" : "=r"(ok) : "r"(bar), "r"(parity) : "memory");
    return ok != 0;
}
__device__ __forceinline__ void mbar_wait(uint32_t bar, uint32_t parity) {
    int n = 0;
    while (!mbar_try(bar, parity) && ++n < SPIN_LIMIT) {}
}
__device__ __forceinline__ uint32_t gtime32() { uint32_t t; asm volatile("mov.u32 %0, %globaltimer_lo;" : "=r"(t)); return t; }
__device__ __forceinline__ void bar_main() { asm volatile("bar.sync 1, 256;" ::: "memory"); }

__device__ __forceinline__ void mma16816(float (&c)[4], uint32_t a0, uint32_t a1, uint32_t a2, uint32_t a3, uint32_t b0, uint32_t b1) {
    asm("mma.sync.aligned.m16n8k16.row.col.f32.bf16.bf16.f32 {%0,%1,%2,%3}, {%4,%5,%6,%7}, {%8,%9}, {%0,%1,%2,%3};"
        : "+f"(c[0]), "+f"(c[1]), "+f"(c[2]), "+f"(c[3]) : "r"(a0), "r"(a1), "r"(a2), "r"(a3), "r"(b0), "r"(b1));
}
__device__ __forceinline__ void mmaA(float (&c)[4], const uint32_t (&a)[4], uint32_t b0, uint32_t b1) { mma16816(c, a[0], a[1], a[2], a[3], b0, b1); }
__device__ __forceinline__ void mma8(float (&c)[4], uint32_t a0, uint32_t a1, uint32_t b0) {
    asm("mma.sync.aligned.m16n8k8.row.col.f32.bf16.bf16.f32 {%0,%1,%2,%3}, {%4,%5}, {%6}, {%0,%1,%2,%3};"
        : "+f"(c[0]), "+f"(c[1]), "+f"(c[2]), "+f"(c[3]) : "r"(a0), "r"(a1), "r"(b0));
}
struct W80 { uint32_t a[2][4], c[2]; };
template <int N> __device__ __forceinline__ void mul80(float (&acc)[N][4], const W80 (&W)[N], const uint4& b, uint32_t b4) {
#pragma unroll
    for (int m = 0; m < N; m++) mmaA(acc[m], W[m].a[0], b.x, b.y);
#pragma unroll
    for (int m = 0; m < N; m++) mmaA(acc[m], W[m].a[1], b.z, b.w);
#pragma unroll
    for (int m = 0; m < N; m++) mma8(acc[m], W[m].c[0], W[m].c[1], b4);
}
__device__ __forceinline__ void ldsm2t(uint32_t (&r)[2], uint32_t addr) {
    asm volatile("ldmatrix.sync.aligned.m8n8.x2.trans.shared.b16 {%0,%1}, [%2];" : "=r"(r[0]), "=r"(r[1]) : "r"(addr) : "memory");
}
__device__ __forceinline__ void mmaV(float (&c)[4], const uint4& a, uint32_t b0, uint32_t b1) { mma16816(c, a.x, a.y, a.z, a.w, b0, b1); }
__device__ __forceinline__ void ldsm4(uint32_t (&r)[4], uint32_t addr) {
    asm volatile("ldmatrix.sync.aligned.m8n8.x4.shared.b16 {%0,%1,%2,%3}, [%4];" : "=r"(r[0]), "=r"(r[1]), "=r"(r[2]), "=r"(r[3]) : "r"(addr) : "memory");
}
__device__ __forceinline__ void ldsm4t(uint32_t (&r)[4], uint32_t addr) {
    asm volatile("ldmatrix.sync.aligned.m8n8.x4.trans.shared.b16 {%0,%1,%2,%3}, [%4];" : "=r"(r[0]), "=r"(r[1]), "=r"(r[2]), "=r"(r[3]) : "r"(addr) : "memory");
}
__device__ __forceinline__ uint32_t lds16(uint32_t a) { uint16_t v; asm volatile("ld.shared.u16 %0, [%1];" : "=h"(v) : "r"(a) : "memory"); return v; }
__device__ __forceinline__ uint32_t lds32(uint32_t a) { uint32_t v; asm volatile("ld.shared.u32 %0, [%1];" : "=r"(v) : "r"(a) : "memory"); return v; }
__device__ __forceinline__ float ldsf(uint32_t a) { return __uint_as_float(lds32(a)); }
__device__ __forceinline__ uint2 lds64(uint32_t a) { uint2 v; asm volatile("ld.shared.v2.u32 {%0,%1}, [%2];" : "=r"(v.x), "=r"(v.y) : "r"(a) : "memory"); return v; }
__device__ __forceinline__ uint4 lds128(uint32_t a) { uint4 v; asm volatile("ld.shared.v4.u32 {%0,%1,%2,%3}, [%4];" : "=r"(v.x), "=r"(v.y), "=r"(v.z), "=r"(v.w) : "r"(a) : "memory"); return v; }
__device__ __forceinline__ int ldsvol(uint32_t a) { int v; asm volatile("ld.volatile.shared.u32 %0, [%1];" : "=r"(v) : "r"(a) : "memory"); return v; }
__device__ __forceinline__ uint2 ldsvol64(uint32_t a) { uint2 v; asm volatile("{\n .reg .b64 d;\n ld.volatile.shared.b64 d, [%2];\n mov.b64 {%0,%1}, d;\n}" : "=r"(v.x), "=r"(v.y) : "r"(a) : "memory"); return v; }
__device__ __forceinline__ void stsvol64(uint32_t a, uint32_t x, uint32_t y) { asm volatile("{\n .reg .b64 d;\n mov.b64 d, {%1,%2};\n st.volatile.shared.b64 [%0], d;\n}" :: "r"(a), "r"(x), "r"(y) : "memory"); }
__device__ __forceinline__ void stsvol(uint32_t a, int v) { asm volatile("st.volatile.shared.u32 [%0], %1;" :: "r"(a), "r"(v) : "memory"); }
__device__ __forceinline__ void sts_hi16(uint32_t a, float v) { asm volatile("{\n .reg .b16 lo, hi;\n mov.b32 {lo, hi}, %1;\n st.shared.u16 [%0], hi;\n}" :: "r"(a), "r"(__float_as_uint(v)) : "memory"); }
__device__ __forceinline__ void sts16(uint32_t a, uint32_t v) { asm volatile("st.shared.u16 [%0], %1;" :: "r"(a), "r"(v) : "memory"); }
__device__ __forceinline__ void sts32(uint32_t a, uint32_t v) { asm volatile("st.shared.u32 [%0], %1;" :: "r"(a), "r"(v) : "memory"); }
__device__ __forceinline__ void stsf(uint32_t a, float v) { sts32(a, __float_as_uint(v)); }
__device__ __forceinline__ void sts64(uint32_t a, uint32_t x, uint32_t y) { asm volatile("st.shared.v2.u32 [%0], {%1,%2};" :: "r"(a), "r"(x), "r"(y) : "memory"); }

__device__ __forceinline__ void sts32_if(bool p, uint32_t a, uint32_t v) {
    asm volatile("{\n .reg .pred p;\n setp.ne.u32 p, %2, 0;\n @p st.shared.u32 [%0], %1;\n}" :: "r"(a), "r"(v), "r"((uint32_t)p) : "memory");
}
__device__ __forceinline__ void arrive_if(bool p, uint32_t bar) {
    asm volatile("{\n .reg .pred p;\n setp.ne.u32 p, %1, 0;\n @p mbarrier.arrive.shared::cta.b64 _, [%0];\n}" :: "r"(bar), "r"((uint32_t)p) : "memory");
}
__device__ __forceinline__ void keep(uint32_t& v) { asm volatile("" : "+r"(v)); }
__device__ __forceinline__ void keep(float& v) { asm volatile("" : "+f"(v)); }

__device__ __forceinline__ uint32_t ldp32(const char* p) { uint32_t v; asm volatile("ld.relaxed.gpu.global.u32 %0, [%1];" : "=r"(v) : "l"(p) : "memory"); return v; }
__device__ __forceinline__ uint2 ldp64(const char* p) {
    uint2 v; asm volatile("{\n .reg .b64 d;\n ld.relaxed.gpu.global.b64 d, [%2];\n mov.b64 {%0,%1}, d;\n}" : "=r"(v.x), "=r"(v.y) : "l"(p) : "memory"); return v;
}
__device__ __forceinline__ uint32_t tagw(float f, uint32_t par) { return (__float_as_uint(f) & ~31u) | par; }
__device__ __forceinline__ void stp32(char* p, float a, uint32_t par) { asm volatile("st.relaxed.gpu.global.u32 [%0], %1;" :: "l"(p), "r"(tagw(a, par)) : "memory"); }
__device__ __forceinline__ void stp64(char* p, float a, float b, uint32_t par) {
    asm volatile("{\n .reg .b64 d;\n mov.b64 d, {%1,%2};\n st.relaxed.gpu.global.b64 [%0], d;\n}" :: "l"(p), "r"(tagw(a, par)), "r"(tagw(b, par)) : "memory");
}
__device__ __forceinline__ void stp32_if(bool p, char* d, float a, uint32_t par) {
    asm volatile("{\n .reg .pred p;\n setp.ne.u32 p, %2, 0;\n @p st.relaxed.gpu.global.u32 [%0], %1;\n @p st.relaxed.gpu.global.u32 [%0+4096], %1;\n}" :: "l"(d), "r"(tagw(a, par)), "r"((uint32_t)p) : "memory");
}
__device__ __forceinline__ void stp32_if(bool p, uint32_t both, char* d, char* e, float a, uint32_t par) {
    asm volatile("{\n .reg .pred p, q;\n setp.ne.u32 p, %2, 0;\n setp.ne.and.u32 q, %4, 0, p;\n @p st.relaxed.gpu.global.u32 [%3], %1;\n @q st.relaxed.gpu.global.u32 [%0], %1;\n}" :: "l"(d), "r"(tagw(a, par)), "r"((uint32_t)p), "l"(e), "r"(both) : "memory");
}
__device__ __forceinline__ void stp64_if(bool p, uint32_t both, char* d, char* e, uint32_t lo, uint32_t hi) {
    asm volatile("{\n .reg .pred p, q;\n .reg .b64 d;\n setp.ne.u32 p, %3, 0;\n setp.ne.and.u32 q, %5, 0, p;\n mov.b64 d, {%1,%2};\n @p st.relaxed.gpu.global.b64 [%4], d;\n @q st.relaxed.gpu.global.b64 [%0], d;\n}" :: "l"(d), "r"(lo), "r"(hi), "r"((uint32_t)p), "l"(e), "r"(both) : "memory");
}
__device__ __forceinline__ uint32_t add3(uint32_t a, uint32_t b, uint32_t c) { uint32_t r; asm("{\n .reg .u32 t;\n add.u32 t, %1, %2;\n add.u32 %0, t, %3;\n}" : "=r"(r) : "r"(a), "r"(b), "r"(c)); return r; }
__device__ __forceinline__ uint32_t cnt8(const uint32_t (&v)[8], uint32_t c) { return add3(add3(v[0], v[1], c), add3(v[2], v[3], v[4]), add3(v[5], v[6], v[7])); }
__device__ __forceinline__ uint32_t cnt8(const uint2 (&v)[4], uint32_t c) { return add3(add3(v[0].x, v[0].y, c), add3(v[1].x, v[1].y, v[2].x), add3(v[2].y, v[3].x, v[3].y)); }
__device__ __forceinline__ uint32_t cnt16(const uint2 (&v)[8], uint32_t c) {
    return add3(add3(add3(v[0].x, v[0].y, c), add3(v[1].x, v[1].y, v[2].x), add3(v[2].y, v[3].x, v[3].y)), add3(add3(v[4].x, v[4].y, v[5].x), v[5].y, v[6].x), add3(v[6].y, v[7].x, v[7].y));
}
__device__ __forceinline__ uint32_t cnt16(const uint32_t (&v)[8], const uint32_t (&u)[8], uint32_t c) { return add3(cnt8(v, c), add3(add3(u[0], u[1], u[2]), u[3], u[4]), add3(u[5], u[6], u[7])); }
__device__ __forceinline__ float asf(uint32_t v) { return __uint_as_float(v); }
__device__ __forceinline__ float sum8(const uint32_t (&v)[8]) { return ((asf(v[0]) + asf(v[1])) + (asf(v[2]) + asf(v[3]))) + ((asf(v[4]) + asf(v[5])) + (asf(v[6]) + asf(v[7]))); }
__device__ __forceinline__ float sum8x(const uint2 (&v)[8]) { return ((asf(v[0].x) + asf(v[1].x)) + (asf(v[2].x) + asf(v[3].x))) + ((asf(v[4].x) + asf(v[5].x)) + (asf(v[6].x) + asf(v[7].x))); }
__device__ __forceinline__ float sum8y(const uint2 (&v)[8]) { return ((asf(v[0].y) + asf(v[1].y)) + (asf(v[2].y) + asf(v[3].y))) + ((asf(v[4].y) + asf(v[5].y)) + (asf(v[6].y) + asf(v[7].y))); }

__device__ __forceinline__ uint32_t pack2(float lo, float hi) { uint32_t r; asm("cvt.rn.bf16x2.f32 %0, %1, %2;" : "=r"(r) : "f"(hi), "f"(lo)); return r; }
__device__ __forceinline__ float bfr(float x) { return __uint_as_float(pack2(0.0f, x)); }
__device__ __forceinline__ float ex2(float x) { float r; asm("ex2.approx.ftz.f32 %0, %1;" : "=f"(r) : "f"(x)); return r; }
__device__ __forceinline__ float rcp(float x) { float r; asm("rcp.approx.ftz.f32 %0, %1;" : "=f"(r) : "f"(x)); return r; }
__device__ __forceinline__ float sqrt_(float x) { float r; asm("sqrt.approx.ftz.f32 %0, %1;" : "=f"(r) : "f"(x)); return r; }
__device__ __forceinline__ float bf_lo(uint32_t v) { return __uint_as_float(v << 16); }
__device__ __forceinline__ float bf_hi(uint32_t v) { return __uint_as_float(v & 0xffff0000u); }
__device__ __forceinline__ float sel4(int k, float a, float b, float c, float d) { return (k & 2) ? ((k & 1) ? d : c) : ((k & 1) ? b : a); }
constexpr float LOG2E = 1.4426950408889634f;
constexpr uint32_t ONES = 0x3f803f80u;

__device__ __forceinline__ void ln_stats(float sum, float sq, float& mean, float& den) {
    const float m = sum * (1.0f / 640.0f);
    const float var = fmaxf(fmaf(sq, 1.0f / 640.0f, -m * m), 0.0f);
    mean = bfr(m);
    den = bfr(sqrt_(bfr(bfr(var) + 1e-5f)));
}
__device__ __forceinline__ float sigmoidf_(float x) { return rcp(1.0f + ex2(-x * LOG2E)); }

#define TSTAMP(k) do {} while (0)
#define TST(k) do {} while (0)

#define CSTAMP(k) do {} while (0)
template <int N> __device__ __forceinline__ uint32_t lag(uint32_t sb, uint32_t z = 0) {
#pragma unroll
    for (int k = 0; k < N; k++) z = ldsvol(sb + S_ZERO + z);
    return z;
}
__device__ __forceinline__ void warm_mma(uint32_t& a, uint32_t& b) {
    asm volatile("mma.sync.aligned.m16n8k8.row.col.f16.f16.f16.f16 {%0,%1}, {%0,%1}, {%0}, {%0,%1};" : "+r"(a), "+r"(b) :: "memory");
}
#define KWNS2 20
#define KWNS 200
template <class F>
__device__ __forceinline__ void gather16(const char* p, uint32_t par, int k, F use) {
    uint32_t v[8], u[8];
    int guard = 0;
    bool again;
    do {
#pragma unroll
        for (int s = 0; s < 8; s++) v[s] = ldp32(p + s * 512);
#pragma unroll
        for (int s = 0; s < 8; s++) u[s] = ldp32(p + HALF + s * 512);
        const uint32_t stale = use(sum8(v) + sum8(u), ((v[0] ^ par) & 1) * 8);
        again = __any_sync(~0u, ((cnt16(v, u, 16 * par) | stale) & 31) != 0);
    } while (again & (++guard < SPIN_LIMIT));
    SWEEPS(k, guard - 1);
}

struct Params {
    const __nv_bfloat16 *x, *k, *v, *wr, *wq;
    __nv_bfloat16* out;
};
struct Maps { CUtensorMap k, v, vu, wq, wo, wg, wu, wd; };

constexpr int KV_BATCH_KEYS = 32 * 4096;

__device__ __forceinline__ void tma2d(uint32_t dst, const CUtensorMap* m, int c0, int c1, uint32_t bar, uint32_t bytes, uint64_t pol) {
    asm volatile("{\n .reg .pred p;\n elect.sync _|p, 0xffffffff;\n"
                 " @p mbarrier.arrive.expect_tx.shared::cta.b64 _, [%2], %6;\n"
                 " @p cp.async.bulk.tensor.2d.shared::cluster.global.mbarrier::complete_tx::bytes.L2::cache_hint [%0], [%1, {%3, %4}], [%2], %5;\n}"
                 :: "r"(dst), "l"(m), "r"(bar), "r"(c0), "r"(c1), "l"(pol), "r"(bytes) : "memory");
}
__device__ __forceinline__ void scrap_copy(uint32_t dst, const char* src, uint32_t bar) {
    asm volatile("{\n .reg .pred p;\n elect.sync _|p, 0xffffffff;\n"
                 " @p mbarrier.arrive.expect_tx.shared::cta.b64 _, [%2], 12288;\n"
                 " @p cp.async.bulk.shared::cluster.global.mbarrier::complete_tx::bytes [%0], [%1], 4096, [%2];\n"
                 " @p cp.async.bulk.shared::cluster.global.mbarrier::complete_tx::bytes [%0], [%1+4096], 4096, [%2];\n"
                 " @p cp.async.bulk.shared::cluster.global.mbarrier::complete_tx::bytes [%0], [%1+8192], 4096, [%2];\n}"
                 :: "r"(dst), "l"(src), "r"(bar) : "memory");
}
__device__ __forceinline__ void prefetch_l2(const void* p, uint32_t bytes) {
    asm volatile("{\n .reg .pred p;\n elect.sync _|p, 0xffffffff;\n @p cp.async.bulk.prefetch.L2.global [%0], %1;\n}" :: "l"(p), "r"(bytes) : "memory");
}
__device__ __forceinline__ uint64_t pol_first() { uint64_t p; asm("createpolicy.fractional.L2::evict_first.b64 %0, 1.0;" : "=l"(p)); return p; }
__device__ __forceinline__ uint64_t pol_normal() { uint64_t p; asm("createpolicy.fractional.L2::evict_normal.b64 %0, 1.0;" : "=l"(p)); return p; }
__device__ __forceinline__ bool utest(uint32_t bar, uint32_t parity) { return __all_sync(~0u, mbar_test(bar, parity)); }
__device__ __forceinline__ void uwait(uint32_t bar, uint32_t parity) {
    int n = 0;
    while (!__all_sync(~0u, mbar_try(bar, parity)) && ++n < SPIN_LIMIT) {}
}
template <int A, int B, int CNT> __device__ __forceinline__ void init_bars(uint32_t sb) {
#pragma unroll 1
    for (int k = A; k < B; k++)
        asm volatile("{\n .reg .pred p;\n elect.sync _|p, 0xffffffff;\n @p mbarrier.init.shared::cta.b64 [%0], %1;\n}" :: "r"(sb + S_BAR + 8 * k), "n"(CNT) : "memory");
}
__device__ __forceinline__ int unit_key(uint32_t b, uint32_t u) {
    return (blockIdx.x >> 2) * 4096 + 3072 + (blockIdx.x & 3) * (16 * ILV) + b * KV_BATCH_KEYS + (u & ~(ILV - 1u)) * 64 + (u & (ILV - 1)) * 16;
}
__device__ __forceinline__ void load_tile(const CUtensorMap* m, uint32_t dst, uint32_t bar, uint32_t bytes, int key, uint64_t pol) { tma2d(dst, m, 0, 3 * key, bar, bytes, pol); }
__device__ __forceinline__ const char* unit_ptr(const Params& P, int n) { return (const char*)((n & 16) ? P.v : P.k) + (size_t)unit_key(n >> 5, n & 15) * 384; }
#define LSTAMP(k) do {} while (0)

__device__ __forceinline__ uint32_t k_place(uint32_t b, uint32_t s) { return s + 3 + 5 * (b & 1); }
__device__ __forceinline__ uint32_t v_place(uint32_t b, uint32_t s) { return s < 3 ? s : s + 8 - 8 * (b & 1); }
__device__ __forceinline__ void k_load(const Maps& M, uint32_t dst, uint32_t bar, int key8, uint64_t pol) {
    asm volatile("{\n .reg .pred p;\n elect.sync _|p, 0xffffffff;\n"
                 " @p mbarrier.arrive.expect_tx.shared::cta.b64 _, [%2], 6144;\n"
                 " @p cp.async.bulk.tensor.4d.shared::cluster.global.mbarrier::complete_tx::bytes.L2::cache_hint [%0], [%1, {0, 0, 0, %3}], [%2], %4;\n}"
                 :: "r"(dst), "l"(&M.k), "r"(bar), "r"(key8), "l"(pol) : "memory");
}
__device__ __forceinline__ int unit_key8(uint32_t n) { return unit_key(n >> 4, n & 15) >> 3; }
__device__ __forceinline__ void ring_load(const Maps& M, uint32_t sb, uint32_t b, uint32_t u, uint32_t pos) {
    if (u < 16) k_load(M, sb + pos * UNIT, sb + S_RING + 8 * pos, unit_key8(16 * b + u), pol_normal());
    else load_tile(&M.vu, sb + pos * UNIT, sb + S_FV + 4 * (pos & 6), UNIT, unit_key(b, pos), pol_first());
}
__device__ __forceinline__ uint32_t token(bool p, uint32_t a, uint32_t n) {
    uint32_t v;
    asm volatile("{\n .reg .pred p;\n setp.ne.u32 p, %2, 0;\n mov.u32 %0, 0;\n @p atom.shared.exch.b32 %0, [%1], %3;\n}" : "=r"(v) : "r"(a), "r"((uint32_t)p), "r"(n) : "memory");
    return v;
}
__device__ __forceinline__ void place_load(const Maps& M, uint32_t sb, uint32_t n) {
    k_load(M, sb + k_place(n >> 4, 0) * SLOT + (n & 15) * UNIT, sb + S_FK + 4 * (n & 14), unit_key8(n), pol_first());
}
__device__ __forceinline__ void v_load(const Maps& M, uint32_t sb, uint32_t b, uint32_t s) {
    load_tile(&M.v, sb + v_place(b, s) * SLOT, sb + S_FV + 8 * s, SLOT, unit_key(b, 2 * s), pol_first());
}

__device__ __forceinline__ void stream_warp(const Params& P, const Maps& M, uint32_t sb, uint32_t lane) {
    const uint64_t pol = pol_first();
    const int bid = blockIdx.x, g = bid >> 3, i = bid & 7;
    const uint32_t wf = sb + S_WFULL;
    uint32_t tn = __shfl_sync(~0u, gtime32(), 0) * 16;
    int still = 0;
    auto until = [&](uint32_t t) {
        uint32_t now = __shfl_sync(~0u, gtime32(), 0) * 16;
        while ((int)(now - t) < 0 && still < 16) {
            const uint32_t last = now;
            now = __shfl_sync(~0u, gtime32(), 0) * 16;
            still = now == last ? still + 1 : 0;
        }
        return now;
    };
    auto pace = [&](uint32_t dt) {
        const uint32_t now = until(tn);
        if ((int)(now - tn) > SLACK0) tn = now - SLACK0;
        tn += dt;
    };
#pragma unroll
    for (int k = 0; k < 10; k++) {
        if (k < 2) {
            if (k == 0) init_bars<26, 27, 1>(sb); else init_bars<27, 37, 1>(sb);
            asm volatile("fence.mbarrier_init.release.cluster;" ::: "memory");
            if (k == 1) { asm volatile("bar.arrive 2, %0;" :: "n"(NTHR) : "memory"); asm volatile("bar.sync 3, 128;" ::: "memory"); }
        }
        if (k >= WIN_W) uwait(wf + 8 * (k - WIN_W), 0);
        pace(TAUW * 5 / 2 - (k == 0 || k == 2 ? LEADW : 0));
        if (k < 4) tma2d(sb + ST_WQ + 15360 * k, &M.wq, 384 * g + 192 * (k >> 1), 80 * i + 40 * (k & 1), wf + 8 * k, 15360, pol);
        else if (k < 6) tma2d(sb + ST_WG + 15360 * (k - 4), k == 4 ? &M.wg : &M.wu, 96 * g, 80 * i, wf + 8 * k, 15360, pol);
        else tma2d(sb + ST_WO + 15360 * (k - 6), &M.wo, 80 * i, 384 * g + 96 * (k - 6), wf + 8 * k, 15360, pol);
    }
#pragma unroll 1
    for (int n = 0; n < 16; n++) {
        if (n == 0 || n == 5 || n == 11) uwait(sb + S_RELW + (n == 0 ? 0 : n == 5 ? 8 : 16), 0);
        uwait(n < WIN_S ? wf + 8 * (10 - WIN_S + n) : sb + S_FV + 8 * ((n - WIN_S) ^ 8), 0);
        pace(2 * TAU0);
        if (n >= WIN_S && !utest(sb + S_FV + 8 * ((n - WIN_S + 1) ^ 8), 0)) tn += XB;
        if (n < 8) { place_load(M, sb, 2 * n); place_load(M, sb, 2 * n + 1); }
        else if (n < 11) { ring_load(M, sb, 0, 2 * n, 2 * n - 16); ring_load(M, sb, 0, 2 * n + 1, 2 * n - 15); }
        else v_load(M, sb, 0, n - 8);
        if (n == 7) { pace(TAUW * 5 / 2); tma2d(sb + S_WD, &M.wd, 80 * i, 96 * g, wf + 80, 15360, pol); }
    }
    int nd = 0;
    uint32_t q[4];
#pragma unroll
    for (int r = 0; r < 4; r++) q[r] = sb + S_FV + 8 * (7 - r);
    uint32_t td = tn;
    uint32_t pos = 2;
#pragma unroll 1
    for (int m = 16; m < 64; m++) {
        const int b = m >> 4, j = m & 15;
        const char* src = unit_ptr(P, 2 * m);
        const uint32_t tok = sb + S_TOK + (j < 3 ? 4 * pos : j < 11 ? 24 + 4 * pos : 16 + 4 * j) + 4 * lane;
        static_assert(WIN_U <= 12, "a ring position has at most one token of the timetable");
        int k = 0;
        while (true) {
            const uint2 c = lds64(sb + S_KF);
            if (__all_sync(~0u, mbar_test(q[WIN_S - 1] & ~1u, q[WIN_S - 1] & 1) & (min((int)c.x + 1, (int)c.y) >= 16 * b + min(2 * j + 2 - WIN_U, 16))) || ++k >= SPIN_FAST) break;
        }
        const uint32_t now = until(td);
        const uint32_t mine = __ballot_sync(~0u, token(lane < (j < 11 ? 2 : 1), tok, 2 * m + lane) == 2 * m + lane);
        {
            const uint2 c = lds64(sb + S_KF);
            if (!__all_sync(~0u, mbar_test(q[WIN_S - 2] & ~1u, q[WIN_S - 2] & 1) & (min((int)c.x + 1, (int)c.y) >= 16 * b + min(2 * j + 4 - WIN_U, 16)))) tn += XB;
        }
        q[3] = q[2]; q[2] = q[1]; q[1] = q[0]; q[0] = sb + S_QRDY;
        if (j < 11) {
            if (mine & 1) ring_load(M, sb, b, 2 * j, pos); else prefetch_l2(src, UNIT);
            if (mine & 2) ring_load(M, sb, b, 2 * j + 1, pos + 1); else prefetch_l2(src + UNIT, UNIT);
            if (j >= 8) q[0] = (sb + S_FV + 8 * (j - 8)) | (b & 1);
        } else if (mine) { v_load(M, sb, b, j - 8); q[0] = (sb + S_FV + 8 * (j - 8)) | (b & 1); }
        else if (j - 8 >= VPF) prefetch_l2(src, SLOT);
        else {
            scrap_copy(sb + S_DUMMY, src, sb + S_DBAR + 8 * (nd & 3));
            q[0] = (sb + S_DBAR + 8 * (nd & 3)) | ((nd >> 2) & 1);
            nd++;
        }
        pos = j == 15 ? 2 : pos == 4 ? 0 : pos + 2;
        if ((int)(now - tn) > SLACK) tn = now - SLACK;
        tn += 2 * TAU;
        td = (int)(tn - now) > 2 * TMIN ? tn : now + 2 * TMIN;
    }
#pragma unroll 1
    for (int m = max(nd - 4, 0); m < nd; m++) uwait(sb + S_DBAR + 8 * (m & 3), (m >> 2) & 1);
}

__host__ __device__ constexpr uint64_t bit_list(uint32_t m) { uint64_t r = 0; int n = 0; for (int k = 0; k < 12; k++) if ((m >> k) & 1) r |= (uint64_t)k << (4 * n++); return r; }
__device__ __forceinline__ float scaled(float s) { return bfr(bfr(s) * 0.07216878364870322f); }
__device__ __forceinline__ void probs(float s, uint32_t ps, uint32_t src, uint32_t ln) {
    const uint32_t q8 = ln >> 2, t4 = ln & 3;
    int key = __float_as_int(s);
    key ^= (key >> 31) & 0x7fffffff;
    key = __reduce_max_sync(~0u, key);
    key ^= (key >> 31) & 0x7fffffff;
    const float ml = __int_as_float(key) * LOG2E;
    sts16(ps + 64 * src + (q8 >> 1) * 16 + t4 * 4 + (q8 & 1) * 2, pack2(ex2(fmaf(s, LOG2E, -ml)), 0.f));
    stsf(ps + PS_MAX + 4 * src, ml);
}
template <int H> __device__ __forceinline__ uint32_t b_pos(uint32_t e) { const uint32_t h = e >= H, k = e - H * h; return h * 192 + (k & 6) * 24 + (k >> 3) * 4 + (k & 1) * 2; }
__device__ __forceinline__ uint32_t a_pos(uint32_t e) { const uint32_t h = e >= 40, k = e - 40 * h; return (k & 6) * 24 + (k >> 3) * 8 + h * 4 + (k & 1) * 2; }
__device__ __forceinline__ uint32_t q_pos(uint32_t d) { const uint32_t s = 3 * ((d >> 4) & 3) + (d >> 6); return s * 32 + (d & 6) * 4 + ((d >> 3) & 1) * 4 + (d & 1) * 2; }
__device__ __forceinline__ uint32_t k_off(uint32_t ln) { return (ln & 8) * 384 + (ln & 7) * 128 + (((ln & 7) ^ (ln >> 4)) << 4); }

#define HSTAMP(k) do {} while (0)
__device__ __forceinline__ char* xwindow() { return reinterpret_cast<char*>((reinterpret_cast<uintptr_t>(g_x) + (2u << 20) - 1) & ~(uintptr_t)((2u << 20) - 1)); }

struct XPtr {
    uint32_t lo, hi;
    __device__ __forceinline__ explicit XPtr(char* p) : lo((uint32_t)(uintptr_t)p), hi((uint32_t)((uintptr_t)p >> 32)) {}
    __device__ __forceinline__ XPtr(uint32_t l, uint32_t h) : lo(l), hi(h) {}
    __device__ __forceinline__ XPtr operator+(uint32_t o) const { return XPtr(lo + o, hi); }
    __device__ __forceinline__ operator char*() const { uint64_t p; asm("mov.b64 %0, {%1, %2};" : "=l"(p) : "r"(lo), "r"(hi)); return (char*)p; }
};

__device__ __forceinline__ char* side_word(uint32_t g, uint32_t i) { return xwindow() + pairG(1, 0, i) * 8192 + (g >> 3) * HALF + (g & 7) * 512 + 320; }

__device__ __forceinline__ uint32_t probe_side() {
    const uint32_t bid = blockIdx.x, g = bid >> 3, i = bid & 7, P = pairG(0, 0, i);
    char* p = xwindow() + P * 8192 + (g >> 3) * HALF + (g & 7) * 512 + 352;
    uint32_t best[2] = {~0u, ~0u};
#pragma unroll
    for (int k = 0; k < 4; k++) *reinterpret_cast<uint4*>(p + (k & 1) * 16 + (k >> 1) * COPY) = make_uint4(1, 1, 1, 1);
#pragma unroll 1
    for (int r = 0; r < 64; r++) {
        if (r >= 4 && !(r & 1) && min(best[0], best[1]) < 380 && max(best[0], best[1]) > min(best[0], best[1]) + 80) break;
        uint32_t c0, c1, v;
        asm volatile("mov.u32 %0, %clock;" : "=r"(c0) :: "memory");
        asm volatile("atom.relaxed.gpu.global.exch.b32 %0, [%1], 0;" : "=r"(v) : "l"(p + (r & 1) * COPY) : "memory");
        asm volatile("{\n .reg .pred q;\n setp.eq.u32 q, %1, 0x13579bdf;\n mov.u32 %0, 0;\n @!q mov.u32 %0, %clock;\n}" : "=r"(c1) : "r"(v) : "memory");
        if (r & 1) best[1] = min(best[1], c1 - c0); else best[0] = min(best[0], c1 - c0);
    }
    return 1 + ((best[1] < best[0]) ^ (__popc(P & PMASK) & 1));
}

template <int N>
__device__ __forceinline__ void hop_a(const char* src, uint32_t par, uint32_t dst, bool st, int k) {
    uint2 v[N][4];
    float e[4], rl;
    int guard = 0;
    bool again;
    do {
#pragma unroll
        for (int s = 0; s < 4 * N; s++) v[s / 4][s % 4] = ldp64(src + (s / 4) * 256 + (s % 4) * 1024);
        again = __any_sync(~0u, ((N == 1 ? cnt8(v[0], 24 * par) : cnt8(v[N - 1], cnt8(v[0], 16 * par))) & 31) != 0);
        const uint32_t M = (uint32_t)max(max((int)v[0][0].x, (int)v[0][1].x), max((int)v[0][2].x, (int)v[0][3].x)) - 127 * 32;
#pragma unroll
        for (int s = 0; s < 4; s++) e[s] = asf((uint32_t)max((int)(v[0][s].x - M), 0) << 18);
        rl = rcp(fmaf(e[0], asf(v[0][0].y), e[1] * asf(v[0][1].y)) + fmaf(e[2], asf(v[0][2].y), e[3] * asf(v[0][3].y)));
#pragma unroll
        for (int s = 0; s < 4; s++) e[s] = __shfl_sync(~0u, e[s], 24);
        keep(rl);
    } while (again & (++guard < SPIN_LIMIT));
    rl = __shfl_sync(~0u, rl, 24);
#pragma unroll
    for (int n = 0; n < N; n++) {
        const float o0 = fmaf(e[0], asf(v[n][0].x), e[1] * asf(v[n][1].x)) + fmaf(e[2], asf(v[n][2].x), e[3] * asf(v[n][3].x));
        const float o1 = fmaf(e[0], asf(v[n][0].y), e[1] * asf(v[n][1].y)) + fmaf(e[2], asf(v[n][2].y), e[3] * asf(v[n][3].y));
        sts32_if(st, dst + 192 * n, pack2(o0 * rl, o1 * rl));
    }
    SWEEPS(k, guard - 1);
    __syncwarp();
}

__device__ __forceinline__ void score_warp(const Maps& M, uint32_t sb, uint32_t h, uint32_t ln) {
    const uint32_t lane0 = ln;
    uwait(sb + S_QRDY, 0);
    const uint32_t q8 = ln >> 2;
    const uint32_t k0 = k_off(ln);
    uint32_t pos = h + 6, bar = sb + S_FK, par = 0, phases = 0;
    uint2 q = lds64(sb + S_QS + 8 * ln), qh = lds64(sb + S_QS + 8 * ln + 256);
    auto first_round = [&](uint32_t b, uint32_t ln) {
        uwait(sb + S_RELR, b & 1);
        const uint32_t u = h + 2 * ln, p = u < 4 ? u + 2 : u - 4;
        uint32_t todo = __ballot_sync(~0u, token(ln < 3, sb + S_TOK + 4 * p, 32 * b + 32 + u) == 32 * b + 32 + u);
#pragma unroll 1
        for (uint32_t r = h; todo; todo >>= 1, r += 2) if (todo & 1) ring_load(M, sb, b + 1, r, r < 4 ? r + 2 : r - 4);
    };
#pragma unroll 1
    for (uint32_t n = h; n < 64; n += 2) {
        HSTAMP(0);
        const uint32_t ua = sb + pos * UNIT;
        if (!__all_sync(~0u, mbar_try(bar, par))) uwait(bar, par);
        HSTAMP(1);
        float acc[2][4] = {};
        uint32_t mine = 0;
        const uint32_t id = n + (n & 48) + 6;
#pragma unroll
        for (int s = 0; s < 12; s++) {
            uint32_t kf[4];
            ldsm4(kf, (k0 ^ (32 * (s / 3))) + (ua + 1024 * (s % 3)));
            if (s == 11) {
                __syncwarp();
                mine = token(ln == 0 && n >= 16, sb + S_TOK + 24 + 4 * pos, id);
                stsvol(sb + S_KF + 4 * h, n + 1);
            }
            const bool m = q8 == (s & 7);
            mmaA(acc[s & 1], kf, m ? (s < 8 ? q.x : qh.x) : 0u, m ? (s < 8 ? q.y : qh.y) : 0u);
        }
        const uint32_t pos0 = pos;
        const bool last = (n & 14) == 14;
        pos = last ? h + 2 : n >= 16 && pos >= 4 ? h : pos + 2;
        bar = n >= 14 ? sb + S_RING + 8 * pos : bar + 8;
        par = n >= 14 ? (phases >> pos) & 1 : 0;
        phases ^= n >= 14 ? 1u << pos : 0;
        const float w0 = (acc[0][0] + acc[0][1]) + (acc[1][0] + acc[1][1]), w1 = (acc[0][2] + acc[0][3]) + (acc[1][2] + acc[1][3]);
        HSTAMP(2);
        if (__any_sync(~0u, mine == id)) ring_load(M, sb, n >> 4, (n & 15) + 6, pos0);
        HSTAMP(3);
        float s = ((ln & 1) ? w1 : w0) + __shfl_xor_sync(~0u, (ln & 1) ? w0 : w1, 1);
        s += __shfl_xor_sync(~0u, s, 2);
        sts_hi16(sb + S_SC + (((n & 12) >> 1) + h) * 64 + (n & 2) * 2 + (ln & 29) * 2, scaled(s));
        if (last) {
            __syncwarp();
            arrive_if(ln == 0, sb + S_SCO);
            const uint32_t b = n >> 4, ln = lane0 + lag<1>(sb);
            if (b > 0) {
                uwait(sb + S_RELK, (b - 1) & 1);
                if (h == 0) LSTAMP(64 + 2 * b);
                const uint32_t sl = 3 + h + 2 * ln, idv = 32 * b + 16 + 2 * sl;
                uint32_t todo = __ballot_sync(~0u, token(sl < 8, sb + S_TOK + 48 + 4 * sl, idv) == idv);
#pragma unroll 1
                for (uint32_t r = 3 + h; todo; todo >>= 1, r += 2) if (todo & 1) v_load(M, sb, b, r);
                const uint32_t g = blockIdx.x >> 3, pr = pairL(RA, 1, g), side = ldsvol(sb + S_SIDE);
                const char* src = xwindow() + pr * 8192 + ((side ^ 1 ^ __popc(pr & PMASK)) & 1) * COPY + h * HALF + 8 * min(ln, 24u);
                uwait(sb + S_RELV, (b - 1) & 1);
                __nanosleep(HOP1_NS);
#pragma unroll 1
                for (uint32_t r = 0; r < 4; r += 2) {
                    hop_a<2>(src + 256 * r, b & 1, sb + S_OS + 192 * (4 * h + r) + 96 + 4 * ln, ln < 24, 25);
                    if (r == 0 && b < 3) first_round(b, ln);
                }
                arrive_if(ln == 0, sb + S_OS1);
            } else first_round(0, ln);
            q = lds64(sb + S_QS + 24 * ((n + 2) & 48) + 8 * ln); qh = lds64(sb + S_QS + 24 * ((n + 2) & 48) + 8 * ln + 256);
        }
    }
}

__global__ void __launch_bounds__(NTHR, 1)
fused_kernel(const Params P, const __grid_constant__ Maps M) {
    extern __shared__ __align__(1024) unsigned char smem[];
    const uint32_t sb = smem_u32(smem);
    const int tid = threadIdx.x, bid = blockIdx.x;
    if (tid == 0) {
        asm volatile("prefetch.tensormap [%0];" :: "l"(&M.wq) : "memory");
        asm volatile("cp.async.bulk.prefetch.L2.global [%0], 12288;" :: "l"(P.wq + (80 * (bid & 7) + (bid >> 3)) * 6144) : "memory");
    }
    const int w = __shfl_sync(~0u, tid >> 5, 0), lane = tid & 31;

    if (w >= 8) {
        asm volatile("setmaxnreg.dec.sync.aligned.u32 " REG_LO ";");
        if (w == 8) {
            stream_warp(P, M, sb, lane);
        } else {
            if (w == 9) { init_bars<0, 3, 2>(sb); init_bars<3, 8, 1>(sb); init_bars<16, 22, 1>(sb); }
            else if (w == 10) { init_bars<8, 16, 2>(sb); init_bars<22, 26, 1>(sb); }
            else { init_bars<37, 38, 1>(sb); init_bars<38, 40, 8>(sb); init_bars<40, 41, 1>(sb); init_bars<41, 44, 8>(sb); init_bars<44, 46, 2>(sb); stsvol(sb + S_ZERO + 4 * lane, 0); if (lane < 16) stsvol(sb + S_LN + 4 * lane, 0); }
            asm volatile("fence.mbarrier_init.release.cluster;" ::: "memory");
            asm volatile("bar.arrive 3, 128;" ::: "memory");
            if (w == 11) asm volatile("bar.arrive 2, %0;" :: "n"(NTHR) : "memory");
            else {
                if (lane < 4) asm volatile("prefetch.tensormap [%0];" :: "l"(&M.k + lane + 4 * (w - 9)) : "memory");
                __syncwarp();
                asm volatile("bar.sync 2, %0;" :: "n"(NTHR) : "memory");
            }
            if (w < 11) score_warp(M, sb, w - 9, lane);
            else {
                uint32_t mine = 0;
                if (lane == 0) mine = probe_side();
                mine = __shfl_sync(~0u, mine, 0);
                if (lane < 8) stp32(side_word(bid >> 3, bid & 7) + 4 * lane, asf(mine << 5), 1);
                uint32_t a = 0, b = 0;
                int k = 0;
                while (!utest(sb + S_QRDY, 0) && ++k < SPIN_FAST) { warm_mma(a, b); __nanosleep(KWNS); }
                while (true) {
                    const uint32_t v = ldp32(side_word(bid >> 3, lane & 7));
                    const bool late = !__all_sync(~0u, v & 1);
                    if (!late || ++k >= SPIN_FAST) { stsvol(sb + S_SIDE, mine | (FORCE_BOTH || late || __any_sync(~0u, (v >> 5) != mine) ? 4 : 0)); break; }
                    warm_mma(a, b); __nanosleep(KWNS);
                }
                while (ldsvol(sb + S_GATE) == 0 && ++k < SPIN_FAST) { warm_mma(a, b); __nanosleep(KWNS); }
                uint32_t rl = lane, rq = 0;
                auto reset = [&] {
                    if (rq < 128) *reinterpret_cast<uint4*>(reinterpret_cast<char*>(g_s) + (rl < 60 ? XS + bid * 7680 + 128 * rl : XS2 + bid * 768 + 128 * (rl - 60)) + rq) = make_uint4(0, 0, 0, 0);
                    rl += 32;
                    if (rl >= 66) { rl -= 66; rq += 16; }
                };
                reset(); reset();
                if (lane < 8) stp32(side_word(bid >> 3, bid & 7) + 4 * lane, 0.f, 0);
                const uint32_t side = (ldsvol(sb + S_SIDE) & 1) ^ 1, g = bid >> 3, i = bid & 7;
                const XPtr gx(xwindow());
                auto nearp = [&](uint32_t pr) { return gx.lo + pr * 8192 + ((side ^ __popc(pr & PMASK)) & 1) * COPY; };
                const uint32_t own = (i >> 2) * HALF + (i & 3) * 1024 + (lane & 7) * 128;
                const uint32_t cut = (lane & 7) == 7 ? 128 : 0;
                const uint32_t pAC = nearp(pairL(lane >> 4, (lane >> 3) & 1, g)) + own - (lane >> 4) * cut, pE = nearp(pairL(RE, (lane >> 3) & 1, g)) + own - cut;
                const uint32_t pG = nearp(pairG((lane >> 2) & 1, (lane >> 3) & 1, i)) + min(lane & 3, 2) * 128;
                uint32_t tr = 0, tk = 0, ph = 0, src = g + (lane >> 4), seen = 0, n = 16;
                bool go = false, first = true;
                while (n < 64 && ++k < SPIN_FAST) {
                    const uint32_t now = __shfl_sync(~0u, gtime32(), 0) * 16;
                    if (!go && utest((n & 15) < 6 ? sb + S_RELK : sb + S_RELV, ((n >> 4) & 1) ^ 1)) { go = true; if ((int)(now - tk) > 0 || !(n & 15)) tk = now; }
                    if (go && (int)(now - tk) >= 0) {
                        place_load(M, sb, (n & 16) ? n : (n & 48) | ((n + 10) & 15));
                        tk += KRE_TAU;
                        n++;
                        go = (n & 15) != 0 && (n & 15) != 6;
                        if (!(n & 15)) LSTAMP(63 + (n >> 3));
                    } else if (first || (int)(now - tr) >= 0) {
                        first = false;
                        tr = now + RFR_TAU;
                        b |= seen & a;
                        warm_mma(a, b);
                        seen = ldp32(XPtr(ph == 0 ? pAC : ph == 1 && lane < 16 ? pE : pG + (src & 8) * (HALF / 8) + (src & 7) * 512, gx.hi));
                        reset();
                        src += ph == 0 ? 0 : ph == 1 ? 2 : 1;
                        ph = ph == 2 ? 0 : ph + 1;
                    } else __nanosleep(KWNS2);
                }
                while (rq < 128) reset();
                __syncwarp();
                while (ldsvol(sb + S_GATE) < 6 && ++k < SPIN_FAST) { warm_mma(a, b); __nanosleep(KWNS); }
                if (a | b) stsvol(sb + S_GATE, 6);
            }
        }
        return;
    }
    asm volatile("setmaxnreg.inc.sync.aligned.u32 " REG_HI ";");

    const int g = bid >> 3, i = bid & 7;
    const int g8 = lane >> 2, t = lane & 3;
    char* const gs = reinterpret_cast<char*>(g_s);
    const XPtr gx(xwindow());

    W80 Wq[6], Wgu[3];
    uint32_t Wo[5][3][4];
    if (w < 4) {
        const uint32_t* xp = reinterpret_cast<const uint32_t*>(P.x + 640 * w);
        float sum = 0.f, sq = 0.f;
#pragma unroll
        for (int u = 0; u < 10; u++) { uint32_t v = xp[lane + 32 * u]; float a = bf_lo(v), b = bf_hi(v); sum += a + b; sq += a * a + b * b; }
#pragma unroll
        for (int o = 16; o > 0; o >>= 1) { sum += __shfl_xor_sync(~0u, sum, o); sq += __shfl_xor_sync(~0u, sq, o); }
        float mean, den; ln_stats(sum, sq, mean, den);
        if (lane < 20) {
            const uint2 v = reinterpret_cast<const uint2*>(P.x + 640 * w + 80 * i)[lane];
            sts64(sb + S_X0 + 160 * w + 8 * lane, v.x, v.y);
            sts32(sb + S_L0 + 384 * w + b_pos<40>(4 * lane), pack2(__fdiv_rn(bfr(bf_lo(v.x) - mean), den), __fdiv_rn(bfr(bf_hi(v.x) - mean), den)));
            sts32(sb + S_L0 + 384 * w + b_pos<40>(4 * lane + 2), pack2(__fdiv_rn(bfr(bf_lo(v.y) - mean), den), __fdiv_rn(bfr(bf_hi(v.y) - mean), den)));
        }
    } else if (w == 4) {
        const uint32_t* xp = reinterpret_cast<const uint32_t*>(P.wr);
        float sum = 0.f;
#pragma unroll
        for (int u = 0; u < 10; u++) { uint32_t v = xp[lane + 32 * u]; sum += bf_lo(v) + bf_hi(v); }
#pragma unroll
        for (int o = 16; o > 0; o >>= 1) sum += __shfl_xor_sync(~0u, sum, o);
        if (lane == 0) stsf(sb + S_SWR, sum);
        if (lane < 20) {
            const uint2 v = reinterpret_cast<const uint2*>(P.wr + 80 * i)[lane];
            sts32(sb + S_XA + 576 + a_pos(4 * lane), v.x); sts32(sb + S_XA + 576 + a_pos(4 * lane + 2), v.y);
            sts32(sb + S_XA + a_pos(4 * lane), ONES); sts32(sb + S_XA + a_pos(4 * lane + 2), ONES);
        }
    }
    asm volatile("bar.sync 2, %0;" :: "n"(NTHR) : "memory");
    auto frag = [](uint32_t (&a)[4], uint32_t p, int pitch) {
        const uint32_t r0 = lds32(p), r1 = lds32(p + pitch), r2 = lds32(p + 2 * pitch), r3 = lds32(p + 3 * pitch);
        a[0] = __byte_perm(r0, r1, 0x5410); a[1] = __byte_perm(r0, r1, 0x7632);
        a[2] = __byte_perm(r2, r3, 0x5410); a[3] = __byte_perm(r2, r3, 0x7632);
    };
    mbar_wait(sb + S_WFULL + 16 * (w >> 2), 0);
    mbar_wait(sb + S_WFULL + 16 * (w >> 2) + 8, 0);
    {
        const uint32_t p = sb + ST_WQ + (w >> 2) * 30720 + (2 * t) * 384 + (48 * (w & 3) + 2 * g8) * 2;
#pragma unroll
        for (int r = 0; r < 10; r++)
#pragma unroll
            for (int m = 0; m < 3; m++) {
                const uint32_t q = p + ((r & 1) * 40 + (r >> 1) * 8) * 384 + 32 * m, r0 = lds32(q), r1 = lds32(q + 384);
                (r < 8 ? Wq[2 * m].a[(r >> 2) & 1][r & 3] : Wq[2 * m].c[r & 1]) = __byte_perm(r0, r1, 0x5410);
                (r < 8 ? Wq[2 * m + 1].a[(r >> 2) & 1][r & 3] : Wq[2 * m + 1].c[r & 1]) = __byte_perm(r0, r1, 0x7632);
            }
    }
    __syncwarp();
    if (lane == 0) mbar_arrive(sb + S_RELW);
    TSTAMP(1);
    {
        char* d = gs + XS + bid * 7680 + (w >> 2) * 3840 + (48 * (w & 3) + 2 * g8) * 4;
        float acc[6][4] = {};
        mul80(acc, Wq, lds128(sb + S_L0 + 48 * lane), lds32(sb + S_L0 + 48 * lane + 16));
#pragma unroll
        for (int m = 0; m < 6; m += 2) stp64(d + t * 768 + 32 * m, acc[m][0] + acc[m][3], acc[m + 1][0] + acc[m + 1][3], 1);
        float sum[6][4] = {};
        mul80(sum, Wq, make_uint4(ONES, ONES, ONES, ONES), ONES);
        if (t == 0)
#pragma unroll
            for (int m = 0; m < 6; m += 2) stp64(d + 4 * 768 + 32 * m, sum[m][0] + sum[m][3], sum[m + 1][0] + sum[m + 1][3], 1);
    }
    mbar_wait(sb + S_WFULL + 32, 0);
    mbar_wait(sb + S_WFULL + 40, 0);
    const uint32_t oct = 3 * (w >> 1) + (w & 1), oct2 = 3 * (w >> 1) + 2;
    {
        const uint32_t p = sb + ST_WG + ((lane & 7) + 40 * ((lane >> 3) & 1) + 8 * (lane >> 4)) * 192;
#pragma unroll
        for (int T = 0; T < 3; T++) {
            const uint32_t q = p + (T < 2 ? T * 15360 + 16 * oct : (w & 1) * 15360 + 16 * oct2);
            ldsm4t(Wgu[T].a[0], q); ldsm4t(Wgu[T].a[1], q + 16 * 192); ldsm2t(Wgu[T].c, q + 32 * 192);
        }
        float sum[3][4] = {};
        mul80(sum, Wgu, make_uint4(ONES, ONES, ONES, ONES), ONES);
        if (t < 3) stp32(gs + XS2 + bid * 768 + (t < 2 ? 64 * oct + 4 * t : 64 * oct2 + 4 * (w & 1)) + 8 * g8,
                         sel4(t, sum[0][0] + sum[0][3], sum[1][0] + sum[1][3], sum[2][0] + sum[2][3], 0.f), 1);
    }
    __syncwarp();
    if (lane == 0) mbar_arrive(sb + S_RELW + 8);
    mbar_wait(sb + S_WFULL + 48 + 8 * (w >> 1), 0);
    {
        const uint32_t po = sb + ST_WO + (48 * w + 12 * t) * 160 + 4 * g8;
#pragma unroll
        for (int s = 0; s < 3; s++)
#pragma unroll
            for (int m = 0; m < 5; m++) frag(Wo[m][s], po + 4 * s * 160 + 32 * m, 160);
    }
    __syncwarp();
    if (lane == 0) mbar_arrive(sb + S_RELW + 16);
    mbar_wait(sb + S_WFULL + 64, 0);
    if (tid < 192) {
        const char* srcS = gs + XS + g * 8 * 7680 + (i >> 2) * 3840 + tid * 4;
        uint32_t vs[5][8];
        int guard = 0;
        do {
#pragma unroll
            for (int b = 0; b < 5; b++)
#pragma unroll
                for (int s = 0; s < 8; s++) vs[b][s] = ldp32(srcS + b * 768 + s * 7680);
        } while (((cnt16(vs[0], vs[1], 16) | cnt16(vs[2], vs[3], 16) | cnt8(vs[4], 24)) & 31) && ++guard < SPIN_LIMIT);
        const uint32_t qpos = sb + S_QS + q_pos(tid);
#pragma unroll
        for (int b = 0; b < 4; b++) {
            sts_hi16(qpos + 384 * b, bfr(sum8(vs[b])));
        }
        stsf(sb + S_CSQ + 4 * tid, sum8(vs[4]));
    }
    if (tid < 192) {
        uint32_t v[8];
        int guard = 0;
        do {
#pragma unroll
            for (int s = 0; s < 8; s++) v[s] = ldp32(gs + XS2 + (g * 8 + s) * 768 + tid * 4);
        } while ((cnt8(v, 24) & 31) && ++guard < SPIN_LIMIT);
        stsf(sb + S_CSGU + 4 * tid, sum8(v));
    }
    __syncwarp();
    bar_main();
    arrive_if(tid == 0, sb + S_QRDY);
    TSTAMP(2);

    uint32_t side;
    { int k = 0; while ((side = ldsvol(sb + S_SIDE)) == 0 && ++k < SPIN_FAST) {} }
    const uint32_t both = __any_sync(~0u, side & 4) ? COPY : 0;
    uint32_t td = __shfl_sync(~0u, tid, lane);
    const uint32_t wp = __shfl_sync(~0u, tid >> 5, 0);
    const uint32_t cc = wp >= 3;
    auto uni = [](uint32_t v) { return __shfl_sync(~0u, v, 0); };
    auto pin = [&](uint32_t v) { return __shfl_sync(~0u, v, td); };
    auto nearp = [&](uint32_t P) { return gx.lo + P * 8192 + ((side ^ 1 ^ __popc(P & PMASK)) & 1) * COPY; };
    constexpr uint32_t COL = 32 * 8192;
    const uint32_t ownL = (i >> 2) * HALF + (i & 3) * 1024, ownG = gx.lo + (g >> 3) * HALF + (g & 7) * 512;
    const uint32_t uPubA = uni(ownL + nearp(pairL(RA, 0, g)) + (wp >> 1) * 256 + (wp & 1) * 96), uPolA = uni(nearp(pairL(RA, 0, g)) + (wp >> 2) * HALF + (wp & 3) * 256);
    const uint32_t uPubB = uni(ownG + pairG(0, cc, i) * 8192), uPolB = uni(nearp(pairG(0, cc, i)));
    const uint32_t uPubC = uni(ownL + nearp(pairL(RC, 0, g))), uPolC = uni(nearp(pairL(RC, wp < 6 ? cc : 0, g)));
    const uint32_t uPubD = uni(ownG + pairG(1, 0, i) * 8192 + (wp < 7 ? 32 * wp : 256)), uPolD = uni(nearp(pairG(1, cc, i)));
    const uint32_t uPubE = uni(ownL + nearp(pairL(RE, 0, g))), uPolE = uni(nearp(pairL(RE, i >> 2, g)));
    const uint32_t uOS = uni(sb + S_OS + 192 * wp);
    auto xp = [&](uint32_t lo) { return (char*)XPtr(lo, gx.hi); };
    {
        const uint4 z = make_uint4(0, 0, 0, 0);
        const uint32_t c = ((tid >> 6) & 1) * COL, cp = (tid >> 7) * both, k = (tid & 63) * 16;
        *reinterpret_cast<uint4*>(xp((ownL + nearp(pairL(RA, 0, g)) + c + k) ^ cp)) = z;
        if (k < 800) { *reinterpret_cast<uint4*>(xp((uPubC + c + k) ^ cp)) = z; *reinterpret_cast<uint4*>(xp((uPubE + c + k) ^ cp)) = z; }
        if ((tid & 31) < 20) *reinterpret_cast<uint4*>(xp(ownG + pairG((tid >> 5) & 1, 0, i) * 8192 + c + (tid >> 7) * COPY + (tid & 31) * 16)) = z;
    }
#define IDS() __syncwarp(); const uint32_t z0_ = lag<1>(sb), z_ = td + z0_; const uint32_t ln = z_ & 31, q8 = ln >> 2, t4 = z_ & 3, n96 = z_ - 96 * cc, n80 = min(n96, 79u); (void)q8; (void)t4; (void)n80; (void)ln

    auto vaddr = [&](uint32_t (&voff)[3]) {
        const uint32_t ln = td & 31;
        const uint32_t key3 = 3 * ((ln & 7) + 2 * (ln & 8) + ((ln >> 1) & 8));
#pragma unroll
        for (int T = 0; T < 3; T++) {
            const uint32_t u = 3 * wp + T, r = key3 + (u >> 3);
            voff[T] = r * 128 + (((u ^ r) & 7) << 4);
        }
    };
    auto values = [&](uint32_t (&vf)[8][3][4], float (&acc)[3][4], auto step, uint32_t ps, auto col, uint32_t par) {
        constexpr int CUT = col.value ? 8 : 6;
        const uint32_t ln = td & 31, q8 = ln >> 2, t4 = td & 3;
        uint4 p = lds128(ps + 16 * ln);
        float f0 = 0.f, f1 = 0.f, r3 = 0.f, o = 0.f;
        int M = 0;
#pragma unroll
        for (int s = 0; s < 8; s++) {
            if (s == 0 || s == CUT)
#pragma unroll
                for (int k = 0; k < 12; k++) acc[k / 4][k % 4] = 0.f;
            step(s);
            const bool m = s >= CUT || (q8 >> 1) == (s >> 1);
            const uint32_t b0 = m ? ((s & 1) ? p.z : p.x) : 0u, b1 = m ? ((s & 1) ? p.w : p.y) : 0u;
#pragma unroll
            for (int T = 0; T < 3; T++) mmaA(acc[T], vf[s][T], b0, b1);
            if (s == FSTEP) {
                const uint2 mp = lds64(ps + PS_MAX + 8 * t4);
                M = __reduce_max_sync(~0u, __float2int_ru(fmaxf(asf(mp.x), asf(mp.y))));
                f0 = ex2(asf(mp.x) - (float)M); f1 = ex2(asf(mp.y) - (float)M);
                float l[4] = {};
                mma16816(l, ONES, ONES, ONES, ONES, p.x, p.y); mma16816(l, ONES, ONES, ONES, ONES, p.z, p.w);
                r3 = fmaf(f0, l[0], f1 * l[1]);
            }
            if (s == CUT - 1) {
                if (CUT < 8) p = lds128(ps + 384 + 16 * (ln & 7));
                const float r0 = fmaf(f0, acc[0][0], f1 * acc[0][3]), r1 = fmaf(f0, acc[1][0], f1 * acc[1][3]), r2 = fmaf(f0, acc[2][0], f1 * acc[2][3]);
                const bool hi = t4 & 2, od = t4 & 1;
                const float u0 = (hi ? r2 : r0) + __shfl_xor_sync(~0u, hi ? r0 : r2, 2), u1 = (hi ? r3 : r1) + __shfl_xor_sync(~0u, hi ? r1 : r3, 2);
                o = (od ? u1 : u0) + __shfl_xor_sync(~0u, od ? u0 : u1, 1);
                if (ln == 3) o = asf(32 * (uint32_t)M);
                if (CUT < 8) { f0 = __shfl_sync(~0u, f0, 3); f1 = __shfl_sync(~0u, f1, 3); }
            }
        }
        CSTAMP(25);
        const uint32_t pubA = uPubA + col.value * COL + 32 * t4 + 4 * q8;
        if (CUT < 8 && t4 < 3) o = fmaf(f0, sel4(t4, acc[0][0], acc[1][0], acc[2][0], acc[2][0]), fmaf(f1, sel4(t4, acc[0][3], acc[1][3], acc[2][3], acc[2][3]), o));
        stp32_if(t4 < 3 || ((wp & 1) && q8 < 2), both, xp(pubA ^ COPY), xp(pubA), o, par);
    };

    uint32_t left[36] = {};
#pragma unroll 1
    for (int ch = 0; ch < 5; ch++) {
        const uint32_t par0 = (ch + 1) & 1, par1 = ch & 1;
        uint32_t voff[3], vf[8][3][4];
        float acc_[3][4];
        if (ch < 4) {
            td = pin(td);
            vaddr(voff);
            mbar_wait(sb + S_SCO, par1);
            if (ch == 0) mbar_wait(sb + S_WFULL + 80, 0);
            TST(0);
            auto ldw = [&](int s) {
                mbar_wait(sb + S_FV + 8 * s, par1);
#pragma unroll
                for (int T = 0; T < 3; T++) ldsm4t(vf[s][T], voff[T] + (sb + v_place(ch, s) * SLOT));
            };
            probs(bf_lo(lds16(sb + S_SC + 2 * td)), sb + S_PS, wp, td & 31);
            ldw(0); ldw(1); ldw(2);
            bar_main();
            arrive_if(td == 0, sb + S_RELR);
            values(vf, acc_, [&](int s) {
                if (s >= 3) ldw(s);
            }, sb + S_PS, std::integral_constant<int, 0>(), par0);
            TST(1);
            CSTAMP(5);
            if (ch > 0) mbar_wait(sb + S_OS1, par0);
        } else {
#pragma unroll
            for (int s = 0; s < 36; s++) vf[s / 12][(s / 4) % 3][s & 3] = left[s];
        }
        const bool has0 = ch < 4, has1 = ch > 0;
        const bool actc = wp < 6 && (cc ? has1 : has0);
        const uint32_t parc = cc ? par1 : par0;
        const uint32_t pub0 = has0 ? par0 : 0;
        uint32_t rr, pubB;
        {
            IDS();
            const uint32_t c = ch == 4;
            const uint32_t osa = pin(uOS + 96 * c + 4 * ln), oa = pin(uOS + 48 * (q8 & 2) + 24 * t4), ra = pin(sb + S_RED + 640 * wp + 320 * (t4 & 1) + 8 * q8);
            rr = pin(sb + S_RED + 320 * cc + 4 * n80); pubB = pin(uPubB + 4 * n80);
            hop_a<1>(xp(uPolA + c * COL + 8 * min(ln, 24u) + lag<DELAY_L>(sb, z0_)), pub0, osa, ln < 24, 5 * ch);
            TST(2);
            CSTAMP(6);
            float acc[5][4] = {};
            const uint2 b0 = lds64(oa), b1 = lds64(oa + 8), b2 = lds64(oa + 16);
#pragma unroll
            for (int m = 0; m < 5; m++) mmaA(acc[m], Wo[m][0], b0.x, b0.y);
#pragma unroll
            for (int m = 0; m < 5; m++) mmaA(acc[m], Wo[m][1], b1.x, b1.y);
#pragma unroll
            for (int m = 0; m < 5; m++) mmaA(acc[m], Wo[m][2], b2.x, b2.y);
#pragma unroll
            for (int m = 0; m < 5; m++) { stsf(ra + 64 * m, acc[m][0]); stsf(ra + 64 * m + 4, acc[m][2]); }
        }
        CSTAMP(7);
        uint32_t xr, fl, pubC, pubC2;
        auto prepC = [&](uint32_t ln) {
            const uint32_t q8 = ln >> 2, t4 = ln & 3;
            xr = pin(sb + S_XB + 48 * (ln & 15));
            pubC = pin(uPubC + (t4 & 1) * COL + 192 * (wp >> 1) + 64 * (wp & 1) + 8 * q8);
            pubC2 = pin(uPubC + (t4 & 1) * COL + ((t4 & 2) ? 192 * (wp >> 1) + 128 + 4 * (wp & 1) + 8 * q8 : 768 + 2 * ((q8 + 1) & 6)));
            fl = pin(((t4 & 1) ? par1 : pub0) | (t4 >= 2 || (wp == 7 && q8 < 4 && q8 != 2 - t4) ? 2 : 0));
        };
        auto stats = [&](uint32_t xa, const uint4& b, uint32_t b4) {
            float a0[4] = {}, a1[4] = {}, a2[4] = {};
            const uint4 p0 = lds128(xa), p1 = lds128(xa + 16);
            const uint2 p2 = lds64(xa + 32);
            mmaV(a0, p0, b.x, b.y); mmaV(a1, p1, b.z, b.w); mma8(a2, p2.x, p2.y, b4);
            return ((a0[0] + a0[3]) + (a1[0] + a1[3])) + (a2[0] + a2[3]);
        };
        auto give_ln = [&](uint32_t src0, uint32_t par, uint32_t dst, uint32_t ln, float& mean, float& den, auto also) {
            const char* src = xp(src0 + 768 + (ln & 1) * HALF);
            float sx, sq;
            int guard = 0;
            bool again;
            do {
                uint2 st[4];
#pragma unroll
                for (int s = 0; s < 4; s++) st[s] = ldp64(src + s * 1024);
                again = __any_sync(~0u, ((cnt8(st, 24 * par) | also()) & 31) != 0);
                sx = (asf(st[0].x) + asf(st[1].x)) + (asf(st[2].x) + asf(st[3].x)); sq = (asf(st[0].y) + asf(st[1].y)) + (asf(st[2].y) + asf(st[3].y));
                sx += __shfl_xor_sync(~0u, sx, 1); sq += __shfl_xor_sync(~0u, sq, 1);
            } while (again & (++guard < SPIN_LIMIT));
            ln_stats(sx, sq, mean, den);
            stsvol64(dst, __byte_perm(__float_as_uint(den), __float_as_uint(mean), 0x7632), (__float_as_uint(rcp(den)) & ~7u) | (ch + 1));
        };
        auto take_ln = [&](uint2& c, uint32_t a) { int k = 0; do c = ldsvol64(a); while (__any_sync(~0u, (c.y & 7) != ch + 1) & (++k < SPIN_FAST)); };
        {
            auto gate_up = [&](auto with_stats) {
                bar_main();
                TST(3);
                CSTAMP(11);
                const uint4 b = lds128(xr);
                uint32_t b4 = lds32(xr + 16);
                float acc[3][4] = {};
                if (with_stats.value) {
                    stp32_if(fl > 1 && !(td & 2), both, xp(pubC2 ^ COPY), xp(pubC2), stats(xr + (S_XA - S_XB), b, b4), fl & 1);
                    __syncwarp();
                    b4 = lds32(xr + 16);
                }
                mul80(acc, Wgu, b, b4);
                stp64_if(!(td & 2), both, xp(pubC ^ COPY), xp(pubC), tagw(acc[0][0] + acc[0][3], fl & 1), tagw(acc[1][0] + acc[1][3], fl & 1));
                stp32_if(td & 2, both, xp(pubC2 ^ COPY), xp(pubC2), acc[2][0] + acc[2][3], fl & 1);
            };
            if (wp == 7) {
                bar_main();
                IDS();
                prepC(ln);
                sts32(sb + S_ZERO + 4, add3(pubC, pubC2, fl));
                gate_up(std::true_type());
            } else {
                if (actc) {
                    bar_main();
                    CSTAMP(8);
                    uint32_t r[8];
#pragma unroll
                    for (int s = 0; s < 8; s++) r[s] = lds32(rr + 640 * s);
                    stp32_if(true, xp(pubB), sum8(r), parc);
                    CSTAMP(9);
                    IDS();
                    prepC(ln);
                    const uint32_t n4 = 4 * n80;
                    const uint32_t xas = pin(sb + S_XA + 192 + 192 * cc + a_pos(n80)), xbs = pin(sb + S_XB + 384 * cc + b_pos<40>(n80));
                    const float x0 = cc ? ldsf(sb + S_XCAR + n4) : bf_lo(lds16(sb + S_X0 + 160 * (ch & 3) + n4 / 2));
                    gather16(xp(uPolB + n4 + lag<DELAY_G>(sb, z0_)), parc, 5 * ch + 1, [&](float y, uint32_t) {
                        const uint32_t x = pack2(x0 + bfr(y), 0.f);
                        sts16(xbs, x);
                        sts16(xas, x);
                        return 0u;
                    });
                    CSTAMP(10);
                } else {
                    bar_main();
                    IDS();
                    prepC(ln);
                }
                gate_up(std::false_type());
            }
        }
        CSTAMP(12);
        float mean = 0.f, den = 1.f;
        {
            IDS();
            const uint32_t wh = pin((((ln & 7) + 48 * ((ln >> 3) & 1) + 8 * (ln >> 4)) * 160 + (wp < 7 ? 16 * wp : 128)) | ((384 * cc + b_pos<48>(n96)) << 16));
            const uint32_t pubD = pin(uPubD + (t4 & 1) * COL + 16 * (t4 & 2) + 4 * q8 + (fl & 1)), ha = xr + (S_HS - S_XB);
            auto down = [&](const uint32_t (&W)[3][4], const uint4& h0, const uint2& h1) {
                float a0[4] = {}, a1[4] = {}, a2[4] = {};
                mmaA(a0, W[0], h0.x, h0.y); mmaA(a1, W[1], h0.z, h0.w); mmaA(a2, W[2], h1.x, h1.y);
                return ((a0[0] + a0[3]) + (a1[0] + a1[3])) + (a2[0] + a2[3]);
            };
            if (wp < 6) {
                uint32_t Wd[3][4];
                auto ldd = [&](uint32_t z) {
#pragma unroll
                    for (int s = 0; s < 3; s++) ldsm4t(Wd[s], ((wh ^ z) & 0xffff) + (sb + S_WD + s * 2560));
                };
                ldd(0);
                if (actc) {
                    const char* srcv = xp(uPolC + lag<DELAY_C>(sb, z0_) + 8 * n96);
                    const uint2 cs = lds64(sb + S_CSGU + 8 * n96);
                    float gt, up;
                    int guard = 0;
                    while (true) {
                        uint2 v[8];
#pragma unroll
                        for (int s = 0; s < 8; s++) v[s] = ldp64(srcv + (s >> 2) * HALF + (s & 3) * 1024);
                        uint2 c = ldsvol64(sb + S_LN + 8 * cc + ((v[7].x ^ parc) & 1) * 32);
                        const bool stale = __any_sync(~0u, (cnt16(v, 16 * parc) & 31) != 0), late = __any_sync(~0u, (c.y & 7) != ch + 1);
                        const float pg = sum8x(v), pu = sum8y(v);
                        auto norm = [&] {
                            mean = bf_hi(c.x); den = bf_lo(c.x);
                            gt = bfr(fmaf(-mean, asf(cs.x), pg) * asf(c.y)); up = fmaf(-mean, asf(cs.y), pu) * asf(c.y);
                            keep(gt); keep(up);
                        };
                        norm();
                        if (!((stale | late) & (++guard < SPIN_LIMIT))) break;
                        if (!stale) { take_ln(c, sb + S_LN + 8 * cc); norm(); break; }
                    }
                    CSTAMP(13);
                    SWEEPS(5 * ch + 2, guard - 1);
                    const uint32_t h = pack2(bfr(gt * sigmoidf_(gt)) * bfr(up), 0.f);
                    sts16((wh >> 16) + (sb + S_HS), h);
                    CSTAMP(14);
                    if (ch == 3) CSTAMP(0);
                }
                bar_main();
                TST(4);
                CSTAMP(15);
                const uint4 h0 = lds128(ha);
                const uint2 h1 = lds64(ha + 16);
                stp32_if(!(td & 2), xp(pubD & ~1u), down(Wd, h0, h1), pubD & 1);
            } else {
                uint32_t v = 0;
                const uint32_t col = wp == 7 || !has0;
                const bool serve = wp == 6 || (has0 && has1);
                if (serve) {
                    const uint32_t par = col ? par1 : par0;
                    const char* src = xp(uPolC + col * COL + 776 + (td & 4) * (HALF / 4) + (td & 3) * 1024);
                    give_ln(uPolC + col * COL, par, sb + S_LN + 8 * col, td, mean, den, [&] { v = ldp32(src); return v ^ par; });
                }
                stsvol(sb + S_GATE, ch + 1);
                uint32_t Wd[2][3][4];
#pragma unroll
                for (int s = 0; s < 6; s++) ldsm4t(Wd[s / 3][s % 3], (wh & 0xffff) + (sb + S_WD + (s / 3) * 16 + (s % 3) * 2560));
                bar_main();
                const uint4 h0 = lds128(ha);
                const uint2 h1 = lds64(ha + 16);
                const float d0 = down(Wd[0], h0, h1), d1 = down(Wd[1], h0, h1);
                stp32_if(true, xp(pubD & ~1u), (td & 2) ? d1 : d0, pubD & 1);
                if (serve) {
                    float xw = asf(v);
                    xw += __shfl_xor_sync(~0u, xw, 1); xw += __shfl_xor_sync(~0u, xw, 2); xw += __shfl_xor_sync(~0u, xw, 4);
                    const float r = bfr(fmaf(-mean, ldsf(sb + S_SWR), xw) * rcp(den));
                    sts32(sb + S_STAT + 4 * col, __float_as_uint(bfr(sigmoidf_(r))) | (ch + 1));
                }
            }
        }
        CSTAMP(16);
        {
            IDS();
            const uint32_t pubE = pin(uPubE + (t4 < 3 ? (wp >> 2) * COL + 192 * (wp & 3) + 64 * t4 + 8 * q8 : (q8 >> 2) * COL + 768 + 4 * (q8 & 1)));
            xr = pin(sb + S_XB + 48 * (ln & 7));
            uint32_t x2 = 0;
            auto hop_d = [&](auto col) {
                const uint32_t xbs = pin(sb + S_XB + 384 * col.value + b_pos<40>(n80)), xas = col.value ? 0 : pin(sb + S_XA + 192 + a_pos(n80));
                const float x1 = bf_lo(lds16(xbs));
                const float lnx = __uint_as_float(pin(__float_as_uint(bfr(__fdiv_rn(bfr(x1 - mean), den)))));
                gather16(xp(uPolD + 4 * n80 + lag<DELAY_D>(sb, z0_)), col.value ? par1 : par0, 5 * ch + 3, [&](float y, uint32_t z) {
                    const uint32_t gate = ldsvol(sb + S_STAT + 4 * col.value + z);
                    x2 = pack2(x1 + bfr(lnx + bfr(bfr(y) * bf_hi(gate))), 0.f);
                    if (col.value) keep(x2); else { sts16(xbs, x2); sts16(xas, x2); }
                    return (uint32_t)((gate & 7) != ch + 1);
                });
                CSTAMP(17);
            };
            auto qproj = [&](auto with_stats) {
                bar_main();
                TST(5);
                CSTAMP(19);
                const uint32_t t4 = td & 3;
                const uint4 b = lds128(xr);
                uint32_t b4 = lds32(xr + 16);
                float acc[6][4] = {};
                if (with_stats.value) {
                    stp32_if((td & 11) == 3, both, xp(pubE ^ COPY), xp(pubE), stats(xr + (S_XA - S_XB), b, b4), par0);
                    __syncwarp();
                    b4 = lds32(xr + 16);
                }
                mul80(acc, Wq, b, b4);
                const float v0 = sel4(t4, acc[0][0] + acc[0][3], acc[2][0] + acc[2][3], acc[4][0] + acc[4][3], acc[4][0] + acc[4][3]);
                const float v1 = sel4(t4, acc[1][0] + acc[1][3], acc[3][0] + acc[3][3], acc[5][0] + acc[5][3], acc[5][0] + acc[5][3]);
                stp64_if(t4 < 3, both, xp(pubE ^ COPY), xp(pubE), tagw(v0, par0), tagw(v1, par0));
            };
            if (wp == 7) {
                if (!has0) break;
                qproj(std::true_type());
            } else {
                if (actc && !cc) hop_d(std::integral_constant<int, 0>());
                else {
                    if (actc && g == 0) {
                        const uint32_t po = pin(1280 * (ch - 1) + 160 * i + 2 * n80);
                        hop_d(std::integral_constant<int, 1>());
                        *reinterpret_cast<unsigned short*>(reinterpret_cast<char*>(P.out) + po) = (unsigned short)x2;
                    }
                    if (!has0) break;
                }
                qproj(std::false_type());
                sts32_if(td < 80, sb + S_XCAR + 4 * td, x2 << 16);
            }
        }
        CSTAMP(20);
        if (wp == 6) give_ln(uPolE, par0, sb + S_LN + 16, td, mean, den, [] { return 0u; });
        auto pass2 = [&](auto d0, auto d1, auto d2) {
            constexpr int D0 = d0.value, D1 = d1.value, D = D0 + D1 + d2.value;
            IDS();
            const uint32_t ua = sb + k_place(ch, wp & 6) * SLOT + (wp & 1) * UNIT, k0 = k_off(ln);
            uint32_t kf[12][2][4];
            auto ldk = [&](int s) { const uint32_t a = (k0 ^ (32 * (s / 3))) + (ua + 1024 * (s % 3)); ldsm4(kf[s][0], a); ldsm4(kf[s][1], a + SLOT); };
            auto ldv1 = [&](int k) { ldsm4t(vf[k / 3][k % 3], voff[k % 3] + (sb + v_place(ch, k / 3) * SLOT)); };
            auto ldv = [&](int s) { ldv1(3 * s); ldv1(3 * s + 1); ldv1(3 * s + 2); };
            constexpr uint32_t LATE = LAST_LATE;
            constexpr uint64_t EARLY_LIST = bit_list(~LATE), LATE_LIST = bit_list(LATE);
            auto early = [&](int k) {
                if (D1 == 0) ldk(k);
                else if (k < 3) { ldv1(9 + 2 * k); ldv1(10 + 2 * k); }
                else ldk((EARLY_LIST >> (4 * (k - 3))) & 15);
            };
            uint32_t v[8] = {}, qsa = 0;
            const char* srcv = xp(uPolE + lag<(D1 > 0 ? 0 : DELAY_E)>(sb, z0_) + 4 * td);
            auto look = [&] {
#pragma unroll
                for (int s = 0; s < 8; s++) v[s] = ldp32(srcv + (s >> 2) * HALF + (s & 3) * 1024);
            };
            if (D1 > 0) vaddr(voff);
            if (!(mbar_try(sb + S_FK + 8 * (wp & 6), par1) & mbar_try(sb + S_FK + 8 * (wp | 1), par1))) { mbar_wait(sb + S_FK + 8 * (wp & 6), par1); mbar_wait(sb + S_FK + 8 * (wp | 1), par1); }
#pragma unroll
            for (int s = 0; s < D0; s++) early(s);
            if (wp < 6) { look(); qsa = pin(sb + S_QS + 384 * ch + q_pos(z_)); }
#pragma unroll
            for (int s = D0; s < D0 + D1; s++) early(s);
            if (wp < 6) {
                const float cs = ldsf(sb + S_CSQ + 4 * td);
                int guard = 0;
                while (true) {
                    uint2 c = ldsvol64(sb + S_LN + 16 + ((v[0] ^ par0) & 1) * 32);
                    const bool stale = __any_sync(~0u, (cnt8(v, 24 * par0) & 31) != 0), late = __any_sync(~0u, (c.y & 7) != ch + 1);
                    const float qs = sum8(v);
                    auto norm = [&] {
                        const uint32_t q = pack2(fmaf(-bf_hi(c.x), cs, qs) * asf(c.y), 0.f);
                        sts16(qsa, q);
                    };
                    norm();
                    if (!((stale | late) & (++guard < SPIN_LIMIT))) break;
                    if (!stale) { take_ln(c, sb + S_LN + 16); norm(); break; }
                    look();
                }
                SWEEPS(5 * ch + 4, guard - 1);
                CSTAMP(22);
            }
#pragma unroll
            for (int s = D0 + D1; s < D; s++) early(s);
            CSTAMP(21);
            bar_main();
            TST(6);
            CSTAMP(1);
            uint2 q = lds64(sb + S_QS + 384 * ch + 8 * ln);
            float acc[2][4] = {};
            constexpr int V0 = 13 - D, NV = D1 > 0 ? 2 : (2 * (D - 1)) / 3;
            static_assert(D1 == 0 || D - 3 + __builtin_popcount(LATE) == 12, "plan");
#pragma unroll
            for (int s = 0; s < 12; s++) {
                const bool m = q8 == (s & 7);
                const uint32_t b0 = m ? q.x : 0u, b1 = m ? q.y : 0u;
                if (s == 7) q = lds64(sb + S_QS + 384 * ch + 8 * ln + 256);
                mmaA(acc[0], kf[s][0], b0, b1);
                mmaA(acc[1], kf[s][1], b0, b1);
                if (D1 > 0) {
                    if (s >= 1 && s <= __builtin_popcount(LATE)) ldk((LATE_LIST >> (4 * (s - 1))) & 15);
                } else {
                    if (s >= 1 && s + D - 1 < 12) ldk(s + D - 1);
                    if (s >= 1 && s + D - 1 == 11) { __syncwarp(); arrive_if(ln == 0, sb + S_RELK); }
                    if (s == V0) vaddr(voff);
                    if (s >= V0 && 2 * (s - V0) < 3 * NV) ldv1(9 + 2 * (s - V0));
                    if (s >= V0 && 2 * (s - V0) + 1 < 3 * NV) ldv1(10 + 2 * (s - V0));
                }
            }
            CSTAMP(24);
            {
                const float v0 = acc[0][0] + acc[0][1], v1 = acc[0][2] + acc[0][3], v2 = acc[1][0] + acc[1][1], v3 = acc[1][2] + acc[1][3];
                const bool hi = t4 & 2, od = t4 & 1;
                const float u0 = (hi ? v2 : v0) + __shfl_xor_sync(~0u, hi ? v0 : v2, 2), u1 = (hi ? v3 : v1) + __shfl_xor_sync(~0u, hi ? v1 : v3, 2);
                const float s = (od ? u1 : u0) + __shfl_xor_sync(~0u, od ? u0 : u1, 1);
                CSTAMP(2);
                probs(scaled(s), sb + S_PS + PS_PASS, wp, ln);
                CSTAMP(3);
            }
            bar_main();
            TST(10);
            CSTAMP(4);
            if (D1 > 0) values(vf, acc_, [&](int s) { if (s < 3) ldv(s + 5); }, sb + S_PS + PS_PASS, std::integral_constant<int, 1>(), par0);
            else values(vf, acc_, [&](int s) { if (s >= (NV > 1 ? 2 : 1) && s + NV + (NV > 1 ? 1 : 2) < 8) ldv(s + NV + (NV > 1 ? 1 : 2)); }, sb + S_PS + PS_PASS, std::integral_constant<int, 1>(), par0);
            arrive_if(ln == 0, sb + S_RELV);
        };
        if (ch == 3) {
            pass2(std::integral_constant<int, LAST0>(), std::integral_constant<int, LAST1>(), std::integral_constant<int, LAST2>());
#pragma unroll
            for (int m = 0; m < 48; m++) Wq[m / 8].a[(m / 4) % 2][m % 4] = vf[3 + m / 12][(m / 4) % 3][m % 4];
#pragma unroll
            for (int m = 0; m < 12; m++) Wq[m / 2].c[m % 2] = vf[7][m / 4][m % 4];
#pragma unroll
            for (int m = 0; m < 36; m++) left[m] = m < 12 ? __float_as_uint(acc_[m / 4][m % 4]) : vf[m / 12][(m / 4) % 3][m % 4];
        } else {
            pass2(std::integral_constant<int, KPRE>(), std::integral_constant<int, 0>(), std::integral_constant<int, KPRE2>());
#pragma unroll
            for (int m = 0; m < 36; m++) left[m] = m < 12 ? __float_as_uint(acc_[m / 4][m % 4]) : vf[4 + m / 12][(m / 4) % 3][m % 4];
        }
        TST(11);
        CSTAMP(23);
    }
    sts32_if(td == 255, sb + S_GATE, 6);
    TSTAMP(3);
}

typedef CUresult (*EncodeFn)(CUtensorMap*, CUtensorMapDataType, cuuint32_t, void*, const cuuint64_t*, const cuuint64_t*, const cuuint32_t*,
                             const cuuint32_t*, CUtensorMapInterleave, CUtensorMapSwizzle, CUtensorMapL2promotion, CUtensorMapFloatOOBfill);

void make_map(EncodeFn enc, CUtensorMap* m, const void* base, uint64_t cols, uint64_t rows, uint32_t box_cols, uint32_t box_rows, bool swizzle) {
    cuuint64_t dims[2] = {cols, rows};
    cuuint64_t strides[1] = {cols * 2};
    cuuint32_t box[2] = {box_cols, box_rows};
    cuuint32_t es[2] = {1, 1};
    enc(m, CU_TENSOR_MAP_DATA_TYPE_BFLOAT16, 2, const_cast<void*>(base), dims, strides, box, es, CU_TENSOR_MAP_INTERLEAVE_NONE,
        swizzle ? CU_TENSOR_MAP_SWIZZLE_128B : CU_TENSOR_MAP_SWIZZLE_NONE, CU_TENSOR_MAP_L2_PROMOTION_NONE, CU_TENSOR_MAP_FLOAT_OOB_FILL_NONE);
}

}

extern "C" void kernel_launch(void* const* d_in, const int* in_sizes, int n_in, void* d_out, int out_size) {
    (void)in_sizes; (void)n_in; (void)out_size;
    static EncodeFn enc = nullptr;
    if (!enc) {
        void* f = nullptr;
        cudaDriverEntryPointQueryResult q;
        cudaGetDriverEntryPoint("cuTensorMapEncodeTiled", &f, cudaEnableDefault, &q);
        enc = (EncodeFn)f;
        cudaFuncSetAttribute(fused_kernel, cudaFuncAttributeMaxDynamicSharedMemorySize, SMEM_BYTES);
    }
    Params P;
    P.x = (const __nv_bfloat16*)d_in[0]; P.k = (const __nv_bfloat16*)d_in[1]; P.v = (const __nv_bfloat16*)d_in[2];
    P.wr = (const __nv_bfloat16*)d_in[6]; P.wq = (const __nv_bfloat16*)d_in[3];
    P.out = (__nv_bfloat16*)d_out;
    Maps M;
    {
        cuuint64_t dims[4] = {64, 8, 3, (cuuint64_t)KV_BATCH_KEYS / 2}, strides[3] = {384, 128, 3072};
        cuuint32_t box[4] = {64, 8, 3, 2}, es[4] = {1, 1, 1, 1};
        enc(&M.k, CU_TENSOR_MAP_DATA_TYPE_BFLOAT16, 4, d_in[1], dims, strides, box, es, CU_TENSOR_MAP_INTERLEAVE_NONE, CU_TENSOR_MAP_SWIZZLE_128B,
            CU_TENSOR_MAP_L2_PROMOTION_NONE, CU_TENSOR_MAP_FLOAT_OOB_FILL_NONE);
    }
    make_map(enc, &M.v, P.v, 64, (uint64_t)12 * KV_BATCH_KEYS, 64, 96, true);
    make_map(enc, &M.vu, P.v, 64, (uint64_t)12 * KV_BATCH_KEYS, 64, 48, true);
    make_map(enc, &M.wq, d_in[3], 6144, 640, 192, 40, false);
    make_map(enc, &M.wo, d_in[4], 640, 6144, 80, 96, false);
    make_map(enc, &M.wg, d_in[7], 1536, 640, 96, 80, false);
    make_map(enc, &M.wu, d_in[8], 1536, 640, 96, 80, false);
    make_map(enc, &M.wd, d_in[9], 640, 1536, 80, 96, false);
    fused_kernel<<<NCTA, NTHR, SMEM_BYTES, cudaStreamPerThread>>>(P, M);
}
```
